```python
import torch

def _softmax(x, axis=-1):
    return torch.softmax(x, dim=axis)

def _gelu(x):
    return torch.nn.functional.gelu(x, approximate='tanh')

def _silu(x):
    return torch.nn.functional.silu(x)

def _sigmoid(x):
    return torch.sigmoid(x)

def _layernorm(x, axis=-1, eps=1e-05):
    m = x.mean(dim=axis, keepdim=True)
    v = x.var(dim=axis, keepdim=True, unbiased=False)
    return (x - m) / torch.sqrt(v + eps)

def _scatter_add(tgt, idx, src, axis=0):
    return tgt.clone().index_add_(axis, idx, src)

def _segment_sum(src, seg, n):
    out = torch.zeros((n,) + src.shape[1:], dtype=src.dtype)
    return out.index_add_(0, seg, src)

def _pad(x, pw):
    flat = tuple((v for pair in reversed(pw) for v in pair))
    return torch.nn.functional.pad(x, flat)
kernel_name = 'interleave_layers__ssm_conv_s4d__memory_aug_recurrent_mem_tr__prompt'

def setup_inputs():

    _w = lambda a: (lambda t: t.to(torch.bfloat16) if t.is_floating_point() else t)(torch.as_tensor(a))

    def _A_setup():
        Bsz, L, D, N = (1, 2048, 512, 128)
        return {'u': _w((lambda *s: torch.randn(*s, dtype=torch.bfloat16) * 0.05)(Bsz, L, D)), 'log_A_real': _w((lambda *s: torch.randn(*s, dtype=torch.bfloat16) * 3.2)(D, N) * 0.5), 'A_imag': _w((lambda *s: torch.randn(*s, dtype=torch.bfloat16) * 0.05)(D, N) * 3.14), 'C_real': _w((lambda *s: torch.randn(*s, dtype=torch.bfloat16) * 0.05)(D, N) / N ** 0.5), 'C_imag': _w((lambda *s: torch.randn(*s, dtype=torch.bfloat16) * 0.05)(D, N) / N ** 0.5), 'log_dt': _w((lambda *s: torch.randn(*s, dtype=torch.bfloat16) * 0.05)(D) * 0.5 - 4.0), 'D_skip': _w((lambda *s: torch.randn(*s, dtype=torch.bfloat16) * 0.05)(D))}
    _A_in = _A_setup()

    def _B_setup():
        B, S, Dm = (1, 2048, 512)
        H, Dh = (32, 128)
        M, seg = (8, 32)
        seg = min(seg, S)
        S = S // seg * seg
        return {'x': _w((lambda *s: torch.randn(*s, dtype=torch.bfloat16) * 0.05)(B, S, Dm)), 'mem0': _w((lambda *s: torch.randn(*s, dtype=torch.bfloat16) * 0.8)(B, M, Dm)), 'Wq': _w((lambda *s: torch.randn(*s, dtype=torch.bfloat16) * 1.6)(Dm, H, Dh) * Dm ** (-0.5)), 'Wk': _w((lambda *s: torch.randn(*s, dtype=torch.bfloat16) * 1.6)(Dm, H, Dh) * Dm ** (-0.5)), 'Wv': _w((lambda *s: torch.randn(*s, dtype=torch.bfloat16) * 0.8)(Dm, H, Dh) * Dm ** (-0.5)), 'Wo': _w((lambda *s: torch.randn(*s, dtype=torch.bfloat16) * 0.8)(H, Dh, Dm) * (H * Dh) ** (-0.5)), 'seg_len': seg}
    _B_in = _B_setup()
    return {'A_u': _A_in['u'], 'A_log_A_real': _A_in['log_A_real'], 'A_A_imag': _A_in['A_imag'], 'A_C_real': _A_in['C_real'], 'A_C_imag': _A_in['C_imag'], 'A_log_dt': _A_in['log_dt'], 'A_D_skip': _A_in['D_skip'], 'B_x': _B_in['x'], 'B_mem0': _B_in['mem0'], 'B_Wq': _B_in['Wq'], 'B_Wk': _B_in['Wk'], 'B_Wv': _B_in['Wv'], 'B_Wo': _B_in['Wo'], 'B_seg_len': _B_in['seg_len']}

def reference(A_u, A_log_A_real, A_A_imag, A_C_real, A_C_imag, A_log_dt, A_D_skip, B_x, B_mem0, B_Wq, B_Wk, B_Wv, B_Wo, B_seg_len):

    def _A_ref(u, log_A_real, A_imag, C_real, C_imag, log_dt, D_skip):
        L = u.shape[1]
        dt = torch.exp(log_dt)
        A = -torch.exp(log_A_real) + 1j * A_imag
        C = (C_real + 1j * C_imag) * dt[:, None]
        pos = (lambda x, dt: x.to(dt))(torch.arange(L), log_dt.dtype)
        P = torch.exp((A * dt[:, None])[:, :, None] * pos[None, None, :])
        K = 2.0 * torch.einsum('dn,dnl->dl', C, P).real
        L2 = 2 * L
        u_t = (lambda x, *d: x.permute(*d))(u, 0, 2, 1)
        Kf = (lambda x, *a, **k: torch.fft.rfft(x.float(), *a, **k))(K, L2)
        Uf = (lambda x, *a, **k: torch.fft.rfft(x.float(), *a, **k))(u_t, L2)
        y = (lambda x, *a, **k: torch.fft.irfft(x, *a, **k).to(torch.bfloat16))(Uf * Kf[None, :, :], L2)[:, :, :L]
        y = (lambda x, *d: x.permute(*d))(y, 0, 2, 1)
        return y + u * D_skip[None, None, :]

    def _B_ref(x, mem0, Wq, Wk, Wv, Wo, seg_len):
        B, S, Dm = x.shape
        H, Dh = (Wq.shape[1], Wq.shape[2])
        M = mem0.shape[1]
        scale = Dh ** (-0.5)
        n_seg = S // seg_len
        L = M + seg_len
        idx = torch.arange(L)
        mask = (idx[:, None] < M) | (idx[:, None] >= idx[None, :])
        mem = mem0
        outs = []
        for s in range(n_seg):
            xs = x[:, s * seg_len:(s + 1) * seg_len, :].clone()
            h = torch.concatenate([mem, xs], axis=1)
            q = torch.einsum('btd,dhe->bhte', h, Wq)
            k = torch.einsum('btd,dhe->bhte', h, Wk)
            v = torch.einsum('btd,dhe->bhte', h, Wv)
            scores = torch.einsum('bhqe,bhke->bhqk', q, k) * scale
            scores = torch.where(mask[None, None], scores, -1000000000.0)
            p = _softmax(scores, axis=-1)
            o = torch.einsum('bhqk,bhke->bhqe', p, v)
            o = torch.einsum('bhte,hed->btd', o, Wo)
            mem = o[:, :M, :].clone()
            outs.append(o[:, M:, :])
        return torch.concatenate(outs, axis=1)
    x = A_u
    x = x + _A_ref(_layernorm(x, axis=-1), A_log_A_real, A_A_imag, A_C_real, A_C_imag, A_log_dt, A_D_skip)
    x = x + _B_ref(_layernorm(x, axis=-1), B_mem0, B_Wq, B_Wk, B_Wv, B_Wo, B_seg_len)
    x = x + _A_ref(_layernorm(x, axis=-1), A_log_A_real, A_A_imag, A_C_real, A_C_imag, A_log_dt, A_D_skip)
    x = x + _B_ref(_layernorm(x, axis=-1), B_mem0, B_Wq, B_Wk, B_Wv, B_Wo, B_seg_len)
    return x
```

```cpp
#include <cuda_runtime.h>
#include <cuda_bf16.h>
#include <cuda.h>
#include <stdint.h>
#include <string.h>
#include <math.h>

namespace {

constexpr int NCL = 66;
constexpr int MAXT = 64;
constexpr int OPS1 = 8;
constexpr int MAXSPLIT = 16;
constexpr int HSPLIT = 10;
constexpr int PW = 144;

__device__ uint4 g_xA[2][16 * 8 * 1024];
__device__ float2 g_st[2][16 * 2048];
__device__ float2 g_st2[16 * 16 * 128];
__device__ uint4 g_qkv[2][64 * 64 * 768];
__device__ uint4 g_o[2][16 * 64 * 1024];
__device__ uint4 g_pp[2][16 * MAXSPLIT * 8192];
__device__ uint4 g_xch[133 * 512];
__device__ unsigned g_sel[64];
__device__ unsigned g_side[96];
__device__ unsigned g_probe[4096];
__device__ unsigned g_gate[32];
__device__ uint32_t g_P[16 * 16 * 32 * PW];
__device__ uint4 g_u[16 * 16 * 512];
__device__ float4 g_carry[3][16 * 16 * 4 * 256];
__device__ float g_cs[2 * 12288 + 64];
__device__ unsigned g_cnt[9 * 16 * 32];
__device__ uint32_t g_ln0[2048];

enum { C_QKV0 = 0, C_QKV1 = 1, C_O0 = 2, C_O1 = 3, C_OP0 = 4, C_OP1 = 5, C_CV = 6, C_ST = 7, C_H = 8 };
__device__ __forceinline__ unsigned* cnt_ptr(int kind, int chunk) { return g_cnt + (kind * 16 + chunk) * 32; }

enum { T_END = 0, T_QKV = 1, T_OP = 2, T_CV = 3, T_FIN = 4 };
struct ProArgs { const __nv_bfloat16 *x, *lAr, *Ai, *Cr, *Ci, *ldt, *Dk, *Wq, *Wk, *Wv, *Wo; };
struct Params {
    CUtensorMap tm[4];
    CUtensorMap t3[4];
    ProArgs pa;
    int dopro;
    const __nv_bfloat16* mem0;
    const __nv_bfloat16* Wo;
    const __nv_bfloat16* Dskip;
    __nv_bfloat16* out;
    int rec0;
    int chains;
    int lag;
    int zero;
    int dostats;
    int nst[2];
    uint32_t task[NCL][MAXT];
};

__device__ __forceinline__ uint32_t smem_u32(const void* p) { return (uint32_t)__cvta_generic_to_shared(p); }
__device__ __forceinline__ uint32_t mapa(uint32_t a, uint32_t r) {
    uint32_t o; asm("mapa.shared::cluster.u32 %0,%1,%2;" : "=r"(o) : "r"(a), "r"(r)); return o;
}
__device__ __forceinline__ void mbar_init(uint32_t b, int c) { asm volatile("mbarrier.init.shared::cta.b64 [%0],%1;" ::"r"(b), "r"(c) : "memory"); }
__device__ __forceinline__ void mbar_expect(uint32_t b, int bytes) { asm volatile("mbarrier.arrive.expect_tx.shared::cta.b64 _,[%0],%1;" ::"r"(b), "r"(bytes) : "memory"); }
__device__ __forceinline__ void mbar_arrive(uint32_t b) { asm volatile("mbarrier.arrive.shared::cta.b64 _,[%0];" ::"r"(b) : "memory"); }
__device__ __forceinline__ void mbar_arrive_cluster(uint32_t b) { asm volatile("mbarrier.arrive.shared::cluster.b64 _,[%0];" ::"r"(b) : "memory"); }
__device__ __forceinline__ void mbar_wait(uint32_t b, uint32_t ph) {
    asm volatile(
        "{.reg .pred p; .reg .u32 n; mov.u32 n,0;\n"
        "W%=: mbarrier.try_wait.parity.shared::cta.b64 p,[%0],%1;\n"
        "@p bra D%=;\n"
        "add.u32 n,n,1; setp.lt.u32 p,n,2000000; @p bra W%=;\n"
        "trap;\n"
        "D%=: }" ::"r"(b), "r"(ph) : "memory");
}
__device__ __forceinline__ bool wait_lds128(uint32_t b, uint32_t ph, uint32_t a, uint4& v) {
    uint32_t ok;
    asm volatile("{.reg .pred p; mbarrier.try_wait.parity.shared::cta.b64 p,[%5],%6,20000; ld.shared.v4.u32 {%0,%1,%2,%3},[%7]; selp.u32 %4,1,0,p;}"
                 : "=r"(v.x), "=r"(v.y), "=r"(v.z), "=r"(v.w), "=r"(ok) : "r"(b), "r"(ph), "r"(a) : "memory");
    return ok;
}
__device__ __forceinline__ bool wait_lds64(uint32_t b, uint32_t ph, uint32_t a, uint2& v) {
    uint32_t ok;
    asm volatile("{.reg .pred p; mbarrier.try_wait.parity.shared::cta.b64 p,[%3],%4,20000; ld.shared.v2.u32 {%0,%1},[%5]; selp.u32 %2,1,0,p;}"
                 : "=r"(v.x), "=r"(v.y), "=r"(ok) : "r"(b), "r"(ph), "r"(a) : "memory");
    return ok;
}
template <int PH> __device__ __forceinline__ void mbar_wait_c(uint32_t b) {
    asm volatile(
        "{.reg .pred p; .reg .u32 n; mov.u32 n,%2;\n"
        "W%=: mbarrier.try_wait.parity.shared::cta.b64 p,[%0],%1;\n"
        "@p bra D%=;\n"
        "add.u32 n,n,1; setp.lt.u32 p,n,2000000; @p bra W%=;\n"
        "trap;\n"
        "D%=: }" ::"r"(b), "n"(PH), "n"(PH) : "memory");
}
__device__ __forceinline__ void bar_sync(int id, int n) { asm volatile("bar.sync %0,%1;" ::"r"(id), "r"(n) : "memory"); }
__device__ __forceinline__ void bar_arrive(int id, int n) { asm volatile("bar.arrive %0,%1;" ::"r"(id), "r"(n) : "memory"); }
__device__ __forceinline__ void cluster_sync() { asm volatile("barrier.cluster.arrive.relaxed.aligned; barrier.cluster.wait.aligned;" ::: "memory"); }
__device__ __forceinline__ void fence_async() { asm volatile("fence.proxy.async;" ::: "memory"); }
__device__ __forceinline__ void fence_async_smem() { asm volatile("fence.proxy.async.shared::cta;" ::: "memory"); }
#define EFR 1
#define EFW 2
constexpr uint64_t POL_N = 0x1000000000000000ull, POL_F = 0x12F0000000000000ull;
constexpr uint64_t POL_LAST = EFR ? POL_F : POL_N  , POL_LATE = EFW ? POL_F : POL_N  , POL_SOON = EFW > 1 ? POL_F : POL_N;
__device__ __forceinline__ void bulk_g2s(uint32_t dst, const void* src, int bytes, uint32_t bar, uint64_t pol) {
    asm volatile("cp.async.bulk.shared::cluster.global.mbarrier::complete_tx::bytes.L2::cache_hint [%0],[%1],%2,[%3],%4;" ::"r"(dst), "l"(src), "r"(bytes), "r"(bar), "l"(pol) : "memory");
}
__device__ __forceinline__ void bulk_g2s_mc(uint32_t dst, const void* src, int bytes, uint32_t bar, uint64_t pol) {
    asm volatile("cp.async.bulk.shared::cluster.global.mbarrier::complete_tx::bytes.multicast::cluster.L2::cache_hint [%0],[%1],%2,[%3],%4,%5;" ::"r"(dst), "l"(src), "r"(bytes), "r"(bar), "h"((uint16_t)3), "l"(pol) : "memory");
}
__device__ __forceinline__ void stg128(uint4* p, uint4 v, uint64_t pol) {
    asm volatile("st.global.L2::cache_hint.v4.u32 [%0],{%1,%2,%3,%4},%5;" ::"l"(p), "r"(v.x), "r"(v.y), "r"(v.z), "r"(v.w), "l"(pol));
}
__device__ __forceinline__ void stg32(uint32_t* p, uint32_t v, uint64_t pol) { asm volatile("st.global.L2::cache_hint.u32 [%0],%1,%2;" ::"l"(p), "r"(v), "l"(pol)); }
__device__ __forceinline__ uint4 ldcg128_last(const uint4* p) {
    uint4 v; asm volatile("ld.global.cg.L2::cache_hint.v4.u32 {%0,%1,%2,%3},[%4],%5;" : "=r"(v.x), "=r"(v.y), "=r"(v.z), "=r"(v.w) : "l"(p), "l"(POL_LAST) : "memory"); return v;
}
__device__ __forceinline__ void tma2d(uint32_t dst, const CUtensorMap* tm, int x, int y, uint32_t bar) {
    asm volatile("cp.async.bulk.tensor.2d.shared::cluster.global.mbarrier::complete_tx::bytes [%0],[%1,{%2,%3}],[%4];" ::"r"(dst), "l"(tm), "r"(x), "r"(y), "r"(bar) : "memory");
}
__device__ __forceinline__ void tma3d(uint32_t dst, const CUtensorMap* tm, int y, int z, uint32_t bar) {
    asm volatile("cp.async.bulk.tensor.3d.shared::cluster.global.mbarrier::complete_tx::bytes [%0],[%1,{0,%2,%3}],[%4];" ::"r"(dst), "l"(tm), "r"(y), "r"(z), "r"(bar) : "memory");
}
__device__ __forceinline__ void st_async4(uint32_t a, uint32_t x, uint32_t y, uint32_t z, uint32_t w, uint32_t mb) {
    asm volatile("st.async.shared::cluster.mbarrier::complete_tx::bytes.v4.b32 [%0],{%1,%2,%3,%4},[%5];" ::"r"(a), "r"(x), "r"(y), "r"(z), "r"(w), "r"(mb) : "memory");
}
__device__ __forceinline__ void st_async2(uint32_t a, uint32_t x, uint32_t y, uint32_t mb) {
    asm volatile("st.async.shared::cluster.mbarrier::complete_tx::bytes.v2.b32 [%0],{%1,%2},[%3];" ::"r"(a), "r"(x), "r"(y), "r"(mb) : "memory");
}
#define LDSQ "ld.shared"
__device__ __forceinline__ uint4 lds128(uint32_t a) { uint4 v; asm volatile(LDSQ ".v4.u32 {%0,%1,%2,%3},[%4];" : "=r"(v.x), "=r"(v.y), "=r"(v.z), "=r"(v.w) : "r"(a) : "memory"); return v; }
__device__ __forceinline__ uint2 lds64(uint32_t a) { uint2 v; asm volatile(LDSQ ".v2.u32 {%0,%1},[%2];" : "=r"(v.x), "=r"(v.y) : "r"(a) : "memory"); return v; }
__device__ __forceinline__ uint32_t lds32(uint32_t a) { uint32_t v; asm volatile(LDSQ ".u32 %0,[%1];" : "=r"(v) : "r"(a) : "memory"); return v; }
__device__ __forceinline__ void sts128(uint32_t a, uint32_t x, uint32_t y, uint32_t z, uint32_t w) { asm volatile("st.shared.v4.u32 [%0],{%1,%2,%3,%4};" ::"r"(a), "r"(x), "r"(y), "r"(z), "r"(w) : "memory"); }
__device__ __forceinline__ void sts64(uint32_t a, uint32_t x, uint32_t y) { asm volatile("st.shared.v2.u32 [%0],{%1,%2};" ::"r"(a), "r"(x), "r"(y) : "memory"); }
__device__ __forceinline__ void sts32(uint32_t a, uint32_t x) { asm volatile("st.shared.u32 [%0],%1;" ::"r"(a), "r"(x) : "memory"); }
__device__ __forceinline__ uint4 ldsm4(uint32_t a) { uint4 v; asm volatile("ldmatrix.sync.aligned.m8n8.x4.shared.b16 {%0,%1,%2,%3},[%4];" : "=r"(v.x), "=r"(v.y), "=r"(v.z), "=r"(v.w) : "r"(a) : "memory"); return v; }
__device__ __forceinline__ uint4 ldsm4t(uint32_t a) { uint4 v; asm volatile("ldmatrix.sync.aligned.m8n8.x4.trans.shared.b16 {%0,%1,%2,%3},[%4];" : "=r"(v.x), "=r"(v.y), "=r"(v.z), "=r"(v.w) : "r"(a) : "memory"); return v; }
__device__ __forceinline__ uint32_t movm(uint32_t a) { uint32_t d; asm volatile("movmatrix.sync.aligned.m8n8.trans.b16 %0,%1;" : "=r"(d) : "r"(a)); return d; }
__device__ __forceinline__ uint32_t pack2(float lo, float hi) { uint32_t d; asm("cvt.rn.bf16x2.f32 %0,%1,%2;" : "=r"(d) : "f"(hi), "f"(lo)); return d; }
__device__ __forceinline__ uint32_t hadd2(uint32_t a, uint32_t b) { uint32_t d; asm("add.rn.bf16x2 %0,%1,%2;" : "=r"(d) : "r"(a), "r"(b)); return d; }
__device__ __forceinline__ float blo(uint32_t v) { return __uint_as_float(v << 16); }
__device__ __forceinline__ float bhi(uint32_t v) { return __uint_as_float(v & 0xffff0000u); }
__device__ __forceinline__ float rbf(float x) { return __uint_as_float(pack2(0.f, x)); }
__device__ __forceinline__ float ex2(float x) { float y; asm("ex2.approx.ftz.f32 %0,%1;" : "=f"(y) : "f"(x)); return y; }
__device__ __forceinline__ float rcp(float x) { float y; asm("rcp.approx.ftz.f32 %0,%1;" : "=f"(y) : "f"(x)); return y; }
__device__ __forceinline__ void mma16(float* c, uint32_t a0, uint32_t a1, uint32_t a2, uint32_t a3, uint32_t b0, uint32_t b1) {
    asm volatile("mma.sync.aligned.m16n8k16.row.col.f32.bf16.bf16.f32 {%0,%1,%2,%3},{%4,%5,%6,%7},{%8,%9},{%0,%1,%2,%3};"
                 : "+f"(c[0]), "+f"(c[1]), "+f"(c[2]), "+f"(c[3]) : "r"(a0), "r"(a1), "r"(a2), "r"(a3), "r"(b0), "r"(b1));
}
__device__ __forceinline__ void mma16_top(float& d0, float& d1, uint32_t a0, uint32_t a2, uint32_t b0, uint32_t b1) {
    asm volatile("{.reg .b32 j; .reg .f32 e,f; mma.sync.aligned.m16n8k16.row.col.f32.bf16.bf16.f32 {%0,%1,e,f},{%2,j,%3,j},{%4,%5},{0f00000000,0f00000000,0f00000000,0f00000000};}"
                 : "=f"(d0), "=f"(d1) : "r"(a0), "r"(a2), "r"(b0), "r"(b1));
}
__device__ __forceinline__ void mma8(float* c, uint32_t a0, uint32_t a1, uint32_t b0) {
    asm volatile("mma.sync.aligned.m16n8k8.row.col.f32.bf16.bf16.f32 {%0,%1,%2,%3},{%4,%5},{%6},{%0,%1,%2,%3};"
                 : "+f"(c[0]), "+f"(c[1]), "+f"(c[2]), "+f"(c[3]) : "r"(a0), "r"(a1), "r"(b0));
}
__device__ __forceinline__ uint4 ld_rlx128(const uint4* p) {
    uint4 v;
    asm volatile("{.reg .b128 t; ld.relaxed.gpu.global.b128 t,[%4]; mov.b128 {%0,%1,%2,%3},t;}" : "=r"(v.x), "=r"(v.y), "=r"(v.z), "=r"(v.w) : "l"(p) : "memory");
    return v;
}
__device__ __forceinline__ void st_rlx128(uint4* p, uint32_t x, uint32_t y, uint32_t z, uint32_t w) {
    asm volatile("{.reg .b128 t; mov.b128 t,{%1,%2,%3,%4}; st.relaxed.gpu.global.b128 [%0],t;}" ::"l"(p), "r"(x), "r"(y), "r"(z), "r"(w) : "memory");
}
__device__ __forceinline__ uint4 ldcg128(const uint4* p) { uint4 v; asm volatile("ld.global.cg.v4.u32 {%0,%1,%2,%3},[%4];" : "=r"(v.x), "=r"(v.y), "=r"(v.z), "=r"(v.w) : "l"(p) : "memory"); return v; }
__device__ __forceinline__ void red_release(unsigned* p, unsigned v) {
    asm volatile("fence.proxy.async; red.relaxed.gpu.global.add.u32 [%0],%1;" ::"l"(p), "r"(v) : "memory");
}
__device__ __forceinline__ void wait_cnt(const unsigned* p, unsigned target) {
    unsigned v; int n = 0;
    while (true) {
        asm volatile("ld.acquire.gpu.global.u32 %0,[%1];" : "=r"(v) : "l"(p) : "memory");
        if (v >= target) break;
        if (++n > 3000000) __trap();
        __nanosleep(40);
    }
}
__device__ __forceinline__ void wait_cnt_warp(const unsigned* p, unsigned target) {
    unsigned v; int n = 0;
    while (true) {
        asm volatile("ld.acquire.gpu.global.u32 %0,[%1];" : "=r"(v) : "l"(p) : "memory");
        if (__all_sync(0xffffffffu, v >= target)) break;
        if (++n > 3000000) __trap();
        __nanosleep(40);
    }
}
__device__ __forceinline__ uint64_t mkdesc(uint32_t addr, uint32_t lbo, uint32_t sbo, uint32_t sw) {
    return (uint64_t)((addr & 0x3FFFF) >> 4) | ((uint64_t)(lbo >> 4) << 16) | ((uint64_t)(sbo >> 4) << 32) | ((uint64_t)sw << 62);
}
__device__ __forceinline__ void wg_fence() { asm volatile("wgmma.fence.sync.aligned;" ::: "memory"); }
__device__ __forceinline__ void wg_commit() { asm volatile("wgmma.commit_group.sync.aligned;" ::: "memory"); }
template <int N> __device__ __forceinline__ void wg_wait() { asm volatile("wgmma.wait_group.sync.aligned %0;" ::"n"(N) : "memory"); }
#define R8(c, o) "+f"(c[o]), "+f"(c[o + 1]), "+f"(c[o + 2]), "+f"(c[o + 3]), "+f"(c[o + 4]), "+f"(c[o + 5]), "+f"(c[o + 6]), "+f"(c[o + 7])
#define R32(c, o) R8(c, o), R8(c, o + 8), R8(c, o + 16), R8(c, o + 24)
#define S32A "%0,%1,%2,%3,%4,%5,%6,%7,%8,%9,%10,%11,%12,%13,%14,%15,%16,%17,%18,%19,%20,%21,%22,%23,%24,%25,%26,%27,%28,%29,%30,%31"
#define S32B ",%32,%33,%34,%35,%36,%37,%38,%39,%40,%41,%42,%43,%44,%45,%46,%47,%48,%49,%50,%51,%52,%53,%54,%55,%56,%57,%58,%59,%60,%61,%62,%63"
#define S32C ",%64,%65,%66,%67,%68,%69,%70,%71,%72,%73,%74,%75,%76,%77,%78,%79,%80,%81,%82,%83,%84,%85,%86,%87,%88,%89,%90,%91,%92,%93,%94,%95"
#define S32D ",%96,%97,%98,%99,%100,%101,%102,%103,%104,%105,%106,%107,%108,%109,%110,%111,%112,%113,%114,%115,%116,%117,%118,%119,%120,%121,%122,%123,%124,%125,%126,%127"
__device__ __forceinline__ void wgmma256(float* c, uint64_t da, uint64_t db, int acc) {
    asm volatile("{.reg .pred p; setp.ne.b32 p,%130,0; wgmma.mma_async.sync.aligned.m64n256k16.f32.bf16.bf16 {" S32A S32B S32C S32D "},%128,%129,p,1,1,0,1;}"
                 : R32(c, 0), R32(c, 32), R32(c, 64), R32(c, 96) : "l"(da), "l"(db), "r"(acc));
}
__device__ __forceinline__ void wgmma192(float* c, uint64_t da, uint64_t db, int acc) {
    asm volatile("{.reg .pred p; setp.ne.b32 p,%98,0; wgmma.mma_async.sync.aligned.m64n192k16.f32.bf16.bf16 {" S32A S32B S32C "},%96,%97,p,1,1,0,1;}"
                 : R32(c, 0), R32(c, 32), R32(c, 64) : "l"(da), "l"(db), "r"(acc));
}
__device__ __forceinline__ void wgmma8_first(float* c, uint64_t da, uint64_t db) {
    asm volatile("wgmma.mma_async.sync.aligned.m64n8k16.f32.bf16.bf16 {%0,%1,%2,%3},%4,%5,0,1,1,1,0;"
                 : "=f"(c[0]), "=f"(c[1]), "=f"(c[2]), "=f"(c[3]) : "l"(da), "l"(db));
}
template <int ACC> __device__ __forceinline__ void wgmma16_ta(float* c, float* e, uint64_t da, uint64_t db) {
    if (ACC) asm volatile("wgmma.mma_async.sync.aligned.m64n16k16.f32.bf16.bf16 {%0,%1,%2,%3,%4,%5,%6,%7},%8,%9,1,1,1,1,0;"
                 : "+f"(c[0]), "+f"(c[1]), "+f"(c[2]), "+f"(c[3]), "+f"(e[0]), "+f"(e[1]), "+f"(e[2]), "+f"(e[3]) : "l"(da), "l"(db));
    else asm volatile("wgmma.mma_async.sync.aligned.m64n16k16.f32.bf16.bf16 {%0,%1,%2,%3,%4,%5,%6,%7},%8,%9,0,1,1,1,0;"
                 : "=f"(c[0]), "=f"(c[1]), "=f"(c[2]), "=f"(c[3]), "=f"(e[0]), "=f"(e[1]), "=f"(e[2]), "=f"(e[3]) : "l"(da), "l"(db));
}
__device__ __forceinline__ void wgmma8_ta(float* c, uint64_t da, uint64_t db) {
    asm volatile("wgmma.mma_async.sync.aligned.m64n8k16.f32.bf16.bf16 {%0,%1,%2,%3},%4,%5,1,1,1,1,0;"
                 : "+f"(c[0]), "+f"(c[1]), "+f"(c[2]), "+f"(c[3]) : "l"(da), "l"(db));
}
template <int N> __device__ __forceinline__ void reg_inc() { asm volatile("setmaxnreg.inc.sync.aligned.u32 %0;" ::"n"(N)); }
template <int N> __device__ __forceinline__ void reg_dec() { asm volatile("setmaxnreg.dec.sync.aligned.u32 %0;" ::"n"(N)); }

#define PROF(cond, idx) do {} while (0)
#define CPROF(k) do {} while (0)

constexpr int S_GATE = 232440, S_XBAR = 232432, S_VCL = 232444;
constexpr float SC_LOG2E = 0.08838834764831845f * 1.4426950408889634f;

__device__ __forceinline__ float2 ln_finish(float mean, float var) {
    float sd; asm("sqrt.approx.f32 %0,%1;" : "=f"(sd) : "f"(rbf(rbf(var) + 1e-5f)));
    sd = rbf(sd);
    return make_float2(rbf(mean), sd);
}

__device__ __forceinline__ float2 row_stats512(const uint4* src, int s1, int s2) {
    const int g = (threadIdx.x & 31) >> 2;
    uint4 v[16];
#pragma unroll
    for (int i = 0; i < 16; i++) v[i] = ldcg128(src + (i >> 1) * s1 + (i & 1) * s2);
    float a[4] = {0, 0, 0, 0}, q0[4] = {0, 0, 0, 0}, q1[4] = {0, 0, 0, 0};
#pragma unroll
    for (int i = 0; i < 16; i++) {
        mma16(a, v[i].x, v[i].y, v[i].z, v[i].w, 0x3f803f80u, 0x3f803f80u);
        mma8(q0, v[i].x, v[i].y, v[i].x); mma8(q1, v[i].x, v[i].y, v[i].y);
        mma8(q0, v[i].z, v[i].w, v[i].z); mma8(q1, v[i].z, v[i].w, v[i].w);
    }
    const float sum = a[0] + a[2], sq = (g & 1) ? q0[1] + q1[3] : q0[0] + q1[2];
    return make_float2(sum, fmaxf(sq - sum * sum * (1.f / 512.f), 0.f));
}
__device__ __forceinline__ void x1_stats(int rg) {
    const int lane = threadIdx.x & 31, g = lane >> 2, c = lane & 3;
    const float2 r = row_stats512(g_xA[0] + (rg >> 4) * 8192 + (rg & 15) * 64 + c * 8 + g, 1024, 32);
    if (c == (g >> 1)) { g_st[0][rg * 8 + g] = r; g_ln0[rg * 8 + g] = 0; }
    __syncwarp();
    if (lane == 0) red_release(cnt_ptr(C_ST, rg >> 4), 1);
}
__global__ void stats_kernel() { x1_stats(blockIdx.x * 4 + (threadIdx.x >> 5)); }

#define NWO 10
#define VMASK 0x4444
#define VQ 16
#define VPRE 2
#define MPRE 1
#define NPM NPX
#define SCHED(i) do {} while (0)
#define VPX 0
#define OA 0
#define QA 0
#define NPX 2
#define NPF 4
constexpr int SLOT = 24576, SL_V = 8192, SL_Q = 16384, SL_KM = 20480, SL_VM = 22528;
constexpr int R_WV = 0, R_SL = 65536, R_WO = R_SL + 4 * SLOT, R_M = 196608  , R_U = R_M + 8192  ,
              R_OS = R_U + 8192  , R_SB = R_OS + 8192  , R_OB = R_SB + 5248  , R_PB = R_OB + 2048  ,
              R_IL = R_PB + 1024  , R_SEL = 231680, R_BAR = R_SEL + 256, R_STQ = 65536, R_STK = 131072;
static_assert(R_WO + (16 - NWO) * 4096 <= R_M && R_IL + 64 <= R_SEL && R_BAR + 512 <= 232448, "smem map");
enum { RB_XFULL = 0  , RB_GO = 4  , RB_QK = 8  , RB_INIT = 24, RB_SV = 25  , RB_N = 29 };
#define GATE 1
enum { NB_MFULL = 1  , NB_PART = 3  , NB_S = 5, NB_P = 6, NB_O = 7, NB_W = 10 };
#define WDEP 1
#define RH 56
#define RW0 224
#define D1 300
#define D2 300
#define DX 0
__device__ __forceinline__ uint32_t clk32() { uint32_t c; asm volatile("mov.u32 %0,%%clock;" : "=r"(c)::"memory"); return c; }
__device__ __forceinline__ void spin(int cycles) {
    if (cycles <= 0) return;
    const uint32_t t0 = clk32();
    while (clk32() - t0 < (uint32_t)cycles) {}
}
__device__ __forceinline__ uint4* xregion(int X, int r) { return (uint4*)(((size_t)g_xch + 8191) & ~(size_t)8191) + (X * 66 + r) * 512; }

struct RecW { uint32_t po, dp, lw, swr, pwr, w, wv; };

template <int X>
__device__ __forceinline__ void rec_step(const RecW& k, uint32_t sb, int s, uint32_t z, uint32_t gate, const uint32_t (*wq)[4], const uint32_t (*wk)[4], uint4* wv, uint4* wo) {
    const uint32_t wz = k.w + z, w5 = wz * 512, so = (s & 1) * SLOT + w5;
    constexpr int SL = R_SL + X * 2 * SLOT;
    const uint32_t qb = sb + R_BAR + (RB_QK + X * 8) * 8 + wz * 8;
    const uint32_t l8 = ((k.lw + z) >> 1) + (sb - (sb >> 1) + SL + (s & 1) * SLOT + wz * 256);
    uint4 mk[8];
#define WVF(ks) wv[ks]
#define WVL(a, b) _Pragma("unroll") for (int ks_ = (a); ks_ < (b); ks_++) if (ks_ < 16 && !((VMASK >> ks_) & 1)) wv[ks_] = ldsm4t(k.wv + ks_ * 2048)
    WVL(0, VPRE);
    bar_sync(NB_MFULL + X, 288);
    uint32_t x[4], vv[2];
    float av[2][4] = {{0, 0, 0, 0}, {0, 0, 0, 0}};
    {
        float aq[2][4] = {{0, 0, 0, 0}, {0, 0, 0, 0}}, ak[2][4] = {{0, 0, 0, 0}, {0, 0, 0, 0}};
#pragma unroll
        for (int i = 0; i < MPRE; i++) mk[i] = ldsm4(k.lw + X * 4096 + R_M + i * 512);
#pragma unroll
        for (int i = 0; i < 8; i++) {
            if (i + MPRE < 8) mk[i + MPRE] = ldsm4(k.lw + X * 4096 + R_M + (i + MPRE) * 512);
            if (2 * i < VQ) { WVL(2 * i + VPRE, min(2 * i + 2 + VPRE, VQ + VPX)); }
            SCHED(i);
            const uint4 mf = mk[i];
            mma16(aq[0], wq[2 * i][0], wq[2 * i][1], wq[2 * i][2], wq[2 * i][3], mf.x, mf.y);
            mma16(ak[0], wk[2 * i][0], wk[2 * i][1], wk[2 * i][2], wk[2 * i][3], mf.x, mf.y);
            if (2 * i < VQ) mma16(av[0], WVF(2 * i).x, WVF(2 * i).y, WVF(2 * i).z, WVF(2 * i).w, mf.x, mf.y);
            mma16(aq[QA & 1], wq[2 * i + 1][0], wq[2 * i + 1][1], wq[2 * i + 1][2], wq[2 * i + 1][3], mf.z, mf.w);
            mma16(ak[(QA >> 1) & 1], wk[2 * i + 1][0], wk[2 * i + 1][1], wk[2 * i + 1][2], wk[2 * i + 1][3], mf.z, mf.w);
            if (2 * i < VQ) mma16(av[QA >> 2], WVF(2 * i + 1).x, WVF(2 * i + 1).y, WVF(2 * i + 1).z, WVF(2 * i + 1).w, mf.z, mf.w);
        }
        if (QA) {
#pragma unroll
            for (int i = 0; i < 4; i++) { if (QA & 1) aq[0][i] += aq[1][i]; if (QA & 2) ak[0][i] += ak[1][i]; }
        }
        x[0] = movm(pack2(aq[0][0], aq[0][1])); x[1] = movm(pack2(aq[0][2], aq[0][3]));
        x[2] = movm(pack2(ak[0][0], ak[0][1])); x[3] = movm(pack2(ak[0][2], ak[0][3]));
        st_async4(k.lw + (R_U + X * 4096 + w5 + k.dp), x[0], x[1], x[2], x[3], qb + k.dp);
    }
    {
#pragma unroll
        for (int i = VQ / 2; i < 8; i++) {
            const uint4 mf = mk[i];
            WVL(2 * i + VPX, 2 * i + 2 + VPX);
            mma16(av[0], WVF(2 * i).x, WVF(2 * i).y, WVF(2 * i).z, WVF(2 * i).w, mf.x, mf.y);
            mma16(av[1], WVF(2 * i + 1).x, WVF(2 * i + 1).y, WVF(2 * i + 1).z, WVF(2 * i + 1).w, mf.z, mf.w);
        }
        if (VQ < 16 || QA >= 4) {
#pragma unroll
            for (int i = 0; i < 4; i++) av[0][i] += av[1][i];
        }
        vv[0] = pack2(av[0][0], av[0][1]); vv[1] = pack2(av[0][2], av[0][3]);
        st_async2(l8 + (SL_VM + k.dp), vv[0], vv[1], qb + k.dp);
        asm volatile("{.reg .pred p; setp.eq.u32 p,%1,%2; @p mbarrier.arrive.shared::cta.b64 _,[%0];}" ::"r"(gate), "r"(k.swr), "r"(gate ? sb + R_SB : 0) : "memory");
        const uint4 k0 = lds128(k.lw + so + SL), k1 = lds128(k.lw + so + SL + 4096);
#pragma unroll
        for (int i = 0; i < NPX; i++) wo[i] = lds128(k.lw + w5 + R_WO + i * 4096);
        mbar_wait(qb, s & 1);
        const uint4 u = lds128(k.lw + w5 + R_U + X * 4096);
        const uint32_t q0 = hadd2(x[0], u.x), q1 = hadd2(x[1], u.y);
        x[2] = hadd2(x[2], u.z); x[3] = hadd2(x[3], u.w);
        float sa[4] = {0, 0, 0, 0}, sc[4] = {0, 0, 0, 0}, sm0, sm1;
        mma16(sa, k0.x, k0.y, k0.z, k0.w, q0, q1);
        mma16(sc, k1.x, k1.y, k1.z, k1.w, q0, q1);
        mma16_top(sm0, sm1, x[2], x[3], q0, q1);
        asm volatile("stmatrix.sync.aligned.m8n8.x4.trans.shared.b16 [%0],{%1,%2,%3,%4};" ::"r"(k.swr), "r"(pack2(sa[0], sa[1])), "r"(pack2(sa[2], sa[3])),
                     "r"(pack2(sc[0], sc[1])), "r"(pack2(sc[2], sc[3])) : "memory");
        asm volatile("stmatrix.sync.aligned.m8n8.x1.trans.shared.b16 [%0],{%1};" ::"r"(k.swr + 512), "r"(pack2(sm0, sm1)) : "memory");
    }
    bar_sync(NB_S, 256);
    uint4 v0, v1;
    {
        const uint4 y = ldsm4t(k.lw + wz * 656 + R_SB);
        uint32_t y4; asm volatile("ldmatrix.sync.aligned.m8n8.x1.trans.shared.b16 {%0},[%1];" : "=r"(y4) : "r"(k.lw + wz * 656 + R_SB + 512) : "memory");
        const uint2 vp = lds64(l8 + SL_VM);
        sts64(l8 + SL_KM, x[2], x[3]);
        v0 = lds128(k.lw + so + SL + SL_V); v1 = lds128(k.lw + so + SL + SL_V + 4096);
        vv[0] = hadd2(vv[0], vp.x); vv[1] = hadd2(vv[1], vp.y);
        sts64(l8 + SL_VM, vv[0], vv[1]);
#pragma unroll
        for (int i = NPX; i < NPM; i++) wo[i] = lds128(k.lw + w5 + R_WO + i * 4096);
        const uint32_t ONE = 0x3f803f80u;
        float a[4] = {0, 0, 0, 0}, b[4] = {0, 0, 0, 0}, e[4] = {0, 0, 0, 0};
        mma16(a, ONE, 0, 0, ONE, y.x, y.y); mma16(b, ONE, 0, 0, ONE, y.z, y.w); mma8(e, ONE, 0, y4);
        float s0, s1;
        asm("{.reg .pred p1,p2,p4; .reg .f32 t0,t1,u0,u1; .reg .b32 m; and.b32 m,%12,64; setp.ne.u32 p1,m,0; and.b32 m,%12,128; setp.ne.u32 p2,m,0; and.b32 m,%12,256; setp.ne.u32 p4,m,0;"
            "selp.f32 t0,%4,%2,p1; selp.f32 t1,%5,%3,p1; selp.f32 u0,%8,%6,p1; selp.f32 u1,%9,%7,p1; selp.f32 t0,u0,t0,p2; selp.f32 t1,u1,t1,p2; selp.f32 %0,%10,t0,p4; selp.f32 %1,%11,t1,p4;}"
            : "=f"(s0), "=f"(s1) : "f"(a[0]), "f"(a[1]), "f"(a[2]), "f"(a[3]), "f"(b[0]), "f"(b[1]), "f"(b[2]), "f"(b[3]), "f"(e[0]), "f"(e[1]), "r"(k.lw));
        const int mi = __float_as_int(fmaxf(s0, s1));
        const int mp = __reduce_max_sync(0xffffffffu, mi), mn = (int)__reduce_min_sync(0xffffffffu, (unsigned)mi);
        const float mo = -__int_as_float(mp >= 0 ? mp : mn) * SC_LOG2E;
        sts32(k.pwr, pack2(ex2(fmaf(s0, SC_LOG2E, mo)), ex2(fmaf(s1, SC_LOG2E, mo))));
    }
    bar_sync(NB_P, 256);
    float i0, i1;
    {
        const uint4 pp = lds128(k.lw + R_PB);
        const uint32_t pm = lds32(((k.lw + z) >> 2) + (sb - (sb >> 2) + R_PB + 512));
        float o0[4] = {0, 0, 0, 0}, o1[4] = {0, 0, 0, 0}, o2[4] = {0, 0, 0, 0};
        mma16(o0, v0.x, v0.y, v0.z, v0.w, pp.x, pp.y);
        mma16(o1, v1.x, v1.y, v1.z, v1.w, pp.z, pp.w);
        mma8(o2, vv[0], vv[1], pm);
        asm volatile("stmatrix.sync.aligned.m8n8.x2.trans.shared.b16 [%0],{%1,%2};" ::"r"(k.lw + wz * 256 + R_OB),
                     "r"(pack2(o0[0] + o1[0] + o2[0], o0[1] + o1[1] + o2[1])), "r"(pack2(o0[2] + o1[2] + o2[2], o0[3] + o1[3] + o2[3])) : "memory");
        const uint32_t ONE = 0x3f803f80u;
        float l[4] = {0, 0, 0, 0};
        mma16(l, ONE, ONE, ONE, ONE, pp.x, pp.y); mma16(l, ONE, ONE, ONE, ONE, pp.z, pp.w); mma8(l, ONE, ONE, pm);
        i0 = rcp(l[0]); i1 = rcp(l[1]);
#pragma unroll
        for (int i = NPM; i < NPF; i++) wo[i] = lds128(k.lw + w5 + R_WO + i * 4096);
    }
    bar_sync(NB_O, 256);
    {
        const uint32_t po = k.po + z, tag = (s + 1) & 1;
        float r0[2][4] = {{0, 0, 0, 0}, {0, 0, 0, 0}}, r1[2][4] = {{0, 0, 0, 0}, {0, 0, 0, 0}};
        uint4 b[4];
#pragma unroll
        for (int i = 0; i < 4; i++) b[i] = ldsm4(k.lw + R_OB + i * 512);
        SCHED(8);
#pragma unroll
        for (int m = NWO + NPF; m < 16; m++) wo[m] = lds128(k.lw + w5 + R_WO + (m - NWO) * 4096);
#pragma unroll
        for (int i = 0; i < 4; i++) {
            mma16(r0[0], wo[4 * i].x, wo[4 * i].y, wo[4 * i].z, wo[4 * i].w, b[i].x, b[i].y);
            mma16(r1[0], wo[4 * i + 1].x, wo[4 * i + 1].y, wo[4 * i + 1].z, wo[4 * i + 1].w, b[i].x, b[i].y);
            mma16(r0[OA], wo[4 * i + 2].x, wo[4 * i + 2].y, wo[4 * i + 2].z, wo[4 * i + 2].w, b[i].z, b[i].w);
            mma16(r1[OA], wo[4 * i + 3].x, wo[4 * i + 3].y, wo[4 * i + 3].z, wo[4 * i + 3].w, b[i].z, b[i].w);
        }
#pragma unroll
        for (int i = 0; i < 4; i++) { r0[0][i] = (OA ? r0[0][i] + r0[1][i] : r0[0][i]) * ((i & 1) ? i1 : i0); r1[0][i] = (OA ? r1[0][i] + r1[1][i] : r1[0][i]) * ((i & 1) ? i1 : i0); }
        st_rlx128((uint4*)((char*)xregion(X, 0) + ((po & ~1u) ^ ((po & X) << 12))), (pack2(r0[0][0], r0[0][2]) & ~1u) | tag,
                  pack2(r1[0][0], r1[0][2]), pack2(r0[0][1], r0[0][3]), pack2(r1[0][1], r1[0][3]));
        bar_arrive(NB_PART + X, 288);
    }
}

__device__ __forceinline__ void rec_weights(const Params& p, uint32_t sb, int head, uint32_t rank, int w) {
    const int lane = threadIdx.x & 31, g = lane >> 2, c = lane & 3;
    const int t = w & 3, WG = w >> 2;
    uint32_t wq[16][4], wk[16][4];
    uint4 wo[16], wv[16];
    const uint32_t woff = sb + WG * 32768 + (((lane >> 4) << 3) + (lane & 7)) * 128 + (((2 * t + ((lane >> 3) & 1)) ^ (lane & 7)) << 4);
    const uint32_t lw = sb + lane * 16;
    PROF(threadIdx.x == 0, 3501);
    if (w >= 4 && p.dostats) { wait_cnt_warp(g_gate, lds32(sb + S_GATE)); x1_stats((head * 2 + rank) * 4 + w - 4); }
    PROF(threadIdx.x == 0, 3502);
    mbar_wait(sb + R_BAR + RB_INIT * 8, 0);
    PROF(threadIdx.x == 0, 3503);
#pragma unroll
    for (int ks = 0; ks < 16; ks++) {
        uint4 a = ldsm4t(woff + R_STQ + ks * 2048), b = ldsm4t(woff + R_STK + ks * 2048);
        wq[ks][0] = a.x; wq[ks][1] = a.y; wq[ks][2] = a.z; wq[ks][3] = a.w;
        wk[ks][0] = b.x; wk[ks][1] = b.y; wk[ks][2] = b.z; wk[ks][3] = b.w;
    }
#pragma unroll
    for (int i = 0; i < 16; i++) if ((VMASK >> i) & 1) wv[i] = ldsm4t(woff + R_WV + i * 2048);
    bar_sync(NB_W, 256);
    {
        const __nv_bfloat16* wp = p.Wo + (size_t)(head * 128 + 2 * c) * 512 + rank * 256 + w * 32 + g * 4;
#pragma unroll
        for (int ks = 0; ks < 8; ks++) {
            const uint2 r0 = *(const uint2*)(wp + (ks * 16) * 512), r1 = *(const uint2*)(wp + (ks * 16 + 1) * 512);
            const uint2 r2 = *(const uint2*)(wp + (ks * 16 + 8) * 512), r3 = *(const uint2*)(wp + (ks * 16 + 9) * 512);
            const uint4 f[2] = {make_uint4(__byte_perm(r0.x, r1.x, 0x5410), __byte_perm(r0.x, r1.x, 0x7632), __byte_perm(r2.x, r3.x, 0x5410), __byte_perm(r2.x, r3.x, 0x7632)),
                                make_uint4(__byte_perm(r0.y, r1.y, 0x5410), __byte_perm(r0.y, r1.y, 0x7632), __byte_perm(r2.y, r3.y, 0x5410), __byte_perm(r2.y, r3.y, 0x7632))};
#pragma unroll
            for (int h = 0; h < 2; h++) {
                const int m = 2 * ks + h;
                if (m >= NPF && m < NPF + NWO) wo[m] = f[h];
                else sts128(lw + w * 512 + R_WO + (m < NPF ? m : m - NWO) * 4096, f[h].x, f[h].y, f[h].z, f[h].w);
            }
        }
    }
    fence_async_smem();
    PROF(threadIdx.x == 0, 3504);
    __syncthreads();
    cluster_sync();
    PROF(threadIdx.x == 0, 3505);
    RecW k;
    {
        const int r = (w * 4 + (lane >> 3)) * 2 + rank;
        const uint32_t sl = lds32(sb + R_SEL + r * 4);
        const int slot = head * 8 + (lane & 7);
        k.po = (r * 512 + slot + (sl & 1) * 256) * 16 + (((sl >> 1) ^ sl) & 1);
    }
    k.dp = mapa(sb, rank ^ 1) - sb;
    k.lw = __shfl_sync(0xffffffffu, lw, lane);
    k.swr = __shfl_sync(0xffffffffu, sb + R_SB + (lane & 7) * 656 + (lane >> 3) * 128 + w * 16, lane);
    k.pwr = __shfl_sync(0xffffffffu, sb + R_PB + (g < 4 ? (w * 4 + c) * 16 + g * 4 : 512 + (w * 4 + c) * 4), lane);
    k.w = w;
    k.wv = __shfl_sync(0xffffffffu, woff + R_WV, lane);
    const int e0 = (p.chains & 1) ? 64 : 0, o1 = (p.chains & 2) ? p.lag : 1000, nit = (p.chains & 2) ? p.lag + 64 : 64;
    const uint32_t zero = p.zero;
#pragma unroll 1
    for (int it = 0; it < nit; it++) {
        const uint32_t g0 = sb + R_BAR + (RB_GO + (it & 1)) * 8, g1 = sb + R_BAR + (RB_GO + 2 + ((it - o1) & 1)) * 8;
        if (it < e0) {
            rec_step<0>(k, sb, it, it & zero, GATE && it > o1 ? g1 ^ 8 : 0, wq, wk, wv, wo);
            if ((!GATE || it < o1) && threadIdx.x == 0) mbar_arrive(g0);
        }
        if (it >= o1) {
            rec_step<1>(k, sb, it - o1, it & zero, GATE && it < e0 ? g0 : 0, wq, wk, wv, wo);
            if ((!GATE || it + 1 >= e0) && threadIdx.x == 0) mbar_arrive(g1);
        }
    }
}

__device__ __forceinline__ uint32_t mism(uint32_t a, uint32_t b, uint32_t t) {
    uint32_t d; asm("lop3.b32 %0,%1,%2,%3,0x7e;" : "=r"(d) : "r"(a), "r"(b), "r"(t)); return d;
}
template <bool TWO>
__device__ __forceinline__ void poll8(uint4* x, const uint4* src, uint32_t tag) {
#pragma unroll
    for (int j = 0; j < 8; j++) x[j] = ld_rlx128(src + j * 32);
    int n = 0;
    while (true) {
        uint32_t bad = 0;
#pragma unroll
        for (int j = 0; j < 8; j += 2) bad |= TWO ? mism(x[j].x, x[j].z, tag) | mism(x[j + 1].x, x[j + 1].z, tag) : mism(x[j].x, x[j + 1].x, tag);
        if (!__any_sync(0xffffffffu, bad & 1)) break;
#pragma unroll
        for (int j = 0; j < 8; j++)
            asm volatile("{.reg .pred p; .reg .b128 t; setp.ne.u32 p,%5,0; mov.b128 t,{%0,%1,%2,%3}; @p ld.relaxed.gpu.global.b128 t,[%4]; mov.b128 {%0,%1,%2,%3},t;}"
                         : "+r"(x[j].x), "+r"(x[j].y), "+r"(x[j].z), "+r"(x[j].w) : "l"(src + j * 32), "r"((TWO ? mism(x[j].x, x[j].z, tag) : x[j].x ^ tag) & 1) : "memory");
        if (++n > 2000000) __trap();
    }
}

__device__ __forceinline__ void rec_comm(const Params& p, uint32_t sb, int X, int head, uint32_t rank) {
    const int lane = threadIdx.x & 31, g = lane >> 2, c = lane & 3;
    const int me = head * 2 + rank;
    const uint32_t mb = sb + R_M + X * 4096 + lane * 16;
    uint4 x[8];
#pragma unroll
    for (int j = 0; j < 8; j++) x[j] = *(const uint4*)(p.mem0 + (lane & 7) * 512 + rank * 256 + (j * 4 + (lane >> 3)) * 8);
    const uint32_t sl = lds32(sb + R_SEL + me * 4);
    const uint4* src1 = xregion(X, me) + ((sl >> X) & 1) * 256 + c * 8 + g;
    const uint4* src2 = xregion(X, 64 + rank) + ((sl >> (2 + X)) & 1) * 256 + lane;
    uint2* mdst = (uint2*)(xregion(X, 64 + rank) + (c >> 1) * 256 + head * 8 + (g & 3) * 2 + (c & 1)) + (g >> 2);
    const uint32_t one = (g & 1) ? 0x3f800000u : 0x00003f80u, selA = (g & 2) ? 0u : one, selB = (g & 2) ? one : 0u;
    const uint32_t qb = sb + R_BAR + (RB_QK + X * 8 + lane) * 8;
    if (lane < 8) mbar_expect(qb, 768);
    mbar_wait(sb + R_BAR + (RB_XFULL + X * 2) * 8, 0);
#pragma unroll 1
    for (int s = 0;; s++) {
#pragma unroll
        for (int j = 0; j < 8; j++) sts128(mb + j * 512, x[j].x, x[j].y, x[j].z, x[j].w);
        bar_arrive(NB_MFULL + X, 288);
        PROF(lane == 0, X * 64 + s);
        bar_sync(NB_PART + X, 288);
        if (s == 63) break;
        const uint32_t tag = (s + 1) & 1;
        if (lane < 8) mbar_expect(qb, 768);
        spin(D1 + (lds32(sb + R_SEL) >> 20));
        poll8<false>(x, src1, tag);
        float a[4][4];
#pragma unroll
        for (int j = 0; j < 4; j++) {
            a[j][0] = a[j][1] = a[j][2] = a[j][3] = 0;
            mma16(a[j], x[j].x, x[j].y, x[j].z, x[j].w, selA, selB);
        }
#pragma unroll
        for (int j = 0; j < 4; j++) mma16(a[j], x[j + 4].x, x[j + 4].y, x[j + 4].z, x[j + 4].w, selA, selB);
#pragma unroll
        for (int i = 0; i < 4; i++) a[0][i] = (a[0][i] + a[1][i]) + (a[2][i] + a[3][i]);
        asm volatile("st.relaxed.gpu.global.b64 [%0],%1;" ::"l"(mdst), "l"(((uint64_t)pack2(a[0][2], a[0][3]) << 32) | ((pack2(a[0][0], a[0][1]) & ~1u) | tag)) : "memory");
        const uint32_t t2 = clk32();
        mbar_wait(sb + R_BAR + (RB_XFULL + X * 2 + tag) * 8, ((s + 1) >> 1) & 1);
        while (clk32() - t2 < D2) {}
        poll8<true>(x, src2, tag);
    }
}

template <int MT>
__device__ __forceinline__ void xattn(uint32_t l16, uint32_t l8, uint32_t os, int g, int c) {
    constexpr int NT = 3 + 2 * MT;
    float S[NT][4];
#pragma unroll
    for (int i = 0; i < NT; i++) S[i][0] = S[i][1] = S[i][2] = S[i][3] = 0;
#pragma unroll 2
    for (int ks = 0; ks < 8; ks++) {
        const uint4 q = lds128(l16 + SL_Q + ks * 512);
        const uint2 u = lds64(l8 + SL_KM + ks * 256);
        mma16(S[0], q.x, q.y, q.z, q.w, u.x, u.y);
#pragma unroll
        for (int m = 0; m <= MT; m++) {
            const uint4 kk = lds128(l16 + m * 4096 + ks * 512);
            mma16(S[1 + 2 * m], q.x, q.y, q.z, q.w, kk.x, kk.z); mma16(S[2 + 2 * m], q.x, q.y, q.z, q.w, kk.y, kk.w);
        }
    }
    const float NEG = -__int_as_float(0x7f800000);
    if (2 * c > g) { S[NT - 2][0] = NEG; S[NT - 1][2] = NEG; }
    if (2 * c + 1 > g) { S[NT - 2][1] = NEG; S[NT - 1][3] = NEG; }
    S[NT - 1][0] = S[NT - 1][1] = NEG;
    float m0 = fmaxf(S[0][0], S[0][1]), m1 = fmaxf(S[0][2], S[0][3]);
#pragma unroll
    for (int i = 1; i < NT; i++) { if (i < NT - 1) m0 = fmaxf(m0, fmaxf(S[i][0], S[i][1])); m1 = fmaxf(m1, fmaxf(S[i][2], S[i][3])); }
    m0 = fmaxf(m0, __shfl_xor_sync(0xffffffffu, m0, 1)); m1 = fmaxf(m1, __shfl_xor_sync(0xffffffffu, m1, 1));
    m0 = fmaxf(m0, __shfl_xor_sync(0xffffffffu, m0, 2)); m1 = fmaxf(m1, __shfl_xor_sync(0xffffffffu, m1, 2));
    m0 *= -SC_LOG2E; m1 *= -SC_LOG2E;
    float l0 = 0, l1 = 0;
#pragma unroll
    for (int i = 0; i < NT; i++) {
        if (i < NT - 1) { S[i][0] = ex2(fmaf(S[i][0], SC_LOG2E, m0)); S[i][1] = ex2(fmaf(S[i][1], SC_LOG2E, m0)); l0 += S[i][0] + S[i][1]; }
        S[i][2] = ex2(fmaf(S[i][2], SC_LOG2E, m1)); S[i][3] = ex2(fmaf(S[i][3], SC_LOG2E, m1)); l1 += S[i][2] + S[i][3];
    }
    l0 += __shfl_xor_sync(0xffffffffu, l0, 1); l1 += __shfl_xor_sync(0xffffffffu, l1, 1);
    l0 += __shfl_xor_sync(0xffffffffu, l0, 2); l1 += __shfl_xor_sync(0xffffffffu, l1, 2);
    l0 = rcp(l0); l1 = rcp(l1);
    uint32_t P[NT][2];
#pragma unroll
    for (int i = 0; i < NT; i++) { P[i][0] = i < NT - 1 ? pack2(S[i][0] * l0, S[i][1] * l0) : 0u; P[i][1] = pack2(S[i][2] * l1, S[i][3] * l1); }
#pragma unroll 2
    for (int et = 0; et < 8; et++) {
        float a[4] = {0, 0, 0, 0}, b[4] = {0, 0, 0, 0};
        const uint2 vm = lds64(l8 + SL_VM + et * 256);
        mma8(a, vm.x, vm.y, P[0][0]); mma8(b, vm.x, vm.y, P[0][1]);
#pragma unroll
        for (int m = 0; m <= MT; m++) {
            const uint4 v = lds128(l16 + SL_V + m * 4096 + et * 512);
            mma16(a, v.x, v.y, v.z, v.w, P[1 + 2 * m][0], P[2 + 2 * m][0]); mma16(b, v.x, v.y, v.z, v.w, P[1 + 2 * m][1], P[2 + 2 * m][1]);
        }
        asm volatile("stmatrix.sync.aligned.m8n8.x4.trans.shared.b16 [%0],{%1,%2,%3,%4};" ::"r"(os + (et >> 2) * 2048 + (et & 3) * 256),
                     "r"(pack2(a[0], a[1])), "r"(pack2(a[2], a[3])), "r"(pack2(b[0], b[1])), "r"(pack2(b[2], b[3])) : "memory");
    }
}

__device__ __forceinline__ void rec_tiles(uint32_t sb, int X, int head, uint32_t rank, int& nxt, int lim, int need) {
#pragma unroll 1
    while (nxt <= lim) {
        if ((nxt & 3) == 0) {
            unsigned v; int n = 0;
            while (true) {
                asm volatile("ld.relaxed.gpu.global.u32 %0,[%1];" : "=r"(v) : "l"(cnt_ptr(C_QKV0 + X, nxt >> 2)) : "memory");
                if (__all_sync(0xffffffffu, v >= 384)) break;
                if (nxt > need) return;
                if (++n > 3000000) __trap();
            }
        }
        if ((threadIdx.x & 31) == 0) {
            const uint32_t bar = sb + R_BAR + (RB_XFULL + X * 2 + (nxt & 1)) * 8, dst = sb + R_SL + (X * 2 + (nxt & 1)) * SLOT;
            const uint4* src = g_qkv[X] + (size_t)(nxt * 32 + head) * 1536;
            mbar_expect(bar, 20480);
            bulk_g2s_mc(dst + rank * 8192, src + 512 + rank * 512, 8192, bar, POL_LAST);
            bulk_g2s(dst + SL_Q, src + (rank ^ X) * 256, 4096, bar, POL_LAST);
        }
        __syncwarp();
        nxt++;
    }
}

__device__ __forceinline__ void rec_attn(const Params& p, uint32_t sb, int X, int head, uint32_t rank) {
    const int lane = threadIdx.x & 31, g = lane >> 2, c = lane & 3;
    const int mt = rank ^ X;
    const uint32_t dp = mapa(sb, rank ^ 1) - sb;
    int nxt = 0;
    rec_tiles(sb, X, head, rank, nxt, 1, 0);
#pragma unroll 1
    for (int s = 0; s < 64; s++) {
        const uint32_t so = sb + R_SL + (X * 2 + (s & 1)) * SLOT;
        mbar_wait(sb + R_BAR + (RB_GO + X * 2 + (s & 1)) * 8, (s >> 1) & 1);
        rec_tiles(sb, X, head, rank, nxt, min(s + 1, 63), -1);
        spin(DX);
        mbar_wait(sb + R_BAR + (RB_XFULL + X * 2 + (s & 1)) * 8, (s >> 1) & 1);
        if (lane == 0) asm volatile("cp.async.bulk.wait_group.read 0;" ::: "memory");
        __syncwarp();
        const uint32_t os = sb + R_OS + X * 4096 + (lane >> 4) * 1024 + (lane & 15) * 16;
        if (mt) xattn<1>(so + lane * 16, so + lane * 8, os, g, c); else xattn<0>(so + lane * 16, so + lane * 8, os, g, c);
        fence_async_smem();
        __syncwarp();
        const uint32_t svb = sb + R_BAR + (RB_SV + X * 2 + (s & 1)) * 8;
        if (lane == 0) {
            mbar_arrive(svb); mbar_arrive_cluster(svb + dp);
            const uint64_t pol = (X && s < 40) ? POL_LATE : POL_SOON;
#pragma unroll
            for (int kb = 0; kb < 2; kb++)
                asm volatile("cp.async.bulk.global.shared::cta.bulk_group.L2::cache_hint [%0],[%1],%2,%3;" ::"l"(g_o[X] + ((s >> 2) * 64 + head * 2 + kb) * 1024 + ((s & 3) * 4 + mt * 2) * 64),
                             "r"(sb + R_OS + X * 4096 + kb * 2048), "r"(2048), "l"(pol) : "memory");
            asm volatile("cp.async.bulk.commit_group;" ::: "memory");
            if ((s & 3) == 3) { asm volatile("cp.async.bulk.wait_group 0;" ::: "memory"); red_release(cnt_ptr(C_O0 + X, s >> 2), 8); }
        }
        __syncwarp();
        rec_tiles(sb, X, head, rank, nxt, min(s + 1, 63), s + 1);
        mbar_wait(svb, (s >> 1) & 1);
        rec_tiles(sb, X, head, rank, nxt, min(s + 2, 63), -1);
    }
}

__device__ __forceinline__ uint32_t probe1(unsigned* r, int lane) {
    uint32_t v = 0;
    const uint32_t t0 = clk32();
    asm volatile("{.reg .pred p; setp.eq.u32 p,%2,0; @p atom.relaxed.gpu.global.or.b32 %0,[%1],0;}" : "+r"(v) : "l"(r), "r"(lane) : "memory");
    v = __shfl_sync(0xffffffffu, v, 0);
    asm volatile("{.reg .pred p; setp.eq.u32 p,%0,0x5a5a5a5b; @p nanosleep.u32 1;}" ::"r"(v) : "memory");
    return clk32() - t0;
}
__device__ __forceinline__ void rec_probe(uint32_t sb, int me, int w) {
    const int lane = threadIdx.x & 31;
    unsigned* r = (unsigned*)xregion(w & 1, (w & 2) ? 64 + (me & 1) : me) + ((w & 2) ? (me >> 1) * 32 : 0);
    uint32_t b0 = ~0u, b1 = ~0u;
#pragma unroll 1
    for (int i = 0; i < 5; i++) { b0 = min(b0, probe1(r, lane)); b1 = min(b1, probe1(r + 1024, lane)); }
    sts32(sb + R_BAR + 480 + w * 4, b1 < b0);
}
__device__ __forceinline__ void rec_sides(uint32_t sb, int me, int w) {
    const int lane = threadIdx.x & 31;
    if (lane == 0) asm volatile("red.relaxed.gpu.global.add.u32 [%0],%1;" ::"l"(g_sel + me), "r"((lds32(sb + R_BAR + 480 + w * 4) << w) + 256u) : "memory");
    __syncwarp();
    if (w < 2) {
        unsigned v; int n = 0;
        while (true) {
            asm volatile("ld.relaxed.gpu.global.u32 %0,[%1];" : "=r"(v) : "l"(g_sel + w * 32 + lane) : "memory");
            if (__all_sync(0xffffffffu, v >= 1024)) break;
            if (++n > 2000000) __trap();
        }
        sts32(sb + R_SEL + (w * 32 + lane) * 4, v);
    }
}

__device__ __forceinline__ void rec_init(const Params& p, uint32_t sb, int head, uint32_t rank) {
    const uint32_t b = sb + R_BAR;
    const int i = threadIdx.x & 31;
    mbar_init(b + i * 8, i >= RB_SV ? 2 : 1);
    if (i == RB_INIT) mbar_expect(b + RB_INIT * 8, 196608);
    asm volatile("fence.mbarrier_init.release.cluster;" ::: "memory");
}
__device__ __forceinline__ void rec_fetch(const Params& p, uint32_t sb, int head, uint32_t rank, int which, int dst) {
#pragma unroll 1
    for (int j = 0; j < 8; j++) tma2d(sb + dst + j * 8192, &p.tm[which], head * 128 + (j >> 2) * 64, rank * 256 + (j & 3) * 64, sb + R_BAR + RB_INIT * 8);
}

constexpr int NSTG = 4, STG_B = 49152;
constexpr int NSB = 7;
constexpr int B_OUT = NSTG * STG_B  , B_UT = B_OUT, B_YT = B_UT + 8192  ,
              B_ST = B_OUT + 8 * NSB * 512  , B_BAR = 231936;
static_assert(B_ST + 4096 <= B_BAR && B_YT + 10240 <= B_ST, "smem map");
enum { BB_FULL = 0, BB_EMPTY = 4, BB_STF = 8  , BB_STE = 10  , BB_SF = 12  , BB_DONE = 13  , BB_N = 15 };
enum { NB_C = 11, NB_WG = 12   };

__device__ __forceinline__ void bulk_init(uint32_t sb) {
    const int i = threadIdx.x - 320;
    if (i >= 0 && i < BB_N) {
        mbar_init(sb + B_BAR + i * 8, (i >= BB_EMPTY && i < BB_EMPTY + 4) ? 4 : (i >= BB_STF && i < BB_STF + 2) ? 2 : i >= BB_DONE ? 8 : 1);
        asm volatile("fence.mbarrier_init.release.cluster;" ::: "memory");
    }
}

__device__ __forceinline__ void bulk_producer(const Params& p, uint32_t sb, int cl, uint32_t rank) {
    if (threadIdx.x != 256) return;
    int st = 0; uint32_t ph = 1;
    bool gated = false;
#pragma unroll 1
    for (int ti = 0; ti < MAXT; ti++) {
        const uint32_t tk = p.task[cl][ti];
        const int type = tk & 7, layer = (tk >> 3) & 1, ch = (tk >> 4) & 15, a = (tk >> 8) & 255, b = (tk >> 16) & 255;
        if (type == T_END) break;
        if (type == T_QKV || type == T_OP) {
            const bool qkv = type == T_QKV, first = qkv && !layer;
            const uint4* A = (qkv ? g_xA[layer] + ch * 8192 : g_o[layer] + (ch * 64 + a) * 1024) + rank * 512;
            const int nkb = qkv ? 8 : b, blk = (qkv ? a : 192) + rank * 4, row = qkv ? 0 : a * 64;
            const unsigned* dep = first ? g_gate : cnt_ptr(qkv ? C_CV : C_O0 + layer, ch);
            const unsigned need = first ? lds32(sb + S_GATE) : qkv ? 16 : 512;
            int pend = 0;
            if (!(tk >> 31) && !(first && gated)) {
                unsigned v;
                asm volatile("ld.relaxed.gpu.global.u32 %0,[%1];" : "=r"(v) : "l"(dep) : "memory");
                if (v < need) pend = first ? 2 : NSTG;
                gated = true;
            }
#pragma unroll 1
            for (int kb = 0; kb < nkb; kb++) {
                mbar_wait(sb + B_BAR + (BB_EMPTY + st) * 8, ph);
                mbar_expect(sb + B_BAR + (BB_FULL + st) * 8, STG_B);
                tma3d(sb + st * STG_B + 16384, &p.t3[blk >> 6], row + kb * 64, blk & 63, sb + B_BAR + (BB_FULL + st) * 8);
                int k = kb;
                if (kb == pend - 1) { wait_cnt(dep, need); k = 0; }
                if (kb >= pend - 1) {
#pragma unroll 1
                    for (; k <= kb; k++) {
                        const int s2 = (st + k - kb) & (NSTG - 1);
                        bulk_g2s_mc(sb + s2 * STG_B + rank * 8192, A + k * 1024, 8192, sb + B_BAR + (BB_FULL + s2) * 8, qkv ? POL_N : POL_LAST);
                    }
                }
                if (++st == NSTG) { st = 0; ph ^= 1; }
            }
        } else if (type == T_CV) {
            const int q = a + rank, jhi = layer ? b : min(ch, 1), jlo = layer ? (tk >> 24) & 127 : 0;
            if (jhi && !(tk >> 31)) wait_cnt(cnt_ptr(C_CV, ch - (layer ? jlo : 1)), 16);
            if (!layer && ch) {
                const int n = min(ch, 3);
                const uint32_t full = sb + B_BAR + (BB_FULL + st) * 8;
                mbar_wait(sb + B_BAR + (BB_EMPTY + st) * 8, ph);
                mbar_expect(full, n * 16384);
#pragma unroll 1
                for (int i = 0; i < n; i++) {
                    if (i && !(tk >> 31)) wait_cnt(cnt_ptr(C_H, ch - (i != 1)), ch - (i != 1) >= HSPLIT ? 32 : 16);
                    bulk_g2s(sb + st * STG_B + i * 16384, g_carry[i] + ((ch - (i != 1)) * 16 + q) * 1024, 16384, full, POL_LAST);
                }
                if (++st == NSTG) { st = 0; ph ^= 1; }
            }
#pragma unroll 1
            for (int j = jhi; j >= jlo; j--) {
                const uint32_t full = sb + B_BAR + (BB_FULL + st) * 8, dst = sb + st * STG_B;
                mbar_wait(sb + B_BAR + (BB_EMPTY + st) * 8, ph);
                mbar_expect(full, 32 * PW * 4 + (j ? 8192 : 0));
                bulk_g2s(dst, g_P + (q * 16 + j) * 32 * PW, 32 * PW * 4, full, POL_N);
                if (j) bulk_g2s(dst + 20480, g_u + (q * 16 + ch - j) * 512, 8192, full, POL_N);
                if (++st == NSTG) { st = 0; ph ^= 1; }
            }
        }
    }
}

__device__ __forceinline__ void bulk_stats(const Params& p, uint32_t sb, int cl, uint32_t rank) {
    const int r0 = threadIdx.x - 288;
    int n = 0;
    bool gated = false;
    for (int ti = 0; ti < MAXT; ti++) {
        const uint32_t tk = p.task[cl][ti];
        const int type = tk & 7, layer = (tk >> 3) & 1, ch = (tk >> 4) & 15;
        if (type == T_END) break;
        if (type != T_QKV) continue;
        if (!(tk >> 31)) {
            if (!gated) { wait_cnt_warp(g_gate, lds32(sb + S_GATE)); gated = true; }
            wait_cnt_warp(cnt_ptr(layer ? C_CV : C_ST, ch), 16);
        }
        const int np = p.nst[layer];
        const float n0 = 512.f / np, in0 = np * (1.f / 512.f);
        mbar_wait(sb + B_BAR + (BB_STE + (n & 1)) * 8, ((n >> 1) & 1) ^ 1);
        {
            const int nb = (tk >> 16) & 255;
            if (r0 < nb * 16) {
                const float4* cp = (const float4*)g_cs + (((tk >> 8) & 255) + rank * nb) * 16 + r0;
                const float4 cs = __ldcg(cp), ct = __ldcg(cp + 3072);
                sts128(sb + B_ST + (n & 1) * 2048 + 1024 + r0 * 16, __float_as_uint(cs.x + ct.x), __float_as_uint(cs.y + ct.y), __float_as_uint(cs.z + ct.z), __float_as_uint(cs.w + ct.w));
            }
        }
        const float4* src = (const float4*)(g_st[layer] + ch * 128) + r0;
        const float4 f = __ldcg(src);
        const float m0 = f.x * in0, m1 = f.z * in0;
        float sd0 = 0, sq0 = 0, M0 = f.y, sd1 = 0, sq1 = 0, M1 = f.w;
#pragma unroll 5
        for (int i = 1; i < np; i++) {
            const float4 v = __ldcg(src + i * 1024);
            const float d0 = v.x * in0 - m0, d1 = v.z * in0 - m1;
            sd0 += d0; sq0 += d0 * d0; M0 += v.y; sd1 += d1; sq1 += d1 * d1; M1 += v.w;
        }
        const float b0 = sd0 / np, b1 = sd1 / np;
        const float2 o0 = ln_finish(m0 + b0, (M0 + fmaxf(n0 * (sq0 - np * b0 * b0), 0.f)) * (1.f / 512.f));
        const float2 o1 = ln_finish(m1 + b1, (M1 + fmaxf(n0 * (sq1 - np * b1 * b1), 0.f)) * (1.f / 512.f));
        sts128(sb + B_ST + (n & 1) * 2048 + r0 * 16, __float_as_uint(o0.x), __float_as_uint(1.f / o0.y), __float_as_uint(o1.x), __float_as_uint(1.f / o1.y));
        __syncwarp();
        if ((r0 & 31) == 0) mbar_arrive(sb + B_BAR + (BB_STF + (n & 1)) * 8);
        n++;
    }
}

__device__ __forceinline__ uint4* qkv_dst(int layer, int ch, int w, int blk);
__device__ __forceinline__ uint4* op_dst(int layer, int ch, int slot, int w, uint32_t rank);
__device__ __forceinline__ uint64_t out_pol(int type, int layer, int ch) { return (type == T_QKV ? (!layer && ch > 1) : (layer && ch < 10)) ? POL_LATE : POL_SOON; }
__device__ __forceinline__ void bulk_release(const Params& p, uint32_t sb, int cl, uint32_t rank) {
    if ((threadIdx.x & 31) != 0) return;
    int nd = 0, nq = 0;
    for (int ti = 0; ti < MAXT; ti++) {
        const uint32_t tk = p.task[cl][ti];
        const int type = tk & 7, layer = (tk >> 3) & 1, ch = (tk >> 4) & 15, a = (tk >> 8) & 255, b = (tk >> 16) & 255;
        if (type == T_END) break;
        if (type == T_FIN) continue;
        mbar_wait(sb + B_BAR + (BB_DONE + (nd & 1)) * 8, (nd >> 1) & 1);
        nd++;
        if (type == T_QKV) { mbar_arrive(sb + B_BAR + (BB_STE + (nq & 1)) * 8); nq++; }
        if (type != T_CV) {
#pragma unroll 1
            for (int w = 0; w < 8; w++) {
                const uint4* dst = type == T_QKV ? qkv_dst(layer, ch, w, a + rank * 4 + 2) + (8 - NSB) * 32 : op_dst(layer, ch, (tk >> 24) & 127, w, rank) + (16 - NSB) * 32;
                asm volatile("cp.async.bulk.global.shared::cta.bulk_group.L2::cache_hint [%0],[%1],%2,%3;" ::"l"(dst), "r"(sb + B_OUT + w * NSB * 512), "r"(NSB * 512), "l"(out_pol(type, layer, ch)) : "memory");
            }
            asm volatile("cp.async.bulk.commit_group;" ::: "memory");
            asm volatile("cp.async.bulk.wait_group 0;" ::: "memory");
        }
        mbar_arrive(sb + B_BAR + BB_SF * 8);
        if (!(tk >> 31)) red_release(cnt_ptr(type == T_QKV ? C_QKV0 + layer : type == T_OP ? C_OP0 + layer : layer ? C_H : C_CV, ch), type == T_CV ? 1 : 2 * b);
        PROF(true, 3600 + ti * 4 + 3);
    }
}

template <int NB>
__device__ __forceinline__ void gemm_main(float* acc, uint32_t sb, uint32_t peer, int nkb, int& st, uint32_t& ph) {
    const int wg = threadIdx.x >> 7;
    const bool el = (threadIdx.x & 127) == 0;
    int prev = -1;
#pragma unroll
    for (int i = 0; i < NB * 32; i++) acc[i] = 0.f;
#pragma unroll 1
    for (int kb = 0; kb < nkb; kb++) {
        mbar_wait(sb + B_BAR + (BB_FULL + st) * 8, ph);
        const uint64_t da = mkdesc(sb + st * STG_B + wg * 8192, 128, 1024, 0), db = mkdesc(sb + st * STG_B + 16384, 8192, 1024, 1);
        wg_fence();
#pragma unroll
        for (int kk = 0; kk < 4; kk++) {
            if (NB == 4) wgmma256(acc, da + kk * 16, db + kk * 128, kb | kk);
            else wgmma192(acc, da + kk * 16, db + kk * 128, kb | kk);
        }
        wg_commit();
        wg_wait<1>();
        if (prev >= 0) {
            if (el) { mbar_arrive_cluster(mapa(sb + B_BAR + (BB_EMPTY + prev) * 8, 0)); mbar_arrive_cluster(mapa(sb + B_BAR + (BB_EMPTY + prev) * 8, 1)); }
        }
        prev = st;
        if (++st == NSTG) { st = 0; ph ^= 1; }
    }
    wg_wait<0>();
    if (el) { mbar_arrive_cluster(mapa(sb + B_BAR + (BB_EMPTY + prev) * 8, 0)); mbar_arrive_cluster(mapa(sb + B_BAR + (BB_EMPTY + prev) * 8, 1)); }
}

__device__ __forceinline__ uint4* qkv_dst(int layer, int ch, int w, int blk) {
    return g_qkv[layer] + (size_t)((ch * 4 + (w >> 1)) * 32 + ((blk & 63) >> 1)) * 1536 + (blk >> 6) * 512 + (w & 1) * 256;
}
__device__ __forceinline__ uint4* op_dst(int layer, int ch, int slot, int w, uint32_t rank) {
    return g_pp[layer] + (size_t)(ch * MAXSPLIT + slot) * 8192 + (w * 32 + rank * 16) * 32;
}
template <bool VT>
__device__ __forceinline__ void qkv_epilogue(const float* acc, uint32_t sb, int layer, int ch, int blk0, int n, int nd) {
    const int lane = threadIdx.x & 31, w = threadIdx.x >> 5, g = lane >> 2, c = lane & 3;
    mbar_wait(sb + B_BAR + (BB_STF + (n & 1)) * 8, (n >> 1) & 1);
    mbar_wait(sb + B_BAR + BB_SF * 8, (nd & 1) ^ 1);
    const uint32_t stb = sb + B_ST + (n & 1) * 2048;
    const uint2 s0 = lds64(stb + (w * 16 + g) * 8), s1 = lds64(stb + (w * 16 + g + 8) * 8);
    const float mu0 = -__uint_as_float(s0.x), r0 = __uint_as_float(s0.y), mu1 = -__uint_as_float(s1.x), r1 = __uint_as_float(s1.y);
    uint32_t dep = 0; asm volatile("" : "+r"(dep)::"memory");
    uint4* dst = qkv_dst(layer, ch, w, blk0) + lane;
    const uint64_t pol = out_pol(T_QKV, layer, ch);
#pragma unroll
    for (int j = 0; j < 16; j++) {
        const float* a = acc + j * 8;
        float2 ca, cb;
        asm("ld.shared.v2.f32 {%0,%1},[%2];" : "=f"(ca.x), "=f"(ca.y) : "r"(stb + 1024 + (j * 16 + 2 * c) * 4 + dep));
        asm("ld.shared.v2.f32 {%0,%1},[%2];" : "=f"(cb.x), "=f"(cb.y) : "r"(stb + 1024 + (j * 16 + 8 + 2 * c) * 4 + dep));
        uint4 v;
        v.x = pack2(fmaf(mu0, ca.x, a[0]) * r0, fmaf(mu0, ca.y, a[1]) * r0);
        v.y = pack2(fmaf(mu1, ca.x, a[2]) * r1, fmaf(mu1, ca.y, a[3]) * r1);
        v.z = pack2(fmaf(mu0, cb.x, a[4]) * r0, fmaf(mu0, cb.y, a[5]) * r0);
        v.w = pack2(fmaf(mu1, cb.x, a[6]) * r1, fmaf(mu1, cb.y, a[7]) * r1);
        if (VT) v = make_uint4(movm(v.x), movm(v.z), movm(v.y), movm(v.w));
        if (j < 16 - NSB) stg128(dst + (j >> 3) * 1536 + (j & 7) * 32, v, pol);
        else asm volatile("st.shared.v4.u32 [%0],{%1,%2,%3,%4};" ::"r"(sb + B_OUT + (w * NSB + j - (16 - NSB)) * 512 + lane * 16), "r"(v.x), "r"(v.y), "r"(v.z), "r"(v.w));
    }
    fence_async_smem();
}

template <int NB>
__device__ __forceinline__ void load_resid(uint32_t* r, int layer, int ch, int w, int cb) {
    const uint32_t* rp = (const uint32_t*)(g_xA[layer] + (ch * 8 + (cb >> 2)) * 1024 + w * 128 + (cb & 3) * 16) + (threadIdx.x & 31);
#pragma unroll
    for (int i = 0; i < NB * 4; i++) r[i] = __ldcg(rp + (i >> 1) * 32 + (i & 1) * 256);
}
template <int NB, int NS>
__device__ __forceinline__ void sum_partials(float* x, const uint32_t* r, int layer, int ch, int w, int cb, int ns) {
    const uint4* src = g_pp[layer] + (size_t)ch * MAXSPLIT * 8192 + (w * 32 + cb) * 32 + (threadIdx.x & 31);
    const int dg = ((threadIdx.x & 31) >> 2) - 2 * (threadIdx.x & 3);
    const uint32_t idm = dg == 0 ? 0x00003f80u : dg == 1 ? 0x3f800000u : 0u;
    uint4 v[NB][NS];
#pragma unroll
    for (int b = 0; b < NB; b++)
#pragma unroll
        for (int s = 0; s < NS; s++) { v[b][s] = make_uint4(0, 0, 0, 0); if (s < ns) v[b][s] = ldcg128_last(src + b * 32 + s * 8192); }
#pragma unroll
    for (int b = 0; b < NB; b++) {
        float* y = x + b * 8;
#pragma unroll
        for (int i = 0; i < 8; i++) y[i] = 0;
#pragma unroll
        for (int s = 0; s < NS; s++) { mma8(y, v[b][s].x, v[b][s].y, idm); mma8(y + 4, v[b][s].z, v[b][s].w, idm); }
#pragma unroll
        for (int i = 0; i < 4; i++) { y[2 * i] = rbf(rbf(y[2 * i]) + blo(r[b * 4 + i])); y[2 * i + 1] = rbf(rbf(y[2 * i + 1]) + bhi(r[b * 4 + i])); }
    }
}

__device__ __forceinline__ float4 row_stats32(const float* x) {
    float a = (x[0] + x[1]) + (x[4] + x[5]) + (x[8] + x[9]) + (x[12] + x[13]);
    float b = (x[2] + x[3]) + (x[6] + x[7]) + (x[10] + x[11]) + (x[14] + x[15]);
    a += __shfl_xor_sync(0xffffffffu, a, 1); b += __shfl_xor_sync(0xffffffffu, b, 1);
    a += __shfl_xor_sync(0xffffffffu, a, 2); b += __shfl_xor_sync(0xffffffffu, b, 2);
    const float ma = a * (1.f / 32.f), mb = b * (1.f / 32.f);
    float qa = 0, qb = 0;
#pragma unroll
    for (int i = 0; i < 4; i++) {
        float d0 = x[4 * i] - ma, d1 = x[4 * i + 1] - ma, d2 = x[4 * i + 2] - mb, d3 = x[4 * i + 3] - mb;
        qa += d0 * d0 + d1 * d1; qb += d2 * d2 + d3 * d3;
    }
    qa += __shfl_xor_sync(0xffffffffu, qa, 1); qb += __shfl_xor_sync(0xffffffffu, qb, 1);
    qa += __shfl_xor_sync(0xffffffffu, qa, 2); qb += __shfl_xor_sync(0xffffffffu, qb, 2);
    return make_float4(a, qa, b, qb);
}

__device__ __forceinline__ void conv_stage(float* Y, uint32_t pbase, uint32_t ubase) {
    const int lane = threadIdx.x & 31, w = threadIdx.x >> 5, g = lane >> 2, c = lane & 3;
#pragma unroll
    for (int cp = 0; cp < 2; cp++) {
        const int chl = w * 4 + cp * 2 + (lane >> 4);
        const uint4 b = ldsm4(ubase + chl * 256 + ((lane >> 3) & 1) * 128 + (((lane & 7) ^ (chl & 7)) << 4));
#pragma unroll
        for (int h = 0; h < 2; h++) {
            const uint32_t pa = pbase + ((w * 4 + cp * 2 + h) * PW + 16 + g - 2 * c) * 4;
            uint32_t lo = lds32(pa - 32);
#pragma unroll
            for (int d = 0; d < 8; d++) {
                const uint32_t a0 = lds32(pa + d * 64), a1 = lds32(pa + d * 64 + 32);
                mma16(Y + ((cp * 2 + h) * 8 + d) * 4, a0, a1, lo, a0, h ? b.z : b.x, h ? b.w : b.y);
                lo = a1;
            }
        }
    }
}

__device__ __forceinline__ void conv_combine(const float* y8, float* cur, float* nxt) {
    const int lane = threadIdx.x & 31, c = lane & 3;
    cur[0] = y8[0]; cur[1] = y8[1] + y8[4]; cur[2] = y8[2]; cur[3] = y8[3] + y8[6];
    nxt[0] = y8[29]; nxt[1] = 0.f; nxt[2] = y8[31]; nxt[3] = 0.f;
#pragma unroll
    for (int e = 1; e < 4; e++) {
        const int src = (lane & ~3) | ((c - e) & 3);
        const float v0 = __shfl_sync(0xffffffffu, y8[8 * e] + y8[8 * e - 3], src), v1 = __shfl_sync(0xffffffffu, y8[8 * e + 1] + y8[8 * e + 4], src);
        const float v2 = __shfl_sync(0xffffffffu, y8[8 * e + 2] + y8[8 * e - 1], src), v3 = __shfl_sync(0xffffffffu, y8[8 * e + 3] + y8[8 * e + 6], src);
        if (c >= e) { cur[0] += v0; cur[1] += v1; cur[2] += v2; cur[3] += v3; }
        else { nxt[0] += v0; nxt[1] += v1; nxt[2] += v2; nxt[3] += v3; }
    }
}

__device__ __forceinline__ void conv_task(const Params& p, float* Y, uint32_t sb, int ch, int q, bool hist, int hhi, int hlo, bool dry, int& st, uint32_t& ph, int nd) {
    const int tid = threadIdx.x, lane = tid & 31, w = tid >> 5, g = lane >> 2, c = lane & 3;
    const bool el = (tid & 127) == 0;
#pragma unroll
    for (int i = 0; i < 128; i++) Y[i] = 0;
    const int jhi = hist ? hhi : min(ch, 1), jlo = hist ? hlo : 1;
    uint32_t rs[8], dk[4];
    if (!hist) {
        load_resid<2>(rs, 0, ch, w, 2 * q);
#pragma unroll
        for (int i = 0; i < 4; i++) dk[i] = __ldg((const uint32_t*)(p.Dskip + q * 32 + i * 8 + 2 * c));
        if (ch) {
            mbar_wait(sb + B_BAR + (BB_FULL + st) * 8, ph);
#pragma unroll 1
            for (int i = 0; i < 3 && i < ch; i++) {
#pragma unroll
                for (int k = 0; k < 4; k++) {
                    const uint4 cr = lds128(sb + st * STG_B + i * 16384 + k * 4096 + tid * 16);
                    Y[k * 32] += __uint_as_float(cr.x); Y[k * 32 + 1] += __uint_as_float(cr.y); Y[k * 32 + 2] += __uint_as_float(cr.z); Y[k * 32 + 3] += __uint_as_float(cr.w);
                }
            }
            bar_sync(NB_WG + (w >> 2), 128);
            if (el) { mbar_arrive_cluster(mapa(sb + B_BAR + (BB_EMPTY + st) * 8, 0)); mbar_arrive_cluster(mapa(sb + B_BAR + (BB_EMPTY + st) * 8, 1)); }
            if (++st == NSTG) { st = 0; ph ^= 1; }
        }
    }
    for (int j = jhi; j >= jlo; j--) {
        mbar_wait(sb + B_BAR + (BB_FULL + st) * 8, ph);
        conv_stage(Y, sb + st * STG_B, sb + st * STG_B + 20480);
        bar_sync(NB_WG + (w >> 2), 128);
        if (el) { mbar_arrive_cluster(mapa(sb + B_BAR + (BB_EMPTY + st) * 8, 0)); mbar_arrive_cluster(mapa(sb + B_BAR + (BB_EMPTY + st) * 8, 1)); }
        if (++st == NSTG) { st = 0; ph ^= 1; }
    }
    mbar_wait(sb + B_BAR + BB_SF * 8, (nd & 1) ^ 1);
    if (hist) {
        if (jhi < ch) wait_cnt_warp(cnt_ptr(C_H, ch), 16);
#pragma unroll
        for (int k = 0; k < 4; k++) {
            float4* d1 = g_carry[1] + ((ch * 16 + q) * 4 + k) * 256 + tid;
            float4* d2 = g_carry[2] + ((ch * 16 + q) * 4 + k) * 256 + tid;
            float4 o1 = make_float4(0, 0, 0, 0), o2 = o1;
            if (jhi < ch) { o1 = __ldcg(d1); o2 = __ldcg(d2); }
            float cur[4], nxt[4];
            conv_combine(Y + k * 32, cur, nxt);
            *d1 = make_float4(cur[0] + o1.x, cur[1] + o1.y, cur[2] + o1.z, cur[3] + o1.w);
            *d2 = make_float4(nxt[0] + o2.x, nxt[1] + o2.y, nxt[2] + o2.z, nxt[3] + o2.w);
        }
        return;
    }
    mbar_wait(sb + B_BAR + (BB_FULL + st) * 8, ph);
    wait_cnt_warp(cnt_ptr(C_OP0, ch), dry ? 0 : 256);
    PROF(tid == 0, 2048 + ch * 8);
    float x[16];
    sum_partials<2, OPS1>(x, rs, 0, ch, w, 2 * q, OPS1);
    if (x[0] == 1.2345e30f) PROF(true, 0);
    PROF(tid == 0, 2048 + ch * 8 + 1);
    float2 ln0, ln1;
    {
        const float4 s = row_stats32(x);
        float2* dst = g_st2 + (ch * 16 + q) * 128 + w * 16 + g;
        if (c == 0 && !dry) asm volatile("st.relaxed.gpu.global.b64 [%0],%1;" ::"l"(dst), "l"(((uint64_t)__float_as_uint(s.y) << 32) | __float_as_uint(s.x)) : "memory");
        if (c == 1 && !dry) asm volatile("st.relaxed.gpu.global.b64 [%0],%1;" ::"l"(dst + 8), "l"(((uint64_t)__float_as_uint(s.w) << 32) | __float_as_uint(s.z)) : "memory");
        const float2* src = g_st2 + (ch * 16 + (lane >> 4) * 8) * 128 + w * 16 + (lane & 15);
        uint64_t v[8];
        int n = 0;
        while (true) {
            bool bad = false;
#pragma unroll
            for (int i = 0; i < 8; i++) asm volatile("ld.relaxed.gpu.global.b64 %0,[%1];" : "=l"(v[i]) : "l"(src + i * 128) : "memory");
#pragma unroll
            for (int i = 0; i < 8; i++) bad = bad || (uint32_t)(v[i] >> 32) == 0xffffffffu;
            if (!__any_sync(0xffffffffu, bad && !dry)) break;
            if (++n > 2000000) __trap();
        }
        float sm = 0;
#pragma unroll
        for (int i = 0; i < 8; i++) sm += __uint_as_float((uint32_t)v[i]);
        sm += __shfl_xor_sync(0xffffffffu, sm, 16);
        const float mean = sm * (1.f / 512.f);
        float M2 = 0;
#pragma unroll
        for (int i = 0; i < 8; i++) { const float d = __uint_as_float((uint32_t)v[i]) * (1.f / 32.f) - mean; M2 += __uint_as_float((uint32_t)(v[i] >> 32)) + 32.f * d * d; }
        M2 += __shfl_xor_sync(0xffffffffu, M2, 16);
        const float2 o = ln_finish(mean, M2 * (1.f / 512.f));
        ln0.x = __shfl_sync(0xffffffffu, o.x, g); ln0.y = __shfl_sync(0xffffffffu, o.y, g);
        ln1.x = __shfl_sync(0xffffffffu, o.x, g + 8); ln1.y = __shfl_sync(0xffffffffu, o.y, g + 8);
    }
    PROF(tid == 0, 2048 + ch * 8 + 2);
    uint32_t u[8];
#pragma unroll
    for (int i = 0; i < 8; i++) {
        const float2 l = (i & 1) ? ln1 : ln0;
        u[i] = pack2(__fdividef(rbf(x[2 * i] - l.x), l.y), __fdividef(rbf(x[2 * i + 1] - l.x), l.y));
        const int chl = (i >> 1) * 8 + g;
        sts32(sb + B_UT + chl * 256 + (i & 1) * 128 + ((w ^ g) << 4) + c * 4, movm(u[i]));
    }
    fence_async_smem();
    bar_sync(NB_C, 256);
    if (tid == 0 && ch < 15) {
        asm volatile("cp.async.bulk.global.shared::cta.bulk_group [%0],[%1],%2;" ::"l"(g_u + (q * 16 + ch) * 512), "r"(sb + B_UT), "r"(8192) : "memory");
        asm volatile("cp.async.bulk.commit_group;" ::: "memory");
    }
    PROF(tid == 0, 2048 + ch * 8 + 3);
    conv_stage(Y, sb + st * STG_B, sb + B_UT);
    uint32_t yp[4][2];
    {
        float y[4][4];
#pragma unroll
        for (int k = 0; k < 4; k++) {
            float nxt[4];
            conv_combine(Y + k * 32, y[k], nxt);
            g_carry[0][((ch * 16 + q) * 4 + k) * 256 + tid] = make_float4(nxt[0], nxt[1], nxt[2], nxt[3]);
        }
#pragma unroll
        for (int i = 0; i < 4; i++) { yp[i][0] = pack2(y[0][i], y[1][i]); yp[i][1] = pack2(y[2][i], y[3][i]); }
    }
#pragma unroll
    for (int i = 0; i < 4; i++) sts64(sb + B_YT + (16 * (2 * c + (i & 1)) + g + (i >> 1) * 8) * 80 + w * 8, yp[i][0], yp[i][1]);
    bar_sync(NB_C, 256);
    if (el) { mbar_arrive_cluster(mapa(sb + B_BAR + (BB_EMPTY + st) * 8, 0)); mbar_arrive_cluster(mapa(sb + B_BAR + (BB_EMPTY + st) * 8, 1)); }
    if (++st == NSTG) { st = 0; ph ^= 1; }
    PROF(tid == 0, 2048 + ch * 8 + 4);
    uint32_t xo[8];
    uint32_t* dA = (uint32_t*)(g_xA[1] + (ch * 8 + (q >> 1)) * 1024 + (w * 2) * 64 + (q & 1) * 32) + lane;
#pragma unroll
    for (int i = 0; i < 8; i++) {
        const int col = (i >> 1) * 8 + 2 * c;
        const uint32_t yv = lds32(sb + B_YT + (w * 16 + g + (i & 1) * 8) * 80 + col * 2);
        const uint32_t dv = dk[i >> 1];
        x[2 * i] = rbf(x[2 * i] + rbf(blo(yv) + rbf(blo(u[i]) * blo(dv))));
        x[2 * i + 1] = rbf(x[2 * i + 1] + rbf(bhi(yv) + rbf(bhi(u[i]) * bhi(dv))));
        xo[i] = pack2(x[2 * i], x[2 * i + 1]);
        dA[(i >> 1) * 32 + (i & 1) * 256] = xo[i];
    }
    {
        const float4 s = row_stats32(x);
        float2* dst = g_st[1] + q * 2048 + ch * 128 + w * 16 + g;
        if (c == 0) dst[0] = make_float2(s.x, s.y);
        if (c == 1) dst[8] = make_float2(s.z, s.w);
    }
    PROF(tid == 0, 2048 + ch * 8 + 5);
    if (tid == 0) asm volatile("cp.async.bulk.wait_group 0;" ::: "memory");
    PROF(tid == 0, 2048 + ch * 8 + 6);
}

template <int NB, int NS>
__device__ __forceinline__ void fin_blocks(const Params& p, int ch, int cb0, int ncb, int ns, bool dry) {
    const int lane = threadIdx.x & 31, w = threadIdx.x >> 5, g = lane >> 2, c = lane & 3;
    uint32_t rs[NB * 4];
    wait_cnt_warp(cnt_ptr(C_CV, ch), dry ? 0 : 16);
    load_resid<NB>(rs, 1, ch, w, cb0);
    wait_cnt_warp(cnt_ptr(C_OP1, ch), dry ? 0 : 256);
    for (int cb = cb0; cb < cb0 + ncb; cb += NB) {
        float x[NB * 8];
        if (cb != cb0) load_resid<NB>(rs, 1, ch, w, cb);
        sum_partials<NB, NS>(x, rs, 1, ch, w, cb, ns);
#pragma unroll
        for (int b = 0; b < NB; b += 2) {
#pragma unroll
            for (int h = 0; h < 2; h++) {
                const float* y = x + b * 8 + h * 2;
                uint32_t v0 = pack2(y[0], y[1]), v1 = pack2(y[4], y[5]), v2 = pack2(y[8], y[9]), v3 = pack2(y[12], y[13]);
                uint32_t t0 = (c & 1) ? v0 : v1, t1 = (c & 1) ? v2 : v3;
                t0 = __shfl_xor_sync(0xffffffffu, t0, 1); t1 = __shfl_xor_sync(0xffffffffu, t1, 1);
                if (c & 1) { v0 = t0; v2 = t1; } else { v1 = t0; v3 = t1; }
                t0 = (c & 2) ? v0 : v2; t1 = (c & 2) ? v1 : v3;
                t0 = __shfl_xor_sync(0xffffffffu, t0, 2); t1 = __shfl_xor_sync(0xffffffffu, t1, 2);
                if (c & 2) { v0 = t0; v1 = t1; } else { v2 = t0; v3 = t1; }
                stg128((uint4*)(p.out + (size_t)(ch * 128 + w * 16 + g + h * 8) * 512 + (cb + b) * 16 + c * 8), make_uint4(v0, v1, v2, v3), POL_LATE);
            }
        }
    }
}
__device__ __forceinline__ void fin_task(const Params& p, int ch, int cb0, int ncb, int nsplit, bool dry) {
    fin_blocks<2, 16>(p, ch, cb0, ncb, nsplit, dry);
}

__device__ __forceinline__ void bulk_consumer(const Params& p, uint32_t sb, int cl, uint32_t rank) {
    int st = 0; uint32_t ph = 0; int nq = 0, nd = 0;
    const uint32_t peer = 0;
    for (int ti = 0; ti < MAXT; ti++) {
        const uint32_t tk = p.task[cl][ti];
        const int type = tk & 7, layer = (tk >> 3) & 1, ch = (tk >> 4) & 15, a = (tk >> 8) & 255, b = (tk >> 16) & 255, cc = (tk >> 24) & 127;
        const bool dry = tk >> 31;
        if (type == T_END) break;
        PROF(threadIdx.x == 0, 3600 + ti * 4);
        if (type == T_QKV || type == T_OP) {
            float acc[128];
            gemm_main<4>(acc, sb, peer, type == T_QKV ? 8 : b, st, ph);
            PROF(threadIdx.x == 0, 3600 + ti * 4 + 1);
            if (type == T_QKV) {
                if (a + rank * 4 >= 128) qkv_epilogue<true>(acc, sb, layer, ch, a + rank * 4, nq, nd); else qkv_epilogue<false>(acc, sb, layer, ch, a + rank * 4, nq, nd);
                nq++;
            } else {
                const int lane = threadIdx.x & 31, w = threadIdx.x >> 5;
                uint4* dst = op_dst(layer, ch, cc, w, rank) + lane;
                mbar_wait(sb + B_BAR + BB_SF * 8, (nd & 1) ^ 1);
#pragma unroll
                for (int j = 0; j < 16; j++) {
                    const uint4 v = make_uint4(pack2(acc[j * 8], acc[j * 8 + 1]), pack2(acc[j * 8 + 2], acc[j * 8 + 3]), pack2(acc[j * 8 + 4], acc[j * 8 + 5]), pack2(acc[j * 8 + 6], acc[j * 8 + 7]));
                    if (j < 16 - NSB) stg128(dst + j * 32, v, out_pol(T_OP, layer, ch)); else sts128(sb + B_OUT + (w * NSB + j - (16 - NSB)) * 512 + lane * 16, v.x, v.y, v.z, v.w);
                }
                fence_async_smem();
            }
        } else if (type == T_CV) {
            float acc[128];
            conv_task(p, acc, sb, ch, a + rank, layer, b, cc, dry, st, ph, nd);
        } else {
            fin_task(p, ch, a + rank * cc, cc, b, dry);
        }
        if (type != T_FIN) {
            __syncwarp();
            if ((threadIdx.x & 31) == 0) mbar_arrive(sb + B_BAR + (BB_DONE + (nd & 1)) * 8);
            nd++;
        }
        PROF(threadIdx.x == 0, 3600 + ti * 4 + 2);
    }
}

constexpr int P_Y = 131072  , P_PRM = P_Y  , P_K6 = P_PRM + 8192  ,
              P_P = P_Y + 40960  , P_U = P_P + 33280  , P_END = P_U + 17408, P_X = 98304  ;
static_assert(P_END <= B_BAR && P_END <= R_SEL, "prologue scratch");
#define KGUN 2
constexpr int KGU = KGUN;
__device__ __forceinline__ void csq(float& r, float& i) { const float t = r * i; r = fmaf(r, r, -(i * i)); i = t + t; }
__device__ __forceinline__ void cpow(float ar, float ph, float p, float& r, float& i) {
    const float e = ex2(ar * p);
    const float u = ph * p, n = fabsf(u) < 4194304.f ? (u + 12582912.f) - 12582912.f : u;
    const float t = (u - n) * 6.283185307179586f;
    r = e * __cosf(t); i = e * __sinf(t);
}
__device__ __forceinline__ void mma_tf32(float* c, float a0, float a1, float a2, float a3, float b0, float b1) {
    asm volatile("mma.sync.aligned.m16n8k8.row.col.f32.tf32.tf32.f32 {%0,%1,%2,%3},{%4,%5,%6,%7},{%8,%9},{%0,%1,%2,%3};"
                 : "+f"(c[0]), "+f"(c[1]), "+f"(c[2]), "+f"(c[3])
                 : "r"(__float_as_uint(a0)), "r"(__float_as_uint(a1)), "r"(__float_as_uint(a2)), "r"(__float_as_uint(a3)), "r"(__float_as_uint(b0)), "r"(__float_as_uint(b1)));
}

struct ProRegs { uint32_t v[2][4], ldt[2]; };
__device__ __forceinline__ void prologue_load(const ProArgs& a, int b, ProRegs& pr) {
    const int w = threadIdx.x >> 5;
#pragma unroll
    for (int i = 0; i < 2; i++) {
        const int gi = b * 512 + (w & 3) * 128 + ((w >> 2) & 1) * 64 + i * 32 + (threadIdx.x & 31);
        pr.ldt[i] = __ldg((const uint16_t*)a.ldt + b * 4 + (w & 3));
        pr.v[i][0] = __ldg((const uint16_t*)a.lAr + gi); pr.v[i][1] = __ldg((const uint16_t*)a.Ai + gi);
        pr.v[i][2] = __ldg((const uint16_t*)a.Cr + gi); pr.v[i][3] = __ldg((const uint16_t*)a.Ci + gi);
    }
}
__device__ __forceinline__ void prologue(const ProArgs& a, uint32_t sb, int b, int w, const ProRegs& pr) {
    const int tid = threadIdx.x, lane = tid & 31, g = lane >> 2, c = lane & 3;
    const int d0 = b * 4;
    if (w >= 8) {
        const int t2 = tid - 256;
        if (w < 10) {
            const int row = b * 16 + (w - 8) * 8 + g;
            const float2 r = row_stats512((const uint4*)(a.x + (size_t)row * 512) + c, 8, 4);
            const float2 l = ln_finish(r.x * (1.f / 512.f), r.y * (1.f / 512.f));
            if (c == (g >> 1)) asm volatile("st.relaxed.gpu.global.u32 [%0],%1;" ::"l"(g_ln0 + row), "r"(pack2(l.x, l.y)) : "memory");
        }
        PROF(t2 == 0, 3516);
        const int gi = b * 128 + t2;
#pragma unroll 1
        for (int k = gi; k < 133 * 512; k += 16384) g_xch[k] = make_uint4(0, 0, 0, 0);
        ((uint4*)g_st2)[gi] = make_uint4(~0u, ~0u, ~0u, ~0u);
        if (gi < 9 * 16 * 32) g_cnt[gi] = 0;
        if (gi < 64) g_sel[gi] = 0;
        bar_sync(6, 384);
        {
            const int u = b * 3 + (w - 8), blk = u >> 1;
            const uint4* W = w < 11 ? (const uint4*)((blk < 64 ? a.Wq : blk < 128 ? a.Wk : a.Wv) + (size_t)((u & 1) * 256 + c) * 4096 + (blk & 63) * 64) + g
                                    : (const uint4*)a.Wo + (size_t)b * 2048 + lane;
            const int st = w < 11 ? 2048 : 32;
            const uint32_t one = (g & 1) ? 0x3f800000u : 0x00003f80u, selA = (g & 2) ? 0u : one, selB = (g & 2) ? one : 0u;
            float s0[4] = {0, 0, 0, 0}, s1[4] = {0, 0, 0, 0};
#pragma unroll 1
            for (int r = 0; r < 8; r++) {
                uint4 v[8];
#pragma unroll
                for (int i = 0; i < 8; i++) v[i] = __ldg(W + (size_t)(r * 8 + i) * st);
#pragma unroll
                for (int i = 0; i < 8; i++) mma16((i & 1) ? s1 : s0, v[i].x, v[i].y, v[i].z, v[i].w, selA, selB);
            }
            if (c < 2) *(float4*)(g_cs + (w < 11 ? (u & 1) * 12288 + blk * 64 : 24576) + g * 8 + c * 4) = make_float4(s0[0] + s1[0], s0[1] + s1[1], s0[2] + s1[2], s0[3] + s1[3]);
        }
        PROF(t2 == 0, 3517);
        return;
    }
#pragma unroll
    for (int i = 0; i < 2; i++) {
        const float dt = rbf(expf(blo(pr.ldt[i])));
        const float ar = -rbf(expf(blo(pr.v[i][0]))) * dt, ai = blo(pr.v[i][1]) * dt;
        sts128(sb + P_PRM + (w * 64 + i * 32 + lane) * 16, __float_as_uint(ar * 1.4426950408889634f), __float_as_uint(ai * 0.15915494309189535f),
               __float_as_uint(2.f * (blo(pr.v[i][2]) * dt)), __float_as_uint(2.f * (blo(pr.v[i][3]) * dt)));
    }
    if (tid < 64) sts128(sb + P_U + (tid >> 3) * 2176 + (tid & 7) * 16, 0, 0, 0, 0);
    bar_arrive(6, 384);
    __syncwarp();
    PROF(tid == 0, 3510);
    const int ch = w & 3, hf = w >> 2;
    {
        float k0[4] = {0, 0, 0, 0}, k1[4] = {0, 0, 0, 0}, k2[4] = {0, 0, 0, 0}, k3[4] = {0, 0, 0, 0}, k4[4] = {0, 0, 0, 0}, kl = 0;
#pragma unroll KGU
        for (int j = 0; j < 16; j++) {
            const uint4 q = lds128(sb + P_PRM + (w * 64 + j * 4 + c) * 16);
            const float cr = __uint_as_float(q.z), ci = __uint_as_float(q.w);
            float wr[4], wi[4], vr[4], vi[4];
            cpow(__uint_as_float(q.x), __uint_as_float(q.y), (float)g, wr[0], wi[0]);
            cpow(__uint_as_float(q.x), __uint_as_float(q.y), (float)(g + 8), vr[0], vi[0]);
#pragma unroll
            for (int i = 1; i < 4; i++) { wr[i] = wr[i - 1]; wi[i] = wi[i - 1]; csq(wr[i], wi[i]); vr[i] = vr[i - 1]; vi[i] = vi[i - 1]; csq(vr[i], vi[i]); }
            float hr = wr[3], hi = wi[3];
            csq(hr, hi);
            mma_tf32(k0, wr[0], vr[0], wi[0], vi[0], cr * hr - ci * hi, -(cr * hi + ci * hr));
            hr = vr[3]; hi = vi[3]; csq(hr, hi);
            mma_tf32(k1, wr[0], vr[0], wi[0], vi[0], cr * hr - ci * hi, -(cr * hi + ci * hr));
            csq(hr, hi);
            mma_tf32(k2, wr[1], vr[1], wi[1], vi[1], cr * hr - ci * hi, -(cr * hi + ci * hr));
            csq(hr, hi);
            mma_tf32(k3, wr[2], vr[2], wi[2], vi[2], cr * hr - ci * hi, -(cr * hi + ci * hr));
            csq(hr, hi);
            mma_tf32(k4, wr[3], vr[3], wi[3], vi[3], cr * hr - ci * hi, -(cr * hi + ci * hr));
            csq(hr, hi);
            kl += cr * hr - ci * hi;
        }
        kl += __shfl_xor_sync(0xffffffffu, kl, 1); kl += __shfl_xor_sync(0xffffffffu, kl, 2);
        const uint32_t o = sb + P_K6 + (ch * 656 + c * 32 + g) * 4, ol = sb + P_K6 + (ch * 656 + 640) * 4;
#define KST(k, base) sts32(o + (base) * 4, __float_as_uint(k[0])); sts32(o + (base) * 4 + 64, __float_as_uint(k[1])); \
                     sts32(o + (base) * 4 + 32, __float_as_uint(k[2])); sts32(o + (base) * 4 + 96, __float_as_uint(k[3]))
#define KAD(k, base) k[0] += __uint_as_float(lds32(o + (base) * 4)); k[1] += __uint_as_float(lds32(o + (base) * 4 + 64)); \
                     k[2] += __uint_as_float(lds32(o + (base) * 4 + 32)); k[3] += __uint_as_float(lds32(o + (base) * 4 + 96))
        if (hf == 0) {
            bar_sync(2 + ch, 64);
            KAD(k0, 0); KAD(k1, 128); KAD(k2, 256); KAD(k3, 384); KAD(k4, 512);
            kl += __uint_as_float(lds32(ol));
            __syncwarp();
        }
        KST(k0, 0); KST(k1, 128); KST(k2, 256); KST(k3, 384); KST(k4, 512);
        if (lane == 0) sts32(ol, __float_as_uint(kl));
        if (hf == 1) { __syncwarp(); bar_arrive(2 + ch, 64); }
    }
    PROF(tid == 0, 3511);
    {
        uint4 l0, l1;
        int n = 0;
        while (true) {
            l0 = ld_rlx128((const uint4*)g_ln0 + tid * 2); l1 = ld_rlx128((const uint4*)g_ln0 + tid * 2 + 1);
            if (__all_sync(0xffffffffu, l0.x && l0.y && l0.z && l0.w && l1.x && l1.y && l1.z && l1.w)) break;
            if (++n > 2000000) __trap();
        }
        sts128(sb + P_P + tid * 32, l0.x, l0.y, l0.z, l0.w); sts128(sb + P_P + tid * 32 + 16, l1.x, l1.y, l1.z, l1.w);
        bar_sync(8, 384);
        mbar_wait(sb + S_XBAR, 0);
        __syncwarp();
#pragma unroll 2
        for (int i = 0; i < 8; i++) {
            const int t = w * 256 + i * 32 + lane;
            const uint32_t ln = lds32(sb + P_P + t * 4);
            const uint2 x = lds64(sb + P_X + t * 16 + (b & 1) * 8);
            const float m = blo(ln), rs = rcp(bhi(ln));
            const uint32_t u0 = pack2(rbf(blo(x.x) - m) * rs, rbf(bhi(x.x) - m) * rs), u1 = pack2(rbf(blo(x.y) - m) * rs, rbf(bhi(x.y) - m) * rs);
            sts128(sb + P_X + t * 16, x.x, x.y, u0, u1);
            const uint32_t o = sb + P_U + ((t >> 3) & 1) * 2176 + ((t >> 4) + 8) * 16 + (t & 7) * 2;
            asm volatile("st.shared.u16 [%0],%1;" ::"r"(o), "h"((uint16_t)u0) : "memory");
            asm volatile("st.shared.u16 [%0],%1;" ::"r"(o + 4352), "h"((uint16_t)(u0 >> 16)) : "memory");
            asm volatile("st.shared.u16 [%0],%1;" ::"r"(o + 8704), "h"((uint16_t)u1) : "memory");
            asm volatile("st.shared.u16 [%0],%1;" ::"r"(o + 13056), "h"((uint16_t)(u1 >> 16)) : "memory");
        }
    }
    bar_sync(1, 256);
    PROF(tid == 0, 3512);
    if (tid < 64) sts32(sb + P_P + ((tid >> 4) * 2080 + (tid & 15)) * 4, 0);
#pragma unroll 1
    for (int x = tid; x < 2048; x += 512) {
        uint32_t pw[2][4];
#pragma unroll
        for (int h = 0; h < 2; h++) {
            const int y = x + h * 256;
            const int i0 = y <= 256 ? y : 256 + (int)((pack2((float)y, 0.f) & 0xffff) - 0x4380);
            const int i1 = y <= 256 ? max(y - 1, 0) : 256 + (int)((pack2((float)(y - 1), 0.f) & 0xffff) - 0x4380);
#pragma unroll
            for (int k = 0; k < 4; k++) {
                const float lo = __uint_as_float(lds32(sb + P_K6 + k * 2624 + i0 * 4)), hi = __uint_as_float(lds32(sb + P_K6 + k * 2624 + i1 * 4));
                pw[h][k] = pack2(lo, y ? hi : 0.f);
            }
        }
#pragma unroll
        for (int h = 0; h < 2; h++)
#pragma unroll
            for (int k = 0; k < 4; k++) sts32(sb + P_P + (k * 2080 + x + h * 256 + 16) * 4, pw[h][k]);
    }
    fence_async_smem();
    bar_sync(1, 256);
    if (lane < 8) {
        const int k = w >> 1, j = (w & 1) * 8 + lane, d = d0 + k;
        asm volatile("cp.async.bulk.global.shared::cta.bulk_group [%0],[%1],%2;" ::"l"(g_P + (((d >> 5) * 16 + j) * 32 + (d & 31)) * PW),
                     "r"(sb + P_P + (k * 2080 + j * 128) * 4), "r"(PW * 4) : "memory");
        asm volatile("cp.async.bulk.commit_group;" ::: "memory");
    }
    __syncwarp();
    PROF(tid == 0, 3513);
    {
        float acc[16][4];
#pragma unroll
        for (int j = 0; j < 16; j++) acc[j][0] = acc[j][1] = acc[j][2] = acc[j][3] = 0;
#pragma unroll 1
        for (int e = hf * 4; e < hf * 4 + 4; e++) {
            uint32_t B[16][2];
            const uint32_t ua = sb + P_U + ch * 4352 + ((lane >> 3) & 1) * 2176 + (8 + (lane >> 4) * 8 + (lane & 7) - e) * 16;
#pragma unroll
            for (int j = 0; j < 8; j++) { const uint4 v = ldsm4(ua + j * 256); B[2 * j][0] = v.x; B[2 * j][1] = v.y; B[2 * j + 1][0] = v.z; B[2 * j + 1][1] = v.w; }
            const uint32_t pa = sb + P_P + (ch * 2080 + 16 + e * 16 + g - 2 * c) * 4;
#pragma unroll
            for (int d = 0; d < 16; d++) {
                const uint32_t a0 = lds32(pa + d * 512), a1 = lds32(pa + d * 512 + 32), a2 = lds32(pa + d * 512 - 32);
#pragma unroll
                for (int j = d; j < 16; j++) mma16(acc[j], a0, a1, a2, a0, B[j - d][0], B[j - d][1]);
            }
        }
        PROF(tid == 0, 3514);
        const uint32_t o = sb + P_Y + (ch * 2560 + c * 40 + g) * 4;
        if (hf == 0) {
            bar_sync(2 + ch, 64);
#pragma unroll
            for (int j = 0; j < 16; j++) {
                acc[j][0] += __uint_as_float(lds32(o + j * 640)); acc[j][1] += __uint_as_float(lds32(o + j * 640 + 80));
                acc[j][2] += __uint_as_float(lds32(o + j * 640 + 32)); acc[j][3] += __uint_as_float(lds32(o + j * 640 + 112));
            }
        }
#pragma unroll
        for (int j = 0; j < 16; j++) {
            sts32(o + j * 640, __float_as_uint(acc[j][0])); sts32(o + j * 640 + 80, __float_as_uint(acc[j][1]));
            sts32(o + j * 640 + 32, __float_as_uint(acc[j][2])); sts32(o + j * 640 + 112, __float_as_uint(acc[j][3]));
        }
        if (hf == 1) bar_arrive(2 + ch, 64);
    }
    const uint2 dk = __ldg((const uint2*)(a.Dk + d0));
    bar_sync(1, 256);
#pragma unroll 2
    for (int i = 0; i < 8; i++) {
        const int t = i * 256 + tid;
        const uint32_t o = sb + P_Y + (t + 4 * (t >> 4)) * 4;
        const uint4 xu = lds128(sb + P_X + t * 16);
        float y[4];
#pragma unroll
        for (int k = 0; k < 4; k++) y[k] = rbf(__uint_as_float(lds32(o + k * 10240)));
        uint2 r;
        r.x = pack2(blo(xu.x) + rbf(y[0] + rbf(blo(xu.z) * blo(dk.x))), bhi(xu.x) + rbf(y[1] + rbf(bhi(xu.z) * bhi(dk.x))));
        r.y = pack2(blo(xu.y) + rbf(y[2] + rbf(blo(xu.w) * blo(dk.y))), bhi(xu.y) + rbf(y[3] + rbf(bhi(xu.w) * bhi(dk.y))));
        ((uint2*)(g_xA[0] + ((t >> 7) * 8 + (d0 >> 6)) * 1024 + ((t & 127) >> 3) * 64 + ((d0 & 63) >> 3) * 8 + (t & 7)))[(d0 >> 2) & 1] = r;
    }
    PROF(tid == 0, 3515);
    if (lane < 8) asm volatile("cp.async.bulk.wait_group 0;" ::: "memory");
}

__device__ __forceinline__ int pick_role(int cl, uint32_t rank, int rec0) {
    const int lane = threadIdx.x & 31;
    unsigned ep;
    asm volatile("ld.relaxed.gpu.global.u32 %0,[%1];" : "=r"(ep) : "l"(g_gate) : "memory");
    ep = (ep / (4 * NCL) + 1) * 2;
    if (rank == 0) {
        unsigned* r = (unsigned*)(((size_t)g_probe + 8191) & ~(size_t)8191) + cl * 8;
        uint32_t b0 = ~0u, b1 = ~0u;
#pragma unroll 1
        for (int i = 0; i < 6; i++) { b0 = min(b0, probe1(r, lane)); b1 = min(b1, probe1(r + 1024, lane)); }
        if (lane == 0) asm volatile("st.relaxed.gpu.global.u32 [%0],%1;" ::"l"(g_side + cl), "r"(ep + (b1 < b0)) : "memory");
    }
    uint32_t m[3];
#pragma unroll
    for (int i = 0; i < 3; i++) {
        unsigned v; int n = 0;
        const bool on = i * 32 + lane < NCL;
        while (true) {
            asm volatile("ld.relaxed.gpu.global.u32 %0,[%1];" : "=r"(v) : "l"(g_side + i * 32 + lane) : "memory");
            if (__all_sync(0xffffffffu, !on || (v & ~1u) == ep)) break;
            if (++n > 2000000) __trap();
        }
        m[i] = __ballot_sync(0xffffffffu, on && (v & 1));
    }
    if (__popc(m[0]) + __popc(m[1]) + __popc(m[2]) < NCL / 2) { m[0] = ~m[0]; m[1] = ~m[1]; m[2] = ~m[2] & 3; }
    const int tot = __popc(m[0]) + __popc(m[1]) + __popc(m[2]);
    int below = 0;
#pragma unroll
    for (int i = 0; i < 3; i++) below += __popc(m[i] & (cl >= i * 32 + 32 ? ~0u : cl <= i * 32 ? 0u : (1u << (cl - i * 32)) - 1));
    const bool mine = ((cl < 32 ? m[0] : cl < 64 ? m[1] : m[2]) >> (cl & 31)) & 1;
    const int skip = tot - 32;
    if (mine && below >= skip) return rec0 + below - skip;
    const int j = cl - max(below - skip, 0);
    return j < rec0 ? j : j + 32;
}

__global__ void __cluster_dims__(2, 1, 1) __launch_bounds__(384, 1) main_kernel(const __grid_constant__ Params p) {
    extern __shared__ __align__(1024) uint8_t smem[];
    const uint32_t sb = smem_u32(smem);
    uint32_t rank; asm("mov.u32 %0,%%cluster_ctarank;" : "=r"(rank));
    const int wi = __shfl_sync(0xffffffffu, threadIdx.x >> 5, 0);
    int cl = blockIdx.x >> 1;
    const int wg = wi >> 2;
    PROF(threadIdx.x == 0, 3500);
    ProRegs pr;
    prologue_load(p.pa, max((int)blockIdx.x - 4, 0), pr);
    if (threadIdx.x == 352 && p.dopro && cl >= 2) {
        mbar_init(sb + S_XBAR, 1);
        asm volatile("fence.mbarrier_init.release.cluster;" ::: "memory");
        mbar_expect(sb + S_XBAR, 32768);
        for (int j = 0; j < 8; j++) tma2d(sb + P_X + j * 4096, &p.tm[3], ((blockIdx.x - 4) >> 1) * 8, j * 256, sb + S_XBAR);
    }
    if (threadIdx.x == 320) {
        unsigned v = 0;
        if (p.dopro) {
            asm volatile("ld.relaxed.gpu.global.u32 %0,[%1];" : "=r"(v) : "l"(g_gate) : "memory");
            v = (v / (4 * NCL) + 1) * (4 * NCL);
        }
        sts32(sb + S_GATE, v);
    }
    __syncwarp();
    if (wg == 2) bar_arrive(8, 384);
    if (wi == 10) {
        const int v = cl;
        sts32(sb + S_VCL, v);
        if (p.rec0 >= 0 && v >= p.rec0 && v < p.rec0 + 32) rec_init(p, sb, v - p.rec0, rank); else bulk_init(sb);
        __syncwarp();
        asm volatile("barrier.cluster.arrive.aligned;" ::: "memory");
    } else asm volatile("barrier.cluster.arrive.relaxed.aligned;" ::: "memory");
    if (p.dopro && cl >= 2) prologue(p.pa, sb, blockIdx.x - 4, wi, pr); else if (wg < 2) bar_sync(8, 384);
    asm volatile("barrier.cluster.wait.aligned;" ::: "memory");
    cl = __shfl_sync(0xffffffffu, lds32(sb + S_VCL), 0);
    const bool rec = p.rec0 >= 0 && cl >= p.rec0 && cl < p.rec0 + 32;
    fence_async_smem();
    bar_sync(wg == 2 ? 7 : 1, wg == 2 ? 128 : 256);
    if (p.dopro && (threadIdx.x == 32 || threadIdx.x == 352)) red_release(g_gate, 1);
    if (rec) {
        if (threadIdx.x == 0) { rec_fetch(p, sb, cl - p.rec0, rank, 0, R_STQ); rec_fetch(p, sb, cl - p.rec0, rank, 1, R_STK); }
    }
    PROF(threadIdx.x == 0, 3506);
    __syncwarp();
    if (rec) {
        const int head = cl - p.rec0;
        if (wg == 2) {
            reg_dec<RH>();
            const int w = wi & 3;
            rec_probe(sb, head * 2 + rank, w);
            if (threadIdx.x == 256) rec_fetch(p, sb, head, rank, 2, R_WV);
            __syncwarp();
            wait_cnt_warp(g_gate, lds32(sb + S_GATE));
            rec_sides(sb, head * 2 + rank, w);
            __syncthreads();
            cluster_sync();
            if ((p.chains >> (w & 1)) & 1) { if (w < 2) rec_comm(p, sb, w, head, rank); else rec_attn(p, sb, w & 1, head, rank); }
        } else {
            reg_inc<RW0>();
            rec_weights(p, sb, head, rank, wi);
        }
    } else {
        if (wg == 2) {
            reg_dec<40>();
            const int w = wi & 3;
            if (w == 0) bulk_producer(p, sb, cl, rank); else if (w < 3) bulk_stats(p, sb, cl, rank); else bulk_release(p, sb, cl, rank);
        } else { reg_inc<232>(); bulk_consumer(p, sb, cl, rank); }
    }
    __syncwarp();
    cluster_sync();
}

typedef CUresult (*EncFn)(CUtensorMap*, CUtensorMapDataType, cuuint32_t, void*, const cuuint64_t*, const cuuint64_t*, const cuuint32_t*, const cuuint32_t*,
                          CUtensorMapInterleave, CUtensorMapSwizzle, CUtensorMapL2promotion, CUtensorMapFloatOOBfill);
inline uint32_t mk(int type, int layer, int ch, int a, int b, int c) { return type | (layer << 3) | (ch << 4) | (a << 8) | (b << 16) | ((uint32_t)c << 24); }
constexpr int SMEM_BYTES = 232448;

struct Sched {
    Params* P; int n[NCL];
    void clear() { memset(P->task, 0, sizeof(P->task)); memset(n, 0, sizeof(n)); }
    void add(int cl, uint32_t t) { if (n[cl] < MAXT - 1) P->task[cl][n[cl]++] = t; }
};

#define LAG 14
#define TS1 2550
#define TS2 3100
#define REC0 4
#define NS2 6
#define DFN 5000
#define DQN 6300
struct Slot { double s, e; uint32_t w; };
struct Planner {
    Slot sl[NCL][MAXT]; int n[NCL], nc;
    double fit(int i, double r, double d) const {
        double t = r;
        for (int k = 0; k < n[i]; k++) { if (sl[i][k].s >= t + d) break; if (sl[i][k].e > t) t = sl[i][k].e; }
        return t;
    }
    double idle_before(int i, double t) const { double e = 0; for (int k = 0; k < n[i]; k++) if (sl[i][k].e <= t + 1 && sl[i][k].e > e) e = sl[i][k].e; return t - e; }
    void put(int i, double t, double d, uint32_t w) {
        int k = n[i]++;
        while (k > 0 && sl[i][k - 1].s > t) { sl[i][k] = sl[i][k - 1]; k--; }
        sl[i][k] = {t, t + d, w};
    }
    double last_urgent(int i) const { double e = 0; for (int k = 0; k < n[i]; k++) { const uint32_t t = sl[i][k].w & 15; if (t != (T_OP | 8) && t != (T_FIN | 8)) e = sl[i][k].e; } return e; }
    double place(double r, double d, uint32_t w, int lo, bool tight) {
        int bi = -1; double bt = 0, bg = 0;
        for (int i = lo; i < nc; i++) {
            if (n[i] >= MAXT - 2) continue;
            const double t = fit(i, (w & 7) == T_FIN ? fmax(r, last_urgent(i)) : r, d), g = tight ? idle_before(i, t) : -idle_before(i, t);
            if (bi < 0 || t < bt - 1 || (t < bt + 1 && g < bg)) { bi = i; bt = t; bg = g; }
        }
        put(bi, bt, d, w);
        return bt + d;
    }
};
void plan(Params& P) {
    P.rec0 = REC0; P.chains = 3; P.lag = LAG; P.dostats = 1; P.dopro = 1;
    const double DQ = DQN, DKB = 600, DOV = 1000, DH = 520, DHO = 1300, DU = 4300, DF = DFN, HOP = 1600, ODEL = 1000, LEAD = 1500;
    static Planner L;
    int cls[NCL], nc = 0;
    for (int c = REC0 + 32; c < NCL; c++) cls[nc++] = c;
    for (int c = REC0 - 1; c >= 0; c--) cls[nc++] = c;
    for (double grow = 1.0;; grow *= 1.01) {
        memset(L.n, 0, sizeof(L.n)); L.nc = nc;
        double it[100], worst = 1e18, end = 0, cvs[16], cve[16];
        it[0] = DQ + 2 * HOP;
        for (int i = 1; i < 100; i++) it[i] = it[i - 1] + fmax(grow * TS1, (i - 1 >= LAG && i - 1 < 64) ? TS2 : 0);
        const double DO1 = DOV + 8 * DKB, dly = it[4] + ODEL + DO1 + HOP + DU + HOP + DQ + 2 * HOP - it[LAG];
        if (dly > 0) for (int i = LAG; i < 100; i++) it[i] += dly;
        for (int c = 0; c < 16; c++) {
            const double s0 = fmax(it[4 * c + 4] + ODEL, c ? cve[c - 1] : 0);
            for (int i = 0; i < 8; i++) {
                if (c == 0) L.put(i, s0 - 11000, 11000, mk(T_CV, 0, 3, 2 * i, 0, 128));
                L.put(i, s0, DO1, mk(T_OP, 0, c, 8 * i, 8, i));
                L.put(i, s0 + DO1, HOP + DU, mk(T_CV, 0, c, 2 * i, 0, 0));
            }
            cvs[c] = s0 + DO1; cve[c] = cvs[c] + HOP + DU;
        }
        for (int c = 0; c < 16; c++) {
            double e = 0;
            for (int t = 0; t < 24; t++) e = fmax(e, L.place(cve[c] + HOP, DQ, mk(T_QKV, 1, c, t * 8, 4, 0), 0, true));
            worst = fmin(worst, it[LAG + 4 * c] - (c ? LEAD : 0) - HOP - e);
        }
        for (int c = 2; c < 16; c++) {
            double e = 0, r = cve[c - 2] + HOP;
            const int m = c >= HSPLIT ? c / 2 + 1 : c;
            if (m < c) for (int i = 0; i < 8; i++) r = fmax(r, L.place(cve[c - 3] + HOP, DHO + DH * (c - m), mk(T_CV, 1, c, 2 * i, c, m + 1), 8, true));
            for (int i = 0; i < 8; i++) e = fmax(e, L.place(r, DHO + (m < c ? 1500 : 0) + DH * (m - 1), mk(T_CV, 1, c, 2 * i, m, 2), 8, true));
            worst = fmin(worst, cvs[c] - HOP - e);
        }
        for (int c = 0; c < 16; c++) {
            double e = 0;
            for (int t = 0; t < 24; t++) e = fmax(e, L.place(0, DQ, mk(T_QKV, 0, c, t * 8, 4, 0), 0, true));
            worst = fmin(worst, it[4 * c] - (c ? LEAD : 0) - HOP - e);
        }
        for (int cc = 0; cc < 16; cc++) {
            const int c = cc ? cc - 1 : 15, ns = c == 15 ? 16 : c == 14 ? 8 : NS2, nf = c >= 14 ? 8 : 4;
            double e = 0;
            for (int t = 0; t < ns; t++) {
                const int a = t * 64 / ns, b = (t + 1) * 64 / ns - a;
                const double guard = c == 15 ? 9000 : 0;
                e = fmax(e, L.place(it[LAG + 4 * c + 4] + ODEL - guard, DOV + DKB * b + guard, mk(T_OP, 1, c, a, b, t), 0, true));
            }
            for (int t = 0; t < nf; t++) end = fmax(end, L.place(e + HOP, DF, mk(T_FIN, 1, c, t * (32 / nf), ns, 16 / nf), 0, true));
        }
        if (worst >= 0) break;
    }
    for (int lc = 0; lc < 32; lc++) {
        bool used[24] = {};
        for (int pass = 0; pass < 2; pass++)
            for (int i = 0; i < nc; i++)
                for (int k = 0; k < L.n[i]; k++) {
                    uint32_t& w = L.sl[i][k].w;
                    if ((w & 255) != mk(T_QKV, lc & 1, lc >> 1, 0, 0, 0)) continue;
                    int t = i - 8;
                    if (pass == 0) { w |= 0xff00; if (t < 0 || t >= 24 || used[t]) continue; }
                    else { if ((w & 0xff00) != 0xff00) continue; for (t = 0; used[t]; t++) {} }
                    used[t] = true; w = (w & ~0xff00u) | (t * 8) << 8;
                }
    }
    Sched S; S.P = &P; S.clear();
    S.add(0, mk(T_QKV, 1, 15, 124, 4, 128)); S.add(0, mk(T_OP, 1, 15, 0, 4, 128));
    S.add(1, mk(T_CV, 0, 3, 0, 0, 128));
    for (int i = 0; i < nc; i++) {
        bool warm = false;
        for (int k = 0; k < L.n[i]; k++) {
            if (!warm && k + 1 < L.n[i] && (L.sl[i][k + 1].w & 255) == (mk(T_FIN, 1, 15, 0, 0, 0) & 255)) { S.add(cls[i], L.sl[i][k + 1].w | 0x80000000u); warm = true; }
            S.add(cls[i], L.sl[i][k].w);
            if ((L.sl[i][k].w & 7) == T_FIN) warm = true;
        }
    }
}

#define TK() do {} while (0)
}

extern "C" void kernel_launch(void* const* d_in, const int* in_sizes, int n_in, void* d_out, int out_size) {
    typedef const __nv_bfloat16* BP;
    static EncFn enc = nullptr;
    if (!enc) {
        void* fn = nullptr; cudaDriverEntryPointQueryResult qr;
        cudaGetDriverEntryPoint("cuTensorMapEncodeTiled", &fn, cudaEnableDefault, &qr);
        enc = (EncFn)fn;
        cudaFuncSetAttribute(main_kernel, cudaFuncAttributeMaxDynamicSharedMemorySize, SMEM_BYTES);
    }
    static Params P;
    for (int i = 0; i < 4; i++) {
        const cuuint64_t cols = i < 3 ? 4096 : 512, rows = i < 3 ? 512 : 4096;
        cuuint64_t d2[2] = {cols, rows}, d3[3] = {64, rows, cols / 64}, str[2] = {cols * 2, 128};
        cuuint32_t box[3] = {64, 64, 4}, es[3] = {1, 1, 1};
        if (i < 3) enc(&P.tm[i], CU_TENSOR_MAP_DATA_TYPE_BFLOAT16, 2, d_in[9 + i], d2, str, box, es, CU_TENSOR_MAP_INTERLEAVE_NONE, CU_TENSOR_MAP_SWIZZLE_128B,
                       CU_TENSOR_MAP_L2_PROMOTION_L2_128B, CU_TENSOR_MAP_FLOAT_OOB_FILL_NONE);
        enc(&P.t3[i], CU_TENSOR_MAP_DATA_TYPE_BFLOAT16, 3, d_in[9 + i], d3, str, box, es, CU_TENSOR_MAP_INTERLEAVE_NONE, CU_TENSOR_MAP_SWIZZLE_128B,
            CU_TENSOR_MAP_L2_PROMOTION_L2_128B, CU_TENSOR_MAP_FLOAT_OOB_FILL_NONE);
    }
    {
        cuuint64_t dims[2] = {512, 2048}, str[1] = {1024};
        cuuint32_t box[2] = {8, 256}, es[2] = {1, 1};
        enc(&P.tm[3], CU_TENSOR_MAP_DATA_TYPE_BFLOAT16, 2, d_in[0], dims, str, box, es, CU_TENSOR_MAP_INTERLEAVE_NONE, CU_TENSOR_MAP_SWIZZLE_NONE,
            CU_TENSOR_MAP_L2_PROMOTION_NONE, CU_TENSOR_MAP_FLOAT_OOB_FILL_NONE);
    }
    P.mem0 = (BP)d_in[8]; P.Wo = (BP)d_in[12]; P.Dskip = (BP)d_in[6]; P.out = (__nv_bfloat16*)d_out;
    P.nst[0] = 1; P.nst[1] = 16;
    cudaStream_t s = cudaStreamPerThread;
    P.pa = {(BP)d_in[0], (BP)d_in[1], (BP)d_in[2], (BP)d_in[3], (BP)d_in[4], (BP)d_in[5], (BP)d_in[6], (BP)d_in[9], (BP)d_in[10], (BP)d_in[11], (BP)d_in[12]};
    static bool planned = false;
    if (!planned) { plan(P); planned = true; }
    TK(); main_kernel<<<2 * NCL, 384, SMEM_BYTES, s>>>(P); TK();
}
```

```cpp
#include <cuda_runtime.h>
#include <cuda_bf16.h>
#include <cuda.h>
#include <stdint.h>
#include <string.h>
#include <math.h>

namespace {

constexpr int NCL = 66;
constexpr int NQ = 43;
constexpr int V_REC = 8, V_OP = 72, V_QKV = 88;

__device__ uint4 g_x[64 * 4096];
__device__ uint4 g_xn[64 * 4096];
__device__ uint4 g_st[64 * 256];
__device__ uint4 g_qkv[128 * 32 * 1536];
__device__ uint4 g_o[64 * 64 * 512];
__device__ uint4 g_pp[64 * 4 * 4096];
__device__ uint4 g_xch[133 * 512];
__device__ unsigned g_sel[64];
__device__ unsigned g_side[96];
__device__ unsigned g_probe[4096];
__device__ unsigned g_gate[32];
__device__ __align__(16) uint32_t g_P[512 * 272];
__device__ uint4 g_W[512 * 784];
__device__ __align__(16) uint32_t g_u[512 * 1152];
__device__ uint4 g_carry[512 * 40 * 32];
__device__ uint4 g_far[512 * 8 * 32];
__device__ unsigned g_cnt[900 * 8];
__device__ uint32_t g_ln0[2048];

enum { C_XN = 0  , C_QKV = 64  , C_O = 128  , C_PP = 384  , C_FAR = 896 };
__device__ __forceinline__ unsigned* cnt_ptr(int i) { return g_cnt + i * 8; }

struct ProArgs { const __nv_bfloat16 *x, *lAr, *Ai, *Cr, *Ci, *ldt, *Dk, *W[4]; };
struct Params {
    CUtensorMap tm[5];
    CUtensorMap tn[2];
    ProArgs pa;
    int dopro;
    const __nv_bfloat16* mem0;
    const __nv_bfloat16* Wo;
    const __nv_bfloat16* Dskip;
    __nv_bfloat16* out;
    int roles;
    int chains;
    int lag;
    int zero;
    int nl[2];
    uint8_t list[2][64];
};

__device__ __forceinline__ uint32_t smem_u32(const void* p) { return (uint32_t)__cvta_generic_to_shared(p); }
__device__ __forceinline__ uint32_t mapa(uint32_t a, uint32_t r) {
    uint32_t o; asm("mapa.shared::cluster.u32 %0,%1,%2;" : "=r"(o) : "r"(a), "r"(r)); return o;
}
__device__ __forceinline__ void mbar_init(uint32_t b, int c) { asm volatile("mbarrier.init.shared::cta.b64 [%0],%1;" ::"r"(b), "r"(c) : "memory"); }
__device__ __forceinline__ void mbar_expect(uint32_t b, int bytes) { asm volatile("mbarrier.arrive.expect_tx.shared::cta.b64 _,[%0],%1;" ::"r"(b), "r"(bytes) : "memory"); }
__device__ __forceinline__ void mbar_arrive(uint32_t b) { asm volatile("mbarrier.arrive.shared::cta.b64 _,[%0];" ::"r"(b) : "memory"); }
__device__ __forceinline__ void mbar_arrive_cluster(uint32_t b) { asm volatile("mbarrier.arrive.shared::cluster.b64 _,[%0];" ::"r"(b) : "memory"); }
__device__ __forceinline__ void mbar_wait(uint32_t b, uint32_t ph) {
    asm volatile(
        "{.reg .pred p; .reg .u32 n; mov.u32 n,0;\n"
        "W%=: mbarrier.try_wait.parity.shared::cta.b64 p,[%0],%1;\n"
        "@p bra D%=;\n"
        "add.u32 n,n,1; setp.lt.u32 p,n,2000000; @p bra W%=;\n"
        "trap;\n"
        "D%=: }" ::"r"(b), "r"(ph) : "memory");
}
__device__ __forceinline__ bool wait_lds128(uint32_t b, uint32_t ph, uint32_t a, uint4& v) {
    uint32_t ok;
    asm volatile("{.reg .pred p; mbarrier.try_wait.parity.shared::cta.b64 p,[%5],%6,20000; ld.shared.v4.u32 {%0,%1,%2,%3},[%7]; selp.u32 %4,1,0,p;}"
                 : "=r"(v.x), "=r"(v.y), "=r"(v.z), "=r"(v.w), "=r"(ok) : "r"(b), "r"(ph), "r"(a) : "memory");
    return ok;
}
__device__ __forceinline__ bool wait_lds64(uint32_t b, uint32_t ph, uint32_t a, uint2& v) {
    uint32_t ok;
    asm volatile("{.reg .pred p; mbarrier.try_wait.parity.shared::cta.b64 p,[%3],%4,20000; ld.shared.v2.u32 {%0,%1},[%5]; selp.u32 %2,1,0,p;}"
                 : "=r"(v.x), "=r"(v.y), "=r"(ok) : "r"(b), "r"(ph), "r"(a) : "memory");
    return ok;
}
template <int PH> __device__ __forceinline__ void mbar_wait_c(uint32_t b) {
    asm volatile(
        "{.reg .pred p; .reg .u32 n; mov.u32 n,%2;\n"
        "W%=: mbarrier.try_wait.parity.shared::cta.b64 p,[%0],%1;\n"
        "@p bra D%=;\n"
        "add.u32 n,n,1; setp.lt.u32 p,n,2000000; @p bra W%=;\n"
        "trap;\n"
        "D%=: }" ::"r"(b), "n"(PH), "n"(PH) : "memory");
}
__device__ __forceinline__ void bar_sync(int id, int n) { asm volatile("bar.sync %0,%1;" ::"r"(id), "r"(n) : "memory"); }
__device__ __forceinline__ void bar_arrive(int id, int n) { asm volatile("bar.arrive %0,%1;" ::"r"(id), "r"(n) : "memory"); }
__device__ __forceinline__ void cluster_sync() { asm volatile("barrier.cluster.arrive.relaxed.aligned; barrier.cluster.wait.aligned;" ::: "memory"); }
__device__ __forceinline__ void fence_async() { asm volatile("fence.proxy.async;" ::: "memory"); }
__device__ __forceinline__ void fence_async_smem() { asm volatile("fence.proxy.async.shared::cta;" ::: "memory"); }
#define EFR 1
#define EFW 2
constexpr uint64_t POL_N = 0x1000000000000000ull, POL_F = 0x12F0000000000000ull;
constexpr uint64_t POL_LAST = EFR ? POL_F : POL_N  , POL_LATE = EFW ? POL_F : POL_N  , POL_SOON = EFW > 1 ? POL_F : POL_N;
__device__ __forceinline__ void bulk_g2s(uint32_t dst, const void* src, int bytes, uint32_t bar, uint64_t pol) {
    asm volatile("cp.async.bulk.shared::cluster.global.mbarrier::complete_tx::bytes.L2::cache_hint [%0],[%1],%2,[%3],%4;" ::"r"(dst), "l"(src), "r"(bytes), "r"(bar), "l"(pol) : "memory");
}
__device__ __forceinline__ void bulk_g2s_mc(uint32_t dst, const void* src, int bytes, uint32_t bar, uint64_t pol) {
    asm volatile("cp.async.bulk.shared::cluster.global.mbarrier::complete_tx::bytes.multicast::cluster.L2::cache_hint [%0],[%1],%2,[%3],%4,%5;" ::"r"(dst), "l"(src), "r"(bytes), "r"(bar), "h"((uint16_t)3), "l"(pol) : "memory");
}
__device__ __forceinline__ void stg128(uint4* p, uint4 v, uint64_t pol) {
    asm volatile("st.global.L2::cache_hint.v4.u32 [%0],{%1,%2,%3,%4},%5;" ::"l"(p), "r"(v.x), "r"(v.y), "r"(v.z), "r"(v.w), "l"(pol));
}
__device__ __forceinline__ void stg32(uint32_t* p, uint32_t v, uint64_t pol) { asm volatile("st.global.L2::cache_hint.u32 [%0],%1,%2;" ::"l"(p), "r"(v), "l"(pol)); }
__device__ __forceinline__ uint4 ldcg128_last(const uint4* p) {
    uint4 v; asm volatile("ld.global.cg.L2::cache_hint.v4.u32 {%0,%1,%2,%3},[%4],%5;" : "=r"(v.x), "=r"(v.y), "=r"(v.z), "=r"(v.w) : "l"(p), "l"(POL_LAST) : "memory"); return v;
}
__device__ __forceinline__ void tma2d(uint32_t dst, const CUtensorMap* tm, int x, int y, uint32_t bar) {
    asm volatile("cp.async.bulk.tensor.2d.shared::cluster.global.mbarrier::complete_tx::bytes [%0],[%1,{%2,%3}],[%4];" ::"r"(dst), "l"(tm), "r"(x), "r"(y), "r"(bar) : "memory");
}
__device__ __forceinline__ void tma3d(uint32_t dst, const CUtensorMap* tm, int y, int z, uint32_t bar) {
    asm volatile("cp.async.bulk.tensor.3d.shared::cluster.global.mbarrier::complete_tx::bytes [%0],[%1,{0,%2,%3}],[%4];" ::"r"(dst), "l"(tm), "r"(y), "r"(z), "r"(bar) : "memory");
}
__device__ __forceinline__ void st_async4(uint32_t a, uint32_t x, uint32_t y, uint32_t z, uint32_t w, uint32_t mb) {
    asm volatile("st.async.shared::cluster.mbarrier::complete_tx::bytes.v4.b32 [%0],{%1,%2,%3,%4},[%5];" ::"r"(a), "r"(x), "r"(y), "r"(z), "r"(w), "r"(mb) : "memory");
}
__device__ __forceinline__ void st_async2(uint32_t a, uint32_t x, uint32_t y, uint32_t mb) {
    asm volatile("st.async.shared::cluster.mbarrier::complete_tx::bytes.v2.b32 [%0],{%1,%2},[%3];" ::"r"(a), "r"(x), "r"(y), "r"(mb) : "memory");
}
#define LDSQ "ld.shared"
__device__ __forceinline__ uint4 lds128(uint32_t a) { uint4 v; asm volatile(LDSQ ".v4.u32 {%0,%1,%2,%3},[%4];" : "=r"(v.x), "=r"(v.y), "=r"(v.z), "=r"(v.w) : "r"(a) : "memory"); return v; }
__device__ __forceinline__ uint2 lds64(uint32_t a) { uint2 v; asm volatile(LDSQ ".v2.u32 {%0,%1},[%2];" : "=r"(v.x), "=r"(v.y) : "r"(a) : "memory"); return v; }
__device__ __forceinline__ uint32_t lds32(uint32_t a) { uint32_t v; asm volatile(LDSQ ".u32 %0,[%1];" : "=r"(v) : "r"(a) : "memory"); return v; }
__device__ __forceinline__ void sts128(uint32_t a, uint32_t x, uint32_t y, uint32_t z, uint32_t w) { asm volatile("st.shared.v4.u32 [%0],{%1,%2,%3,%4};" ::"r"(a), "r"(x), "r"(y), "r"(z), "r"(w) : "memory"); }
__device__ __forceinline__ void sts64(uint32_t a, uint32_t x, uint32_t y) { asm volatile("st.shared.v2.u32 [%0],{%1,%2};" ::"r"(a), "r"(x), "r"(y) : "memory"); }
__device__ __forceinline__ void sts32(uint32_t a, uint32_t x) { asm volatile("st.shared.u32 [%0],%1;" ::"r"(a), "r"(x) : "memory"); }
__device__ __forceinline__ uint4 ldsm4(uint32_t a) { uint4 v; asm volatile("ldmatrix.sync.aligned.m8n8.x4.shared.b16 {%0,%1,%2,%3},[%4];" : "=r"(v.x), "=r"(v.y), "=r"(v.z), "=r"(v.w) : "r"(a) : "memory"); return v; }
__device__ __forceinline__ uint4 ldsm4t(uint32_t a) { uint4 v; asm volatile("ldmatrix.sync.aligned.m8n8.x4.trans.shared.b16 {%0,%1,%2,%3},[%4];" : "=r"(v.x), "=r"(v.y), "=r"(v.z), "=r"(v.w) : "r"(a) : "memory"); return v; }
__device__ __forceinline__ uint32_t movm(uint32_t a) { uint32_t d; asm volatile("movmatrix.sync.aligned.m8n8.trans.b16 %0,%1;" : "=r"(d) : "r"(a)); return d; }
__device__ __forceinline__ uint32_t pack2(float lo, float hi) { uint32_t d; asm("cvt.rn.bf16x2.f32 %0,%1,%2;" : "=r"(d) : "f"(hi), "f"(lo)); return d; }
__device__ __forceinline__ uint32_t hadd2(uint32_t a, uint32_t b) { uint32_t d; asm("add.rn.bf16x2 %0,%1,%2;" : "=r"(d) : "r"(a), "r"(b)); return d; }
__device__ __forceinline__ uint32_t hmul2(uint32_t a, uint32_t b) { uint32_t d; asm("mul.rn.bf16x2 %0,%1,%2;" : "=r"(d) : "r"(a), "r"(b)); return d; }
__device__ __forceinline__ float blo(uint32_t v) { return __uint_as_float(v << 16); }
__device__ __forceinline__ float bhi(uint32_t v) { return __uint_as_float(v & 0xffff0000u); }
__device__ __forceinline__ float rbf(float x) { return __uint_as_float(pack2(0.f, x)); }
__device__ __forceinline__ float ex2(float x) { float y; asm("ex2.approx.ftz.f32 %0,%1;" : "=f"(y) : "f"(x)); return y; }
__device__ __forceinline__ float rcp(float x) { float y; asm("rcp.approx.ftz.f32 %0,%1;" : "=f"(y) : "f"(x)); return y; }
__device__ __forceinline__ void mma16(float* c, uint32_t a0, uint32_t a1, uint32_t a2, uint32_t a3, uint32_t b0, uint32_t b1) {
    asm volatile("mma.sync.aligned.m16n8k16.row.col.f32.bf16.bf16.f32 {%0,%1,%2,%3},{%4,%5,%6,%7},{%8,%9},{%0,%1,%2,%3};"
                 : "+f"(c[0]), "+f"(c[1]), "+f"(c[2]), "+f"(c[3]) : "r"(a0), "r"(a1), "r"(a2), "r"(a3), "r"(b0), "r"(b1));
}
__device__ __forceinline__ void mma16_top(float& d0, float& d1, uint32_t a0, uint32_t a2, uint32_t b0, uint32_t b1) {
    asm volatile("{.reg .b32 j; .reg .f32 e,f; mma.sync.aligned.m16n8k16.row.col.f32.bf16.bf16.f32 {%0,%1,e,f},{%2,j,%3,j},{%4,%5},{0f00000000,0f00000000,0f00000000,0f00000000};}"
                 : "=f"(d0), "=f"(d1) : "r"(a0), "r"(a2), "r"(b0), "r"(b1));
}
__device__ __forceinline__ void mma8(float* c, uint32_t a0, uint32_t a1, uint32_t b0) {
    asm volatile("mma.sync.aligned.m16n8k8.row.col.f32.bf16.bf16.f32 {%0,%1,%2,%3},{%4,%5},{%6},{%0,%1,%2,%3};"
                 : "+f"(c[0]), "+f"(c[1]), "+f"(c[2]), "+f"(c[3]) : "r"(a0), "r"(a1), "r"(b0));
}
__device__ __forceinline__ uint4 ld_rlx128(const uint4* p) {
    uint4 v;
    asm volatile("{.reg .b128 t; ld.relaxed.gpu.global.b128 t,[%4]; mov.b128 {%0,%1,%2,%3},t;}" : "=r"(v.x), "=r"(v.y), "=r"(v.z), "=r"(v.w) : "l"(p) : "memory");
    return v;
}
__device__ __forceinline__ void st_rlx128(uint4* p, uint32_t x, uint32_t y, uint32_t z, uint32_t w) {
    asm volatile("{.reg .b128 t; mov.b128 t,{%1,%2,%3,%4}; st.relaxed.gpu.global.b128 [%0],t;}" ::"l"(p), "r"(x), "r"(y), "r"(z), "r"(w) : "memory");
}
__device__ __forceinline__ uint4 ldcg128(const uint4* p) { uint4 v; asm volatile("ld.global.cg.v4.u32 {%0,%1,%2,%3},[%4];" : "=r"(v.x), "=r"(v.y), "=r"(v.z), "=r"(v.w) : "l"(p) : "memory"); return v; }
__device__ __forceinline__ void red_release(unsigned* p, unsigned v) {
    asm volatile("fence.proxy.async; red.relaxed.gpu.global.add.u32 [%0],%1;" ::"l"(p), "r"(v) : "memory");
}
__device__ __forceinline__ void wait_cnt(const unsigned* p, unsigned target) {
    unsigned v; int n = 0;
    while (true) {
        asm volatile("ld.acquire.gpu.global.u32 %0,[%1];" : "=r"(v) : "l"(p) : "memory");
        if (v >= target) break;
        if (++n > 3000000) __trap();
        __nanosleep(40);
    }
}
__device__ __forceinline__ void wait_cnt_warp(const unsigned* p, unsigned target) {
    unsigned v; int n = 0;
    while (true) {
        asm volatile("ld.acquire.gpu.global.u32 %0,[%1];" : "=r"(v) : "l"(p) : "memory");
        if (__all_sync(0xffffffffu, v >= target)) break;
        if (++n > 3000000) __trap();
        __nanosleep(40);
    }
}
__device__ __forceinline__ void wait_flag_warp(const unsigned* p, unsigned target) {
    unsigned v; int n = 0;
    while (true) {
        asm volatile("ld.relaxed.gpu.global.u32 %0,[%1];" : "=r"(v) : "l"(p) : "memory");
        if (__all_sync(0xffffffffu, v >= target)) break;
        if (++n > 10000000) __trap();
    }
}
__device__ __forceinline__ uint64_t mkdesc(uint32_t addr, uint32_t lbo, uint32_t sbo, uint32_t sw) {
    return (uint64_t)((addr & 0x3FFFF) >> 4) | ((uint64_t)(lbo >> 4) << 16) | ((uint64_t)(sbo >> 4) << 32) | ((uint64_t)sw << 62);
}
__device__ __forceinline__ void wg_fence() { asm volatile("wgmma.fence.sync.aligned;" ::: "memory"); }
__device__ __forceinline__ void wg_commit() { asm volatile("wgmma.commit_group.sync.aligned;" ::: "memory"); }
template <int N> __device__ __forceinline__ void wg_wait() { asm volatile("wgmma.wait_group.sync.aligned %0;" ::"n"(N) : "memory"); }
#define R8(c, o) "+f"(c[o]), "+f"(c[o + 1]), "+f"(c[o + 2]), "+f"(c[o + 3]), "+f"(c[o + 4]), "+f"(c[o + 5]), "+f"(c[o + 6]), "+f"(c[o + 7])
#define R32(c, o) R8(c, o), R8(c, o + 8), R8(c, o + 16), R8(c, o + 24)
#define S32A "%0,%1,%2,%3,%4,%5,%6,%7,%8,%9,%10,%11,%12,%13,%14,%15,%16,%17,%18,%19,%20,%21,%22,%23,%24,%25,%26,%27,%28,%29,%30,%31"
template <int ACC> __device__ __forceinline__ void wgmma64_rs(float* c, const uint32_t* a, uint64_t db) {
    asm volatile("wgmma.mma_async.sync.aligned.m64n64k16.f32.bf16.bf16 {" S32A "},{%32,%33,%34,%35},%36,%37,1,1,0;"
                 : R32(c, 0) : "r"(a[0]), "r"(a[1]), "r"(a[2]), "r"(a[3]), "l"(db), "n"(ACC));
}
template <int ACC> __device__ __forceinline__ void wgmma64_ta(float* c, uint64_t da, uint64_t db) {
    asm volatile("wgmma.mma_async.sync.aligned.m64n64k16.f32.bf16.bf16 {" S32A "},%32,%33,%34,1,1,1,0;" : R32(c, 0) : "l"(da), "l"(db), "n"(ACC));
}
template <int ACC> __device__ __forceinline__ void wgmma80_tb(float* c, uint64_t da, uint64_t db) {
    asm volatile("wgmma.mma_async.sync.aligned.m64n80k16.f32.bf16.bf16 {" S32A ",%32,%33,%34,%35,%36,%37,%38,%39},%40,%41,%42,1,1,0,1;"
                 : R32(c, 0), R8(c, 32) : "l"(da), "l"(db), "n"(ACC));
}
template <int N> __device__ __forceinline__ void reg_inc() { asm volatile("setmaxnreg.inc.sync.aligned.u32 %0;" ::"n"(N)); }
template <int N> __device__ __forceinline__ void reg_dec() { asm volatile("setmaxnreg.dec.sync.aligned.u32 %0;" ::"n"(N)); }

#define PROF(cond, idx) do {} while (0)
#define CPROF(k) do {} while (0)

constexpr int S_GATE = 232440, S_XBAR = 232432, S_VCL = 232444, B_BAR = 231936;
#define RCB 104
#define RCU 200
#define QLAG 3
constexpr float SC_LOG2E = 0.08838834764831845f * 1.4426950408889634f;

__device__ __forceinline__ float2 ln_finish(float mean, float var) {
    float sd; asm("sqrt.approx.f32 %0,%1;" : "=f"(sd) : "f"(rbf(rbf(var) + 1e-5f)));
    sd = rbf(sd);
    return make_float2(rbf(mean), sd);
}

__device__ __forceinline__ float2 row_stats512(uint4* v, const uint4* src, int s1, int s2) {
    const int g = (threadIdx.x & 31) >> 2;
#pragma unroll
    for (int i = 0; i < 16; i++) v[i] = ldcg128(src + (i >> 1) * s1 + (i & 1) * s2);
    float a[4] = {0, 0, 0, 0}, q0[4] = {0, 0, 0, 0}, q1[4] = {0, 0, 0, 0};
#pragma unroll
    for (int i = 0; i < 16; i++) {
        mma16(a, v[i].x, v[i].y, v[i].z, v[i].w, 0x3f803f80u, 0x3f803f80u);
        mma8(q0, v[i].x, v[i].y, v[i].x); mma8(q1, v[i].x, v[i].y, v[i].y);
        mma8(q0, v[i].z, v[i].w, v[i].z); mma8(q1, v[i].z, v[i].w, v[i].w);
    }
    const float sum = a[0] + a[2], sq = (g & 1) ? q0[1] + q1[3] : q0[0] + q1[2];
    return make_float2(sum, fmaxf(sq - sum * sum * (1.f / 512.f), 0.f));
}
__device__ __forceinline__ void x1_norm(int rg) {
    const int lane = threadIdx.x & 31, g = lane >> 2, c = lane & 3, o = (rg >> 3) * 4096 + (rg & 7) * 64 + c * 8 + g;
    uint4 v[16];
    const float2 r = row_stats512(v, g_x + o, 512, 32);
    const float2 l = ln_finish(r.x * (1.f / 512.f), r.y * (1.f / 512.f));
    const float mu = __shfl_sync(0xffffffffu, l.x, g * 4 + (g >> 1)), rs = rcp(__shfl_sync(0xffffffffu, l.y, g * 4 + (g >> 1)));
    if (c == 0) g_ln0[rg * 8 + g] = 0;
#define NRM(w) pack2(rbf(blo(w) - mu) * rs, rbf(bhi(w) - mu) * rs)
#pragma unroll
    for (int i = 0; i < 16; i++) g_xn[o + (i >> 1) * 512 + (i & 1) * 32] = make_uint4(NRM(v[i].x), NRM(v[i].y), NRM(v[i].z), NRM(v[i].w));
    __syncwarp();
    if (lane == 0) red_release(cnt_ptr(C_XN + (rg >> 3)), 1);
}

#define NWO 10
#define VMASK 0x4444
#define VQ 16
#define VPRE 2
#define MPRE 1
#define NPM NPX
#define SCHED(i) do {} while (0)
#define VPX 0
#define OA 0
#define QA 0
#define NPX 2
#define NPF 4
constexpr int SLOT = 24576, SL_V = 8192, SL_Q = 16384, SL_KM = 20480, SL_VM = 22528;
constexpr int R_WV = 0, R_SL = 65536, R_WO = R_SL + 4 * SLOT, R_M = 196608  , R_U = R_M + 8192  ,
              R_OS = R_U + 8192  , R_SB = R_OS + 8192  , R_OB = R_SB + 5248  , R_PB = R_OB + 2048  ,
              R_IL = R_PB + 1024  , R_SEL = 231680, R_BAR = R_SEL + 256, R_STQ = 65536, R_STK = 131072;
static_assert(R_WO + (16 - NWO) * 4096 <= R_M && R_IL + 64 <= R_SEL && R_BAR + 512 <= 232448, "smem map");
enum { RB_XFULL = 0  , RB_GO = 4  , RB_QK = 8  , RB_INIT = 24, RB_SV = 25  , RB_N = 29 };
#define GATE 1
enum { NB_MFULL = 1  , NB_PART = 3  , NB_S = 5, NB_P = 6, NB_O = 7, NB_W = 10 };
#define WDEP 1
#define RH 56
#define RW0 224
#define D1 300
#define D2 300
#define DX 0
__device__ __forceinline__ uint32_t clk32() { uint32_t c; asm volatile("mov.u32 %0,%%clock;" : "=r"(c)::"memory"); return c; }
__device__ __forceinline__ void spin(int cycles) {
    if (cycles <= 0) return;
    const uint32_t t0 = clk32();
    while (clk32() - t0 < (uint32_t)cycles) {}
}
__device__ __forceinline__ uint4* xregion(int X, int r) { return (uint4*)(((size_t)g_xch + 8191) & ~(size_t)8191) + (X * 66 + r) * 512; }

struct RecW { uint32_t po, dp, lw, swr, pwr, w, wv; };

template <int X>
__device__ __forceinline__ void rec_step(const RecW& k, uint32_t sb, int s, uint32_t z, uint32_t gate, const uint32_t (*wq)[4], const uint32_t (*wk)[4], uint4* wv, uint4* wo) {
    const uint32_t wz = k.w + z, w5 = wz * 512, so = (s & 1) * SLOT + w5;
    constexpr int SL = R_SL + X * 2 * SLOT;
    const uint32_t qb = sb + R_BAR + (RB_QK + X * 8) * 8 + wz * 8;
    const uint32_t l8 = ((k.lw + z) >> 1) + (sb - (sb >> 1) + SL + (s & 1) * SLOT + wz * 256);
    uint4 mk[8];
#define WVF(ks) wv[ks]
#define WVL(a, b) _Pragma("unroll") for (int ks_ = (a); ks_ < (b); ks_++) if (ks_ < 16 && !((VMASK >> ks_) & 1)) wv[ks_] = ldsm4t(k.wv + ks_ * 2048)
    WVL(0, VPRE);
    bar_sync(NB_MFULL + X, 288);
    uint32_t x[4], vv[2];
    float av[2][4] = {{0, 0, 0, 0}, {0, 0, 0, 0}};
    {
        float aq[2][4] = {{0, 0, 0, 0}, {0, 0, 0, 0}}, ak[2][4] = {{0, 0, 0, 0}, {0, 0, 0, 0}};
#pragma unroll
        for (int i = 0; i < MPRE; i++) mk[i] = ldsm4(k.lw + X * 4096 + R_M + i * 512);
#pragma unroll
        for (int i = 0; i < 8; i++) {
            if (i + MPRE < 8) mk[i + MPRE] = ldsm4(k.lw + X * 4096 + R_M + (i + MPRE) * 512);
            if (2 * i < VQ) { WVL(2 * i + VPRE, min(2 * i + 2 + VPRE, VQ + VPX)); }
            SCHED(i);
            const uint4 mf = mk[i];
            mma16(aq[0], wq[2 * i][0], wq[2 * i][1], wq[2 * i][2], wq[2 * i][3], mf.x, mf.y);
            mma16(ak[0], wk[2 * i][0], wk[2 * i][1], wk[2 * i][2], wk[2 * i][3], mf.x, mf.y);
            if (2 * i < VQ) mma16(av[0], WVF(2 * i).x, WVF(2 * i).y, WVF(2 * i).z, WVF(2 * i).w, mf.x, mf.y);
            mma16(aq[QA & 1], wq[2 * i + 1][0], wq[2 * i + 1][1], wq[2 * i + 1][2], wq[2 * i + 1][3], mf.z, mf.w);
            mma16(ak[(QA >> 1) & 1], wk[2 * i + 1][0], wk[2 * i + 1][1], wk[2 * i + 1][2], wk[2 * i + 1][3], mf.z, mf.w);
            if (2 * i < VQ) mma16(av[QA >> 2], WVF(2 * i + 1).x, WVF(2 * i + 1).y, WVF(2 * i + 1).z, WVF(2 * i + 1).w, mf.z, mf.w);
        }
        if (QA) {
#pragma unroll
            for (int i = 0; i < 4; i++) { if (QA & 1) aq[0][i] += aq[1][i]; if (QA & 2) ak[0][i] += ak[1][i]; }
        }
        x[0] = movm(pack2(aq[0][0], aq[0][1])); x[1] = movm(pack2(aq[0][2], aq[0][3]));
        x[2] = movm(pack2(ak[0][0], ak[0][1])); x[3] = movm(pack2(ak[0][2], ak[0][3]));
        st_async4(k.lw + (R_U + X * 4096 + w5 + k.dp), x[0], x[1], x[2], x[3], qb + k.dp);
    }
    {
#pragma unroll
        for (int i = VQ / 2; i < 8; i++) {
            const uint4 mf = mk[i];
            WVL(2 * i + VPX, 2 * i + 2 + VPX);
            mma16(av[0], WVF(2 * i).x, WVF(2 * i).y, WVF(2 * i).z, WVF(2 * i).w, mf.x, mf.y);
            mma16(av[1], WVF(2 * i + 1).x, WVF(2 * i + 1).y, WVF(2 * i + 1).z, WVF(2 * i + 1).w, mf.z, mf.w);
        }
        if (VQ < 16 || QA >= 4) {
#pragma unroll
            for (int i = 0; i < 4; i++) av[0][i] += av[1][i];
        }
        vv[0] = pack2(av[0][0], av[0][1]); vv[1] = pack2(av[0][2], av[0][3]);
        st_async2(l8 + (SL_VM + k.dp), vv[0], vv[1], qb + k.dp);
        asm volatile("{.reg .pred p; setp.eq.u32 p,%1,%2; @p mbarrier.arrive.shared::cta.b64 _,[%0];}" ::"r"(gate), "r"(k.swr), "r"(gate ? sb + R_SB : 0) : "memory");
        const uint4 k0 = lds128(k.lw + so + SL), k1 = lds128(k.lw + so + SL + 4096);
#pragma unroll
        for (int i = 0; i < NPX; i++) wo[i] = lds128(k.lw + w5 + R_WO + i * 4096);
        mbar_wait(qb, s & 1);
        const uint4 u = lds128(k.lw + w5 + R_U + X * 4096);
        const uint32_t q0 = hadd2(x[0], u.x), q1 = hadd2(x[1], u.y);
        x[2] = hadd2(x[2], u.z); x[3] = hadd2(x[3], u.w);
        float sa[4] = {0, 0, 0, 0}, sc[4] = {0, 0, 0, 0}, sm0, sm1;
        mma16(sa, k0.x, k0.y, k0.z, k0.w, q0, q1);
        mma16(sc, k1.x, k1.y, k1.z, k1.w, q0, q1);
        mma16_top(sm0, sm1, x[2], x[3], q0, q1);
        asm volatile("stmatrix.sync.aligned.m8n8.x4.trans.shared.b16 [%0],{%1,%2,%3,%4};" ::"r"(k.swr), "r"(pack2(sa[0], sa[1])), "r"(pack2(sa[2], sa[3])),
                     "r"(pack2(sc[0], sc[1])), "r"(pack2(sc[2], sc[3])) : "memory");
        asm volatile("stmatrix.sync.aligned.m8n8.x1.trans.shared.b16 [%0],{%1};" ::"r"(k.swr + 512), "r"(pack2(sm0, sm1)) : "memory");
    }
    bar_sync(NB_S, 256);
    uint4 v0, v1;
    uint32_t ls;
    {
        const uint4 y = ldsm4t(k.lw + wz * 656 + R_SB);
        uint32_t y4; asm volatile("ldmatrix.sync.aligned.m8n8.x1.trans.shared.b16 {%0},[%1];" : "=r"(y4) : "r"(k.lw + wz * 656 + R_SB + 512) : "memory");
        const uint2 vp = lds64(l8 + SL_VM);
        sts64(l8 + SL_KM, x[2], x[3]);
        v0 = lds128(k.lw + so + SL + SL_V); v1 = lds128(k.lw + so + SL + SL_V + 4096);
        vv[0] = hadd2(vv[0], vp.x); vv[1] = hadd2(vv[1], vp.y);
        sts64(l8 + SL_VM, vv[0], vv[1]);
#pragma unroll
        for (int i = NPX; i < NPM; i++) wo[i] = lds128(k.lw + w5 + R_WO + i * 4096);
        const uint32_t ONE = 0x3f803f80u + z;
        float a[4] = {0, 0, 0, 0}, b[4] = {0, 0, 0, 0}, e[4] = {0, 0, 0, 0};
        mma8(e, ONE, z, y4); mma16(a, ONE, z, z, ONE, y.x, y.y); mma16(b, ONE, z, z, ONE, y.z, y.w);
        float s0, s1;
        asm("{.reg .pred p1,p2,p4; .reg .f32 t0,t1,u0,u1; .reg .b32 m; and.b32 m,%12,64; setp.ne.u32 p1,m,0; and.b32 m,%12,128; setp.ne.u32 p2,m,0; and.b32 m,%12,256; setp.ne.u32 p4,m,0;"
            "selp.f32 t0,%4,%2,p1; selp.f32 t1,%5,%3,p1; selp.f32 u0,%8,%6,p1; selp.f32 u1,%9,%7,p1; selp.f32 t0,u0,t0,p2; selp.f32 t1,u1,t1,p2; selp.f32 %0,%10,t0,p4; selp.f32 %1,%11,t1,p4;}"
            : "=f"(s0), "=f"(s1) : "f"(a[0]), "f"(a[1]), "f"(a[2]), "f"(a[3]), "f"(b[0]), "f"(b[1]), "f"(b[2]), "f"(b[3]), "f"(e[0]), "f"(e[1]), "r"(k.lw));
        const int mi = __float_as_int(fmaxf(s0, s1));
        const int mp = __reduce_max_sync(0xffffffffu, mi), mn = (int)__reduce_min_sync(0xffffffffu, (unsigned)mi);
        const float mo = -__int_as_float(mp >= 0 ? mp : mn) * SC_LOG2E;
        s0 = ex2(fmaf(s0, SC_LOG2E, mo)); s1 = ex2(fmaf(s1, SC_LOG2E, mo));
        sts32(k.pwr, pack2(s0, s1));
        ls = k.lw < sb + 320 ? __float2uint_rn((s0 + s1) * 16777216.f) : 0;
    }
    bar_sync(NB_P, 256);
    {
        const uint4 pp = lds128(k.lw + R_PB);
        const uint32_t pm = lds32(((k.lw + z) >> 2) + (sb - (sb >> 2) + R_PB + 512));
        sts32(sb + R_IL + (wz >> 1) * 16 + (wz & 1) * 4, __float_as_uint(rcp(__uint2float_rn(__reduce_add_sync(0xffffffffu, ls)) * (1.f / 16777216.f))));
        float o0[4] = {0, 0, 0, 0}, o1[4] = {0, 0, 0, 0}, o2[4] = {0, 0, 0, 0};
        mma16(o0, v0.x, v0.y, v0.z, v0.w, pp.x, pp.y);
        mma16(o1, v1.x, v1.y, v1.z, v1.w, pp.z, pp.w);
        mma8(o2, vv[0], vv[1], pm);
        asm volatile("stmatrix.sync.aligned.m8n8.x2.trans.shared.b16 [%0],{%1,%2};" ::"r"(k.lw + wz * 256 + R_OB),
                     "r"(pack2(o0[0] + o1[0] + o2[0], o0[1] + o1[1] + o2[1])), "r"(pack2(o0[2] + o1[2] + o2[2], o0[3] + o1[3] + o2[3])) : "memory");
#pragma unroll
        for (int i = NPM; i < NPF; i++) wo[i] = lds128(k.lw + w5 + R_WO + i * 4096);
    }
    bar_sync(NB_O, 256);
    {
        const uint32_t po = k.po + z, tag = (s + 1) & 1;
        float r0[2][4] = {{0, 0, 0, 0}, {0, 0, 0, 0}}, r1[2][4] = {{0, 0, 0, 0}, {0, 0, 0, 0}};
        uint4 b[4];
#pragma unroll
        for (int i = 0; i < 4; i++) b[i] = ldsm4(k.lw + R_OB + i * 512);
        SCHED(8);
#pragma unroll
        for (int m = NWO + NPF; m < 16; m++) wo[m] = lds128(k.lw + w5 + R_WO + (m - NWO) * 4096);
        const uint2 il = lds64(sb + R_IL + (po & 48));
        const float i0 = __uint_as_float(il.x), i1 = __uint_as_float(il.y);
#pragma unroll
        for (int i = 0; i < 4; i++) {
            mma16(r0[0], wo[4 * i].x, wo[4 * i].y, wo[4 * i].z, wo[4 * i].w, b[i].x, b[i].y);
            mma16(r1[0], wo[4 * i + 1].x, wo[4 * i + 1].y, wo[4 * i + 1].z, wo[4 * i + 1].w, b[i].x, b[i].y);
            mma16(r0[OA], wo[4 * i + 2].x, wo[4 * i + 2].y, wo[4 * i + 2].z, wo[4 * i + 2].w, b[i].z, b[i].w);
            mma16(r1[OA], wo[4 * i + 3].x, wo[4 * i + 3].y, wo[4 * i + 3].z, wo[4 * i + 3].w, b[i].z, b[i].w);
        }
#pragma unroll
        for (int i = 0; i < 4; i++) { r0[0][i] = (OA ? r0[0][i] + r0[1][i] : r0[0][i]) * ((i & 1) ? i1 : i0); r1[0][i] = (OA ? r1[0][i] + r1[1][i] : r1[0][i]) * ((i & 1) ? i1 : i0); }
        st_rlx128((uint4*)((char*)xregion(X, 0) + ((po & ~1u) ^ ((po & X) << 12))), (pack2(r0[0][0], r0[0][2]) & ~1u) | tag,
                  pack2(r1[0][0], r1[0][2]), pack2(r0[0][1], r0[0][3]), pack2(r1[0][1], r1[0][3]));
        bar_arrive(NB_PART + X, 288);
    }
}

__device__ __forceinline__ void rec_weights(const Params& p, uint32_t sb, int head, uint32_t rank, int w) {
    const int lane = threadIdx.x & 31, g = lane >> 2, c = lane & 3;
    const int t = w & 3, WG = w >> 2;
    uint32_t wq[16][4], wk[16][4];
    uint4 wo[16], wv[16];
    const uint32_t woff = sb + WG * 32768 + (((lane >> 4) << 3) + (lane & 7)) * 128 + (((2 * t + ((lane >> 3) & 1)) ^ (lane & 7)) << 4);
    const uint32_t lw = sb + lane * 16;
    PROF(threadIdx.x == 0, 3501);
    if (w >= 4 && p.dopro) { wait_cnt_warp(g_gate, lds32(sb + S_GATE)); x1_norm((w - 4) * 64 + head * 2 + rank); }
    PROF(threadIdx.x == 0, 3502);
    mbar_wait(sb + R_BAR + RB_INIT * 8, 0);
    PROF(threadIdx.x == 0, 3503);
#pragma unroll
    for (int ks = 0; ks < 16; ks++) {
        uint4 a = ldsm4t(woff + R_STQ + ks * 2048), b = ldsm4t(woff + R_STK + ks * 2048);
        wq[ks][0] = a.x; wq[ks][1] = a.y; wq[ks][2] = a.z; wq[ks][3] = a.w;
        wk[ks][0] = b.x; wk[ks][1] = b.y; wk[ks][2] = b.z; wk[ks][3] = b.w;
    }
#pragma unroll
    for (int i = 0; i < 16; i++) if ((VMASK >> i) & 1) wv[i] = ldsm4t(woff + R_WV + i * 2048);
    bar_sync(NB_W, 256);
    {
        const __nv_bfloat16* wp = p.Wo + (size_t)(head * 128 + 2 * c) * 512 + rank * 256 + w * 32 + g * 4;
#pragma unroll
        for (int ks = 0; ks < 8; ks++) {
            const uint2 r0 = *(const uint2*)(wp + (ks * 16) * 512), r1 = *(const uint2*)(wp + (ks * 16 + 1) * 512);
            const uint2 r2 = *(const uint2*)(wp + (ks * 16 + 8) * 512), r3 = *(const uint2*)(wp + (ks * 16 + 9) * 512);
            const uint4 f[2] = {make_uint4(__byte_perm(r0.x, r1.x, 0x5410), __byte_perm(r0.x, r1.x, 0x7632), __byte_perm(r2.x, r3.x, 0x5410), __byte_perm(r2.x, r3.x, 0x7632)),
                                make_uint4(__byte_perm(r0.y, r1.y, 0x5410), __byte_perm(r0.y, r1.y, 0x7632), __byte_perm(r2.y, r3.y, 0x5410), __byte_perm(r2.y, r3.y, 0x7632))};
#pragma unroll
            for (int h = 0; h < 2; h++) {
                const int m = 2 * ks + h;
                if (m >= NPF && m < NPF + NWO) wo[m] = f[h];
                else sts128(lw + w * 512 + R_WO + (m < NPF ? m : m - NWO) * 4096, f[h].x, f[h].y, f[h].z, f[h].w);
            }
        }
    }
    fence_async_smem();
    PROF(threadIdx.x == 0, 3504);
    __syncthreads();
    cluster_sync();
    PROF(threadIdx.x == 0, 3505);
    RecW k;
    {
        const int r = (w * 4 + (lane >> 3)) * 2 + rank;
        const uint32_t sl = lds32(sb + R_SEL + r * 4);
        const int slot = head * 8 + (lane & 7);
        k.po = (r * 512 + slot + (sl & 1) * 256) * 16 + (((sl >> 1) ^ sl) & 1);
    }
    k.dp = mapa(sb, rank ^ 1) - sb;
    k.lw = __shfl_sync(0xffffffffu, lw, lane);
    k.swr = __shfl_sync(0xffffffffu, sb + R_SB + (lane & 7) * 656 + (lane >> 3) * 128 + w * 16, lane);
    k.pwr = __shfl_sync(0xffffffffu, sb + R_PB + (g < 4 ? (w * 4 + c) * 16 + g * 4 : 512 + (w * 4 + c) * 4), lane);
    k.w = w;
    k.wv = __shfl_sync(0xffffffffu, woff + R_WV, lane);
    const int e0 = (p.chains & 1) ? 64 : 0, o1 = (p.chains & 2) ? p.lag : 1000, nit = (p.chains & 2) ? p.lag + 64 : 64;
    const uint32_t zero = p.zero;
#pragma unroll 1
    for (int it = 0; it < nit; it++) {
        const uint32_t g0 = sb + R_BAR + (RB_GO + (it & 1)) * 8, g1 = sb + R_BAR + (RB_GO + 2 + ((it - o1) & 1)) * 8;
        if (it < e0) {
            rec_step<0>(k, sb, it, it & zero, GATE && it > o1 ? g1 ^ 8 : 0, wq, wk, wv, wo);
            if ((!GATE || it < o1) && threadIdx.x == 0) mbar_arrive(g0);
        }
        if (it >= o1) {
            rec_step<1>(k, sb, it - o1, it & zero, GATE && it < e0 ? g0 : 0, wq, wk, wv, wo);
            if ((!GATE || it + 1 >= e0) && threadIdx.x == 0) mbar_arrive(g1);
        }
    }
}

__device__ __forceinline__ uint32_t mism(uint32_t a, uint32_t b, uint32_t t) {
    uint32_t d; asm("lop3.b32 %0,%1,%2,%3,0x7e;" : "=r"(d) : "r"(a), "r"(b), "r"(t)); return d;
}
template <bool TWO>
__device__ __forceinline__ void poll8(uint4* x, const uint4* src, uint32_t tag) {
#pragma unroll
    for (int j = 0; j < 8; j++) x[j] = ld_rlx128(src + j * 32);
    int n = 0;
    while (true) {
        uint32_t bad = 0;
#pragma unroll
        for (int j = 0; j < 8; j += 2) bad |= TWO ? mism(x[j].x, x[j].z, tag) | mism(x[j + 1].x, x[j + 1].z, tag) : mism(x[j].x, x[j + 1].x, tag);
        if (!__any_sync(0xffffffffu, bad & 1)) break;
#pragma unroll
        for (int j = 0; j < 8; j++)
            asm volatile("{.reg .pred p; .reg .b128 t; setp.ne.u32 p,%5,0; mov.b128 t,{%0,%1,%2,%3}; @p ld.relaxed.gpu.global.b128 t,[%4]; mov.b128 {%0,%1,%2,%3},t;}"
                         : "+r"(x[j].x), "+r"(x[j].y), "+r"(x[j].z), "+r"(x[j].w) : "l"(src + j * 32), "r"((TWO ? mism(x[j].x, x[j].z, tag) : x[j].x ^ tag) & 1) : "memory");
        if (++n > 2000000) __trap();
    }
}

__device__ __forceinline__ void rec_comm(const Params& p, uint32_t sb, int X, int head, uint32_t rank) {
    const int lane = threadIdx.x & 31, g = lane >> 2, c = lane & 3;
    const int me = head * 2 + rank;
    const uint32_t mb = sb + R_M + X * 4096 + lane * 16;
    uint4 x[8];
#pragma unroll
    for (int j = 0; j < 8; j++) x[j] = *(const uint4*)(p.mem0 + (lane & 7) * 512 + rank * 256 + (j * 4 + (lane >> 3)) * 8);
    const uint32_t sl = lds32(sb + R_SEL + me * 4);
    const uint4* src1 = xregion(X, me) + ((sl >> X) & 1) * 256 + c * 8 + g;
    const uint4* src2 = xregion(X, 64 + rank) + ((sl >> (2 + X)) & 1) * 256 + lane;
    uint2* mdst = (uint2*)(xregion(X, 64 + rank) + (c >> 1) * 256 + head * 8 + (g & 3) * 2 + (c & 1)) + (g >> 2);
    const uint32_t one = (g & 1) ? 0x3f800000u : 0x00003f80u, selA = (g & 2) ? 0u : one, selB = (g & 2) ? one : 0u;
    const uint32_t qb = sb + R_BAR + (RB_QK + X * 8 + lane) * 8;
    if (lane < 8) mbar_expect(qb, 768);
    mbar_wait(sb + R_BAR + (RB_XFULL + X * 2) * 8, 0);
#pragma unroll 1
    for (int s = 0;; s++) {
#pragma unroll
        for (int j = 0; j < 8; j++) sts128(mb + j * 512, x[j].x, x[j].y, x[j].z, x[j].w);
        bar_arrive(NB_MFULL + X, 288);
        PROF(lane == 0, X * 64 + s);
        bar_sync(NB_PART + X, 288);
        if (s == 63) break;
        const uint32_t tag = (s + 1) & 1;
        if (lane < 8) mbar_expect(qb, 768);
        spin(D1 + (lds32(sb + R_SEL) >> 20));
        poll8<false>(x, src1, tag);
        float a[4][4];
#pragma unroll
        for (int j = 0; j < 4; j++) {
            a[j][0] = a[j][1] = a[j][2] = a[j][3] = 0;
            mma16(a[j], x[j].x, x[j].y, x[j].z, x[j].w, selA, selB);
        }
#pragma unroll
        for (int j = 0; j < 4; j++) mma16(a[j], x[j + 4].x, x[j + 4].y, x[j + 4].z, x[j + 4].w, selA, selB);
#pragma unroll
        for (int i = 0; i < 4; i++) a[0][i] = (a[0][i] + a[1][i]) + (a[2][i] + a[3][i]);
        asm volatile("st.relaxed.gpu.global.b64 [%0],%1;" ::"l"(mdst), "l"(((uint64_t)pack2(a[0][2], a[0][3]) << 32) | ((pack2(a[0][0], a[0][1]) & ~1u) | tag)) : "memory");
        const uint32_t t2 = clk32();
        mbar_wait(sb + R_BAR + (RB_XFULL + X * 2 + tag) * 8, ((s + 1) >> 1) & 1);
        while (clk32() - t2 < D2) {}
        poll8<true>(x, src2, tag);
    }
}

template <int MT>
__device__ __forceinline__ void xattn(uint32_t l16, uint32_t l8, uint32_t os, int g, int c) {
    constexpr int NT = 3 + 2 * MT;
    float S[NT][4];
#pragma unroll
    for (int i = 0; i < NT; i++) S[i][0] = S[i][1] = S[i][2] = S[i][3] = 0;
#pragma unroll 2
    for (int ks = 0; ks < 8; ks++) {
        const uint4 q = lds128(l16 + SL_Q + ks * 512);
        const uint2 u = lds64(l8 + SL_KM + ks * 256);
        mma16(S[0], q.x, q.y, q.z, q.w, u.x, u.y);
#pragma unroll
        for (int m = 0; m <= MT; m++) {
            const uint4 kk = lds128(l16 + m * 4096 + ks * 512);
            mma16(S[1 + 2 * m], q.x, q.y, q.z, q.w, kk.x, kk.z); mma16(S[2 + 2 * m], q.x, q.y, q.z, q.w, kk.y, kk.w);
        }
    }
    const float NEG = -__int_as_float(0x7f800000);
    if (2 * c > g) { S[NT - 2][0] = NEG; S[NT - 1][2] = NEG; }
    if (2 * c + 1 > g) { S[NT - 2][1] = NEG; S[NT - 1][3] = NEG; }
    S[NT - 1][0] = S[NT - 1][1] = NEG;
    float m0 = fmaxf(S[0][0], S[0][1]), m1 = fmaxf(S[0][2], S[0][3]);
#pragma unroll
    for (int i = 1; i < NT; i++) { if (i < NT - 1) m0 = fmaxf(m0, fmaxf(S[i][0], S[i][1])); m1 = fmaxf(m1, fmaxf(S[i][2], S[i][3])); }
    m0 = fmaxf(m0, __shfl_xor_sync(0xffffffffu, m0, 1)); m1 = fmaxf(m1, __shfl_xor_sync(0xffffffffu, m1, 1));
    m0 = fmaxf(m0, __shfl_xor_sync(0xffffffffu, m0, 2)); m1 = fmaxf(m1, __shfl_xor_sync(0xffffffffu, m1, 2));
    m0 *= -SC_LOG2E; m1 *= -SC_LOG2E;
    float l0 = 0, l1 = 0;
#pragma unroll
    for (int i = 0; i < NT; i++) {
        if (i < NT - 1) { S[i][0] = ex2(fmaf(S[i][0], SC_LOG2E, m0)); S[i][1] = ex2(fmaf(S[i][1], SC_LOG2E, m0)); l0 += S[i][0] + S[i][1]; }
        S[i][2] = ex2(fmaf(S[i][2], SC_LOG2E, m1)); S[i][3] = ex2(fmaf(S[i][3], SC_LOG2E, m1)); l1 += S[i][2] + S[i][3];
    }
    l0 += __shfl_xor_sync(0xffffffffu, l0, 1); l1 += __shfl_xor_sync(0xffffffffu, l1, 1);
    l0 += __shfl_xor_sync(0xffffffffu, l0, 2); l1 += __shfl_xor_sync(0xffffffffu, l1, 2);
    l0 = rcp(l0); l1 = rcp(l1);
    uint32_t P[NT][2];
#pragma unroll
    for (int i = 0; i < NT; i++) { P[i][0] = i < NT - 1 ? pack2(S[i][0] * l0, S[i][1] * l0) : 0u; P[i][1] = pack2(S[i][2] * l1, S[i][3] * l1); }
#pragma unroll 2
    for (int et = 0; et < 8; et++) {
        float a[4] = {0, 0, 0, 0}, b[4] = {0, 0, 0, 0};
        const uint2 vm = lds64(l8 + SL_VM + et * 256);
        mma8(a, vm.x, vm.y, P[0][0]); mma8(b, vm.x, vm.y, P[0][1]);
#pragma unroll
        for (int m = 0; m <= MT; m++) {
            const uint4 v = lds128(l16 + SL_V + m * 4096 + et * 512);
            mma16(a, v.x, v.y, v.z, v.w, P[1 + 2 * m][0], P[2 + 2 * m][0]); mma16(b, v.x, v.y, v.z, v.w, P[1 + 2 * m][1], P[2 + 2 * m][1]);
        }
        asm volatile("stmatrix.sync.aligned.m8n8.x4.trans.shared.b16 [%0],{%1,%2,%3,%4};" ::"r"(os + (et >> 2) * 2048 + (et & 3) * 256),
                     "r"(pack2(a[0], a[1])), "r"(pack2(a[2], a[3])), "r"(pack2(b[0], b[1])), "r"(pack2(b[2], b[3])) : "memory");
    }
}

__device__ __forceinline__ void rec_tiles(uint32_t sb, int X, int head, uint32_t rank, int& nxt, int lim, int need) {
#pragma unroll 1
    while (nxt <= lim) {
        if ((nxt & 1) == 0) {
            unsigned v; int n = 0;
            while (true) {
                asm volatile("ld.relaxed.gpu.global.u32 %0,[%1];" : "=r"(v) : "l"(cnt_ptr(C_QKV + X * 32 + (nxt >> 1))) : "memory");
                if (__all_sync(0xffffffffu, v >= 2 * NQ)) break;
                if (nxt > need) return;
                if (++n > 3000000) __trap();
            }
        }
        if ((threadIdx.x & 31) == 0) {
            const uint32_t bar = sb + R_BAR + (RB_XFULL + X * 2 + (nxt & 1)) * 8, dst = sb + R_SL + (X * 2 + (nxt & 1)) * SLOT;
            const uint4* src = g_qkv + (size_t)((X * 64 + nxt) * 32 + head) * 1536;
            mbar_expect(bar, 20480);
            bulk_g2s_mc(dst + rank * 8192, src + 512 + rank * 512, 8192, bar, POL_LAST);
            bulk_g2s(dst + SL_Q, src + (rank ^ X) * 256, 4096, bar, POL_LAST);
        }
        __syncwarp();
        nxt++;
    }
}

__device__ __forceinline__ void rec_attn(const Params& p, uint32_t sb, int X, int head, uint32_t rank) {
    const int lane = threadIdx.x & 31, g = lane >> 2, c = lane & 3;
    const int mt = rank ^ X;
    const uint32_t dp = mapa(sb, rank ^ 1) - sb;
    int nxt = 0;
    rec_tiles(sb, X, head, rank, nxt, 1, 0);
#pragma unroll 1
    for (int s = 0; s < 64; s++) {
        const uint32_t so = sb + R_SL + (X * 2 + (s & 1)) * SLOT;
        mbar_wait(sb + R_BAR + (RB_GO + X * 2 + (s & 1)) * 8, (s >> 1) & 1);
        rec_tiles(sb, X, head, rank, nxt, min(s + 1, 63), -1);
        spin(DX);
        mbar_wait(sb + R_BAR + (RB_XFULL + X * 2 + (s & 1)) * 8, (s >> 1) & 1);
        if (lane == 0) asm volatile("cp.async.bulk.wait_group.read 0;" ::: "memory");
        __syncwarp();
        const uint32_t os = sb + R_OS + X * 4096 + (lane >> 4) * 1024 + (lane & 15) * 16;
        if (mt) xattn<1>(so + lane * 16, so + lane * 8, os, g, c); else xattn<0>(so + lane * 16, so + lane * 8, os, g, c);
        fence_async_smem();
        __syncwarp();
        const uint32_t svb = sb + R_BAR + (RB_SV + X * 2 + (s & 1)) * 8;
        if (lane == 0) {
            mbar_arrive(svb); mbar_arrive_cluster(svb + dp);
            const uint64_t pol = POL_SOON;
#pragma unroll
            for (int kb = 0; kb < 2; kb++)
                asm volatile("cp.async.bulk.global.shared::cta.bulk_group.L2::cache_hint [%0],[%1],%2,%3;" ::"l"(g_o + ((X * 32 + (s >> 1)) * 64 + head * 2 + kb) * 512 + ((s & 1) * 4 + mt * 2) * 64),
                             "r"(sb + R_OS + X * 4096 + kb * 2048), "r"(2048), "l"(pol) : "memory");
            asm volatile("cp.async.bulk.commit_group;" ::: "memory");
            if (s & 1) { asm volatile("cp.async.bulk.wait_group 0;" ::: "memory"); red_release(cnt_ptr(C_O + (X * 32 + (s >> 1)) * 4 + (head >> 3)), 1); }
        }
        __syncwarp();
        rec_tiles(sb, X, head, rank, nxt, min(s + 1, 63), s + 1);
        mbar_wait(svb, (s >> 1) & 1);
        rec_tiles(sb, X, head, rank, nxt, min(s + 2, 63), -1);
    }
}

__device__ __forceinline__ uint32_t probe1(unsigned* r, int lane) {
    uint32_t v = 0;
    const uint32_t t0 = clk32();
    asm volatile("{.reg .pred p; setp.eq.u32 p,%2,0; @p atom.relaxed.gpu.global.or.b32 %0,[%1],0;}" : "+r"(v) : "l"(r), "r"(lane) : "memory");
    v = __shfl_sync(0xffffffffu, v, 0);
    asm volatile("{.reg .pred p; setp.eq.u32 p,%0,0x5a5a5a5b; @p nanosleep.u32 1;}" ::"r"(v) : "memory");
    return clk32() - t0;
}
__device__ __forceinline__ void rec_probe(uint32_t sb, int me, int w) {
    const int lane = threadIdx.x & 31;
    unsigned* r = (unsigned*)xregion(w & 1, (w & 2) ? 64 + (me & 1) : me) + ((w & 2) ? (me >> 1) * 32 : 0);
    uint32_t b0 = ~0u, b1 = ~0u;
#pragma unroll 1
    for (int i = 0; i < 5; i++) { b0 = min(b0, probe1(r, lane)); b1 = min(b1, probe1(r + 1024, lane)); }
    sts32(sb + R_BAR + 480 + w * 4, b1 < b0);
}
__device__ __forceinline__ void rec_sides(uint32_t sb, int me, int w) {
    const int lane = threadIdx.x & 31;
    if (lane == 0) asm volatile("red.relaxed.gpu.global.add.u32 [%0],%1;" ::"l"(g_sel + me), "r"((lds32(sb + R_BAR + 480 + w * 4) << w) + 256u) : "memory");
    __syncwarp();
    if (w < 2) {
        unsigned v; int n = 0;
        while (true) {
            asm volatile("ld.relaxed.gpu.global.u32 %0,[%1];" : "=r"(v) : "l"(g_sel + w * 32 + lane) : "memory");
            if (__all_sync(0xffffffffu, v >= 1024)) break;
            if (++n > 2000000) __trap();
        }
        sts32(sb + R_SEL + (w * 32 + lane) * 4, v);
    }
}

__device__ __forceinline__ void rec_init(uint32_t sb) {
    const uint32_t b = sb + R_BAR;
    const int i = threadIdx.x & 31;
    mbar_init(b + i * 8, i >= RB_SV ? 2 : 1);
    if (i == RB_INIT) mbar_expect(b + RB_INIT * 8, 196608);
    asm volatile("fence.mbarrier_init.release.cluster;" ::: "memory");
}
__device__ __forceinline__ void rec_fetch(const Params& p, uint32_t sb, int head, uint32_t rank, int which, int dst) {
#pragma unroll 1
    for (int j = 0; j < 8; j++) tma2d(sb + dst + j * 8192, &p.tm[which], head * 128 + (j >> 2) * 64, rank * 256 + (j & 3) * 64, sb + R_BAR + RB_INIT * 8);
}

constexpr int G_BAR = B_BAR;
enum { GB_FULL = 0  , GB_EMPTY = 8  , GB_RS = 16, GB_SS = 17, GB_LAG = 18, GB_FREE = 19, GB_DONE = 20  , GB_N = 24 };
constexpr int Q_PRE = 6, Q_STG = Q_PRE * 16384;
constexpr int NQRS = 2 * NQ - 64;
__device__ __forceinline__ void gemm_init(uint32_t sb, bool op) {
    const int i = threadIdx.x & 31;
    if (i < GB_N) mbar_init(sb + G_BAR + i * 8, i >= GB_DONE ? 4 : i == GB_FREE ? 8 : (i >= GB_EMPTY && i < GB_RS) ? 2 : 1);
    if (i == GB_RS) mbar_expect(sb + G_BAR + i * 8, 131072);
    if (i == GB_SS) mbar_expect(sb + G_BAR + i * 8, op ? 131072 : 163840);
    asm volatile("fence.mbarrier_init.release.cluster;" ::: "memory");
}
__device__ __forceinline__ int qkv_blk(int id, int j) { return NQRS * 4 + id * 10 + j; }
__device__ __forceinline__ void qkv_fetch(const Params& p, uint32_t sb, int id, int j0, int j1) {
#pragma unroll 1
    for (int j = j0 * 2; j < j1 * 2; j++) {
        const int blk = min(qkv_blk(id, j >> 1), 511);
        tma2d(sb + j * 8192, &p.tn[blk >> 8], (blk & 255) * 16, (j & 1) * 256, sb + G_BAR + GB_SS * 8);
    }
}
__device__ __forceinline__ void gemm_stage(const Params& p, uint32_t sb, int id, bool op) {
#pragma unroll 1
    for (int j = 0; j < 16; j++) {
        const int u = id * 2 + (j >> 3);
        tma2d(sb + (op ? 0 : Q_STG) + j * 8192, &p.tm[op ? 4 : u < 64 ? 2 : 0], (u & (op ? 7 : 63)) * 64, op ? (id >> 2) * 1024 + (j & 7) * 128 : (j & 7) * 64, sb + G_BAR + GB_RS * 8);
    }
}
template <bool OP>
__device__ __forceinline__ void gemm_producer(const Params& p, uint32_t sb, int id) {
    constexpr int NS = OP ? 6 : 8, SB = OP ? 16384 : 8192, RING = OP ? 131072 : 163840;
    if (threadIdx.x != 256) return;
    mbar_wait(sb + G_BAR + GB_FREE * 8, 0);
    if (OP) {
#pragma unroll 1
        for (int j = 0; j < 16; j++) tma2d(sb + j * 8192, &p.tm[4], ((id * 2 + (j >> 3)) & 7) * 64, (id >> 2) * 1024 + (j & 7) * 128 + 64, sb + G_BAR + GB_SS * 8);
    } else qkv_fetch(p, sb, id, Q_PRE, 10);
    wait_cnt(g_gate, lds32(sb + S_GATE));
    int st = 0; uint32_t ph = 1;
#pragma unroll 1
    for (int n = 0; n < p.nl[OP]; n++) {
        const int e = p.list[OP][n];
        wait_cnt(OP ? cnt_ptr(C_O + e * 4 + (id >> 2)) : cnt_ptr(C_XN + e), OP ? 16 : 8);
        PROF(true, 1024 + n * 4);
        const uint4* src = OP ? g_o + (e * 64 + (id >> 2) * 16) * 512 : g_xn + e * 4096;
#pragma unroll 1
        for (int s = 0; s < 8; s++) {
            mbar_wait(sb + G_BAR + (GB_EMPTY + st) * 8, ph);
            mbar_expect(sb + G_BAR + (GB_FULL + st) * 8, SB);
            bulk_g2s(sb + RING + st * SB, src + s * (SB / 16), SB, sb + G_BAR + (GB_FULL + st) * 8, POL_N);
            if (++st == NS) { st = 0; ph ^= 1; }
        }
    }
}
template <bool OP>
__device__ __forceinline__ void gemm_release(const Params& p, uint32_t sb, int id) {
    if (threadIdx.x != 288) return;
#pragma unroll 1
    for (int n = 0; n < 2 * p.nl[OP]; n++) {
        const int e = p.list[OP][n >> 1];
        mbar_wait(sb + G_BAR + (GB_DONE + (n & 3)) * 8, (n >> 2) & 1);
        red_release(OP ? cnt_ptr(C_PP + e * 8 + (id & 3) * 2 + (n & 1)) : cnt_ptr(C_QKV + e), 1);
        PROF(n & 1, 1024 + (n >> 1) * 4 + 3);
    }
}
__device__ __forceinline__ void op_permute(uint32_t sb) {
#pragma unroll 2
    for (int i = threadIdx.x; i < 4096; i += 256) {
        const uint32_t a = sb + i * 32 + ((i >> 2) & 1) * 16, b = a ^ 16;
        const uint4 x = lds128(a), y = lds128(b);
        sts128(a, __byte_perm(x.x, x.y, 0x5410), __byte_perm(x.z, x.w, 0x5410), __byte_perm(y.x, y.y, 0x5410), __byte_perm(y.z, y.w, 0x5410));
        sts128(b, __byte_perm(x.x, x.y, 0x7632), __byte_perm(x.z, x.w, 0x7632), __byte_perm(y.x, y.y, 0x7632), __byte_perm(y.z, y.w, 0x7632));
    }
    fence_async_smem();
    bar_sync(1, 256);
}
template <bool OP>
__device__ __forceinline__ void gemm_consumer(const Params& p, uint32_t sb, int id, int w) {
    constexpr int NS = OP ? 6 : 8, SB = OP ? 16384 : 8192, RING = OP ? 131072 : 163840;
    const int lane = threadIdx.x & 31, wg = w >> 2, t = w & 3, u = id * 2 + wg;
    uint32_t a[128];
    mbar_wait(sb + G_BAR + GB_RS * 8, 0);
    if (OP) op_permute(sb);
    {
        const uint32_t wo = sb + (OP ? 0 : Q_STG) + wg * 65536 + (((lane >> 4) << 3) + (lane & 7)) * 128 + (((2 * t + ((lane >> 3) & 1)) ^ (lane & 7)) << 4);
#pragma unroll
        for (int ks = 0; ks < 32; ks++) { const uint4 v = ldsm4t(wo + ks * 2048); a[ks * 4] = v.x; a[ks * 4 + 1] = v.y; a[ks * 4 + 2] = v.z; a[ks * 4 + 3] = v.w; }
    }
    fence_async_smem();
    __syncwarp();
    if (lane == 0) mbar_arrive(sb + G_BAR + GB_FREE * 8);
    mbar_wait(sb + G_BAR + GB_SS * 8, 0);
    if (OP) op_permute(sb);
    float c0[32], c1[OP ? 32 : 40];
    int st = 0; uint32_t ph = 0;
    const bool el = (threadIdx.x & 127) == 0;
#pragma unroll 1
    for (int n = 0; n < p.nl[OP]; n++) {
        int prev = 0;
        const uint32_t wb = sb + wg * (OP ? 65536 : 81920) + (n & p.zero);
        const uint64_t dw = OP ? mkdesc(wb, 0, 1024, 1) : mkdesc(wb, 16384, 256, 3);
        if (!OP && wg) mbar_wait(sb + G_BAR + GB_LAG * 8, n & 1);
#pragma unroll
        for (int s = 0; s < 8; s++) {
            mbar_wait(sb + G_BAR + (GB_FULL + st) * 8, ph);
            const uint64_t dx = mkdesc(sb + RING + st * SB, 128, 1024, 0);
            wg_fence();
#pragma unroll
            for (int kk = 0; kk < 4; kk++) {
                const int ks = s * 4 + kk;
                if (ks == 0) { wgmma64_rs<0>(c0, a, dx); if (OP) wgmma64_ta<0>(c1, dw, dx + 512); else wgmma80_tb<0>(c1, dx, dw); }
                else { wgmma64_rs<1>(c0, a + ks * 4, dx + kk * 16); if (OP) wgmma64_ta<1>(c1, dw + ks * 128, dx + 512 + kk * 16); else wgmma80_tb<1>(c1, dx + kk * 16, dw + ks * 32); }
            }
            wg_commit();
            if (s) {
                wg_wait<1>();
                if (el) { mbar_arrive(sb + G_BAR + (GB_EMPTY + prev) * 8); if (!OP && s == QLAG && !wg) mbar_arrive(sb + G_BAR + GB_LAG * 8); }
            }
            prev = st;
            if (++st == NS) { st = 0; ph ^= 1; }
        }
        const int e = p.list[OP][n];
        wg_wait<0>();
        if (el) mbar_arrive(sb + G_BAR + (GB_EMPTY + prev) * 8);
        PROF(threadIdx.x == 128, 1024 + n * 4 + 1);
        if (OP) {
            uint4* dst = g_pp + (e * 4 + (id >> 2)) * 4096 + ((u & 7) * 32 + t * 8) * 16 + (lane >> 2) * 16 + (lane & 3);
#pragma unroll
            for (int j = 0; j < 4; j++) {
                const float* x = c0 + j * 8; const float* y = c1 + j * 8;
                stg128(dst + j * 4, make_uint4(pack2(x[0] + y[0], x[1] + y[1]), pack2(x[2] + y[2], x[3] + y[3]), pack2(x[4] + y[4], x[5] + y[5]), pack2(x[6] + y[6], x[7] + y[7])), POL_SOON);
            }
        } else {
            uint4* dst = g_qkv + (size_t)e * 2 * 32 * 1536 + lane;
            const uint64_t pol = POL_SOON;
#pragma unroll
            for (int j = 0; j < 4; j++) {
                const float* x = c0 + j * 8;
                uint4 v = make_uint4(pack2(x[0], x[1]), pack2(x[2], x[3]), pack2(x[4], x[5]), pack2(x[6], x[7]));
                if (u >= 64) v = make_uint4(movm(v.x), movm(v.z), movm(v.y), movm(v.w));
                stg128(dst + (((j >> 1) * 32 + ((u & 63) >> 1)) * 1536 + (u < 64 ? 1024 : 0) + (j & 1) * 256 + ((u & 1) * 4 + t) * 32), v, pol);
            }
#pragma unroll
            for (int j = 0; j < 5; j++) {
                const float* x = c1 + (OP ? 0 : j * 8);
                const int blk = qkv_blk(id, wg * 5 + j);
                if (blk < 512) stg128(dst + (((t >> 1) * 32 + ((blk >> 3) & 31)) * 1536 + (blk >> 8) * 512 + (t & 1) * 256 + (blk & 7) * 32),
                                      make_uint4(pack2(x[0], x[1]), pack2(x[2], x[3]), pack2(x[4], x[5]), pack2(x[6], x[7])), pol);
            }
        }
        __syncwarp();
        if (lane == 0) mbar_arrive(sb + G_BAR + (GB_DONE + (n & 1) * 2 + wg) * 8);
        PROF(threadIdx.x == 128, 1024 + n * 4 + 2);
    }
}

template <int NP, bool MMA>
__device__ __forceinline__ void sum_partials(float* x, const uint2* src, const uint32_t* r0, const uint32_t* r1, uint32_t idm) {
    uint2 v[4][NP];
#pragma unroll
    for (int s = 0; s < 4; s++)
#pragma unroll
        for (int i = 0; i < NP; i++) asm volatile("ld.global.cg.L2::cache_hint.v2.u32 {%0,%1},[%2],%3;" : "=r"(v[s][i].x), "=r"(v[s][i].y) : "l"(src + s * 8192 + i * 32), "l"(POL_LAST) : "memory");
#pragma unroll
    for (int i = 0; i < NP; i++) {
        uint32_t a, b;
        if (MMA) {
            float t[4] = {0, 0, 0, 0};
            mma16(t, v[0][i].x, v[0][i].y, v[1][i].x, v[1][i].y, idm, idm); mma16(t, v[2][i].x, v[2][i].y, v[3][i].x, v[3][i].y, idm, idm);
            a = pack2(t[0], t[2]); b = pack2(t[1], t[3]);
        } else {
            a = pack2((blo(v[0][i].x) + blo(v[1][i].x)) + (blo(v[2][i].x) + blo(v[3][i].x)), (blo(v[0][i].y) + blo(v[1][i].y)) + (blo(v[2][i].y) + blo(v[3][i].y)));
            b = pack2((bhi(v[0][i].x) + bhi(v[1][i].x)) + (bhi(v[2][i].x) + bhi(v[3][i].x)), (bhi(v[0][i].y) + bhi(v[1][i].y)) + (bhi(v[2][i].y) + bhi(v[3][i].y)));
        }
        const uint32_t s0 = hadd2(a, r0[i]), s1 = hadd2(b, r1[i]);
        x[4 * i] = blo(s0); x[4 * i + 2] = bhi(s0); x[4 * i + 1] = blo(s1); x[4 * i + 3] = bhi(s1);
    }
}
__device__ __forceinline__ const uint2* pp_src(int e, int tile, int lane) { return (const uint2*)g_pp + e * 32768 + tile * 128 + (lane >> 3) * 8 + (lane & 3) * 2 + ((lane >> 2) & 1); }
__device__ __forceinline__ int x_off(int e, int tile, int lane) { return e * 4096 + (tile >> 3) * 512 + (lane >> 2) * 64 + (tile & 7) * 8 + (lane & 3) * 2; }

__device__ __forceinline__ void fin_warp(const Params& p, uint32_t sb, int tile) {
    const int lane = threadIdx.x & 31;
    wait_cnt_warp(g_gate, lds32(sb + S_GATE));
#pragma unroll 1
    for (int e = 32; e < 64; e++) {
        wait_cnt_warp(cnt_ptr(C_PP + e * 8 + (tile >> 3)), 4);
        const uint4 r0 = ldcg128(g_x + x_off(e, tile, lane)), r1 = ldcg128(g_x + x_off(e, tile, lane) + 1);
        uint32_t o0[4], o1[4];
#pragma unroll
        for (int h = 0; h < 2; h++) {
            const uint32_t a[2] = {h ? r0.z : r0.x, h ? r0.w : r0.y}, b[2] = {h ? r1.z : r1.x, h ? r1.w : r1.y};
            float x[8];
            sum_partials<2, false>(x, pp_src(e, tile, lane) + h * 64, a, b, 0);
#pragma unroll
            for (int i = 0; i < 2; i++) {
                o0[h * 2 + i] = __byte_perm(__float_as_uint(x[4 * i]), __float_as_uint(x[4 * i + 2]), 0x7632);
                o1[h * 2 + i] = __byte_perm(__float_as_uint(x[4 * i + 1]), __float_as_uint(x[4 * i + 3]), 0x7632);
            }
        }
        uint4* dst = (uint4*)p.out + ((e - 32) * 64 + lane * 2) * 64 + tile;
        dst[0] = make_uint4(o0[0], o0[1], o0[2], o0[3]); dst[64] = make_uint4(o1[0], o1[1], o1[2], o1[3]);
        PROF(lane == 0, 1536 + e);
    }
}

constexpr int PROW = 272, UROW = 2304, UPRE = 256;
constexpr int C_UR = 0  , C_TB = 65536  , C_BG = C_TB + 51200,
              CB_M = 8960, CB_U = CB_M + 1792, CB_BIG = CB_U + 2560, C_ST = C_BG + 8 * CB_BIG  ;
static_assert(C_ST + 4736 <= B_BAR, "smem map");
enum { CB_TB = 0, CB_UF = 1  , CB_CF = 5  , CB_LD = 9   };
__device__ __forceinline__ void conv_init(uint32_t sb, bool spare) {
    const int i = threadIdx.x & 31;
    mbar_init(sb + B_BAR + i * 8, (i >= CB_UF && i < CB_CF && !spare) ? 2 : 1);
    if (i == CB_TB && !spare) mbar_expect(sb + B_BAR + i * 8, 51200);
    asm volatile("fence.mbarrier_init.release.cluster;" ::: "memory");
}
__device__ __forceinline__ void mma_q(float* c, const uint32_t* a, const uint4& q) {
    mma16(c, a[0], a[1], a[2], a[3], q.x, q.y); mma16(c, a[4], a[5], a[6], a[7], q.z, q.w);
}
__device__ __forceinline__ void ld_acc(float* c, const uint4* p) { const uint4 v = ldcg128(p); c[0] = __uint_as_float(v.x); c[1] = __uint_as_float(v.y); c[2] = __uint_as_float(v.z); c[3] = __uint_as_float(v.w); }
__device__ __forceinline__ void ld_acc_if(float* c, const uint4* p, bool on) {
    c[0] = c[1] = c[2] = c[3] = 0;
    asm volatile("{.reg .pred p; setp.ne.u32 p,%5,0; @p ld.global.cg.v4.f32 {%0,%1,%2,%3},[%4];}" : "+f"(c[0]), "+f"(c[1]), "+f"(c[2]), "+f"(c[3]) : "l"(p), "r"((uint32_t)on) : "memory");
}
__device__ __forceinline__ void st_acc(uint4* p, const float* c) { *p = make_uint4(__float_as_uint(c[0]), __float_as_uint(c[1]), __float_as_uint(c[2]), __float_as_uint(c[3])); }
__device__ __forceinline__ float sum8(const uint4* v, int k) {
#define VK(i) __uint_as_float(k == 0 ? v[i].x : k == 1 ? v[i].y : k == 2 ? v[i].z : v[i].w)
    return ((VK(0) + VK(1)) + (VK(2) + VK(3))) + ((VK(4) + VK(5)) + (VK(6) + VK(7)));
}
__device__ __forceinline__ void conv_mid(float (*acc)[4], const uint4* win, uint32_t ta) {
#pragma unroll
    for (int m = 3; m >= 0; m--) {
        const uint4 a = lds128(ta + m * 448), e = lds128(ta + m * 448 + 224);
#pragma unroll
        for (int r = 0; r < 4; r++) mma16(acc[r], a.x, a.y, a.z, a.w, win[4 + r - m].x, win[4 + r - m].y);
#pragma unroll
        for (int r = 0; r < 4; r++) mma16(acc[r], e.x, e.y, e.z, e.w, win[4 + r - m].z, win[4 + r - m].w);
    }
}
template <int XW, class F>
__device__ __forceinline__ float4 conv_stats(uint32_t sb, uint32_t l16, const float* x, uint4* gs, int q, int w, F&& meanwhile) {
    float s0 = 0, s1 = 0, m0 = 0, m1 = 0;
#pragma unroll
    for (int i = 0; i < 8; i++) { s0 += x[2 * i]; s1 += x[2 * i + 1]; m0 = fmaf(x[2 * i], x[2 * i], m0); m1 = fmaf(x[2 * i + 1], x[2 * i + 1], m1); }
    sts128(l16 + C_ST + w * 512, __float_as_uint(s0), __float_as_uint(m0), __float_as_uint(s1), __float_as_uint(m1));
    if (w == XW) {
        bar_sync(2, 256);
        uint4 v[8];
#pragma unroll
        for (int i = 0; i < 8; i++) v[i] = lds128(l16 + C_ST + i * 512);
        st_rlx128(gs + q * 32, __float_as_uint(sum8(v, 0)), __float_as_uint(sum8(v, 1)) & 0x7fffffffu, __float_as_uint(sum8(v, 2)), __float_as_uint(sum8(v, 3)));
    } else bar_arrive(2, 256);
    meanwhile();
    if (w == XW) {
        uint4 v[8];
        int n = 0;
        while (true) {
            uint32_t bad = 0;
#pragma unroll
            for (int i = 0; i < 8; i++) v[i] = ld_rlx128(gs + i * 32);
#pragma unroll
            for (int i = 0; i < 8; i++) bad |= v[i].y;
            if (!__any_sync(0xffffffffu, bad >> 31)) break;
            if (++n > 2000000) __trap();
        }
        s0 = sum8(v, 0) * (1.f / 512.f); s1 = sum8(v, 2) * (1.f / 512.f);
        const float2 l0 = ln_finish(s0, fmaxf(fmaf(sum8(v, 1), 1.f / 512.f, -s0 * s0), 0.f)), l1 = ln_finish(s1, fmaxf(fmaf(sum8(v, 3), 1.f / 512.f, -s1 * s1), 0.f));
        sts128(l16 + C_ST + 4096, __float_as_uint(l0.x), __float_as_uint(rcp(l0.y)), __float_as_uint(l1.x), __float_as_uint(rcp(l1.y)));
    }
    bar_sync(3, 256);
    const uint4 r = lds128(l16 + C_ST + 4096);
    return make_float4(__uint_as_float(r.x), __uint_as_float(r.y), __uint_as_float(r.z), __uint_as_float(r.w));
}

__device__ __forceinline__ void conv_tile(const Params& p, uint32_t sb, int q, int w) {
    const int lane = __shfl_sync(0xffffffffu, threadIdx.x & 31, threadIdx.x & 31), g = lane >> 2, c = lane & 3, tile = q * 8 + w;
    const uint32_t l16 = sb + lane * 16;
#pragma unroll
    for (int i = 0; i < 16; i++) sts128(l16 + C_UR + w * 8192 + i * 512, 0, 0, 0, 0);
    wait_cnt_warp(g_gate, lds32(sb + S_GATE));
    if (lane < 8) bulk_g2s(sb + C_TB + (w * 8 + lane) * 800, g_P + (tile * 8 + lane) * PROW + 72, 800, sb + B_BAR + CB_TB * 8, POL_N);
    uint32_t A[8][8];
#pragma unroll
    for (int k = 0; k < 8; k++)
#pragma unroll
        for (int j = 0; j < 8; j++) A[k][j] = __ldcg(g_P + (tile * 8 + k) * PROW + 16 + 8 * j + g - 2 * c);
    if (lane == 0) { const uint4 d = __ldg((const uint4*)p.Dskip + tile); sts128(sb + C_ST + 4608 + w * 16, d.x, d.y, d.z, d.w); }
    float acc[8][4];
#pragma unroll
    for (int k = 0; k < 8; k++) acc[k][0] = acc[k][1] = acc[k][2] = acc[k][3] = 0;
    const uint32_t row = sb + C_UR + w * 8192, to = (8 + g - 2 * c) * 4, qo = (lane & 7) * 16 - (lane >> 3) * 32;
    auto near = [&](int z, int m) {
        const uint32_t qa = row + ((qo + z * 128) & 1023);
#pragma unroll
        for (int k = 0; k < 8; k++) {
            uint32_t a[8];
#pragma unroll
            for (int j = 0; j < 8; j++) a[j] = lds32(to + (sb + C_TB + w * 6400 + (m - 1) * 256) + k * 800 + j * 32);
            mma_q(acc[k], a, ldsm4(qa + k * 1024));
        }
    };
    bar_sync(4, 384);
    mbar_wait(sb + B_BAR + CB_TB * 8, 0);
#pragma unroll 1
    for (int b = 0; b < 32; b++) {
        const int lz = lane + (b & p.zero);
        const uint4 r0 = ldcg128(g_x + x_off(b, tile, lz)), r1 = ldcg128(g_x + x_off(b, tile, lz) + 1);
#pragma unroll 1
        for (int m = w == 1 ? 3 : 2; m > (w ? 1 : 0); m--) near(b - m, m);
        PROF(threadIdx.x == 0, 2048 + b * 8);
        const uint2* pps = pp_src(b, tile, lz);
        asm volatile("" : "+l"(pps));
        wait_flag_warp(cnt_ptr(C_PP + b * 8 + q), 4);
        PROF(threadIdx.x == 0, 2048 + b * 8 + 1);
        float x[16];
        {
            const uint32_t a[4] = {r0.x, r0.y, r0.z, r0.w}, bb[4] = {r1.x, r1.y, r1.z, r1.w};
            sum_partials<4, true>(x, pps, a, bb, (2 * (lz & 3) == lz >> 2) ? 0x00003f80u : (2 * (lz & 3) + 1 == lz >> 2) ? 0x3f800000u : 0u);
        }
        float4 ln = conv_stats<0>(sb, l16, x, g_st + b * 256 + lz, q, w, [&]() {
            PROF(threadIdx.x == 0, 2048 + b * 8 + 2);
            if (w) near(b - 1, 1);
            if (b) mbar_wait(sb + B_BAR + (CB_CF + (w >> 1)) * 8, (b - 1) & 1);
            if (b < 4) return;
            const uint4* cb = g_carry + ((tile * 320 + b) * 32 + lz);
            float cr[8][4];
#pragma unroll
            for (int k = 0; k < 8; k++) ld_acc(cr[k], cb + k * 1280);
#pragma unroll
            for (int k = 0; k < 8; k++) { acc[k][0] += cr[k][0]; acc[k][1] += cr[k][1]; acc[k][2] += cr[k][2]; acc[k][3] += cr[k][3]; }
        });
        PROF(threadIdx.x == 0, 2048 + b * 8 + 3);
        uint32_t u[8];
#pragma unroll
        for (int k = 0; k < 8; k++) {
            u[k] = pack2(rbf(x[2 * k] - ln.x) * ln.y, rbf(x[2 * k + 1] - ln.z) * ln.w);
            sts32(row + k * 1024 + (b & 7) * 128 + lane * 4, u[k]);
        }
        __syncwarp();
        const uint32_t qa = row + ((qo + b * 128) & 1023);
#pragma unroll
        for (int k = 0; k < 8; k++) mma_q(acc[k], A[k], ldsm4(qa + k * 1024));
        const uint4 dk = lds128(sb + C_ST + 4608 + w * 16);
#pragma unroll
        for (int k = 0; k < 8; k++) {
            const float t = __shfl_sync(0xffffffffu, acc[k][3], (lz & ~3) | ((lz - 1) & 3));
            const uint32_t y = movm(pack2(acc[k][0] + (c ? t : 0.f), acc[k][1] + acc[k][2]));
            acc[k][0] = c ? 0.f : t; acc[k][1] = acc[k][2] = acc[k][3] = 0;
            const uint32_t dw = k >> 1 == 0 ? dk.x : k >> 1 == 1 ? dk.y : k >> 1 == 2 ? dk.z : dk.w;
            const uint32_t s = hadd2(hadd2(y, hmul2(u[k], __byte_perm(dw, 0, (k & 1) ? 0x3232 : 0x1010))), __byte_perm(__float_as_uint(x[2 * k]), __float_as_uint(x[2 * k + 1]), 0x7632));
            x[2 * k] = blo(s); x[2 * k + 1] = bhi(s);
        }
        if (lane == 0) mbar_arrive(sb + B_BAR + (CB_UF + (w >> 1)) * 8);
        ln = conv_stats<1>(sb, l16, x, g_st + (32 + b) * 256 + lz, q, w, [&]() {
            PROF(threadIdx.x == 0, 2048 + b * 8 + 4);
            uint4* dst = g_x + x_off(32 + b, tile, lz);
#pragma unroll
            for (int e = 0; e < 2; e++)
                dst[e] = make_uint4(__byte_perm(__float_as_uint(x[e]), __float_as_uint(x[2 + e]), 0x7632), __byte_perm(__float_as_uint(x[4 + e]), __float_as_uint(x[6 + e]), 0x7632),
                                    __byte_perm(__float_as_uint(x[8 + e]), __float_as_uint(x[10 + e]), 0x7632), __byte_perm(__float_as_uint(x[12 + e]), __float_as_uint(x[14 + e]), 0x7632));
            uint32_t* du = g_u + (tile * 8 * (UROW / 2) + UPRE / 2 + b * 32 + lz);
#pragma unroll
            for (int k = 0; k < 8; k++) du[k * (UROW / 2)] = u[k];
            if (w != 1) near(b - 2, 3);
        });
        PROF(threadIdx.x == 0, 2048 + b * 8 + 5);
        uint4* dst = g_xn + x_off(32 + b, tile, lz);
#pragma unroll
        for (int e = 0; e < 2; e++) {
            const float mu = e ? ln.z : ln.x, rs = e ? ln.w : ln.y;
            dst[e] = make_uint4(pack2(rbf(x[e] - mu) * rs, rbf(x[2 + e] - mu) * rs), pack2(rbf(x[4 + e] - mu) * rs, rbf(x[6 + e] - mu) * rs),
                                pack2(rbf(x[8 + e] - mu) * rs, rbf(x[10 + e] - mu) * rs), pack2(rbf(x[12 + e] - mu) * rs, rbf(x[14 + e] - mu) * rs));
        }
        if (w == 7) {
            bar_sync(5, 256);
            if (lane == 0) red_release(cnt_ptr(C_XN + 32 + b), 1);
            PROF(lane == 0, 2048 + b * 8 + 6);
            __syncwarp();
        } else bar_arrive(5, 256);
    }
}

template <int P0, bool TRI = false>
__device__ __forceinline__ void bg_half(float (*acc)[4], uint4* win, uint32_t ta, uint32_t qa, uint32_t mask, uint32_t row) {
#pragma unroll
    for (int i = 0; i < 4; i++) {
        win[P0 + i] = ldsm4(((qa + i * 128) & mask) + row);
        const uint4 a = lds128(ta + (3 - i) * 448), e = lds128(ta + (3 - i) * 448 + 224);
#pragma unroll
        for (int r = TRI ? 7 - P0 - i : 0; r < 8; r++) mma16(acc[r], a.x, a.y, a.z, a.w, win[(P0 + i + 1 + r) & 7].x, win[(P0 + i + 1 + r) & 7].y);
#pragma unroll
        for (int r = TRI ? 7 - P0 - i : 0; r < 8; r++) mma16(acc[r], e.x, e.y, e.z, e.w, win[(P0 + i + 1 + r) & 7].z, win[(P0 + i + 1 + r) & 7].w);
    }
}
__device__ __forceinline__ void bg_fetch(uint32_t sb, int q, int j, int n, int lane) {
    const int b0 = n >> 1, ch = q * 64 + j * 16 + (n & 1) * 8 + (b0 & 7), lo = max(b0 - 24, -4), nu = b0 > 4 ? (b0 - 4 - lo) * 128 : 0;
    const uint32_t bar = sb + B_BAR + (CB_LD + j * 2 + (n & 1)) * 8, buf = sb + C_BG + (j * 2 + (n & 1)) * CB_BIG;
    const int nt = min((b0 + 7) >> 2, 5) * 1792;
    if (lane == 0) {
        mbar_expect(bar, nt + nu + 1792);
        bulk_g2s(buf, g_W + ch * 784, nt, bar, POL_N);
        bulk_g2s(buf + CB_M, g_W + (ch ^ 4) * 784, 1792, bar, POL_N);
        if (nu) bulk_g2s(buf + CB_U + (lo - b0 + 24) * 128, g_u + ch * (UROW / 2) + UPRE / 2 + lo * 32, nu, bar, POL_N);
    }
    __syncwarp();
}
__device__ __forceinline__ void conv_back(uint32_t sb, int q, int j) {
    const int lane = __shfl_sync(0xffffffffu, threadIdx.x & 31, threadIdx.x & 31), g = lane >> 2, c = lane & 3;
    wait_cnt_warp(g_gate, lds32(sb + S_GATE));
    bg_fetch(sb, q, j, 2, lane);
    bar_sync(4, 384);
    const uint32_t to = (6 + g - 2 * c) * 16, qo = (lane & 7) * 16 - (lane >> 3) * 32;
#pragma unroll 1
    for (int n = 2; n < 64; n++) {
        const int b0 = n >> 1, i = n & 1, chl = j * 16 + i * 8 + (b0 & 7), hm = (b0 + 7) >> 2;
        const uint32_t buf = sb + C_BG + (j * 2 + i) * CB_BIG, ta = buf + to;
        float acc[8][4], ma[4][4];
        uint4 win[8];
        if (n == 34) wait_flag_warp(cnt_ptr(C_FAR), 12);
        const uint4* fr = g_far + (((q * 64 + chl) * 8 + b0 - 24) * 32 + lane);
#pragma unroll
        for (int r = 0; r < 8; r++) ld_acc_if(acc[r], fr + r * 32, (unsigned)(b0 + r - 24) < 8u);
        if (n < 63) bg_fetch(sb, q, j, n + 1, lane);
        mbar_wait(sb + B_BAR + (CB_LD + j * 2 + i) * 8, (b0 - 1) & 1);
#pragma unroll
        for (int r = 0; r < 8; r++) {
            win[r] = make_uint4(0, 0, 0, 0);
            if (r) asm volatile("{.reg .pred p; setp.ge.s32 p,%5,24; @p ldmatrix.sync.aligned.m8n8.x4.shared.b16 {%0,%1,%2,%3},[%4];}"
                                : "+r"(win[r].x), "+r"(win[r].y), "+r"(win[r].z), "+r"(win[r].w) : "r"(buf + CB_U + qo + r * 128), "r"(b0 + r) : "memory");
        }
#pragma unroll 1
        for (int h = hm > 3 ? 5 : 3; h >= 3; h -= 2) {
            if (h <= hm) bg_half<0>(acc, win, ta + (h - 1) * 1792, qo + (28 - 4 * h) * 128, ~0u, buf + CB_U);
            if (h == 3 && i == 0) mbar_wait(sb + B_BAR + (CB_UF + j) * 8, (b0 - 1) & 1);
            bg_half<4>(acc, win, ta + (h - 2) * 1792, qo + (h == 3 ? b0 - 4 : 12) * 128, h == 3 ? 1023u : ~0u, h == 3 ? sb + C_UR + chl * 1024 : buf + CB_U);
        }
        uint4* cr = g_carry + (((q * 64 + chl) * 40 + b0) * 32 + lane);
        uint4* cm = g_carry + (((q * 64 + (chl ^ 4)) * 40 + b0) * 32 + lane);
#pragma unroll
        for (int r = 0; r < 4; r++) ld_acc_if(ma[r], cm + r * 32, b0 > 4);
#pragma unroll
        for (int r = 4; r < 8; r++) st_acc(cr + r * 32, acc[r]);
        conv_mid(acc, win, ta);
#pragma unroll
        for (int r = 1; r < 8; r++) win[r] = ldsm4(sb + C_UR + (chl ^ 4) * 1024 + ((qo + (b0 + r) * 128) & 1023));
#pragma unroll
        for (int r = 0; r < 4; r++) st_acc(cr + r * 32, acc[r]);
        conv_mid(ma, win, ta + CB_M);
#pragma unroll
        for (int r = 0; r < 4; r++) st_acc(cm + r * 32, ma[r]);
        __syncwarp();
        if (lane == 0 && i) mbar_arrive(sb + B_BAR + (CB_CF + j) * 8);
        PROF(j == 0 && lane == 0 && i, 2048 + b0 * 8 + 7);
    }
}
__device__ __forceinline__ void conv_far(uint32_t sb, int w) {
    const int lane = threadIdx.x & 31, g = lane >> 2, c = lane & 3;
    wait_cnt_warp(g_gate, lds32(sb + S_GATE));
    wait_cnt_warp(cnt_ptr(C_XN + 39), 8);
    const uint32_t to = (6 + g - 2 * c) * 16, qo = (lane & 7) * 16 - (lane >> 3) * 32;
#pragma unroll 1
    for (int n = -1; n * 12 + w < 512; n++) {
        const int ch = n * 12 + w;
        const uint32_t bar = sb + B_BAR + (w * 2 + (n & 1)) * 8, buf = sb + (w * 2 + (n & 1)) * 5120;
        if (lane == 0 && ch + 12 < 512) {
            const uint32_t nb = sb + (w * 2 + (~n & 1)) * 5120;
            mbar_expect(bar ^ 8, 3584 + 1152);
            bulk_g2s(nb, g_W + (ch + 12) * 784 + 560, 3584, bar ^ 8, POL_N);
            bulk_g2s(nb + 3584, g_u + (ch + 12) * (UROW / 2) + UPRE / 2 - 32, 1152, bar ^ 8, POL_N);
        }
        __syncwarp();
        if (n < 0) continue;
        float acc[8][4];
        uint4 win[8];
#pragma unroll
        for (int r = 0; r < 8; r++) { acc[r][0] = acc[r][1] = acc[r][2] = acc[r][3] = 0; win[r] = make_uint4(0, 0, 0, 0); }
        mbar_wait(bar, (n >> 1) & 1);
        bg_half<0, true>(acc, win, buf + to + 1792, qo + 128, ~0u, buf + 3584);
        bg_half<4, true>(acc, win, buf + to, qo + 640, ~0u, buf + 3584);
#pragma unroll
        for (int r = 0; r < 8; r++) st_acc(g_far + (ch * 8 + r) * 32 + lane, acc[r]);
        __syncwarp();
    }
    if (lane == 0) red_release(cnt_ptr(C_FAR), 1);
    PROF(threadIdx.x == 0, 2048);
}

constexpr int P_Y = 131072  , P_PRM = P_Y  , P_K6 = P_PRM + 8192  ,
              P_P = P_Y + 40960  , P_U = P_P + 33280  , P_END = P_U + 17408, P_X = 98304  ;
static_assert(P_END <= B_BAR && P_END <= R_SEL, "prologue scratch");
#define KGUN 2
constexpr int KGU = KGUN;
__device__ __forceinline__ void csq(float& r, float& i) { const float t = r * i; r = fmaf(r, r, -(i * i)); i = t + t; }
__device__ __forceinline__ void cpow(float ar, float ph, float p, float& r, float& i) {
    const float e = ex2(ar * p);
    const float u = ph * p, n = fabsf(u) < 4194304.f ? (u + 12582912.f) - 12582912.f : u;
    const float t = (u - n) * 6.283185307179586f;
    r = e * __cosf(t); i = e * __sinf(t);
}
__device__ __forceinline__ void mma_tf32(float* c, float a0, float a1, float a2, float a3, float b0, float b1) {
    asm volatile("mma.sync.aligned.m16n8k8.row.col.f32.tf32.tf32.f32 {%0,%1,%2,%3},{%4,%5,%6,%7},{%8,%9},{%0,%1,%2,%3};"
                 : "+f"(c[0]), "+f"(c[1]), "+f"(c[2]), "+f"(c[3])
                 : "r"(__float_as_uint(a0)), "r"(__float_as_uint(a1)), "r"(__float_as_uint(a2)), "r"(__float_as_uint(a3)), "r"(__float_as_uint(b0)), "r"(__float_as_uint(b1)));
}

struct ProRegs { uint32_t v[2][4], ldt[2]; };
__device__ __forceinline__ void prologue_load(const ProArgs& a, int b, ProRegs& pr) {
    const int w = threadIdx.x >> 5;
#pragma unroll
    for (int i = 0; i < 2; i++) {
        const int gi = b * 512 + (w & 3) * 128 + ((w >> 2) & 1) * 64 + i * 32 + (threadIdx.x & 31);
        pr.ldt[i] = __ldg((const uint16_t*)a.ldt + b * 4 + (w & 3));
        pr.v[i][0] = __ldg((const uint16_t*)a.lAr + gi); pr.v[i][1] = __ldg((const uint16_t*)a.Ai + gi);
        pr.v[i][2] = __ldg((const uint16_t*)a.Cr + gi); pr.v[i][3] = __ldg((const uint16_t*)a.Ci + gi);
    }
}
__device__ __forceinline__ void prologue(const ProArgs& a, uint32_t sb, int b, int w, const ProRegs& pr) {
    const int tid = threadIdx.x, lane = tid & 31, g = lane >> 2, c = lane & 3;
    const int d0 = b * 4;
    if (w >= 8) {
        const int t2 = tid - 256;
        if (w < 10) {
            const int row = b * 16 + (w - 8) * 8 + g;
            uint4 v[16];
            const float2 r = row_stats512(v, (const uint4*)(a.x + (size_t)row * 512) + c, 8, 4);
            const float2 l = ln_finish(r.x * (1.f / 512.f), r.y * (1.f / 512.f));
            if (c == (g >> 1)) asm volatile("st.relaxed.gpu.global.u32 [%0],%1;" ::"l"(g_ln0 + row), "r"(pack2(l.x, l.y)) : "memory");
        }
        PROF(t2 == 0, 3516);
        const int gi = b * 128 + t2;
#pragma unroll 1
        for (int k = gi; k < 133 * 512; k += 16384) g_xch[k] = make_uint4(0, 0, 0, 0);
        g_st[gi] = make_uint4(~0u, ~0u, ~0u, ~0u);
        if (gi < 900 * 8) g_cnt[gi] = 0;
        if (gi < 64) g_sel[gi] = 0;
        bar_sync(6, 384);
        if (lane < 4) asm volatile("cp.async.bulk.prefetch.L2.global [%0],%1;" ::"l"(a.W[w - 8] + (b * 4 + lane) * 4096), "r"(8192) : "memory");
        bar_sync(9, 384);
#pragma unroll 2
        for (int i = t2; i < 4 * 784; i += 128) {
            const int ch = i / 784, k = i - ch * 784;
            const uint32_t o = sb + P_P + (ch * 2080 + 266 + (k / 14) * 18 + k) * 4;
            g_W[d0 * 784 + i] = make_uint4(lds32(o), lds32(o + 32), lds32(o + 64), lds32(o + 96));
        }
        bar_arrive(10, 384);
        PROF(t2 == 0, 3517);
        return;
    }
#pragma unroll
    for (int i = 0; i < 2; i++) {
        const float dt = rbf(expf(blo(pr.ldt[i])));
        const float ar = -rbf(expf(blo(pr.v[i][0]))) * dt, ai = blo(pr.v[i][1]) * dt;
        sts128(sb + P_PRM + (w * 64 + i * 32 + lane) * 16, __float_as_uint(ar * 1.4426950408889634f), __float_as_uint(ai * 0.15915494309189535f),
               __float_as_uint(2.f * (blo(pr.v[i][2]) * dt)), __float_as_uint(2.f * (blo(pr.v[i][3]) * dt)));
    }
    if (tid < 64) sts128(sb + P_U + (tid >> 3) * 2176 + (tid & 7) * 16, 0, 0, 0, 0);
    bar_arrive(6, 384);
    __syncwarp();
    PROF(tid == 0, 3510);
    const int ch = w & 3, hf = w >> 2;
    {
        float k0[4] = {0, 0, 0, 0}, k1[4] = {0, 0, 0, 0}, k2[4] = {0, 0, 0, 0}, k3[4] = {0, 0, 0, 0}, k4[4] = {0, 0, 0, 0}, kl = 0;
#pragma unroll KGU
        for (int j = 0; j < 16; j++) {
            const uint4 q = lds128(sb + P_PRM + (w * 64 + j * 4 + c) * 16);
            const float cr = __uint_as_float(q.z), ci = __uint_as_float(q.w);
            float wr[4], wi[4], vr[4], vi[4];
            cpow(__uint_as_float(q.x), __uint_as_float(q.y), (float)g, wr[0], wi[0]);
            cpow(__uint_as_float(q.x), __uint_as_float(q.y), (float)(g + 8), vr[0], vi[0]);
#pragma unroll
            for (int i = 1; i < 4; i++) { wr[i] = wr[i - 1]; wi[i] = wi[i - 1]; csq(wr[i], wi[i]); vr[i] = vr[i - 1]; vi[i] = vi[i - 1]; csq(vr[i], vi[i]); }
            float hr = wr[3], hi = wi[3];
            csq(hr, hi);
            mma_tf32(k0, wr[0], vr[0], wi[0], vi[0], cr * hr - ci * hi, -(cr * hi + ci * hr));
            hr = vr[3]; hi = vi[3]; csq(hr, hi);
            mma_tf32(k1, wr[0], vr[0], wi[0], vi[0], cr * hr - ci * hi, -(cr * hi + ci * hr));
            csq(hr, hi);
            mma_tf32(k2, wr[1], vr[1], wi[1], vi[1], cr * hr - ci * hi, -(cr * hi + ci * hr));
            csq(hr, hi);
            mma_tf32(k3, wr[2], vr[2], wi[2], vi[2], cr * hr - ci * hi, -(cr * hi + ci * hr));
            csq(hr, hi);
            mma_tf32(k4, wr[3], vr[3], wi[3], vi[3], cr * hr - ci * hi, -(cr * hi + ci * hr));
            csq(hr, hi);
            kl += cr * hr - ci * hi;
        }
        kl += __shfl_xor_sync(0xffffffffu, kl, 1); kl += __shfl_xor_sync(0xffffffffu, kl, 2);
        const uint32_t o = sb + P_K6 + (ch * 656 + c * 32 + g) * 4, ol = sb + P_K6 + (ch * 656 + 640) * 4;
#define KST(k, base) sts32(o + (base) * 4, __float_as_uint(k[0])); sts32(o + (base) * 4 + 64, __float_as_uint(k[1])); \
                     sts32(o + (base) * 4 + 32, __float_as_uint(k[2])); sts32(o + (base) * 4 + 96, __float_as_uint(k[3]))
#define KAD(k, base) k[0] += __uint_as_float(lds32(o + (base) * 4)); k[1] += __uint_as_float(lds32(o + (base) * 4 + 64)); \
                     k[2] += __uint_as_float(lds32(o + (base) * 4 + 32)); k[3] += __uint_as_float(lds32(o + (base) * 4 + 96))
        if (hf == 0) {
            bar_sync(2 + ch, 64);
            KAD(k0, 0); KAD(k1, 128); KAD(k2, 256); KAD(k3, 384); KAD(k4, 512);
            kl += __uint_as_float(lds32(ol));
            __syncwarp();
        }
        KST(k0, 0); KST(k1, 128); KST(k2, 256); KST(k3, 384); KST(k4, 512);
        if (lane == 0) sts32(ol, __float_as_uint(kl));
        if (hf == 1) { __syncwarp(); bar_arrive(2 + ch, 64); }
    }
    PROF(tid == 0, 3511);
    {
        uint4 l0, l1;
        int n = 0;
        while (true) {
            l0 = ld_rlx128((const uint4*)g_ln0 + tid * 2); l1 = ld_rlx128((const uint4*)g_ln0 + tid * 2 + 1);
            if (__all_sync(0xffffffffu, l0.x && l0.y && l0.z && l0.w && l1.x && l1.y && l1.z && l1.w)) break;
            if (++n > 2000000) __trap();
        }
        sts128(sb + P_P + tid * 32, l0.x, l0.y, l0.z, l0.w); sts128(sb + P_P + tid * 32 + 16, l1.x, l1.y, l1.z, l1.w);
        bar_sync(8, 384);
        mbar_wait(sb + S_XBAR, 0);
        __syncwarp();
#pragma unroll 2
        for (int i = 0; i < 8; i++) {
            const int t = w * 256 + i * 32 + lane;
            const uint32_t ln = lds32(sb + P_P + t * 4);
            const uint2 x = lds64(sb + P_X + t * 16 + (b & 1) * 8);
            const float m = blo(ln), rs = rcp(bhi(ln));
            const uint32_t u0 = pack2(rbf(blo(x.x) - m) * rs, rbf(bhi(x.x) - m) * rs), u1 = pack2(rbf(blo(x.y) - m) * rs, rbf(bhi(x.y) - m) * rs);
            sts128(sb + P_X + t * 16, x.x, x.y, u0, u1);
            const uint32_t o = sb + P_U + ((t >> 3) & 1) * 2176 + ((t >> 4) + 8) * 16 + (t & 7) * 2;
            asm volatile("st.shared.u16 [%0],%1;" ::"r"(o), "h"((uint16_t)u0) : "memory");
            asm volatile("st.shared.u16 [%0],%1;" ::"r"(o + 4352), "h"((uint16_t)(u0 >> 16)) : "memory");
            asm volatile("st.shared.u16 [%0],%1;" ::"r"(o + 8704), "h"((uint16_t)u1) : "memory");
            asm volatile("st.shared.u16 [%0],%1;" ::"r"(o + 13056), "h"((uint16_t)(u1 >> 16)) : "memory");
        }
    }
    bar_sync(1, 256);
    PROF(tid == 0, 3512);
    if (tid < 64) sts32(sb + P_P + ((tid >> 4) * 2080 + (tid & 15)) * 4, 0);
#pragma unroll 1
    for (int x = tid; x < 2048; x += 512) {
        uint32_t pw[2][4];
#pragma unroll
        for (int h = 0; h < 2; h++) {
            const int y = x + h * 256;
            const int i0 = y <= 256 ? y : 256 + (int)((pack2((float)y, 0.f) & 0xffff) - 0x4380);
            const int i1 = y <= 256 ? max(y - 1, 0) : 256 + (int)((pack2((float)(y - 1), 0.f) & 0xffff) - 0x4380);
#pragma unroll
            for (int k = 0; k < 4; k++) {
                const float lo = __uint_as_float(lds32(sb + P_K6 + k * 2624 + i0 * 4)), hi = __uint_as_float(lds32(sb + P_K6 + k * 2624 + i1 * 4));
                pw[h][k] = pack2(lo, y ? hi : 0.f);
            }
        }
#pragma unroll
        for (int h = 0; h < 2; h++)
#pragma unroll
            for (int k = 0; k < 4; k++) sts32(sb + P_P + (k * 2080 + x + h * 256 + 16) * 4, pw[h][k]);
    }
    fence_async_smem();
    bar_arrive(9, 384);
    bar_sync(1, 256);
    if (tid < 4) {
        asm volatile("cp.async.bulk.global.shared::cta.bulk_group [%0],[%1],%2;" ::"l"(g_P + (d0 + tid) * PROW), "r"(sb + P_P + tid * 8320), "r"(PROW * 4) : "memory");
        asm volatile("cp.async.bulk.commit_group;" ::: "memory");
    }
    __syncwarp();
    PROF(tid == 0, 3513);
    {
        float acc[16][4];
#pragma unroll
        for (int j = 0; j < 16; j++) acc[j][0] = acc[j][1] = acc[j][2] = acc[j][3] = 0;
#pragma unroll 1
        for (int e = hf * 4; e < hf * 4 + 4; e++) {
            uint32_t B[16][2];
            const uint32_t ua = sb + P_U + ch * 4352 + ((lane >> 3) & 1) * 2176 + (8 + (lane >> 4) * 8 + (lane & 7) - e) * 16;
#pragma unroll
            for (int j = 0; j < 8; j++) { const uint4 v = ldsm4(ua + j * 256); B[2 * j][0] = v.x; B[2 * j][1] = v.y; B[2 * j + 1][0] = v.z; B[2 * j + 1][1] = v.w; }
            const uint32_t pa = sb + P_P + (ch * 2080 + 16 + e * 16 + g - 2 * c) * 4;
#pragma unroll
            for (int d = 0; d < 16; d++) {
                const uint32_t a0 = lds32(pa + d * 512), a1 = lds32(pa + d * 512 + 32), a2 = lds32(pa + d * 512 - 32);
#pragma unroll
                for (int j = d; j < 16; j++) mma16(acc[j], a0, a1, a2, a0, B[j - d][0], B[j - d][1]);
            }
        }
        PROF(tid == 0, 3514);
        const uint32_t o = sb + P_Y + (ch * 2560 + c * 40 + g) * 4;
        if (hf == 0) {
            bar_sync(2 + ch, 64);
#pragma unroll
            for (int j = 0; j < 16; j++) {
                acc[j][0] += __uint_as_float(lds32(o + j * 640)); acc[j][1] += __uint_as_float(lds32(o + j * 640 + 80));
                acc[j][2] += __uint_as_float(lds32(o + j * 640 + 32)); acc[j][3] += __uint_as_float(lds32(o + j * 640 + 112));
            }
        }
#pragma unroll
        for (int j = 0; j < 16; j++) {
            sts32(o + j * 640, __float_as_uint(acc[j][0])); sts32(o + j * 640 + 80, __float_as_uint(acc[j][1]));
            sts32(o + j * 640 + 32, __float_as_uint(acc[j][2])); sts32(o + j * 640 + 112, __float_as_uint(acc[j][3]));
        }
        if (hf == 1) bar_arrive(2 + ch, 64);
    }
    const uint2 dk = __ldg((const uint2*)(a.Dk + d0));
    bar_sync(10, 384);
#pragma unroll 2
    for (int i = 0; i < 8; i++) {
        const int t = i * 256 + tid;
        const uint32_t o = sb + P_Y + (t + 4 * (t >> 4)) * 4;
        const uint4 xu = lds128(sb + P_X + t * 16);
        float y[4];
#pragma unroll
        for (int k = 0; k < 4; k++) y[k] = rbf(__uint_as_float(lds32(o + k * 10240)));
        uint2 r;
        r.x = pack2(blo(xu.x) + rbf(y[0] + rbf(blo(xu.z) * blo(dk.x))), bhi(xu.x) + rbf(y[1] + rbf(bhi(xu.z) * bhi(dk.x))));
        r.y = pack2(blo(xu.y) + rbf(y[2] + rbf(blo(xu.w) * blo(dk.y))), bhi(xu.y) + rbf(y[3] + rbf(bhi(xu.w) * bhi(dk.y))));
        ((uint2*)(g_x + ((t >> 6) * 8 + (d0 >> 6)) * 512 + ((t & 63) >> 3) * 64 + ((d0 & 63) >> 3) * 8 + (t & 7)))[(d0 >> 2) & 1] = r;
    }
    PROF(tid == 0, 3515);
    if (tid < 4) asm volatile("cp.async.bulk.wait_group 0;" ::: "memory");
}

__device__ __forceinline__ int pick_role(int cl, uint32_t rank, int rec0) {
    const int lane = threadIdx.x & 31;
    unsigned ep;
    asm volatile("ld.relaxed.gpu.global.u32 %0,[%1];" : "=r"(ep) : "l"(g_gate) : "memory");
    ep = (ep / (4 * NCL) + 1) * 2;
    if (rank == 0) {
        unsigned* r = (unsigned*)(((size_t)g_probe + 8191) & ~(size_t)8191) + cl * 8;
        uint32_t b0 = ~0u, b1 = ~0u;
#pragma unroll 1
        for (int i = 0; i < 6; i++) { b0 = min(b0, probe1(r, lane)); b1 = min(b1, probe1(r + 1024, lane)); }
        if (lane == 0) asm volatile("st.relaxed.gpu.global.u32 [%0],%1;" ::"l"(g_side + cl), "r"(ep + (b1 < b0)) : "memory");
    }
    uint32_t m[3];
#pragma unroll
    for (int i = 0; i < 3; i++) {
        unsigned v; int n = 0;
        const bool on = i * 32 + lane < NCL;
        while (true) {
            asm volatile("ld.relaxed.gpu.global.u32 %0,[%1];" : "=r"(v) : "l"(g_side + i * 32 + lane) : "memory");
            if (__all_sync(0xffffffffu, !on || (v & ~1u) == ep)) break;
            if (++n > 2000000) __trap();
        }
        m[i] = __ballot_sync(0xffffffffu, on && (v & 1));
    }
    if (__popc(m[0]) + __popc(m[1]) + __popc(m[2]) < NCL / 2) { m[0] = ~m[0]; m[1] = ~m[1]; m[2] = ~m[2] & 3; }
    const int tot = __popc(m[0]) + __popc(m[1]) + __popc(m[2]);
    int below = 0;
#pragma unroll
    for (int i = 0; i < 3; i++) below += __popc(m[i] & (cl >= i * 32 + 32 ? ~0u : cl <= i * 32 ? 0u : (1u << (cl - i * 32)) - 1));
    const bool mine = ((cl < 32 ? m[0] : cl < 64 ? m[1] : m[2]) >> (cl & 31)) & 1;
    const int skip = tot - 32;
    if (mine && below >= skip) return rec0 + below - skip;
    const int j = cl - max(below - skip, 0);
    return j < rec0 ? j : j + 32;
}

__global__ void __cluster_dims__(2, 1, 1) __launch_bounds__(384, 1) main_kernel(const __grid_constant__ Params p) {
    extern __shared__ __align__(1024) uint8_t smem[];
    const uint32_t sb = smem_u32(smem);
    uint32_t rank; asm("mov.u32 %0,%%cluster_ctarank;" : "=r"(rank));
    const int wi = __shfl_sync(0xffffffffu, threadIdx.x >> 5, 0);
    const int cl = blockIdx.x >> 1, wg = wi >> 2;
    PROF(threadIdx.x == 0, 3500);
    ProRegs pr;
    prologue_load(p.pa, max((int)blockIdx.x - 4, 0), pr);
    if (threadIdx.x == 352 && p.dopro && cl >= 2) {
        mbar_init(sb + S_XBAR, 1);
        asm volatile("fence.mbarrier_init.release.cluster;" ::: "memory");
        mbar_expect(sb + S_XBAR, 32768);
        for (int j = 0; j < 8; j++) tma2d(sb + P_X + j * 4096, &p.tm[3], ((blockIdx.x - 4) >> 1) * 8, j * 256, sb + S_XBAR);
    }
    if (threadIdx.x == 320) {
        unsigned v = 0;
        if (p.dopro) {
            asm volatile("ld.relaxed.gpu.global.u32 %0,[%1];" : "=r"(v) : "l"(g_gate) : "memory");
            v = (v / (4 * NCL) + 1) * (4 * NCL);
        }
        sts32(sb + S_GATE, v);
    }
    __syncwarp();
    if (wg == 2) bar_arrive(8, 384);
    if (wi == 10) {
        const int v = blockIdx.x;
        sts32(sb + S_VCL, v);
        if (v < V_REC || v == 131) conv_init(sb, v == 131); else if (v < V_OP) rec_init(sb); else gemm_init(sb, v < V_QKV);
        __syncwarp();
        if (threadIdx.x == 320 && v >= V_QKV && v < V_QKV + NQ && (p.roles & 8)) qkv_fetch(p, sb, v - V_QKV, 0, Q_PRE);
        __syncwarp();
        asm volatile("barrier.cluster.arrive.aligned;" ::: "memory");
    } else asm volatile("barrier.cluster.arrive.relaxed.aligned;" ::: "memory");
    if (p.dopro && cl >= 2) prologue(p.pa, sb, blockIdx.x - 4, wi, pr); else if (wg < 2) bar_sync(8, 384);
    asm volatile("barrier.cluster.wait.aligned;" ::: "memory");
    const int v = __shfl_sync(0xffffffffu, lds32(sb + S_VCL), 0);
    const int role = (v < V_REC ? 1 : v < V_OP ? 2 : v < V_QKV ? 4 : v < V_QKV + NQ ? 24 : 1) & p.roles;
    fence_async_smem();
    bar_sync(wg == 2 ? 7 : 1, wg == 2 ? 128 : 256);
    if (p.dopro && (threadIdx.x == 32 || threadIdx.x == 352)) red_release(g_gate, 1);
    if (threadIdx.x == 0) {
        if (role == 2) { rec_fetch(p, sb, (v - V_REC) >> 1, rank, 0, R_STQ); rec_fetch(p, sb, (v - V_REC) >> 1, rank, 1, R_STK); }
        if (role & 12) gemm_stage(p, sb, v - (role == 4 ? V_OP : V_QKV), role == 4);
    }
    PROF(threadIdx.x == 0, 3506);
    __syncwarp();
    if (role == 2) {
        const int head = (v - V_REC) >> 1;
        if (wg == 2) {
            reg_dec<RH>();
            const int w = wi & 3;
            rec_probe(sb, head * 2 + rank, w);
            if (threadIdx.x == 256) rec_fetch(p, sb, head, rank, 2, R_WV);
            __syncwarp();
            wait_cnt_warp(g_gate, lds32(sb + S_GATE));
            rec_sides(sb, head * 2 + rank, w);
            __syncthreads();
            cluster_sync();
            if ((p.chains >> (w & 1)) & 1) { if (w < 2) rec_comm(p, sb, w, head, rank); else rec_attn(p, sb, w & 1, head, rank); }
        } else {
            reg_inc<RW0>();
            rec_weights(p, sb, head, rank, wi);
        }
    } else if (role == 1) {
        if (v == 131) conv_far(sb, wi); else if (wg == 2) { reg_dec<RCB>(); conv_back(sb, v, wi & 3); } else { reg_inc<RCU>(); conv_tile(p, sb, v, wi); }
    } else if (role == 4) {
        if (wg == 2) {
            reg_dec<40>();
            if (wi == 8) gemm_producer<true>(p, sb, v - V_OP); else if (wi == 9) gemm_release<true>(p, sb, v - V_OP);
        } else { reg_inc<232>(); gemm_consumer<true>(p, sb, v - V_OP, wi); }
    } else if (role) {
        if (wg == 2) {
            reg_dec<40>();
            if (wi < 10) {
                if (role & 8) { if (wi == 8) gemm_producer<false>(p, sb, v - V_QKV); else gemm_release<false>(p, sb, v - V_QKV); }
            } else if (v < V_QKV + 32 && (role & 16)) fin_warp(p, sb, (v - V_QKV) * 2 + wi - 10);
        } else { reg_inc<232>(); if (role & 8) gemm_consumer<false>(p, sb, v - V_QKV, wi); }
    }
    __syncwarp();
    cluster_sync();
}

typedef CUresult (*EncFn)(CUtensorMap*, CUtensorMapDataType, cuuint32_t, void*, const cuuint64_t*, const cuuint64_t*, const cuuint32_t*, const cuuint32_t*,
                          CUtensorMapInterleave, CUtensorMapSwizzle, CUtensorMapL2promotion, CUtensorMapFloatOOBfill);
constexpr int SMEM_BYTES = 232448;
#define LAG 9
#define QLEAD 6
#define OLEAD (LAG / 2 + 2)
void plan(Params& P) {
    P.roles = 31; P.chains = 3; P.lag = LAG; P.dopro = 1;
    for (int r = 0; r < 2; r++) {
        const int lead = r ? OLEAD : QLEAD;
        int n = 0;
        for (int i = 0; i < 32 + lead; i++) {
            if (i >= lead) P.list[r][n++] = 32 + i - lead;
            if (i < 32) P.list[r][n++] = i;
        }
        P.nl[r] = n;
    }
}

#define TK() do {} while (0)
}

extern "C" void kernel_launch(void* const* d_in, const int* in_sizes, int n_in, void* d_out, int out_size) {
    typedef const __nv_bfloat16* BP;
    static EncFn enc = nullptr;
    if (!enc) {
        void* fn = nullptr; cudaDriverEntryPointQueryResult qr;
        cudaGetDriverEntryPoint("cuTensorMapEncodeTiled", &fn, cudaEnableDefault, &qr);
        enc = (EncFn)fn;
        cudaFuncSetAttribute(main_kernel, cudaFuncAttributeMaxDynamicSharedMemorySize, SMEM_BYTES);
    }
    static Params P;
    for (int i = 0; i < 4; i++) {
        const cuuint64_t cols = i < 3 ? 4096 : 512, rows = i < 3 ? 512 : 4096;
        cuuint64_t d2[2] = {cols, rows}, str[1] = {cols * 2};
        cuuint32_t box[2] = {64, 64}, bn[2] = {16, 256}, es[2] = {1, 1};
        enc(&P.tm[i < 3 ? i : 4], CU_TENSOR_MAP_DATA_TYPE_BFLOAT16, 2, d_in[9 + i], d2, str, box, es, CU_TENSOR_MAP_INTERLEAVE_NONE, CU_TENSOR_MAP_SWIZZLE_128B,
            CU_TENSOR_MAP_L2_PROMOTION_L2_128B, CU_TENSOR_MAP_FLOAT_OOB_FILL_NONE);
        if (i < 2) enc(&P.tn[i], CU_TENSOR_MAP_DATA_TYPE_BFLOAT16, 2, d_in[9 + i], d2, str, bn, es, CU_TENSOR_MAP_INTERLEAVE_NONE, CU_TENSOR_MAP_SWIZZLE_32B,
                       CU_TENSOR_MAP_L2_PROMOTION_L2_128B, CU_TENSOR_MAP_FLOAT_OOB_FILL_NONE);
    }
    {
        cuuint64_t dims[2] = {512, 2048}, str[1] = {1024};
        cuuint32_t box[2] = {8, 256}, es[2] = {1, 1};
        enc(&P.tm[3], CU_TENSOR_MAP_DATA_TYPE_BFLOAT16, 2, d_in[0], dims, str, box, es, CU_TENSOR_MAP_INTERLEAVE_NONE, CU_TENSOR_MAP_SWIZZLE_NONE,
            CU_TENSOR_MAP_L2_PROMOTION_NONE, CU_TENSOR_MAP_FLOAT_OOB_FILL_NONE);
    }
    P.mem0 = (BP)d_in[8]; P.Wo = (BP)d_in[12]; P.Dskip = (BP)d_in[6]; P.out = (__nv_bfloat16*)d_out;
    cudaStream_t s = cudaStreamPerThread;
    P.pa = {(BP)d_in[0], (BP)d_in[1], (BP)d_in[2], (BP)d_in[3], (BP)d_in[4], (BP)d_in[5], (BP)d_in[6], {(BP)d_in[9], (BP)d_in[10], (BP)d_in[11], (BP)d_in[12]}};
    plan(P);
    TK(); main_kernel<<<2 * NCL, 384, SMEM_BYTES, s>>>(P); TK();
}
```

```cpp
#include <cuda_runtime.h>
#include <cuda_bf16.h>
#include <cuda.h>
#include <stdint.h>
#include <string.h>
#include <math.h>

namespace {

constexpr int NCL = 66;
constexpr int NQ = 43;
constexpr int V_REC = 8, V_OP = 72, V_QKV = 88;

__device__ uint4 g_x[64 * 4096];
__device__ uint4 g_xn[64 * 4096];
__device__ uint4 g_st[64 * 256];
__device__ uint4 g_qkv[128 * 32 * 1536];
__device__ uint4 g_o[64 * 64 * 512];
__device__ uint4 g_pp[64 * 4 * 4096];
__device__ uint4 g_xch[133 * 512];
__device__ unsigned g_sel[64];
__device__ unsigned g_side[96];
__device__ unsigned g_probe[4096];
__device__ unsigned g_gate[32];
__device__ __align__(16) uint32_t g_P[512 * 272];
__device__ uint4 g_W[512 * 784];
__device__ __align__(16) uint32_t g_u[512 * 1152];
__device__ uint2 g_carry[512 * 40 * 32];
__device__ uint2 g_far[512 * 8 * 32];
__device__ unsigned g_cnt[900 * 8];
__device__ uint32_t g_ln0[2048];

enum { C_XN = 0  , C_QKV = 64  , C_O = 128  , C_PP = 384  , C_FAR = 896 };
__device__ __forceinline__ unsigned* cnt_ptr(int i) { return g_cnt + i * 8; }

struct ProArgs { const __nv_bfloat16 *x, *lAr, *Ai, *Cr, *Ci, *ldt, *Dk, *W[4]; };
struct Params {
    CUtensorMap tm[5];
    CUtensorMap tn[2];
    ProArgs pa;
    int dopro;
    const __nv_bfloat16* mem0;
    const __nv_bfloat16* Wo;
    const __nv_bfloat16* Dskip;
    __nv_bfloat16* out;
    int roles;
    int chains;
    int lag;
    int zero;
    int nl[2];
    uint8_t list[2][64];
};

__device__ __forceinline__ uint32_t smem_u32(const void* p) { return (uint32_t)__cvta_generic_to_shared(p); }
__device__ __forceinline__ uint32_t mapa(uint32_t a, uint32_t r) {
    uint32_t o; asm("mapa.shared::cluster.u32 %0,%1,%2;" : "=r"(o) : "r"(a), "r"(r)); return o;
}
__device__ __forceinline__ void mbar_init(uint32_t b, int c) { asm volatile("mbarrier.init.shared::cta.b64 [%0],%1;" ::"r"(b), "r"(c) : "memory"); }
__device__ __forceinline__ void mbar_expect(uint32_t b, int bytes) { asm volatile("mbarrier.arrive.expect_tx.shared::cta.b64 _,[%0],%1;" ::"r"(b), "r"(bytes) : "memory"); }
__device__ __forceinline__ void mbar_arrive(uint32_t b) { asm volatile("mbarrier.arrive.shared::cta.b64 _,[%0];" ::"r"(b) : "memory"); }
__device__ __forceinline__ void mbar_arrive_cluster(uint32_t b) { asm volatile("mbarrier.arrive.shared::cluster.b64 _,[%0];" ::"r"(b) : "memory"); }
__device__ __forceinline__ void mbar_wait(uint32_t b, uint32_t ph) {
    asm volatile(
        "{.reg .pred p; .reg .u32 n; mov.u32 n,0;\n"
        "W%=: mbarrier.try_wait.parity.shared::cta.b64 p,[%0],%1;\n"
        "@p bra D%=;\n"
        "add.u32 n,n,1; setp.lt.u32 p,n,2000000; @p bra W%=;\n"
        "trap;\n"
        "D%=: }" ::"r"(b), "r"(ph) : "memory");
}
__device__ __forceinline__ bool wait_lds128(uint32_t b, uint32_t ph, uint32_t a, uint4& v) {
    uint32_t ok;
    asm volatile("{.reg .pred p; mbarrier.try_wait.parity.shared::cta.b64 p,[%5],%6,20000; ld.shared.v4.u32 {%0,%1,%2,%3},[%7]; selp.u32 %4,1,0,p;}"
                 : "=r"(v.x), "=r"(v.y), "=r"(v.z), "=r"(v.w), "=r"(ok) : "r"(b), "r"(ph), "r"(a) : "memory");
    return ok;
}
__device__ __forceinline__ bool wait_lds64(uint32_t b, uint32_t ph, uint32_t a, uint2& v) {
    uint32_t ok;
    asm volatile("{.reg .pred p; mbarrier.try_wait.parity.shared::cta.b64 p,[%3],%4,20000; ld.shared.v2.u32 {%0,%1},[%5]; selp.u32 %2,1,0,p;}"
                 : "=r"(v.x), "=r"(v.y), "=r"(ok) : "r"(b), "r"(ph), "r"(a) : "memory");
    return ok;
}
template <int PH> __device__ __forceinline__ void mbar_wait_c(uint32_t b) {
    asm volatile(
        "{.reg .pred p; .reg .u32 n; mov.u32 n,%2;\n"
        "W%=: mbarrier.try_wait.parity.shared::cta.b64 p,[%0],%1;\n"
        "@p bra D%=;\n"
        "add.u32 n,n,1; setp.lt.u32 p,n,2000000; @p bra W%=;\n"
        "trap;\n"
        "D%=: }" ::"r"(b), "n"(PH), "n"(PH) : "memory");
}
__device__ __forceinline__ bool elect() {
    uint32_t r; asm volatile("{.reg .pred p; elect.sync _|p,0xffffffff; selp.u32 %0,1,0,p;}" : "=r"(r)); return r;
}
__device__ __forceinline__ void bar_sync(int id, int n) { asm volatile("bar.sync %0,%1;" ::"r"(id), "r"(n) : "memory"); }
__device__ __forceinline__ void bar_arrive(int id, int n) { asm volatile("bar.arrive %0,%1;" ::"r"(id), "r"(n) : "memory"); }
__device__ __forceinline__ void cluster_sync() { asm volatile("barrier.cluster.arrive.relaxed.aligned; barrier.cluster.wait.aligned;" ::: "memory"); }
__device__ __forceinline__ void fence_async() { asm volatile("fence.proxy.async;" ::: "memory"); }
__device__ __forceinline__ void fence_async_smem() { asm volatile("fence.proxy.async.shared::cta;" ::: "memory"); }
#define EFR 1
#define EFW 2
constexpr uint64_t POL_N = 0x1000000000000000ull, POL_F = 0x12F0000000000000ull;
constexpr uint64_t POL_LAST = EFR ? POL_F : POL_N  , POL_LATE = EFW ? POL_F : POL_N  , POL_SOON = EFW > 1 ? POL_F : POL_N;
__device__ __forceinline__ void bulk_g2s(uint32_t dst, const void* src, int bytes, uint32_t bar, uint64_t pol) {
    asm volatile("cp.async.bulk.shared::cluster.global.mbarrier::complete_tx::bytes.L2::cache_hint [%0],[%1],%2,[%3],%4;" ::"r"(dst), "l"(src), "r"(bytes), "r"(bar), "l"(pol) : "memory");
}
__device__ __forceinline__ void bulk_g2s_mc(uint32_t dst, const void* src, int bytes, uint32_t bar, uint64_t pol) {
    asm volatile("cp.async.bulk.shared::cluster.global.mbarrier::complete_tx::bytes.multicast::cluster.L2::cache_hint [%0],[%1],%2,[%3],%4,%5;" ::"r"(dst), "l"(src), "r"(bytes), "r"(bar), "h"((uint16_t)3), "l"(pol) : "memory");
}
__device__ __forceinline__ void stg128(uint4* p, uint4 v, uint64_t pol) {
    asm volatile("st.global.L2::cache_hint.v4.u32 [%0],{%1,%2,%3,%4},%5;" ::"l"(p), "r"(v.x), "r"(v.y), "r"(v.z), "r"(v.w), "l"(pol));
}
__device__ __forceinline__ void stg32(uint32_t* p, uint32_t v, uint64_t pol) { asm volatile("st.global.L2::cache_hint.u32 [%0],%1,%2;" ::"l"(p), "r"(v), "l"(pol)); }
__device__ __forceinline__ uint4 ldcg128_last(const uint4* p) {
    uint4 v; asm volatile("ld.global.cg.L2::cache_hint.v4.u32 {%0,%1,%2,%3},[%4],%5;" : "=r"(v.x), "=r"(v.y), "=r"(v.z), "=r"(v.w) : "l"(p), "l"(POL_LAST) : "memory"); return v;
}
__device__ __forceinline__ void tma2d(uint32_t dst, const CUtensorMap* tm, int x, int y, uint32_t bar) {
    asm volatile("cp.async.bulk.tensor.2d.shared::cluster.global.mbarrier::complete_tx::bytes [%0],[%1,{%2,%3}],[%4];" ::"r"(dst), "l"(tm), "r"(x), "r"(y), "r"(bar) : "memory");
}
__device__ __forceinline__ void tma3d(uint32_t dst, const CUtensorMap* tm, int y, int z, uint32_t bar) {
    asm volatile("cp.async.bulk.tensor.3d.shared::cluster.global.mbarrier::complete_tx::bytes [%0],[%1,{0,%2,%3}],[%4];" ::"r"(dst), "l"(tm), "r"(y), "r"(z), "r"(bar) : "memory");
}
__device__ __forceinline__ void st_async4(uint32_t a, uint32_t x, uint32_t y, uint32_t z, uint32_t w, uint32_t mb) {
    asm volatile("st.async.shared::cluster.mbarrier::complete_tx::bytes.v4.b32 [%0],{%1,%2,%3,%4},[%5];" ::"r"(a), "r"(x), "r"(y), "r"(z), "r"(w), "r"(mb) : "memory");
}
__device__ __forceinline__ void st_async2(uint32_t a, uint32_t x, uint32_t y, uint32_t mb) {
    asm volatile("st.async.shared::cluster.mbarrier::complete_tx::bytes.v2.b32 [%0],{%1,%2},[%3];" ::"r"(a), "r"(x), "r"(y), "r"(mb) : "memory");
}
#define LDSQ "ld.shared"
__device__ __forceinline__ uint4 lds128(uint32_t a) { uint4 v; asm volatile(LDSQ ".v4.u32 {%0,%1,%2,%3},[%4];" : "=r"(v.x), "=r"(v.y), "=r"(v.z), "=r"(v.w) : "r"(a) : "memory"); return v; }
__device__ __forceinline__ uint4 lds128v(uint32_t a) { uint4 v; asm volatile("ld.volatile.shared.v4.u32 {%0,%1,%2,%3},[%4];" : "=r"(v.x), "=r"(v.y), "=r"(v.z), "=r"(v.w) : "r"(a) : "memory"); return v; }
__device__ __forceinline__ uint2 lds64(uint32_t a) { uint2 v; asm volatile(LDSQ ".v2.u32 {%0,%1},[%2];" : "=r"(v.x), "=r"(v.y) : "r"(a) : "memory"); return v; }
__device__ __forceinline__ uint32_t lds32(uint32_t a) { uint32_t v; asm volatile(LDSQ ".u32 %0,[%1];" : "=r"(v) : "r"(a) : "memory"); return v; }
__device__ __forceinline__ void sts128(uint32_t a, uint32_t x, uint32_t y, uint32_t z, uint32_t w) { asm volatile("st.shared.v4.u32 [%0],{%1,%2,%3,%4};" ::"r"(a), "r"(x), "r"(y), "r"(z), "r"(w) : "memory"); }
__device__ __forceinline__ void sts64(uint32_t a, uint32_t x, uint32_t y) { asm volatile("st.shared.v2.u32 [%0],{%1,%2};" ::"r"(a), "r"(x), "r"(y) : "memory"); }
__device__ __forceinline__ void sts32(uint32_t a, uint32_t x) { asm volatile("st.shared.u32 [%0],%1;" ::"r"(a), "r"(x) : "memory"); }
__device__ __forceinline__ uint4 ldsm4(uint32_t a) { uint4 v; asm volatile("ldmatrix.sync.aligned.m8n8.x4.shared.b16 {%0,%1,%2,%3},[%4];" : "=r"(v.x), "=r"(v.y), "=r"(v.z), "=r"(v.w) : "r"(a) : "memory"); return v; }
__device__ __forceinline__ uint4 ldsm4t(uint32_t a) { uint4 v; asm volatile("ldmatrix.sync.aligned.m8n8.x4.trans.shared.b16 {%0,%1,%2,%3},[%4];" : "=r"(v.x), "=r"(v.y), "=r"(v.z), "=r"(v.w) : "r"(a) : "memory"); return v; }
__device__ __forceinline__ uint32_t movm(uint32_t a) { uint32_t d; asm volatile("movmatrix.sync.aligned.m8n8.trans.b16 %0,%1;" : "=r"(d) : "r"(a)); return d; }
__device__ __forceinline__ uint32_t pack2(float lo, float hi) { uint32_t d; asm("cvt.rn.bf16x2.f32 %0,%1,%2;" : "=r"(d) : "f"(hi), "f"(lo)); return d; }
__device__ __forceinline__ uint32_t hadd2(uint32_t a, uint32_t b) { uint32_t d; asm("add.rn.bf16x2 %0,%1,%2;" : "=r"(d) : "r"(a), "r"(b)); return d; }
__device__ __forceinline__ uint32_t hmul2(uint32_t a, uint32_t b) { uint32_t d; asm("mul.rn.bf16x2 %0,%1,%2;" : "=r"(d) : "r"(a), "r"(b)); return d; }
__device__ __forceinline__ float blo(uint32_t v) { return __uint_as_float(v << 16); }
__device__ __forceinline__ float bhi(uint32_t v) { return __uint_as_float(v & 0xffff0000u); }
__device__ __forceinline__ float rbf(float x) { return __uint_as_float(pack2(0.f, x)); }
__device__ __forceinline__ float ex2(float x) { float y; asm("ex2.approx.ftz.f32 %0,%1;" : "=f"(y) : "f"(x)); return y; }
__device__ __forceinline__ float rcp(float x) { float y; asm("rcp.approx.ftz.f32 %0,%1;" : "=f"(y) : "f"(x)); return y; }
__device__ __forceinline__ void mma16(float* c, uint32_t a0, uint32_t a1, uint32_t a2, uint32_t a3, uint32_t b0, uint32_t b1) {
    asm volatile("mma.sync.aligned.m16n8k16.row.col.f32.bf16.bf16.f32 {%0,%1,%2,%3},{%4,%5,%6,%7},{%8,%9},{%0,%1,%2,%3};"
                 : "+f"(c[0]), "+f"(c[1]), "+f"(c[2]), "+f"(c[3]) : "r"(a0), "r"(a1), "r"(a2), "r"(a3), "r"(b0), "r"(b1));
}
__device__ __forceinline__ void mma16_top(float& d0, float& d1, uint32_t a0, uint32_t a2, uint32_t b0, uint32_t b1) {
    asm volatile("{.reg .b32 j; .reg .f32 e,f; mma.sync.aligned.m16n8k16.row.col.f32.bf16.bf16.f32 {%0,%1,e,f},{%2,j,%3,j},{%4,%5},{0f00000000,0f00000000,0f00000000,0f00000000};}"
                 : "=f"(d0), "=f"(d1) : "r"(a0), "r"(a2), "r"(b0), "r"(b1));
}
__device__ __forceinline__ void mma8(float* c, uint32_t a0, uint32_t a1, uint32_t b0) {
    asm volatile("mma.sync.aligned.m16n8k8.row.col.f32.bf16.bf16.f32 {%0,%1,%2,%3},{%4,%5},{%6},{%0,%1,%2,%3};"
                 : "+f"(c[0]), "+f"(c[1]), "+f"(c[2]), "+f"(c[3]) : "r"(a0), "r"(a1), "r"(b0));
}
__device__ __forceinline__ uint4 ld_rlx128(const uint4* p) {
    uint4 v;
    asm volatile("{.reg .b128 t; ld.relaxed.gpu.global.b128 t,[%4]; mov.b128 {%0,%1,%2,%3},t;}" : "=r"(v.x), "=r"(v.y), "=r"(v.z), "=r"(v.w) : "l"(p) : "memory");
    return v;
}
__device__ __forceinline__ void st_rlx128(uint4* p, uint32_t x, uint32_t y, uint32_t z, uint32_t w) {
    asm volatile("{.reg .b128 t; mov.b128 t,{%1,%2,%3,%4}; st.relaxed.gpu.global.b128 [%0],t;}" ::"l"(p), "r"(x), "r"(y), "r"(z), "r"(w) : "memory");
}
__device__ __forceinline__ uint4 ldcg128(const uint4* p) { uint4 v; asm volatile("ld.global.cg.v4.u32 {%0,%1,%2,%3},[%4];" : "=r"(v.x), "=r"(v.y), "=r"(v.z), "=r"(v.w) : "l"(p) : "memory"); return v; }
__device__ __forceinline__ void red_release(unsigned* p, unsigned v) {
    asm volatile("fence.proxy.async; red.relaxed.gpu.global.add.u32 [%0],%1;" ::"l"(p), "r"(v) : "memory");
}
__device__ __forceinline__ void wait_cnt(const unsigned* p, unsigned target) {
    unsigned v; int n = 0;
    while (true) {
        asm volatile("ld.acquire.gpu.global.u32 %0,[%1];" : "=r"(v) : "l"(p) : "memory");
        if (v >= target) break;
        if (++n > 3000000) __trap();
        __nanosleep(40);
    }
}
__device__ __forceinline__ void wait_cnt_warp(const unsigned* p, unsigned target) {
    unsigned v; int n = 0;
    while (true) {
        asm volatile("ld.acquire.gpu.global.u32 %0,[%1];" : "=r"(v) : "l"(p) : "memory");
        if (__all_sync(0xffffffffu, v >= target)) break;
        if (++n > 3000000) __trap();
        __nanosleep(40);
    }
}
__device__ __forceinline__ void wait_flag_warp(const unsigned* p, unsigned target) {
    unsigned v; int n = 0;
    while (true) {
        asm volatile("ld.relaxed.gpu.global.u32 %0,[%1];" : "=r"(v) : "l"(p) : "memory");
        if (__all_sync(0xffffffffu, v >= target)) break;
        if (++n > 10000000) __trap();
    }
}
__device__ __forceinline__ uint64_t mkdesc(uint32_t addr, uint32_t lbo, uint32_t sbo, uint32_t sw) {
    return (uint64_t)((addr & 0x3FFFF) >> 4) | ((uint64_t)(lbo >> 4) << 16) | ((uint64_t)(sbo >> 4) << 32) | ((uint64_t)sw << 62);
}
__device__ __forceinline__ void wg_fence() { asm volatile("wgmma.fence.sync.aligned;" ::: "memory"); }
__device__ __forceinline__ void wg_commit() { asm volatile("wgmma.commit_group.sync.aligned;" ::: "memory"); }
template <int N> __device__ __forceinline__ void wg_wait() { asm volatile("wgmma.wait_group.sync.aligned %0;" ::"n"(N) : "memory"); }
#define R8(c, o) "+f"(c[o]), "+f"(c[o + 1]), "+f"(c[o + 2]), "+f"(c[o + 3]), "+f"(c[o + 4]), "+f"(c[o + 5]), "+f"(c[o + 6]), "+f"(c[o + 7])
#define R32(c, o) R8(c, o), R8(c, o + 8), R8(c, o + 16), R8(c, o + 24)
#define S32A "%0,%1,%2,%3,%4,%5,%6,%7,%8,%9,%10,%11,%12,%13,%14,%15,%16,%17,%18,%19,%20,%21,%22,%23,%24,%25,%26,%27,%28,%29,%30,%31"
template <int ACC> __device__ __forceinline__ void wgmma64_rs(float* c, const uint32_t* a, uint64_t db) {
    asm volatile("wgmma.mma_async.sync.aligned.m64n64k16.f32.bf16.bf16 {" S32A "},{%32,%33,%34,%35},%36,%37,1,1,0;"
                 : R32(c, 0) : "r"(a[0]), "r"(a[1]), "r"(a[2]), "r"(a[3]), "l"(db), "n"(ACC));
}
template <int ACC> __device__ __forceinline__ void wgmma64_ta(float* c, uint64_t da, uint64_t db) {
    asm volatile("wgmma.mma_async.sync.aligned.m64n64k16.f32.bf16.bf16 {" S32A "},%32,%33,%34,1,1,1,0;" : R32(c, 0) : "l"(da), "l"(db), "n"(ACC));
}
template <int ACC> __device__ __forceinline__ void wgmma80_tb(float* c, uint64_t da, uint64_t db) {
    asm volatile("wgmma.mma_async.sync.aligned.m64n80k16.f32.bf16.bf16 {" S32A ",%32,%33,%34,%35,%36,%37,%38,%39},%40,%41,%42,1,1,0,1;"
                 : R32(c, 0), R8(c, 32) : "l"(da), "l"(db), "n"(ACC));
}
template <int N> __device__ __forceinline__ void reg_inc() { asm volatile("setmaxnreg.inc.sync.aligned.u32 %0;" ::"n"(N)); }
template <int N> __device__ __forceinline__ void reg_dec() { asm volatile("setmaxnreg.dec.sync.aligned.u32 %0;" ::"n"(N)); }

#define PROF(cond, idx) do {} while (0)
#define CPROF(k) do {} while (0)

constexpr int S_GATE = 232440, S_XBAR = 232432, S_VCL = 232444, B_BAR = 231936;
#define NFE 2
#define QLAG 3
constexpr float SC_LOG2E = 0.08838834764831845f * 1.4426950408889634f;

__device__ __forceinline__ float2 ln_finish(float mean, float var) {
    float sd; asm("sqrt.approx.f32 %0,%1;" : "=f"(sd) : "f"(rbf(rbf(var) + 1e-5f)));
    sd = rbf(sd);
    return make_float2(rbf(mean), sd);
}

__device__ __forceinline__ float2 row_stats512(uint4* v, const uint4* src, int s1, int s2) {
    const int g = (threadIdx.x & 31) >> 2;
#pragma unroll
    for (int i = 0; i < 16; i++) v[i] = ldcg128(src + (i >> 1) * s1 + (i & 1) * s2);
    float a[4] = {0, 0, 0, 0}, q0[4] = {0, 0, 0, 0}, q1[4] = {0, 0, 0, 0};
#pragma unroll
    for (int i = 0; i < 16; i++) {
        mma16(a, v[i].x, v[i].y, v[i].z, v[i].w, 0x3f803f80u, 0x3f803f80u);
        mma8(q0, v[i].x, v[i].y, v[i].x); mma8(q1, v[i].x, v[i].y, v[i].y);
        mma8(q0, v[i].z, v[i].w, v[i].z); mma8(q1, v[i].z, v[i].w, v[i].w);
    }
    const float sum = a[0] + a[2], sq = (g & 1) ? q0[1] + q1[3] : q0[0] + q1[2];
    return make_float2(sum, fmaxf(sq - sum * sum * (1.f / 512.f), 0.f));
}
__device__ __forceinline__ void x1_norm(int rg) {
    const int lane = threadIdx.x & 31, g = lane >> 2, c = lane & 3, o = (rg >> 3) * 4096 + (rg & 7) * 64 + c * 8 + g;
    uint4 v[16];
    const float2 r = row_stats512(v, g_x + o, 512, 32);
    const float2 l = ln_finish(r.x * (1.f / 512.f), r.y * (1.f / 512.f));
    const float mu = __shfl_sync(0xffffffffu, l.x, g * 4 + (g >> 1)), rs = rcp(__shfl_sync(0xffffffffu, l.y, g * 4 + (g >> 1)));
    if (c == 0) g_ln0[rg * 8 + g] = 0;
#define NRM(w) pack2(rbf(blo(w) - mu) * rs, rbf(bhi(w) - mu) * rs)
#pragma unroll
    for (int i = 0; i < 16; i++) g_xn[o + (i >> 1) * 512 + (i & 1) * 32] = make_uint4(NRM(v[i].x), NRM(v[i].y), NRM(v[i].z), NRM(v[i].w));
    __syncwarp();
    if (lane == 0) red_release(cnt_ptr(C_XN + (rg >> 3)), 1);
}

#define NWO 10
#define VMASK 0x4444
#define VQ 16
#define VPRE 2
#define MPRE 1
#define NPM NPX
#define SCHED(i) do {} while (0)
#define VPX 0
#define OA 0
#define QA 0
#define NPX 2
#define NPF 4
constexpr int SLOT = 24576, SL_V = 8192, SL_Q = 16384, SL_KM = 20480, SL_VM = 22528;
constexpr int R_WV = 0, R_SL = 65536, R_WO = R_SL + 4 * SLOT, R_M = 196608  , R_U = R_M + 8192  ,
              R_OS = R_U + 8192  , R_SB = R_OS + 8192  , R_OB = R_SB + 5248  , R_PB = R_OB + 2048  ,
              R_IL = R_PB + 1024  , R_SEL = 231680, R_BAR = R_SEL + 256, R_STQ = 65536, R_STK = 131072;
static_assert(R_WO + (16 - NWO) * 4096 <= R_M && R_IL + 64 <= R_SEL && R_BAR + 512 <= 232448, "smem map");
enum { RB_XFULL = 0  , RB_GO = 4  , RB_QK = 8  , RB_INIT = 24, RB_SV = 25  , RB_N = 29 };
#define GATE 1
enum { NB_MFULL = 1  , NB_PART = 3  , NB_S = 5, NB_P = 6, NB_O = 7, NB_W = 10 };
#define WDEP 1
#define RH 56
#define RW0 224
#define D1 300
#define D2 300
#define DX 0
__device__ __forceinline__ uint32_t clk32() { uint32_t c; asm volatile("mov.u32 %0,%%clock;" : "=r"(c)::"memory"); return c; }
__device__ __forceinline__ void spin(int cycles) {
    if (cycles <= 0) return;
    const uint32_t t0 = clk32();
    while (clk32() - t0 < (uint32_t)cycles) {}
}
__device__ __forceinline__ uint4* xregion(int X, int r) { return (uint4*)(((size_t)g_xch + 8191) & ~(size_t)8191) + (X * 66 + r) * 512; }

struct RecW { uint32_t po, dp, lw, swr, pwr, w, wv; };

template <int X>
__device__ __forceinline__ void rec_step(const RecW& k, uint32_t sb, int s, uint32_t z, uint32_t gate, const uint32_t (*wq)[4], const uint32_t (*wk)[4], uint4* wv, uint4* wo) {
    const uint32_t wz = k.w + z, w5 = wz * 512, so = (s & 1) * SLOT + w5;
    constexpr int SL = R_SL + X * 2 * SLOT;
    const uint32_t qb = sb + R_BAR + (RB_QK + X * 8) * 8 + wz * 8;
    const uint32_t l8 = ((k.lw + z) >> 1) + (sb - (sb >> 1) + SL + (s & 1) * SLOT + wz * 256);
    uint4 mk[8];
#define WVF(ks) wv[ks]
#define WVL(a, b) _Pragma("unroll") for (int ks_ = (a); ks_ < (b); ks_++) if (ks_ < 16 && !((VMASK >> ks_) & 1)) wv[ks_] = ldsm4t(k.wv + ks_ * 2048)
    WVL(0, VPRE);
    bar_sync(NB_MFULL + X, 288);
    uint32_t x[4], vv[2];
    float av[2][4] = {{0, 0, 0, 0}, {0, 0, 0, 0}};
    {
        float aq[2][4] = {{0, 0, 0, 0}, {0, 0, 0, 0}}, ak[2][4] = {{0, 0, 0, 0}, {0, 0, 0, 0}};
#pragma unroll
        for (int i = 0; i < MPRE; i++) mk[i] = ldsm4(k.lw + X * 4096 + R_M + i * 512);
#pragma unroll
        for (int i = 0; i < 8; i++) {
            if (i + MPRE < 8) mk[i + MPRE] = ldsm4(k.lw + X * 4096 + R_M + (i + MPRE) * 512);
            if (2 * i < VQ) { WVL(2 * i + VPRE, min(2 * i + 2 + VPRE, VQ + VPX)); }
            SCHED(i);
            const uint4 mf = mk[i];
            mma16(aq[0], wq[2 * i][0], wq[2 * i][1], wq[2 * i][2], wq[2 * i][3], mf.x, mf.y);
            mma16(ak[0], wk[2 * i][0], wk[2 * i][1], wk[2 * i][2], wk[2 * i][3], mf.x, mf.y);
            if (2 * i < VQ) mma16(av[0], WVF(2 * i).x, WVF(2 * i).y, WVF(2 * i).z, WVF(2 * i).w, mf.x, mf.y);
            mma16(aq[QA & 1], wq[2 * i + 1][0], wq[2 * i + 1][1], wq[2 * i + 1][2], wq[2 * i + 1][3], mf.z, mf.w);
            mma16(ak[(QA >> 1) & 1], wk[2 * i + 1][0], wk[2 * i + 1][1], wk[2 * i + 1][2], wk[2 * i + 1][3], mf.z, mf.w);
            if (2 * i < VQ) mma16(av[QA >> 2], WVF(2 * i + 1).x, WVF(2 * i + 1).y, WVF(2 * i + 1).z, WVF(2 * i + 1).w, mf.z, mf.w);
        }
        if (QA) {
#pragma unroll
            for (int i = 0; i < 4; i++) { if (QA & 1) aq[0][i] += aq[1][i]; if (QA & 2) ak[0][i] += ak[1][i]; }
        }
        x[0] = movm(pack2(aq[0][0], aq[0][1])); x[1] = movm(pack2(aq[0][2], aq[0][3]));
        x[2] = movm(pack2(ak[0][0], ak[0][1])); x[3] = movm(pack2(ak[0][2], ak[0][3]));
        st_async4(k.lw + (R_U + X * 4096 + w5 + k.dp), x[0], x[1], x[2], x[3], qb + k.dp);
    }
    {
#pragma unroll
        for (int i = VQ / 2; i < 8; i++) {
            const uint4 mf = mk[i];
            WVL(2 * i + VPX, 2 * i + 2 + VPX);
            mma16(av[0], WVF(2 * i).x, WVF(2 * i).y, WVF(2 * i).z, WVF(2 * i).w, mf.x, mf.y);
            mma16(av[1], WVF(2 * i + 1).x, WVF(2 * i + 1).y, WVF(2 * i + 1).z, WVF(2 * i + 1).w, mf.z, mf.w);
        }
        if (VQ < 16 || QA >= 4) {
#pragma unroll
            for (int i = 0; i < 4; i++) av[0][i] += av[1][i];
        }
        vv[0] = pack2(av[0][0], av[0][1]); vv[1] = pack2(av[0][2], av[0][3]);
        st_async2(l8 + (SL_VM + k.dp), vv[0], vv[1], qb + k.dp);
        asm volatile("{.reg .pred p; setp.eq.u32 p,%1,%2; @p mbarrier.arrive.shared::cta.b64 _,[%0];}" ::"r"(gate), "r"(k.swr), "r"(gate ? sb + R_SB : 0) : "memory");
        const uint4 k0 = lds128(k.lw + so + SL), k1 = lds128(k.lw + so + SL + 4096);
#pragma unroll
        for (int i = 0; i < NPX; i++) wo[i] = lds128(k.lw + w5 + R_WO + i * 4096);
        mbar_wait(qb, s & 1);
        const uint4 u = lds128(k.lw + w5 + R_U + X * 4096);
        const uint32_t q0 = hadd2(x[0], u.x), q1 = hadd2(x[1], u.y);
        x[2] = hadd2(x[2], u.z); x[3] = hadd2(x[3], u.w);
        float sa[4] = {0, 0, 0, 0}, sc[4] = {0, 0, 0, 0}, sm0, sm1;
        mma16(sa, k0.x, k0.y, k0.z, k0.w, q0, q1);
        mma16(sc, k1.x, k1.y, k1.z, k1.w, q0, q1);
        mma16_top(sm0, sm1, x[2], x[3], q0, q1);
        asm volatile("stmatrix.sync.aligned.m8n8.x4.trans.shared.b16 [%0],{%1,%2,%3,%4};" ::"r"(k.swr), "r"(pack2(sa[0], sa[1])), "r"(pack2(sa[2], sa[3])),
                     "r"(pack2(sc[0], sc[1])), "r"(pack2(sc[2], sc[3])) : "memory");
        asm volatile("stmatrix.sync.aligned.m8n8.x1.trans.shared.b16 [%0],{%1};" ::"r"(k.swr + 512), "r"(pack2(sm0, sm1)) : "memory");
    }
    bar_sync(NB_S, 256);
    uint4 v0, v1;
    uint32_t ls;
    {
        const uint4 y = ldsm4t(k.lw + wz * 656 + R_SB);
        uint32_t y4; asm volatile("ldmatrix.sync.aligned.m8n8.x1.trans.shared.b16 {%0},[%1];" : "=r"(y4) : "r"(k.lw + wz * 656 + R_SB + 512) : "memory");
        const uint2 vp = lds64(l8 + SL_VM);
        sts64(l8 + SL_KM, x[2], x[3]);
        v0 = lds128(k.lw + so + SL + SL_V); v1 = lds128(k.lw + so + SL + SL_V + 4096);
        vv[0] = hadd2(vv[0], vp.x); vv[1] = hadd2(vv[1], vp.y);
        sts64(l8 + SL_VM, vv[0], vv[1]);
#pragma unroll
        for (int i = NPX; i < NPM; i++) wo[i] = lds128(k.lw + w5 + R_WO + i * 4096);
        const uint32_t ONE = 0x3f803f80u + z;
        float a[4] = {0, 0, 0, 0}, b[4] = {0, 0, 0, 0}, e[4] = {0, 0, 0, 0};
        mma8(e, ONE, z, y4); mma16(a, ONE, z, z, ONE, y.x, y.y); mma16(b, ONE, z, z, ONE, y.z, y.w);
        float s0, s1;
        asm("{.reg .pred p1,p2,p4; .reg .f32 t0,t1,u0,u1; .reg .b32 m; and.b32 m,%12,64; setp.ne.u32 p1,m,0; and.b32 m,%12,128; setp.ne.u32 p2,m,0; and.b32 m,%12,256; setp.ne.u32 p4,m,0;"
            "selp.f32 t0,%4,%2,p1; selp.f32 t1,%5,%3,p1; selp.f32 u0,%8,%6,p1; selp.f32 u1,%9,%7,p1; selp.f32 t0,u0,t0,p2; selp.f32 t1,u1,t1,p2; selp.f32 %0,%10,t0,p4; selp.f32 %1,%11,t1,p4;}"
            : "=f"(s0), "=f"(s1) : "f"(a[0]), "f"(a[1]), "f"(a[2]), "f"(a[3]), "f"(b[0]), "f"(b[1]), "f"(b[2]), "f"(b[3]), "f"(e[0]), "f"(e[1]), "r"(k.lw));
        const int mi = __float_as_int(fmaxf(s0, s1));
        const int mp = __reduce_max_sync(0xffffffffu, mi), mn = (int)__reduce_min_sync(0xffffffffu, (unsigned)mi);
        const float mo = -__int_as_float(mp >= 0 ? mp : mn) * SC_LOG2E;
        s0 = ex2(fmaf(s0, SC_LOG2E, mo)); s1 = ex2(fmaf(s1, SC_LOG2E, mo));
        sts32(k.pwr, pack2(s0, s1));
        ls = k.lw < sb + 320 ? __float2uint_rn((s0 + s1) * 16777216.f) : 0;
    }
    bar_sync(NB_P, 256);
    {
        const uint4 pp = lds128(k.lw + R_PB);
        const uint32_t pm = lds32(((k.lw + z) >> 2) + (sb - (sb >> 2) + R_PB + 512));
        sts32(sb + R_IL + (wz >> 1) * 16 + (wz & 1) * 4, __float_as_uint(rcp(__uint2float_rn(__reduce_add_sync(0xffffffffu, ls)) * (1.f / 16777216.f))));
        float o0[4] = {0, 0, 0, 0}, o1[4] = {0, 0, 0, 0}, o2[4] = {0, 0, 0, 0};
        mma16(o0, v0.x, v0.y, v0.z, v0.w, pp.x, pp.y);
        mma16(o1, v1.x, v1.y, v1.z, v1.w, pp.z, pp.w);
        mma8(o2, vv[0], vv[1], pm);
        asm volatile("stmatrix.sync.aligned.m8n8.x2.trans.shared.b16 [%0],{%1,%2};" ::"r"(k.lw + wz * 256 + R_OB),
                     "r"(pack2(o0[0] + o1[0] + o2[0], o0[1] + o1[1] + o2[1])), "r"(pack2(o0[2] + o1[2] + o2[2], o0[3] + o1[3] + o2[3])) : "memory");
#pragma unroll
        for (int i = NPM; i < NPF; i++) wo[i] = lds128(k.lw + w5 + R_WO + i * 4096);
    }
    bar_sync(NB_O, 256);
    {
        const uint32_t po = k.po + z, tag = (s + 1) & 1;
        float r0[2][4] = {{0, 0, 0, 0}, {0, 0, 0, 0}}, r1[2][4] = {{0, 0, 0, 0}, {0, 0, 0, 0}};
        uint4 b[4];
#pragma unroll
        for (int i = 0; i < 4; i++) b[i] = ldsm4(k.lw + R_OB + i * 512);
        SCHED(8);
#pragma unroll
        for (int m = NWO + NPF; m < 16; m++) wo[m] = lds128(k.lw + w5 + R_WO + (m - NWO) * 4096);
        const uint2 il = lds64(sb + R_IL + (po & 48));
        const float i0 = __uint_as_float(il.x), i1 = __uint_as_float(il.y);
#pragma unroll
        for (int i = 0; i < 4; i++) {
            mma16(r0[0], wo[4 * i].x, wo[4 * i].y, wo[4 * i].z, wo[4 * i].w, b[i].x, b[i].y);
            mma16(r1[0], wo[4 * i + 1].x, wo[4 * i + 1].y, wo[4 * i + 1].z, wo[4 * i + 1].w, b[i].x, b[i].y);
            mma16(r0[OA], wo[4 * i + 2].x, wo[4 * i + 2].y, wo[4 * i + 2].z, wo[4 * i + 2].w, b[i].z, b[i].w);
            mma16(r1[OA], wo[4 * i + 3].x, wo[4 * i + 3].y, wo[4 * i + 3].z, wo[4 * i + 3].w, b[i].z, b[i].w);
        }
#pragma unroll
        for (int i = 0; i < 4; i++) { r0[0][i] = (OA ? r0[0][i] + r0[1][i] : r0[0][i]) * ((i & 1) ? i1 : i0); r1[0][i] = (OA ? r1[0][i] + r1[1][i] : r1[0][i]) * ((i & 1) ? i1 : i0); }
        st_rlx128((uint4*)((char*)xregion(X, 0) + ((po & ~1u) ^ ((po & X) << 12))), (pack2(r0[0][0], r0[0][2]) & ~1u) | tag,
                  pack2(r1[0][0], r1[0][2]), pack2(r0[0][1], r0[0][3]), pack2(r1[0][1], r1[0][3]));
        bar_arrive(NB_PART + X, 288);
    }
}

__device__ __forceinline__ void rec_weights(const Params& p, uint32_t sb, int head, uint32_t rank, int w) {
    const int lane = threadIdx.x & 31, g = lane >> 2, c = lane & 3;
    const int t = w & 3, WG = w >> 2;
    uint32_t wq[16][4], wk[16][4];
    uint4 wo[16], wv[16];
    const uint32_t woff = sb + WG * 32768 + (((lane >> 4) << 3) + (lane & 7)) * 128 + (((2 * t + ((lane >> 3) & 1)) ^ (lane & 7)) << 4);
    const uint32_t lw = sb + lane * 16;
    PROF(threadIdx.x == 0, 3501);
    if (w >= 4 && p.dopro) { wait_cnt_warp(g_gate, lds32(sb + S_GATE)); x1_norm((w - 4) * 64 + head * 2 + rank); }
    PROF(threadIdx.x == 0, 3502);
    mbar_wait(sb + R_BAR + RB_INIT * 8, 0);
    PROF(threadIdx.x == 0, 3503);
#pragma unroll
    for (int ks = 0; ks < 16; ks++) {
        uint4 a = ldsm4t(woff + R_STQ + ks * 2048), b = ldsm4t(woff + R_STK + ks * 2048);
        wq[ks][0] = a.x; wq[ks][1] = a.y; wq[ks][2] = a.z; wq[ks][3] = a.w;
        wk[ks][0] = b.x; wk[ks][1] = b.y; wk[ks][2] = b.z; wk[ks][3] = b.w;
    }
    bar_sync(NB_W, 256);
    {
        const __nv_bfloat16* wp = p.Wo + (size_t)(head * 128 + 2 * c) * 512 + rank * 256 + w * 32 + g * 4;
#pragma unroll
        for (int ks = 0; ks < 8; ks++) {
            const uint2 r0 = *(const uint2*)(wp + (ks * 16) * 512), r1 = *(const uint2*)(wp + (ks * 16 + 1) * 512);
            const uint2 r2 = *(const uint2*)(wp + (ks * 16 + 8) * 512), r3 = *(const uint2*)(wp + (ks * 16 + 9) * 512);
            const uint4 f[2] = {make_uint4(__byte_perm(r0.x, r1.x, 0x5410), __byte_perm(r0.x, r1.x, 0x7632), __byte_perm(r2.x, r3.x, 0x5410), __byte_perm(r2.x, r3.x, 0x7632)),
                                make_uint4(__byte_perm(r0.y, r1.y, 0x5410), __byte_perm(r0.y, r1.y, 0x7632), __byte_perm(r2.y, r3.y, 0x5410), __byte_perm(r2.y, r3.y, 0x7632))};
#pragma unroll
            for (int h = 0; h < 2; h++) {
                const int m = 2 * ks + h;
                if (m >= NPF && m < NPF + NWO) wo[m] = f[h];
                else sts128(lw + w * 512 + R_WO + (m < NPF ? m : m - NWO) * 4096, f[h].x, f[h].y, f[h].z, f[h].w);
            }
        }
    }
    fence_async_smem();
    PROF(threadIdx.x == 0, 3504);
    __syncthreads();
#pragma unroll
    for (int i = 0; i < 16; i++) if ((VMASK >> i) & 1) wv[i] = ldsm4t(woff + R_WV + i * 2048);
    cluster_sync();
    PROF(threadIdx.x == 0, 3505);
    RecW k;
    {
        const int r = (w * 4 + (lane >> 3)) * 2 + rank;
        const uint32_t sl = lds32(sb + R_SEL + r * 4);
        const int slot = head * 8 + (lane & 7);
        k.po = (r * 512 + slot + (sl & 1) * 256) * 16 + (((sl >> 1) ^ sl) & 1);
    }
    k.dp = mapa(sb, rank ^ 1) - sb;
    k.lw = __shfl_sync(0xffffffffu, lw, lane);
    k.swr = __shfl_sync(0xffffffffu, sb + R_SB + (lane & 7) * 656 + (lane >> 3) * 128 + w * 16, lane);
    k.pwr = __shfl_sync(0xffffffffu, sb + R_PB + (g < 4 ? (w * 4 + c) * 16 + g * 4 : 512 + (w * 4 + c) * 4), lane);
    k.w = w;
    k.wv = __shfl_sync(0xffffffffu, woff + R_WV, lane);
    const int e0 = (p.chains & 1) ? 64 : 0, o1 = (p.chains & 2) ? p.lag : 1000, nit = (p.chains & 2) ? p.lag + 64 : 64;
    const uint32_t zero = p.zero;
#pragma unroll 1
    for (int it = 0; it < nit; it++) {
        const uint32_t g0 = sb + R_BAR + (RB_GO + (it & 1)) * 8, g1 = sb + R_BAR + (RB_GO + 2 + ((it - o1) & 1)) * 8;
        if (it < e0) {
            rec_step<0>(k, sb, it, it & zero, GATE && it > o1 ? g1 ^ 8 : 0, wq, wk, wv, wo);
            if ((!GATE || it < o1) && threadIdx.x == 0) mbar_arrive(g0);
        }
        if (it >= o1) {
            rec_step<1>(k, sb, it - o1, it & zero, GATE && it < e0 ? g0 : 0, wq, wk, wv, wo);
            if ((!GATE || it + 1 >= e0) && threadIdx.x == 0) mbar_arrive(g1);
        }
    }
}

__device__ __forceinline__ uint32_t mism(uint32_t a, uint32_t b, uint32_t t) {
    uint32_t d; asm("lop3.b32 %0,%1,%2,%3,0x7e;" : "=r"(d) : "r"(a), "r"(b), "r"(t)); return d;
}
template <bool TWO>
__device__ __forceinline__ void poll8(uint4* x, const uint4* src, uint32_t tag) {
#pragma unroll
    for (int j = 0; j < 8; j++) x[j] = ld_rlx128(src + j * 32);
    int n = 0;
    while (true) {
        uint32_t bad = 0;
#pragma unroll
        for (int j = 0; j < 8; j += 2) bad |= TWO ? mism(x[j].x, x[j].z, tag) | mism(x[j + 1].x, x[j + 1].z, tag) : mism(x[j].x, x[j + 1].x, tag);
        if (!__any_sync(0xffffffffu, bad & 1)) break;
#pragma unroll
        for (int j = 0; j < 8; j++)
            asm volatile("{.reg .pred p; .reg .b128 t; setp.ne.u32 p,%5,0; mov.b128 t,{%0,%1,%2,%3}; @p ld.relaxed.gpu.global.b128 t,[%4]; mov.b128 {%0,%1,%2,%3},t;}"
                         : "+r"(x[j].x), "+r"(x[j].y), "+r"(x[j].z), "+r"(x[j].w) : "l"(src + j * 32), "r"((TWO ? mism(x[j].x, x[j].z, tag) : x[j].x ^ tag) & 1) : "memory");
        if (++n > 2000000) __trap();
    }
}

__device__ __forceinline__ void rec_comm(const Params& p, uint32_t sb, int X, int head, uint32_t rank) {
    const int lane = threadIdx.x & 31, g = lane >> 2, c = lane & 3;
    const int me = head * 2 + rank;
    const uint32_t mb = sb + R_M + X * 4096 + lane * 16;
    uint4 x[8];
#pragma unroll
    for (int j = 0; j < 8; j++) x[j] = *(const uint4*)(p.mem0 + (lane & 7) * 512 + rank * 256 + (j * 4 + (lane >> 3)) * 8);
    const uint32_t sl = lds32(sb + R_SEL + me * 4);
    const uint4* src1 = xregion(X, me) + ((sl >> X) & 1) * 256 + c * 8 + g;
    const uint4* src2 = xregion(X, 64 + rank) + ((sl >> (2 + X)) & 1) * 256 + lane;
    uint2* mdst = (uint2*)(xregion(X, 64 + rank) + (c >> 1) * 256 + head * 8 + (g & 3) * 2 + (c & 1)) + (g >> 2);
    const uint32_t one = (g & 1) ? 0x3f800000u : 0x00003f80u, selA = (g & 2) ? 0u : one, selB = (g & 2) ? one : 0u;
    const uint32_t qb = sb + R_BAR + (RB_QK + X * 8 + lane) * 8;
    if (lane < 8) mbar_expect(qb, 768);
    mbar_wait(sb + R_BAR + (RB_XFULL + X * 2) * 8, 0);
#pragma unroll 1
    for (int s = 0;; s++) {
#pragma unroll
        for (int j = 0; j < 8; j++) sts128(mb + j * 512, x[j].x, x[j].y, x[j].z, x[j].w);
        bar_arrive(NB_MFULL + X, 288);
        PROF(lane == 0, X * 64 + s);
        bar_sync(NB_PART + X, 288);
        if (s == 63) break;
        const uint32_t tag = (s + 1) & 1;
        if (lane < 8) mbar_expect(qb, 768);
        spin(D1 + (lds32(sb + R_SEL) >> 20));
        poll8<false>(x, src1, tag);
        float a[4][4];
#pragma unroll
        for (int j = 0; j < 4; j++) {
            a[j][0] = a[j][1] = a[j][2] = a[j][3] = 0;
            mma16(a[j], x[j].x, x[j].y, x[j].z, x[j].w, selA, selB);
        }
#pragma unroll
        for (int j = 0; j < 4; j++) mma16(a[j], x[j + 4].x, x[j + 4].y, x[j + 4].z, x[j + 4].w, selA, selB);
#pragma unroll
        for (int i = 0; i < 4; i++) a[0][i] = (a[0][i] + a[1][i]) + (a[2][i] + a[3][i]);
        asm volatile("st.relaxed.gpu.global.b64 [%0],%1;" ::"l"(mdst), "l"(((uint64_t)pack2(a[0][2], a[0][3]) << 32) | ((pack2(a[0][0], a[0][1]) & ~1u) | tag)) : "memory");
        const uint32_t t2 = clk32();
        mbar_wait(sb + R_BAR + (RB_XFULL + X * 2 + tag) * 8, ((s + 1) >> 1) & 1);
        while (clk32() - t2 < D2) {}
        poll8<true>(x, src2, tag);
    }
}

template <int MT>
__device__ __forceinline__ void xattn(uint32_t l16, uint32_t l8, uint32_t os, int g, int c) {
    constexpr int NT = 3 + 2 * MT;
    float S[NT][4];
#pragma unroll
    for (int i = 0; i < NT; i++) S[i][0] = S[i][1] = S[i][2] = S[i][3] = 0;
#pragma unroll 2
    for (int ks = 0; ks < 8; ks++) {
        const uint4 q = lds128(l16 + SL_Q + ks * 512);
        const uint2 u = lds64(l8 + SL_KM + ks * 256);
        mma16(S[0], q.x, q.y, q.z, q.w, u.x, u.y);
#pragma unroll
        for (int m = 0; m <= MT; m++) {
            const uint4 kk = lds128(l16 + m * 4096 + ks * 512);
            mma16(S[1 + 2 * m], q.x, q.y, q.z, q.w, kk.x, kk.z); mma16(S[2 + 2 * m], q.x, q.y, q.z, q.w, kk.y, kk.w);
        }
    }
    const float NEG = -__int_as_float(0x7f800000);
    if (2 * c > g) { S[NT - 2][0] = NEG; S[NT - 1][2] = NEG; }
    if (2 * c + 1 > g) { S[NT - 2][1] = NEG; S[NT - 1][3] = NEG; }
    S[NT - 1][0] = S[NT - 1][1] = NEG;
    float m0 = fmaxf(S[0][0], S[0][1]), m1 = fmaxf(S[0][2], S[0][3]);
#pragma unroll
    for (int i = 1; i < NT; i++) { if (i < NT - 1) m0 = fmaxf(m0, fmaxf(S[i][0], S[i][1])); m1 = fmaxf(m1, fmaxf(S[i][2], S[i][3])); }
    m0 = fmaxf(m0, __shfl_xor_sync(0xffffffffu, m0, 1)); m1 = fmaxf(m1, __shfl_xor_sync(0xffffffffu, m1, 1));
    m0 = fmaxf(m0, __shfl_xor_sync(0xffffffffu, m0, 2)); m1 = fmaxf(m1, __shfl_xor_sync(0xffffffffu, m1, 2));
    m0 *= -SC_LOG2E; m1 *= -SC_LOG2E;
    float l0 = 0, l1 = 0;
#pragma unroll
    for (int i = 0; i < NT; i++) {
        if (i < NT - 1) { S[i][0] = ex2(fmaf(S[i][0], SC_LOG2E, m0)); S[i][1] = ex2(fmaf(S[i][1], SC_LOG2E, m0)); l0 += S[i][0] + S[i][1]; }
        S[i][2] = ex2(fmaf(S[i][2], SC_LOG2E, m1)); S[i][3] = ex2(fmaf(S[i][3], SC_LOG2E, m1)); l1 += S[i][2] + S[i][3];
    }
    l0 += __shfl_xor_sync(0xffffffffu, l0, 1); l1 += __shfl_xor_sync(0xffffffffu, l1, 1);
    l0 += __shfl_xor_sync(0xffffffffu, l0, 2); l1 += __shfl_xor_sync(0xffffffffu, l1, 2);
    l0 = rcp(l0); l1 = rcp(l1);
    uint32_t P[NT][2];
#pragma unroll
    for (int i = 0; i < NT; i++) { P[i][0] = i < NT - 1 ? pack2(S[i][0] * l0, S[i][1] * l0) : 0u; P[i][1] = pack2(S[i][2] * l1, S[i][3] * l1); }
#pragma unroll 2
    for (int et = 0; et < 8; et++) {
        float a[4] = {0, 0, 0, 0}, b[4] = {0, 0, 0, 0};
        const uint2 vm = lds64(l8 + SL_VM + et * 256);
        mma8(a, vm.x, vm.y, P[0][0]); mma8(b, vm.x, vm.y, P[0][1]);
#pragma unroll
        for (int m = 0; m <= MT; m++) {
            const uint4 v = lds128(l16 + SL_V + m * 4096 + et * 512);
            mma16(a, v.x, v.y, v.z, v.w, P[1 + 2 * m][0], P[2 + 2 * m][0]); mma16(b, v.x, v.y, v.z, v.w, P[1 + 2 * m][1], P[2 + 2 * m][1]);
        }
        asm volatile("stmatrix.sync.aligned.m8n8.x4.trans.shared.b16 [%0],{%1,%2,%3,%4};" ::"r"(os + (et >> 2) * 2048 + (et & 3) * 256),
                     "r"(pack2(a[0], a[1])), "r"(pack2(a[2], a[3])), "r"(pack2(b[0], b[1])), "r"(pack2(b[2], b[3])) : "memory");
    }
}

__device__ __forceinline__ void rec_tiles(uint32_t sb, int X, int head, uint32_t rank, int& nxt, int lim, int need) {
#pragma unroll 1
    while (nxt <= lim) {
        if ((nxt & 1) == 0) {
            unsigned v; int n = 0;
            while (true) {
                asm volatile("ld.relaxed.gpu.global.u32 %0,[%1];" : "=r"(v) : "l"(cnt_ptr(C_QKV + X * 32 + (nxt >> 1))) : "memory");
                if (__all_sync(0xffffffffu, v >= 2 * NQ)) break;
                if (nxt > need) return;
                if (++n > 3000000) __trap();
            }
        }
        if (elect()) {
            const uint32_t bar = sb + R_BAR + (RB_XFULL + X * 2 + (nxt & 1)) * 8, dst = sb + R_SL + (X * 2 + (nxt & 1)) * SLOT;
            const uint4* src = g_qkv + (size_t)((X * 64 + nxt) * 32 + head) * 1536;
            mbar_expect(bar, 20480);
            bulk_g2s_mc(dst + rank * 8192, src + 512 + rank * 512, 8192, bar, POL_LAST);
            bulk_g2s(dst + SL_Q, src + (rank ^ X) * 256, 4096, bar, POL_LAST);
        }
        __syncwarp();
        nxt++;
    }
}

__device__ __forceinline__ void rec_attn(const Params& p, uint32_t sb, int X, int head, uint32_t rank) {
    const int lane = threadIdx.x & 31, g = lane >> 2, c = lane & 3;
    const int mt = rank ^ X;
    const uint32_t dp = mapa(sb, rank ^ 1) - sb;
    int nxt = 0;
    rec_tiles(sb, X, head, rank, nxt, 1, 0);
#pragma unroll 1
    for (int s = 0; s < 64; s++) {
        const uint32_t so = sb + R_SL + (X * 2 + (s & 1)) * SLOT;
        mbar_wait(sb + R_BAR + (RB_GO + X * 2 + (s & 1)) * 8, (s >> 1) & 1);
        rec_tiles(sb, X, head, rank, nxt, min(s + 1, 63), -1);
        spin(DX);
        mbar_wait(sb + R_BAR + (RB_XFULL + X * 2 + (s & 1)) * 8, (s >> 1) & 1);
        if (elect()) asm volatile("cp.async.bulk.wait_group.read 0;" ::: "memory");
        __syncwarp();
        const uint32_t os = sb + R_OS + X * 4096 + (lane >> 4) * 1024 + (lane & 15) * 16;
        if (mt) xattn<1>(so + lane * 16, so + lane * 8, os, g, c); else xattn<0>(so + lane * 16, so + lane * 8, os, g, c);
        fence_async_smem();
        __syncwarp();
        const uint32_t svb = sb + R_BAR + (RB_SV + X * 2 + (s & 1)) * 8;
        if (elect()) {
            mbar_arrive(svb); mbar_arrive_cluster(svb + dp);
            const uint64_t pol = POL_SOON;
#pragma unroll
            for (int kb = 0; kb < 2; kb++)
                asm volatile("cp.async.bulk.global.shared::cta.bulk_group.L2::cache_hint [%0],[%1],%2,%3;" ::"l"(g_o + ((X * 32 + (s >> 1)) * 64 + head * 2 + kb) * 512 + ((s & 1) * 4 + mt * 2) * 64),
                             "r"(sb + R_OS + X * 4096 + kb * 2048), "r"(2048), "l"(pol) : "memory");
            asm volatile("cp.async.bulk.commit_group;" ::: "memory");
            if (s & 1) { asm volatile("cp.async.bulk.wait_group 0;" ::: "memory"); red_release(cnt_ptr(C_O + (X * 32 + (s >> 1)) * 4 + (head >> 3)), 1); }
        }
        __syncwarp();
        rec_tiles(sb, X, head, rank, nxt, min(s + 1, 63), s + 1);
        mbar_wait(svb, (s >> 1) & 1);
        rec_tiles(sb, X, head, rank, nxt, min(s + 2, 63), -1);
    }
}

__device__ __forceinline__ uint32_t probe1(unsigned* r, int lane) {
    uint32_t v = 0;
    const uint32_t t0 = clk32();
    asm volatile("{.reg .pred p; setp.eq.u32 p,%2,0; @p atom.relaxed.gpu.global.or.b32 %0,[%1],0;}" : "+r"(v) : "l"(r), "r"(lane) : "memory");
    v = __shfl_sync(0xffffffffu, v, 0);
    asm volatile("{.reg .pred p; setp.eq.u32 p,%0,0x5a5a5a5b; @p nanosleep.u32 1;}" ::"r"(v) : "memory");
    return clk32() - t0;
}
__device__ __forceinline__ void rec_probe(uint32_t sb, int me, int w) {
    const int lane = threadIdx.x & 31;
    unsigned* r = (unsigned*)xregion(w & 1, (w & 2) ? 64 + (me & 1) : me) + ((w & 2) ? (me >> 1) * 32 : 0);
    uint32_t b0 = ~0u, b1 = ~0u;
#pragma unroll 1
    for (int i = 0; i < 5; i++) { b0 = min(b0, probe1(r, lane)); b1 = min(b1, probe1(r + 1024, lane)); }
    sts32(sb + R_BAR + 480 + w * 4, b1 < b0);
}
__device__ __forceinline__ void rec_sides(uint32_t sb, int me, int w) {
    const int lane = threadIdx.x & 31;
    if (lane == 0) asm volatile("red.relaxed.gpu.global.add.u32 [%0],%1;" ::"l"(g_sel + me), "r"((lds32(sb + R_BAR + 480 + w * 4) << w) + 256u) : "memory");
    __syncwarp();
    if (w < 2) {
        unsigned v; int n = 0;
        while (true) {
            asm volatile("ld.relaxed.gpu.global.u32 %0,[%1];" : "=r"(v) : "l"(g_sel + w * 32 + lane) : "memory");
            if (__all_sync(0xffffffffu, v >= 1024)) break;
            if (++n > 2000000) __trap();
        }
        sts32(sb + R_SEL + (w * 32 + lane) * 4, v);
    }
}

__device__ __forceinline__ void rec_init(uint32_t sb) {
    const uint32_t b = sb + R_BAR;
    const int i = threadIdx.x & 31;
    mbar_init(b + i * 8, i >= RB_SV ? 2 : 1);
    if (i == RB_INIT) mbar_expect(b + RB_INIT * 8, 196608);
    asm volatile("fence.mbarrier_init.release.cluster;" ::: "memory");
}
__device__ __forceinline__ void rec_fetch(const Params& p, uint32_t sb, int head, uint32_t rank, int which, int dst) {
#pragma unroll 1
    for (int j = 0; j < 8; j++) tma2d(sb + dst + j * 8192, &p.tm[which], head * 128 + (j >> 2) * 64, rank * 256 + (j & 3) * 64, sb + R_BAR + RB_INIT * 8);
}

constexpr int G_BAR = B_BAR;
enum { GB_FULL = 0  , GB_EMPTY = 8  , GB_RS = 16, GB_SS = 17, GB_LAG = 18, GB_FREE = 19, GB_DONE = 20  , GB_N = 24 };
constexpr int Q_PRE = 6, Q_STG = Q_PRE * 16384;
constexpr int NQRS = 2 * NQ - 64;
__device__ __forceinline__ void gemm_init(uint32_t sb, bool op) {
    const int i = threadIdx.x & 31;
    if (i < GB_N) mbar_init(sb + G_BAR + i * 8, i >= GB_DONE ? 4 : i == GB_FREE ? 8 : (i >= GB_EMPTY && i < GB_RS) ? 2 : 1);
    if (i == GB_RS) mbar_expect(sb + G_BAR + i * 8, 131072);
    if (i == GB_SS) mbar_expect(sb + G_BAR + i * 8, op ? 131072 : 163840);
    asm volatile("fence.mbarrier_init.release.cluster;" ::: "memory");
}
__device__ __forceinline__ int qkv_blk(int id, int j) { return NQRS * 4 + id * 10 + j; }
__device__ __forceinline__ void qkv_fetch(const Params& p, uint32_t sb, int id, int j0, int j1) {
#pragma unroll 1
    for (int j = j0 * 2; j < j1 * 2; j++) {
        const int blk = min(qkv_blk(id, j >> 1), 511);
        tma2d(sb + j * 8192, &p.tn[blk >> 8], (blk & 255) * 16, (j & 1) * 256, sb + G_BAR + GB_SS * 8);
    }
}
__device__ __forceinline__ void gemm_stage(const Params& p, uint32_t sb, int id, bool op) {
#pragma unroll 1
    for (int j = 0; j < 16; j++) {
        const int u = id * 2 + (j >> 3);
        tma2d(sb + (op ? 0 : Q_STG) + j * 8192, &p.tm[op ? 4 : u < 64 ? 2 : 0], (u & (op ? 7 : 63)) * 64, op ? (id >> 2) * 1024 + (j & 7) * 128 : (j & 7) * 64, sb + G_BAR + GB_RS * 8);
    }
}
template <bool OP>
__device__ __forceinline__ void gemm_producer(const Params& p, uint32_t sb, int id) {
    constexpr int NS = OP ? 6 : 8, SB = OP ? 16384 : 8192, RING = OP ? 131072 : 163840;
    if (!elect()) return;
    mbar_wait(sb + G_BAR + GB_FREE * 8, 0);
    if (OP) {
#pragma unroll 1
        for (int j = 0; j < 16; j++) tma2d(sb + j * 8192, &p.tm[4], ((id * 2 + (j >> 3)) & 7) * 64, (id >> 2) * 1024 + (j & 7) * 128 + 64, sb + G_BAR + GB_SS * 8);
    } else qkv_fetch(p, sb, id, Q_PRE, 10);
    wait_cnt(g_gate, lds32(sb + S_GATE));
    int st = 0; uint32_t ph = 1;
#pragma unroll 1
    for (int n = 0; n < p.nl[OP]; n++) {
        const int e = p.list[OP][n];
        wait_cnt(OP ? cnt_ptr(C_O + e * 4 + (id >> 2)) : cnt_ptr(C_XN + e), OP ? 16 : 8);
        PROF(true, 1024 + n * 4);
        const uint4* src = OP ? g_o + (e * 64 + (id >> 2) * 16) * 512 : g_xn + e * 4096;
#pragma unroll 1
        for (int s = 0; s < 8; s++) {
            mbar_wait(sb + G_BAR + (GB_EMPTY + st) * 8, ph);
            mbar_expect(sb + G_BAR + (GB_FULL + st) * 8, SB);
            bulk_g2s(sb + RING + st * SB, src + s * (SB / 16), SB, sb + G_BAR + (GB_FULL + st) * 8, POL_N);
            if (++st == NS) { st = 0; ph ^= 1; }
        }
    }
}
template <bool OP>
__device__ __forceinline__ void gemm_release(const Params& p, uint32_t sb, int id) {
    if (threadIdx.x != 288) return;
#pragma unroll 1
    for (int n = 0; n < 2 * p.nl[OP]; n++) {
        const int e = p.list[OP][n >> 1];
        mbar_wait(sb + G_BAR + (GB_DONE + (n & 3)) * 8, (n >> 2) & 1);
        red_release(OP ? cnt_ptr(C_PP + e * 8 + (id & 3) * 2 + (n & 1)) : cnt_ptr(C_QKV + e), 1);
        PROF(n & 1, 1024 + (n >> 1) * 4 + 3);
    }
}
__device__ __forceinline__ void op_permute(uint32_t sb) {
#pragma unroll 2
    for (int i = threadIdx.x; i < 4096; i += 256) {
        const uint32_t a = sb + i * 32 + ((i >> 2) & 1) * 16, b = a ^ 16;
        const uint4 x = lds128(a), y = lds128(b);
        sts128(a, __byte_perm(x.x, x.y, 0x5410), __byte_perm(x.z, x.w, 0x5410), __byte_perm(y.x, y.y, 0x5410), __byte_perm(y.z, y.w, 0x5410));
        sts128(b, __byte_perm(x.x, x.y, 0x7632), __byte_perm(x.z, x.w, 0x7632), __byte_perm(y.x, y.y, 0x7632), __byte_perm(y.z, y.w, 0x7632));
    }
    fence_async_smem();
    bar_sync(1, 256);
}
template <bool OP>
__device__ __forceinline__ void gemm_consumer(const Params& p, uint32_t sb, int id, int w) {
    constexpr int NS = OP ? 6 : 8, SB = OP ? 16384 : 8192, RING = OP ? 131072 : 163840;
    const int lane = threadIdx.x & 31, wg = w >> 2, t = w & 3, u = id * 2 + wg;
    uint32_t a[128];
    mbar_wait(sb + G_BAR + GB_RS * 8, 0);
    if (OP) op_permute(sb);
    {
        const uint32_t wo = sb + (OP ? 0 : Q_STG) + wg * 65536 + (((lane >> 4) << 3) + (lane & 7)) * 128 + (((2 * t + ((lane >> 3) & 1)) ^ (lane & 7)) << 4);
#pragma unroll
        for (int ks = 0; ks < 32; ks++) { const uint4 v = ldsm4t(wo + ks * 2048); a[ks * 4] = v.x; a[ks * 4 + 1] = v.y; a[ks * 4 + 2] = v.z; a[ks * 4 + 3] = v.w; }
    }
    fence_async_smem();
    __syncwarp();
    if (lane == 0) mbar_arrive(sb + G_BAR + GB_FREE * 8);
    mbar_wait(sb + G_BAR + GB_SS * 8, 0);
    if (OP) op_permute(sb);
    float c0[32], c1[OP ? 32 : 40];
    int st = 0; uint32_t ph = 0;
    const bool el = (threadIdx.x & 127) == 0;
#pragma unroll 1
    for (int n = 0; n < p.nl[OP]; n++) {
        int prev = 0;
        const uint32_t wb = sb + wg * (OP ? 65536 : 81920) + (n & p.zero);
        const uint64_t dw = OP ? mkdesc(wb, 0, 1024, 1) : mkdesc(wb, 16384, 256, 3);
        if (!OP && wg) mbar_wait(sb + G_BAR + GB_LAG * 8, n & 1);
#pragma unroll
        for (int s = 0; s < 8; s++) {
            mbar_wait(sb + G_BAR + (GB_FULL + st) * 8, ph);
            const uint64_t dx = mkdesc(sb + RING + st * SB, 128, 1024, 0);
            wg_fence();
#pragma unroll
            for (int kk = 0; kk < 4; kk++) {
                const int ks = s * 4 + kk;
                if (ks == 0) { wgmma64_rs<0>(c0, a, dx); if (OP) wgmma64_ta<0>(c1, dw, dx + 512); else wgmma80_tb<0>(c1, dx, dw); }
                else { wgmma64_rs<1>(c0, a + ks * 4, dx + kk * 16); if (OP) wgmma64_ta<1>(c1, dw + ks * 128, dx + 512 + kk * 16); else wgmma80_tb<1>(c1, dx + kk * 16, dw + ks * 32); }
            }
            wg_commit();
            if (s) {
                wg_wait<1>();
                if (el) { mbar_arrive(sb + G_BAR + (GB_EMPTY + prev) * 8); if (!OP && s == QLAG && !wg) mbar_arrive(sb + G_BAR + GB_LAG * 8); }
            }
            prev = st;
            if (++st == NS) { st = 0; ph ^= 1; }
        }
        const int e = p.list[OP][n];
        wg_wait<0>();
        if (el) mbar_arrive(sb + G_BAR + (GB_EMPTY + prev) * 8);
        PROF(threadIdx.x == 128, 1024 + n * 4 + 1);
        if (OP) {
            uint4* dst = g_pp + (e * 4 + (id >> 2)) * 4096 + ((u & 7) * 32 + t * 8) * 16 + (lane >> 2) * 16 + (lane & 3);
#pragma unroll
            for (int j = 0; j < 4; j++) {
                const float* x = c0 + j * 8; const float* y = c1 + j * 8;
                stg128(dst + j * 4, make_uint4(pack2(x[0] + y[0], x[1] + y[1]), pack2(x[2] + y[2], x[3] + y[3]), pack2(x[4] + y[4], x[5] + y[5]), pack2(x[6] + y[6], x[7] + y[7])), POL_SOON);
            }
        } else {
            uint4* dst = g_qkv + (size_t)e * 2 * 32 * 1536 + lane;
            const uint64_t pol = POL_SOON;
#pragma unroll
            for (int j = 0; j < 4; j++) {
                const float* x = c0 + j * 8;
                uint4 v = make_uint4(pack2(x[0], x[1]), pack2(x[2], x[3]), pack2(x[4], x[5]), pack2(x[6], x[7]));
                if (u >= 64) v = make_uint4(movm(v.x), movm(v.z), movm(v.y), movm(v.w));
                stg128(dst + (((j >> 1) * 32 + ((u & 63) >> 1)) * 1536 + (u < 64 ? 1024 : 0) + (j & 1) * 256 + ((u & 1) * 4 + t) * 32), v, pol);
            }
#pragma unroll
            for (int j = 0; j < 5; j++) {
                const float* x = c1 + (OP ? 0 : j * 8);
                const int blk = qkv_blk(id, wg * 5 + j);
                if (blk < 512) stg128(dst + (((t >> 1) * 32 + ((blk >> 3) & 31)) * 1536 + (blk >> 8) * 512 + (t & 1) * 256 + (blk & 7) * 32),
                                      make_uint4(pack2(x[0], x[1]), pack2(x[2], x[3]), pack2(x[4], x[5]), pack2(x[6], x[7])), pol);
            }
        }
        __syncwarp();
        if (lane == 0) mbar_arrive(sb + G_BAR + (GB_DONE + (n & 1) * 2 + wg) * 8);
        PROF(threadIdx.x == 128, 1024 + n * 4 + 2);
    }
}

template <int NP, bool MMA>
__device__ __forceinline__ void sum_partials(float* x, const uint2* src, const uint32_t* r0, const uint32_t* r1, uint32_t idm) {
    uint2 v[4][NP];
#pragma unroll
    for (int s = 0; s < 4; s++)
#pragma unroll
        for (int i = 0; i < NP; i++) asm volatile("ld.global.cg.L2::cache_hint.v2.u32 {%0,%1},[%2],%3;" : "=r"(v[s][i].x), "=r"(v[s][i].y) : "l"(src + s * 8192 + i * 32), "l"(POL_LAST) : "memory");
#pragma unroll
    for (int i = 0; i < NP; i++) {
        uint32_t a, b;
        if (MMA) {
            float t[4] = {0, 0, 0, 0};
            mma16(t, v[0][i].x, v[0][i].y, v[1][i].x, v[1][i].y, idm, idm); mma16(t, v[2][i].x, v[2][i].y, v[3][i].x, v[3][i].y, idm, idm);
            a = pack2(t[0], t[2]); b = pack2(t[1], t[3]);
        } else {
            a = pack2((blo(v[0][i].x) + blo(v[1][i].x)) + (blo(v[2][i].x) + blo(v[3][i].x)), (blo(v[0][i].y) + blo(v[1][i].y)) + (blo(v[2][i].y) + blo(v[3][i].y)));
            b = pack2((bhi(v[0][i].x) + bhi(v[1][i].x)) + (bhi(v[2][i].x) + bhi(v[3][i].x)), (bhi(v[0][i].y) + bhi(v[1][i].y)) + (bhi(v[2][i].y) + bhi(v[3][i].y)));
        }
        const uint32_t s0 = hadd2(a, r0[i]), s1 = hadd2(b, r1[i]);
        x[4 * i] = blo(s0); x[4 * i + 2] = bhi(s0); x[4 * i + 1] = blo(s1); x[4 * i + 3] = bhi(s1);
    }
}
__device__ __forceinline__ const uint2* pp_src(int e, int tile, int lane) { return (const uint2*)g_pp + e * 32768 + tile * 128 + (lane >> 3) * 8 + (lane & 3) * 2 + ((lane >> 2) & 1); }
__device__ __forceinline__ int x_off(int e, int tile, int lane) { return e * 4096 + (tile >> 3) * 512 + (lane >> 2) * 64 + (tile & 7) * 8 + (lane & 3) * 2; }

__device__ __forceinline__ void fin_warp(const Params& p, uint32_t sb, int tile) {
    const int lane = threadIdx.x & 31;
    wait_cnt_warp(g_gate, lds32(sb + S_GATE));
#pragma unroll 1
    for (int e = 32; e < 64; e++) {
        wait_cnt_warp(cnt_ptr(C_PP + e * 8 + (tile >> 3)), 4);
        const uint4 r0 = ldcg128(g_x + x_off(e, tile, lane)), r1 = ldcg128(g_x + x_off(e, tile, lane) + 1);
        uint32_t o0[4], o1[4];
#pragma unroll
        for (int h = 0; h < 2; h++) {
            const uint32_t a[2] = {h ? r0.z : r0.x, h ? r0.w : r0.y}, b[2] = {h ? r1.z : r1.x, h ? r1.w : r1.y};
            float x[8];
            sum_partials<2, false>(x, pp_src(e, tile, lane) + h * 64, a, b, 0);
#pragma unroll
            for (int i = 0; i < 2; i++) {
                o0[h * 2 + i] = __byte_perm(__float_as_uint(x[4 * i]), __float_as_uint(x[4 * i + 2]), 0x7632);
                o1[h * 2 + i] = __byte_perm(__float_as_uint(x[4 * i + 1]), __float_as_uint(x[4 * i + 3]), 0x7632);
            }
        }
        uint4* dst = (uint4*)p.out + ((e - 32) * 64 + lane * 2) * 64 + tile;
        dst[0] = make_uint4(o0[0], o0[1], o0[2], o0[3]); dst[64] = make_uint4(o1[0], o1[1], o1[2], o1[3]);
        PROF(lane == 0, 1536 + e);
    }
}

constexpr int PROW = 272, UROW = 2304, UPRE = 256;
constexpr int C_UR = 0  , C_TB = 65536  , C_BG = C_TB + 51200,
              CB_M = 8960, CB_U = CB_M + 1792, CB_BIG = CB_U + 2560, C_ST = C_BG + 8 * CB_BIG  ;
static_assert(C_ST + 4736 <= B_BAR, "smem map");
enum { CB_TB = 0, CB_UF = 1  , CB_CF = 5  , CB_LD = 9   };
__device__ __forceinline__ void conv_init(uint32_t sb, bool spare) {
    const int i = threadIdx.x & 31;
    mbar_init(sb + B_BAR + i * 8, (i >= CB_UF && i < CB_CF && !spare) ? 2 : 1);
    if (i == CB_TB && !spare) mbar_expect(sb + B_BAR + i * 8, 51200);
    asm volatile("fence.mbarrier_init.release.cluster;" ::: "memory");
}
__device__ __forceinline__ void mma_q(float* c, const uint32_t* a, const uint4& q) {
    mma16(c, a[0], a[1], a[2], a[3], q.x, q.y); mma16(c, a[4], a[5], a[6], a[7], q.z, q.w);
}
__device__ __forceinline__ uint2 ld_acc(const uint2* p, bool on) {
    uint2 v = make_uint2(0, 0);
    asm volatile("{.reg .pred p; setp.ne.u32 p,%3,0; @p ld.global.cg.v2.u32 {%0,%1},[%2];}" : "+r"(v.x), "+r"(v.y) : "l"(p), "r"((uint32_t)on) : "memory");
    return v;
}
__device__ __forceinline__ void add_acc(float* c, uint2 v) { c[0] += blo(v.x); c[1] += bhi(v.x); c[2] += blo(v.y); c[3] += bhi(v.y); }
__device__ __forceinline__ void st_acc(uint2* p, const float* c) { *p = make_uint2(pack2(c[0], c[1]), pack2(c[2], c[3])); }
__device__ __forceinline__ float sum8(const uint4* v, int k) {
#define VK(i) __uint_as_float(k == 0 ? v[i].x : k == 1 ? v[i].y : k == 2 ? v[i].z : v[i].w)
    return ((VK(0) + VK(1)) + (VK(2) + VK(3))) + ((VK(4) + VK(5)) + (VK(6) + VK(7)));
}
template <int XW, class F>
__device__ __forceinline__ float4 conv_stats(uint32_t sb, uint32_t l16, const float* x, uint4* gs, int q, int w, F&& meanwhile) {
    float s0 = 0, s1 = 0, m0 = 0, m1 = 0;
#pragma unroll
    for (int i = 0; i < 8; i++) { s0 += x[2 * i]; s1 += x[2 * i + 1]; m0 = fmaf(x[2 * i], x[2 * i], m0); m1 = fmaf(x[2 * i + 1], x[2 * i + 1], m1); }
    sts128(l16 + C_ST + w * 512, __float_as_uint(s0), __float_as_uint(m0), __float_as_uint(s1), __float_as_uint(m1));
    if (w == XW) {
        bar_sync(2, 256);
        uint4 v[8];
#pragma unroll
        for (int i = 0; i < 8; i++) v[i] = lds128(l16 + C_ST + i * 512);
        st_rlx128(gs + q * 32, __float_as_uint(sum8(v, 0)), __float_as_uint(sum8(v, 1)) & 0x7fffffffu, __float_as_uint(sum8(v, 2)), __float_as_uint(sum8(v, 3)));
    } else bar_arrive(2, 256);
    meanwhile();
    if (w == XW) {
        uint4 v[8];
        int n = 0;
        while (true) {
            uint32_t bad = 0;
#pragma unroll
            for (int i = 0; i < 8; i++) v[i] = ld_rlx128(gs + i * 32);
#pragma unroll
            for (int i = 0; i < 8; i++) bad |= v[i].y;
            if (!__any_sync(0xffffffffu, bad >> 31)) break;
            if (++n > 2000000) __trap();
        }
        s0 = sum8(v, 0) * (1.f / 512.f); s1 = sum8(v, 2) * (1.f / 512.f);
        const float2 l0 = ln_finish(s0, fmaxf(fmaf(sum8(v, 1), 1.f / 512.f, -s0 * s0), 0.f)), l1 = ln_finish(s1, fmaxf(fmaf(sum8(v, 3), 1.f / 512.f, -s1 * s1), 0.f));
        sts128(l16 + C_ST + 4096, __float_as_uint(l0.x), __float_as_uint(rcp(l0.y)), __float_as_uint(l1.x), __float_as_uint(rcp(l1.y)));
    }
    bar_sync(3, 256);
    const uint4 r = lds128(l16 + C_ST + 4096);
    return make_float4(__uint_as_float(r.x), __uint_as_float(r.y), __uint_as_float(r.z), __uint_as_float(r.w));
}

__device__ __forceinline__ void conv_tile(const Params& p, uint32_t sb, int q, int w) {
    const int lane = __shfl_sync(0xffffffffu, threadIdx.x & 31, threadIdx.x & 31), g = lane >> 2, c = lane & 3, tile = q * 8 + w;
    const uint32_t l16 = sb + lane * 16;
#pragma unroll
    for (int i = 0; i < 16; i++) sts128(l16 + C_UR + w * 8192 + i * 512, 0, 0, 0, 0);
    wait_cnt_warp(g_gate, lds32(sb + S_GATE));
    if (lane < 8) bulk_g2s(sb + C_TB + (w * 8 + lane) * 800, g_P + (tile * 8 + lane) * PROW + 72, 800, sb + B_BAR + CB_TB * 8, POL_N);
    uint32_t A[8][8];
#pragma unroll
    for (int k = 0; k < 8; k++)
#pragma unroll
        for (int j = 0; j < 8; j++) A[k][j] = __ldcg(g_P + (tile * 8 + k) * PROW + 16 + 8 * j + g - 2 * c);
    if (lane == 0) { const uint4 d = __ldg((const uint4*)p.Dskip + tile); sts128(sb + C_ST + 4608 + w * 16, d.x, d.y, d.z, d.w); }
    float acc[8][4];
#pragma unroll
    for (int k = 0; k < 8; k++) acc[k][0] = acc[k][1] = acc[k][2] = acc[k][3] = 0;
    const uint32_t row = sb + C_UR + w * 8192, to = (8 + g - 2 * c) * 4, qo = (lane & 7) * 16 - (lane >> 3) * 32;
    auto near = [&](int z, int m) {
        const uint32_t qa = row + ((qo + z * 128) & 1023);
#pragma unroll
        for (int k = 0; k < 8; k++) {
            uint32_t a[8];
#pragma unroll
            for (int j = 0; j < 8; j++) a[j] = lds32(to + (sb + C_TB + w * 6400 + (m - 1) * 256) + k * 800 + j * 32);
            mma_q(acc[k], a, ldsm4(qa + k * 1024));
            if (k % NFE == NFE - 1 && k < 7) asm volatile("{.reg .pred p; setp.eq.u32 p,%0,%1; @p trap;}" ::"r"(p.zero), "r"(k + 1) : "memory");
        }
    };
    bar_sync(4, 384);
    mbar_wait(sb + B_BAR + CB_TB * 8, 0);
#pragma unroll 1
    for (int b = 0; b < 32; b++) {
        const int lz = lane + (b & p.zero);
        const uint4 r0 = ldcg128(g_x + x_off(b, tile, lz)), r1 = ldcg128(g_x + x_off(b, tile, lz) + 1);
#pragma unroll 1
        for (int m = w == 1 ? 3 : 2; m > (w ? 1 : 0); m--) near(b - m, m);
        PROF(threadIdx.x == 0, 2048 + b * 8);
        const uint2* pps = pp_src(b, tile, lz);
        asm volatile("" : "+l"(pps));
        wait_flag_warp(cnt_ptr(C_PP + b * 8 + q), 4);
        PROF(threadIdx.x == 0, 2048 + b * 8 + 1);
        float x[16];
        {
            const uint32_t a[4] = {r0.x, r0.y, r0.z, r0.w}, bb[4] = {r1.x, r1.y, r1.z, r1.w};
            sum_partials<4, true>(x, pps, a, bb, (2 * (lz & 3) == lz >> 2) ? 0x00003f80u : (2 * (lz & 3) + 1 == lz >> 2) ? 0x3f800000u : 0u);
        }
        float4 ln = conv_stats<0>(sb, l16, x, g_st + b * 256 + lz, q, w, [&]() {
            PROF(threadIdx.x == 0, 2048 + b * 8 + 2);
            if (b) mbar_wait(sb + B_BAR + (CB_CF + (w >> 1)) * 8, (b - 1) & 1);
            const uint2* cb = g_carry + ((tile * 320 + b) * 32 + lz);
            uint2 cr[8];
#pragma unroll
            for (int k = 0; k < 8; k++) cr[k] = ld_acc(cb + k * 1280, b >= 4);
            if (w) near(b - 1, 1);
#pragma unroll
            for (int k = 0; k < 8; k++) add_acc(acc[k], cr[k]);
        });
        PROF(threadIdx.x == 0, 2048 + b * 8 + 3);
        uint32_t u[8];
#pragma unroll
        for (int k = 0; k < 8; k++) {
            u[k] = pack2(rbf(x[2 * k] - ln.x) * ln.y, rbf(x[2 * k + 1] - ln.z) * ln.w);
            sts32(row + k * 1024 + (b & 7) * 128 + lane * 4, u[k]);
        }
        __syncwarp();
        const uint32_t qa = row + ((qo + b * 128) & 1023);
#pragma unroll
        for (int k = 0; k < 8; k++) mma_q(acc[k], A[k], ldsm4(qa + k * 1024));
        const uint4 dk = lds128(sb + C_ST + 4608 + w * 16);
#pragma unroll
        for (int k = 0; k < 8; k++) {
            const float t = __shfl_sync(0xffffffffu, acc[k][3], (lz & ~3) | ((lz - 1) & 3));
            const uint32_t y = movm(pack2(acc[k][0] + (c ? t : 0.f), acc[k][1] + acc[k][2]));
            acc[k][0] = c ? 0.f : t; acc[k][1] = acc[k][2] = acc[k][3] = 0;
            const uint32_t dw = k >> 1 == 0 ? dk.x : k >> 1 == 1 ? dk.y : k >> 1 == 2 ? dk.z : dk.w;
            const uint32_t s = hadd2(hadd2(y, hmul2(u[k], __byte_perm(dw, 0, (k & 1) ? 0x3232 : 0x1010))), __byte_perm(__float_as_uint(x[2 * k]), __float_as_uint(x[2 * k + 1]), 0x7632));
            x[2 * k] = blo(s); x[2 * k + 1] = bhi(s);
        }
        if (lane == 0) mbar_arrive(sb + B_BAR + (CB_UF + (w >> 1)) * 8);
        ln = conv_stats<1>(sb, l16, x, g_st + (32 + b) * 256 + lz, q, w, [&]() {
            PROF(threadIdx.x == 0, 2048 + b * 8 + 4);
            uint4* dst = g_x + x_off(32 + b, tile, lz);
#pragma unroll
            for (int e = 0; e < 2; e++)
                dst[e] = make_uint4(__byte_perm(__float_as_uint(x[e]), __float_as_uint(x[2 + e]), 0x7632), __byte_perm(__float_as_uint(x[4 + e]), __float_as_uint(x[6 + e]), 0x7632),
                                    __byte_perm(__float_as_uint(x[8 + e]), __float_as_uint(x[10 + e]), 0x7632), __byte_perm(__float_as_uint(x[12 + e]), __float_as_uint(x[14 + e]), 0x7632));
            uint32_t* du = g_u + (tile * 8 * (UROW / 2) + UPRE / 2 + b * 32 + lz);
#pragma unroll
            for (int k = 0; k < 8; k++) du[k * (UROW / 2)] = u[k];
            if (w != 1) near(b - 2, 3);
        });
        PROF(threadIdx.x == 0, 2048 + b * 8 + 5);
        uint4* dst = g_xn + x_off(32 + b, tile, lz);
#pragma unroll
        for (int e = 0; e < 2; e++) {
            const float mu = e ? ln.z : ln.x, rs = e ? ln.w : ln.y;
            dst[e] = make_uint4(pack2(rbf(x[e] - mu) * rs, rbf(x[2 + e] - mu) * rs), pack2(rbf(x[4 + e] - mu) * rs, rbf(x[6 + e] - mu) * rs),
                                pack2(rbf(x[8 + e] - mu) * rs, rbf(x[10 + e] - mu) * rs), pack2(rbf(x[12 + e] - mu) * rs, rbf(x[14 + e] - mu) * rs));
        }
        if (w == 7) {
            bar_sync(5, 256);
            if (lane == 0) red_release(cnt_ptr(C_XN + 32 + b), 1);
            PROF(lane == 0, 2048 + b * 8 + 6);
            __syncwarp();
        } else bar_arrive(5, 256);
    }
}

template <int P0, bool TRI = false>
__device__ __forceinline__ void bg_half(float (*acc)[4], uint4* win, uint32_t ta, uint32_t qa, uint32_t mask, uint32_t row) {
#pragma unroll
    for (int i = 0; i < 4; i++) {
        win[P0 + i] = ldsm4(((qa + i * 128) & mask) + row);
        const uint4 a = lds128(ta + (3 - i) * 448), e = lds128(ta + (3 - i) * 448 + 224);
#pragma unroll
        for (int r = TRI ? 7 - P0 - i : 0; r < 8; r++) mma16(acc[r], a.x, a.y, a.z, a.w, win[(P0 + i + 1 + r) & 7].x, win[(P0 + i + 1 + r) & 7].y);
#pragma unroll
        for (int r = TRI ? 7 - P0 - i : 0; r < 8; r++) mma16(acc[r], e.x, e.y, e.z, e.w, win[(P0 + i + 1 + r) & 7].z, win[(P0 + i + 1 + r) & 7].w);
    }
}
__device__ __forceinline__ void bg_fetch(uint32_t sb, int q, int j, int n, int lane) {
    const int b0 = n >> 1, ch = q * 64 + j * 16 + (n & 1) * 8 + (b0 & 7), lo = max(b0 - 24, -4), nu = b0 > 4 ? (b0 - 4 - lo) * 128 : 0;
    const uint32_t bar = sb + B_BAR + (CB_LD + j * 2 + (n & 1)) * 8, buf = sb + C_BG + (j * 2 + (n & 1)) * CB_BIG;
    const int nt = min((b0 + 7) >> 2, 5) * 1792;
    if (elect()) {
        mbar_expect(bar, nt + nu + 1792);
        bulk_g2s(buf, g_W + ch * 784, nt, bar, POL_N);
        bulk_g2s(buf + CB_M, g_W + (ch ^ 4) * 784, 1792, bar, POL_N);
        if (nu) bulk_g2s(buf + CB_U + (lo - b0 + 24) * 128, g_u + ch * (UROW / 2) + UPRE / 2 + lo * 32, nu, bar, POL_N);
    }
    __syncwarp();
}
__device__ __forceinline__ void conv_back(uint32_t sb, int q, int j) {
    const int lane = __shfl_sync(0xffffffffu, threadIdx.x & 31, threadIdx.x & 31), g = lane >> 2, c = lane & 3;
    wait_cnt_warp(g_gate, lds32(sb + S_GATE));
    bg_fetch(sb, q, j, 2, lane);
    bar_sync(4, 384);
    const uint32_t to = (6 + g - 2 * c) * 16, qo = (lane & 7) * 16 - (lane >> 3) * 32;
#pragma unroll 1
    for (int n = 2; n < 64; n++) {
        const int b0 = n >> 1, i = n & 1, chl = j * 16 + i * 8 + (b0 & 7), hm = (b0 + 7) >> 2;
        const uint32_t buf = sb + C_BG + (j * 2 + i) * CB_BIG, ta = buf + to;
        float acc[8][4];
        uint4 win[8];
        if (n < 63) bg_fetch(sb, q, j, n + 1, lane);
        if (n == 34 || n == 42) wait_flag_warp(cnt_ptr(C_FAR + (n == 42)), 12);
        mbar_wait(sb + B_BAR + (CB_LD + j * 2 + i) * 8, (b0 - 1) & 1);
#pragma unroll
        for (int r = 0; r < 8; r++) {
            acc[r][0] = acc[r][1] = acc[r][2] = acc[r][3] = 0;
            win[r] = make_uint4(0, 0, 0, 0);
            if (r) asm volatile("{.reg .pred p; setp.ge.s32 p,%5,24; @p ldmatrix.sync.aligned.m8n8.x4.shared.b16 {%0,%1,%2,%3},[%4];}"
                                : "+r"(win[r].x), "+r"(win[r].y), "+r"(win[r].z), "+r"(win[r].w) : "r"(buf + CB_U + qo + r * 128), "r"(b0 + r) : "memory");
        }
        const uint2* fr = g_far + (((q * 64 + chl) * 8 + b0 - 24) * 32 + lane);
        uint2* cr = g_carry + (((q * 64 + chl) * 40 + b0) * 32 + lane);
        uint2* cm = g_carry + (((q * 64 + (chl ^ 4)) * 40 + b0) * 32 + lane);
        const uint32_t fm = 0xff000000u >> b0;
        uint2 pf[8], pm[4];
#pragma unroll
        for (int r = 0; r < 8; r++) pf[r] = ld_acc(fr + r * 32, (fm >> r) & 1);
#pragma unroll
        for (int r = 0; r < 4; r++) pm[r] = ld_acc(cm + r * 32, b0 > 4);
#pragma unroll 1
        for (int h = hm > 3 ? 5 : 3; h >= 3; h -= 2) {
            if (h <= hm) bg_half<0>(acc, win, ta + (h - 1) * 1792, qo + (28 - 4 * h) * 128, ~0u, buf + CB_U);
            if (h == 3 && i == 0) mbar_wait(sb + B_BAR + (CB_UF + j) * 8, (b0 - 1) & 1);
            bg_half<4>(acc, win, ta + (h - 2) * 1792, qo + (h == 3 ? b0 - 4 : 12) * 128, h == 3 ? 1023u : ~0u, h == 3 ? sb + C_UR + chl * 1024 : buf + CB_U);
        }
        uint4 wm[8];
#pragma unroll
        for (int r = 1; r < 8; r++) wm[r] = ldsm4(sb + C_UR + (chl ^ 4) * 1024 + ((qo + (b0 + r) * 128) & 1023));
#pragma unroll
        for (int r = 0; r < 8; r++) add_acc(acc[r], pf[r]);
#pragma unroll
        for (int r = 4; r < 8; r++) { st_acc(cr + r * 32, acc[r]); acc[r][0] = blo(pm[r - 4].x); acc[r][1] = bhi(pm[r - 4].x); acc[r][2] = blo(pm[r - 4].y); acc[r][3] = bhi(pm[r - 4].y); }
#pragma unroll
        for (int t = 7; t >= 0; t--) {
            const uint4 a = lds128(ta + t * 224), e = lds128(ta + CB_M + t * 224);
#pragma unroll
            for (int r = 0; r < 4; r++) { const uint4& x = win[4 + r - (t >> 1)]; mma16(acc[r], a.x, a.y, a.z, a.w, (t & 1) ? x.z : x.x, (t & 1) ? x.w : x.y); }
#pragma unroll
            for (int r = 0; r < 4; r++) { const uint4& x = wm[4 + r - (t >> 1)]; mma16(acc[4 + r], e.x, e.y, e.z, e.w, (t & 1) ? x.z : x.x, (t & 1) ? x.w : x.y); }
        }
#pragma unroll
        for (int r = 0; r < 4; r++) { st_acc(cr + r * 32, acc[r]); st_acc(cm + r * 32, acc[4 + r]); }
        __syncwarp();
        if (lane == 0 && i) mbar_arrive(sb + B_BAR + (CB_CF + j) * 8);
        PROF(j == 0 && lane == 0 && i, 2048 + b0 * 8 + 7);
    }
}
__device__ __forceinline__ void conv_far(uint32_t sb, int w) {
    const int lane = __shfl_sync(0xffffffffu, threadIdx.x & 31, threadIdx.x & 31), g = lane >> 2, c = lane & 3;
    wait_cnt_warp(g_gate, lds32(sb + S_GATE));
    wait_cnt_warp(cnt_ptr(C_XN + 39), 8);
    const uint32_t to = (6 + g - 2 * c) * 16, qo = (lane & 7) * 16 - (lane >> 3) * 32;
#pragma unroll 1
    for (int n = -1; n * 12 + w < 512; n++) {
        const int t = n * 12 + w, ch = (t & 63) * 8 + (((t >> 6) + 1) & 7), cn = ((t + 12) & 63) * 8 + ((((t + 12) >> 6) + 1) & 7);
        const uint32_t bar = sb + B_BAR + (w * 2 + (n & 1)) * 8, buf = sb + (w * 2 + (n & 1)) * 5120;
        if (t + 12 < 512 && elect()) {
            const uint32_t nb = sb + (w * 2 + (~n & 1)) * 5120;
            mbar_expect(bar ^ 8, 3584 + 1152);
            bulk_g2s(nb, g_W + cn * 784 + 560, 3584, bar ^ 8, POL_N);
            bulk_g2s(nb + 3584, g_u + cn * (UROW / 2) + UPRE / 2 - 32, 1152, bar ^ 8, POL_N);
        }
        __syncwarp();
        if (n < 0) continue;
        float acc[8][4];
        uint4 win[8];
#pragma unroll
        for (int r = 0; r < 8; r++) { acc[r][0] = acc[r][1] = acc[r][2] = acc[r][3] = 0; win[r] = make_uint4(0, 0, 0, 0); }
        mbar_wait(bar, (n >> 1) & 1);
        bg_half<0, true>(acc, win, buf + to + 1792, qo + 128, ~0u, buf + 3584);
        bg_half<4, true>(acc, win, buf + to, qo + 640, ~0u, buf + 3584);
#pragma unroll
        for (int r = 0; r < 8; r++) st_acc(g_far + (ch * 256 + lane) + r * 32, acc[r]);
        __syncwarp();
        if (((t + 12) ^ t) >= 256 && elect()) red_release(cnt_ptr(C_FAR + (t >> 8)), 1);
        __syncwarp();
    }
    PROF(threadIdx.x == 0, 2048);
}

constexpr int P_Y = 131072  , P_PRM = P_Y  , P_K6 = P_PRM + 8192  ,
              P_P = P_Y + 40960  , P_U = P_P + 33280  , P_END = P_U + 17408, P_X = 98304  ;
static_assert(P_END <= B_BAR && P_END <= R_SEL, "prologue scratch");
#define KGUN 2
constexpr int KGU = KGUN;
__device__ __forceinline__ void csq(float& r, float& i) { const float t = r * i; r = fmaf(r, r, -(i * i)); i = t + t; }
__device__ __forceinline__ void cpow(float ar, float ph, float p, float& r, float& i) {
    const float e = ex2(ar * p);
    const float u = ph * p, n = fabsf(u) < 4194304.f ? (u + 12582912.f) - 12582912.f : u;
    const float t = (u - n) * 6.283185307179586f;
    r = e * __cosf(t); i = e * __sinf(t);
}
__device__ __forceinline__ void mma_tf32(float* c, float a0, float a1, float a2, float a3, float b0, float b1) {
    asm volatile("mma.sync.aligned.m16n8k8.row.col.f32.tf32.tf32.f32 {%0,%1,%2,%3},{%4,%5,%6,%7},{%8,%9},{%0,%1,%2,%3};"
                 : "+f"(c[0]), "+f"(c[1]), "+f"(c[2]), "+f"(c[3])
                 : "r"(__float_as_uint(a0)), "r"(__float_as_uint(a1)), "r"(__float_as_uint(a2)), "r"(__float_as_uint(a3)), "r"(__float_as_uint(b0)), "r"(__float_as_uint(b1)));
}

struct ProRegs { uint32_t v[2][4], ldt[2]; };
__device__ __forceinline__ void prologue_load(const ProArgs& a, int b, ProRegs& pr) {
    const int w = threadIdx.x >> 5;
#pragma unroll
    for (int i = 0; i < 2; i++) {
        const int gi = b * 512 + (w & 3) * 128 + ((w >> 2) & 1) * 64 + i * 32 + (threadIdx.x & 31);
        pr.ldt[i] = __ldg((const uint16_t*)a.ldt + b * 4 + (w & 3));
        pr.v[i][0] = __ldg((const uint16_t*)a.lAr + gi); pr.v[i][1] = __ldg((const uint16_t*)a.Ai + gi);
        pr.v[i][2] = __ldg((const uint16_t*)a.Cr + gi); pr.v[i][3] = __ldg((const uint16_t*)a.Ci + gi);
    }
}
__device__ __forceinline__ void prologue(const ProArgs& a, uint32_t sb, int b, int w, const ProRegs& pr) {
    const int tid = threadIdx.x, lane = tid & 31, g = lane >> 2, c = lane & 3;
    const int d0 = b * 4;
    if (w >= 8) {
        const int t2 = tid - 256;
        if (w < 10) {
            const int row = b * 16 + (w - 8) * 8 + g;
            uint4 v[16];
            const float2 r = row_stats512(v, (const uint4*)(a.x + (size_t)row * 512) + c, 8, 4);
            const float2 l = ln_finish(r.x * (1.f / 512.f), r.y * (1.f / 512.f));
            if (c == (g >> 1)) asm volatile("st.relaxed.gpu.global.u32 [%0],%1;" ::"l"(g_ln0 + row), "r"(pack2(l.x, l.y)) : "memory");
        }
        PROF(t2 == 0, 3516);
        const int gi = b * 128 + t2;
#pragma unroll 1
        for (int k = gi; k < 133 * 512; k += 16384) g_xch[k] = make_uint4(0, 0, 0, 0);
        g_st[gi] = make_uint4(~0u, ~0u, ~0u, ~0u);
        if (gi < 900 * 8) g_cnt[gi] = 0;
        if (gi < 64) g_sel[gi] = 0;
        bar_sync(6, 384);
        if (lane < 4) asm volatile("cp.async.bulk.prefetch.L2.global [%0],%1;" ::"l"(a.W[w - 8] + (b * 4 + lane) * 4096), "r"(8192) : "memory");
        bar_sync(9, 384);
#pragma unroll 2
        for (int i = t2; i < 4 * 784; i += 128) {
            const int ch = i / 784, k = i - ch * 784;
            const uint32_t o = sb + P_P + (ch * 2080 + 266 + (k / 14) * 18 + k) * 4;
            g_W[d0 * 784 + i] = make_uint4(lds32(o), lds32(o + 32), lds32(o + 64), lds32(o + 96));
        }
        bar_arrive(10, 384);
        PROF(t2 == 0, 3517);
        return;
    }
#pragma unroll
    for (int i = 0; i < 2; i++) {
        const float dt = rbf(expf(blo(pr.ldt[i])));
        const float ar = -rbf(expf(blo(pr.v[i][0]))) * dt, ai = blo(pr.v[i][1]) * dt;
        sts128(sb + P_PRM + (w * 64 + i * 32 + lane) * 16, __float_as_uint(ar * 1.4426950408889634f), __float_as_uint(ai * 0.15915494309189535f),
               __float_as_uint(2.f * (blo(pr.v[i][2]) * dt)), __float_as_uint(2.f * (blo(pr.v[i][3]) * dt)));
    }
    if (tid < 64) sts128(sb + P_U + (tid >> 3) * 2176 + (tid & 7) * 16, 0, 0, 0, 0);
    bar_arrive(6, 384);
    __syncwarp();
    PROF(tid == 0, 3510);
    const int ch = w & 3, hf = w >> 2;
    {
        float k0[4] = {0, 0, 0, 0}, k1[4] = {0, 0, 0, 0}, k2[4] = {0, 0, 0, 0}, k3[4] = {0, 0, 0, 0}, k4[4] = {0, 0, 0, 0}, kl = 0;
#pragma unroll KGU
        for (int j = 0; j < 16; j++) {
            const uint4 q = lds128(sb + P_PRM + (w * 64 + j * 4 + c) * 16);
            const float cr = __uint_as_float(q.z), ci = __uint_as_float(q.w);
            float wr[4], wi[4], vr[4], vi[4];
            cpow(__uint_as_float(q.x), __uint_as_float(q.y), (float)g, wr[0], wi[0]);
            cpow(__uint_as_float(q.x), __uint_as_float(q.y), (float)(g + 8), vr[0], vi[0]);
#pragma unroll
            for (int i = 1; i < 4; i++) { wr[i] = wr[i - 1]; wi[i] = wi[i - 1]; csq(wr[i], wi[i]); vr[i] = vr[i - 1]; vi[i] = vi[i - 1]; csq(vr[i], vi[i]); }
            float hr = wr[3], hi = wi[3];
            csq(hr, hi);
            mma_tf32(k0, wr[0], vr[0], wi[0], vi[0], cr * hr - ci * hi, -(cr * hi + ci * hr));
            hr = vr[3]; hi = vi[3]; csq(hr, hi);
            mma_tf32(k1, wr[0], vr[0], wi[0], vi[0], cr * hr - ci * hi, -(cr * hi + ci * hr));
            csq(hr, hi);
            mma_tf32(k2, wr[1], vr[1], wi[1], vi[1], cr * hr - ci * hi, -(cr * hi + ci * hr));
            csq(hr, hi);
            mma_tf32(k3, wr[2], vr[2], wi[2], vi[2], cr * hr - ci * hi, -(cr * hi + ci * hr));
            csq(hr, hi);
            mma_tf32(k4, wr[3], vr[3], wi[3], vi[3], cr * hr - ci * hi, -(cr * hi + ci * hr));
            csq(hr, hi);
            kl += cr * hr - ci * hi;
        }
        kl += __shfl_xor_sync(0xffffffffu, kl, 1); kl += __shfl_xor_sync(0xffffffffu, kl, 2);
        const uint32_t o = sb + P_K6 + (ch * 656 + c * 32 + g) * 4, ol = sb + P_K6 + (ch * 656 + 640) * 4;
#define KST(k, base) sts32(o + (base) * 4, __float_as_uint(k[0])); sts32(o + (base) * 4 + 64, __float_as_uint(k[1])); \
                     sts32(o + (base) * 4 + 32, __float_as_uint(k[2])); sts32(o + (base) * 4 + 96, __float_as_uint(k[3]))
#define KAD(k, base) k[0] += __uint_as_float(lds32(o + (base) * 4)); k[1] += __uint_as_float(lds32(o + (base) * 4 + 64)); \
                     k[2] += __uint_as_float(lds32(o + (base) * 4 + 32)); k[3] += __uint_as_float(lds32(o + (base) * 4 + 96))
        if (hf == 0) {
            bar_sync(2 + ch, 64);
            KAD(k0, 0); KAD(k1, 128); KAD(k2, 256); KAD(k3, 384); KAD(k4, 512);
            kl += __uint_as_float(lds32(ol));
            __syncwarp();
        }
        KST(k0, 0); KST(k1, 128); KST(k2, 256); KST(k3, 384); KST(k4, 512);
        if (lane == 0) sts32(ol, __float_as_uint(kl));
        if (hf == 1) { __syncwarp(); bar_arrive(2 + ch, 64); }
    }
    PROF(tid == 0, 3511);
    {
        uint4 l0, l1;
        int n = 0;
        while (true) {
            l0 = ld_rlx128((const uint4*)g_ln0 + tid * 2); l1 = ld_rlx128((const uint4*)g_ln0 + tid * 2 + 1);
            if (__all_sync(0xffffffffu, l0.x && l0.y && l0.z && l0.w && l1.x && l1.y && l1.z && l1.w)) break;
            if (++n > 2000000) __trap();
        }
        sts128(sb + P_P + tid * 32, l0.x, l0.y, l0.z, l0.w); sts128(sb + P_P + tid * 32 + 16, l1.x, l1.y, l1.z, l1.w);
        bar_sync(8, 384);
        mbar_wait(sb + S_XBAR, 0);
        __syncwarp();
#pragma unroll 2
        for (int i = 0; i < 8; i++) {
            const int t = w * 256 + i * 32 + lane;
            const uint32_t ln = lds32(sb + P_P + t * 4);
            const uint2 x = lds64(sb + P_X + t * 16 + (b & 1) * 8);
            const float m = blo(ln), rs = rcp(bhi(ln));
            const uint32_t u0 = pack2(rbf(blo(x.x) - m) * rs, rbf(bhi(x.x) - m) * rs), u1 = pack2(rbf(blo(x.y) - m) * rs, rbf(bhi(x.y) - m) * rs);
            sts128(sb + P_X + t * 16, x.x, x.y, u0, u1);
            const uint32_t o = sb + P_U + ((t >> 3) & 1) * 2176 + ((t >> 4) + 8) * 16 + (t & 7) * 2;
            asm volatile("st.shared.u16 [%0],%1;" ::"r"(o), "h"((uint16_t)u0) : "memory");
            asm volatile("st.shared.u16 [%0],%1;" ::"r"(o + 4352), "h"((uint16_t)(u0 >> 16)) : "memory");
            asm volatile("st.shared.u16 [%0],%1;" ::"r"(o + 8704), "h"((uint16_t)u1) : "memory");
            asm volatile("st.shared.u16 [%0],%1;" ::"r"(o + 13056), "h"((uint16_t)(u1 >> 16)) : "memory");
        }
    }
    bar_sync(1, 256);
    PROF(tid == 0, 3512);
    if (tid < 64) sts32(sb + P_P + ((tid >> 4) * 2080 + (tid & 15)) * 4, 0);
#pragma unroll 1
    for (int x = tid; x < 2048; x += 512) {
        uint32_t pw[2][4];
#pragma unroll
        for (int h = 0; h < 2; h++) {
            const int y = x + h * 256;
            const int i0 = y <= 256 ? y : 256 + (int)((pack2((float)y, 0.f) & 0xffff) - 0x4380);
            const int i1 = y <= 256 ? max(y - 1, 0) : 256 + (int)((pack2((float)(y - 1), 0.f) & 0xffff) - 0x4380);
#pragma unroll
            for (int k = 0; k < 4; k++) {
                const float lo = __uint_as_float(lds32(sb + P_K6 + k * 2624 + i0 * 4)), hi = __uint_as_float(lds32(sb + P_K6 + k * 2624 + i1 * 4));
                pw[h][k] = pack2(lo, y ? hi : 0.f);
            }
        }
#pragma unroll
        for (int h = 0; h < 2; h++)
#pragma unroll
            for (int k = 0; k < 4; k++) sts32(sb + P_P + (k * 2080 + x + h * 256 + 16) * 4, pw[h][k]);
    }
    fence_async_smem();
    bar_arrive(9, 384);
    bar_sync(1, 256);
    if (tid < 4) {
        asm volatile("cp.async.bulk.global.shared::cta.bulk_group [%0],[%1],%2;" ::"l"(g_P + (d0 + tid) * PROW), "r"(sb + P_P + tid * 8320), "r"(PROW * 4) : "memory");
        asm volatile("cp.async.bulk.commit_group;" ::: "memory");
    }
    __syncwarp();
    PROF(tid == 0, 3513);
    {
        float acc[16][4];
#pragma unroll
        for (int j = 0; j < 16; j++) acc[j][0] = acc[j][1] = acc[j][2] = acc[j][3] = 0;
#pragma unroll 1
        for (int e = hf * 4; e < hf * 4 + 4; e++) {
            uint32_t B[16][2];
            const uint32_t ua = sb + P_U + ch * 4352 + ((lane >> 3) & 1) * 2176 + (8 + (lane >> 4) * 8 + (lane & 7) - e) * 16;
#pragma unroll
            for (int j = 0; j < 8; j++) { const uint4 v = ldsm4(ua + j * 256); B[2 * j][0] = v.x; B[2 * j][1] = v.y; B[2 * j + 1][0] = v.z; B[2 * j + 1][1] = v.w; }
            const uint32_t pa = sb + P_P + (ch * 2080 + 16 + e * 16 + g - 2 * c) * 4;
#pragma unroll
            for (int d = 0; d < 16; d++) {
                const uint32_t a0 = lds32(pa + d * 512), a1 = lds32(pa + d * 512 + 32), a2 = lds32(pa + d * 512 - 32);
#pragma unroll
                for (int j = d; j < 16; j++) mma16(acc[j], a0, a1, a2, a0, B[j - d][0], B[j - d][1]);
            }
        }
        PROF(tid == 0, 3514);
        const uint32_t o = sb + P_Y + (ch * 2560 + c * 40 + g) * 4;
        if (hf == 0) {
            bar_sync(2 + ch, 64);
#pragma unroll
            for (int j = 0; j < 16; j++) {
                acc[j][0] += __uint_as_float(lds32(o + j * 640)); acc[j][1] += __uint_as_float(lds32(o + j * 640 + 80));
                acc[j][2] += __uint_as_float(lds32(o + j * 640 + 32)); acc[j][3] += __uint_as_float(lds32(o + j * 640 + 112));
            }
        }
#pragma unroll
        for (int j = 0; j < 16; j++) {
            sts32(o + j * 640, __float_as_uint(acc[j][0])); sts32(o + j * 640 + 80, __float_as_uint(acc[j][1]));
            sts32(o + j * 640 + 32, __float_as_uint(acc[j][2])); sts32(o + j * 640 + 112, __float_as_uint(acc[j][3]));
        }
        if (hf == 1) bar_arrive(2 + ch, 64);
    }
    const uint2 dk = __ldg((const uint2*)(a.Dk + d0));
    bar_sync(10, 384);
#pragma unroll 2
    for (int i = 0; i < 8; i++) {
        const int t = i * 256 + tid;
        const uint32_t o = sb + P_Y + (t + 4 * (t >> 4)) * 4;
        const uint4 xu = lds128(sb + P_X + t * 16);
        float y[4];
#pragma unroll
        for (int k = 0; k < 4; k++) y[k] = rbf(__uint_as_float(lds32(o + k * 10240)));
        uint2 r;
        r.x = pack2(blo(xu.x) + rbf(y[0] + rbf(blo(xu.z) * blo(dk.x))), bhi(xu.x) + rbf(y[1] + rbf(bhi(xu.z) * bhi(dk.x))));
        r.y = pack2(blo(xu.y) + rbf(y[2] + rbf(blo(xu.w) * blo(dk.y))), bhi(xu.y) + rbf(y[3] + rbf(bhi(xu.w) * bhi(dk.y))));
        ((uint2*)(g_x + ((t >> 6) * 8 + (d0 >> 6)) * 512 + ((t & 63) >> 3) * 64 + ((d0 & 63) >> 3) * 8 + (t & 7)))[(d0 >> 2) & 1] = r;
    }
    PROF(tid == 0, 3515);
    if (tid < 4) asm volatile("cp.async.bulk.wait_group 0;" ::: "memory");
}

__device__ __forceinline__ int pick_role(int cl, uint32_t rank, int rec0) {
    const int lane = threadIdx.x & 31;
    unsigned ep;
    asm volatile("ld.relaxed.gpu.global.u32 %0,[%1];" : "=r"(ep) : "l"(g_gate) : "memory");
    ep = (ep / (4 * NCL) + 1) * 2;
    if (rank == 0) {
        unsigned* r = (unsigned*)(((size_t)g_probe + 8191) & ~(size_t)8191) + cl * 8;
        uint32_t b0 = ~0u, b1 = ~0u;
#pragma unroll 1
        for (int i = 0; i < 6; i++) { b0 = min(b0, probe1(r, lane)); b1 = min(b1, probe1(r + 1024, lane)); }
        if (lane == 0) asm volatile("st.relaxed.gpu.global.u32 [%0],%1;" ::"l"(g_side + cl), "r"(ep + (b1 < b0)) : "memory");
    }
    uint32_t m[3];
#pragma unroll
    for (int i = 0; i < 3; i++) {
        unsigned v; int n = 0;
        const bool on = i * 32 + lane < NCL;
        while (true) {
            asm volatile("ld.relaxed.gpu.global.u32 %0,[%1];" : "=r"(v) : "l"(g_side + i * 32 + lane) : "memory");
            if (__all_sync(0xffffffffu, !on || (v & ~1u) == ep)) break;
            if (++n > 2000000) __trap();
        }
        m[i] = __ballot_sync(0xffffffffu, on && (v & 1));
    }
    if (__popc(m[0]) + __popc(m[1]) + __popc(m[2]) < NCL / 2) { m[0] = ~m[0]; m[1] = ~m[1]; m[2] = ~m[2] & 3; }
    const int tot = __popc(m[0]) + __popc(m[1]) + __popc(m[2]);
    int below = 0;
#pragma unroll
    for (int i = 0; i < 3; i++) below += __popc(m[i] & (cl >= i * 32 + 32 ? ~0u : cl <= i * 32 ? 0u : (1u << (cl - i * 32)) - 1));
    const bool mine = ((cl < 32 ? m[0] : cl < 64 ? m[1] : m[2]) >> (cl & 31)) & 1;
    const int skip = tot - 32;
    if (mine && below >= skip) return rec0 + below - skip;
    const int j = cl - max(below - skip, 0);
    return j < rec0 ? j : j + 32;
}

__global__ void __cluster_dims__(2, 1, 1) __launch_bounds__(384, 1) main_kernel(const __grid_constant__ Params p) {
    extern __shared__ __align__(1024) uint8_t smem[];
    const uint32_t sb = smem_u32(smem);
    uint32_t rank; asm("mov.u32 %0,%%cluster_ctarank;" : "=r"(rank));
    const int wi = __shfl_sync(0xffffffffu, threadIdx.x >> 5, 0);
    const int cl = blockIdx.x >> 1, wg = wi >> 2;
    PROF(threadIdx.x == 0, 3500);
    ProRegs pr;
    prologue_load(p.pa, max((int)blockIdx.x - 4, 0), pr);
    if (threadIdx.x == 352 && p.dopro && cl >= 2) {
        mbar_init(sb + S_XBAR, 1);
        asm volatile("fence.mbarrier_init.release.cluster;" ::: "memory");
        mbar_expect(sb + S_XBAR, 32768);
        for (int j = 0; j < 8; j++) tma2d(sb + P_X + j * 4096, &p.tm[3], ((blockIdx.x - 4) >> 1) * 8, j * 256, sb + S_XBAR);
    }
    if (threadIdx.x == 320) {
        unsigned v = 0;
        if (p.dopro) {
            asm volatile("ld.relaxed.gpu.global.u32 %0,[%1];" : "=r"(v) : "l"(g_gate) : "memory");
            v = (v / (4 * NCL) + 1) * (4 * NCL);
        }
        sts32(sb + S_GATE, v);
    }
    __syncwarp();
    if (wg == 2) bar_arrive(8, 384);
    if (wi == 10) {
        const int v = blockIdx.x;
        sts32(sb + S_VCL, v);
        if (v < V_REC || v == 131) conv_init(sb, v == 131); else if (v < V_OP) rec_init(sb); else gemm_init(sb, v < V_QKV);
        __syncwarp();
        if (threadIdx.x == 320 && v >= V_QKV && v < V_QKV + NQ && (p.roles & 8)) qkv_fetch(p, sb, v - V_QKV, 0, Q_PRE);
        __syncwarp();
        asm volatile("barrier.cluster.arrive.aligned;" ::: "memory");
    } else asm volatile("barrier.cluster.arrive.relaxed.aligned;" ::: "memory");
    if (p.dopro && cl >= 2) prologue(p.pa, sb, blockIdx.x - 4, wi, pr); else if (wg < 2) bar_sync(8, 384);
    asm volatile("barrier.cluster.wait.aligned;" ::: "memory");
    const int v = __shfl_sync(0xffffffffu, lds32(sb + S_VCL), 0);
    const int role = (v < V_REC ? 1 : v < V_OP ? 2 : v < V_QKV ? 4 : v < V_QKV + NQ ? 24 : 1) & p.roles;
    fence_async_smem();
    bar_sync(wg == 2 ? 7 : 1, wg == 2 ? 128 : 256);
    if (p.dopro && (threadIdx.x == 32 || threadIdx.x == 352)) red_release(g_gate, 1);
    if (threadIdx.x == 0) {
        if (role == 2) { rec_fetch(p, sb, (v - V_REC) >> 1, rank, 0, R_STQ); rec_fetch(p, sb, (v - V_REC) >> 1, rank, 1, R_STK); }
        if (role & 12) gemm_stage(p, sb, v - (role == 4 ? V_OP : V_QKV), role == 4);
    }
    PROF(threadIdx.x == 0, 3506);
    __syncwarp();
    if (role == 2) {
        const int head = (v - V_REC) >> 1;
        if (wg == 2) {
            reg_dec<RH>();
            const int w = wi & 3;
            rec_probe(sb, head * 2 + rank, w);
            if (threadIdx.x == 256) rec_fetch(p, sb, head, rank, 2, R_WV);
            __syncwarp();
            wait_cnt_warp(g_gate, lds32(sb + S_GATE));
            rec_sides(sb, head * 2 + rank, w);
            __syncthreads();
            cluster_sync();
            if ((p.chains >> (w & 1)) & 1) { if (w < 2) rec_comm(p, sb, w, head, rank); else rec_attn(p, sb, w & 1, head, rank); }
        } else {
            reg_inc<RW0>();
            rec_weights(p, sb, head, rank, wi);
        }
    } else if (role == 1) {
        if (v == 131) conv_far(sb, wi); else if (wg == 2) conv_back(sb, v, wi & 3); else conv_tile(p, sb, v, wi);
    } else if (role == 4) {
        if (wg == 2) {
            reg_dec<40>();
            if (wi == 8) gemm_producer<true>(p, sb, v - V_OP); else if (wi == 9) gemm_release<true>(p, sb, v - V_OP);
        } else { reg_inc<232>(); gemm_consumer<true>(p, sb, v - V_OP, wi); }
    } else if (role) {
        if (wg == 2) {
            reg_dec<40>();
            if (wi < 10) {
                if (role & 8) { if (wi == 8) gemm_producer<false>(p, sb, v - V_QKV); else gemm_release<false>(p, sb, v - V_QKV); }
            } else if (v < V_QKV + 32 && (role & 16)) fin_warp(p, sb, (v - V_QKV) * 2 + wi - 10);
        } else { reg_inc<232>(); if (role & 8) gemm_consumer<false>(p, sb, v - V_QKV, wi); }
    }
    __syncwarp();
    cluster_sync();
}

typedef CUresult (*EncFn)(CUtensorMap*, CUtensorMapDataType, cuuint32_t, void*, const cuuint64_t*, const cuuint64_t*, const cuuint32_t*, const cuuint32_t*,
                          CUtensorMapInterleave, CUtensorMapSwizzle, CUtensorMapL2promotion, CUtensorMapFloatOOBfill);
constexpr int SMEM_BYTES = 232448;
#define LAG 9
#define QLEAD 6
#define OLEAD (LAG / 2 + 2)
void plan(Params& P) {
    P.roles = 31; P.chains = 3; P.lag = LAG; P.dopro = 1;
    for (int r = 0; r < 2; r++) {
        const int lead = r ? OLEAD : QLEAD;
        int n = 0;
        for (int i = 0; i < 32 + lead; i++) {
            if (i >= lead) P.list[r][n++] = 32 + i - lead;
            if (i < 32) P.list[r][n++] = i;
        }
        P.nl[r] = n;
    }
}

#define TK() do {} while (0)
}

extern "C" void kernel_launch(void* const* d_in, const int* in_sizes, int n_in, void* d_out, int out_size) {
    typedef const __nv_bfloat16* BP;
    static EncFn enc = nullptr;
    if (!enc) {
        void* fn = nullptr; cudaDriverEntryPointQueryResult qr;
        cudaGetDriverEntryPoint("cuTensorMapEncodeTiled", &fn, cudaEnableDefault, &qr);
        enc = (EncFn)fn;
        cudaFuncSetAttribute(main_kernel, cudaFuncAttributeMaxDynamicSharedMemorySize, SMEM_BYTES);
    }
    static Params P;
    for (int i = 0; i < 4; i++) {
        const cuuint64_t cols = i < 3 ? 4096 : 512, rows = i < 3 ? 512 : 4096;
        cuuint64_t d2[2] = {cols, rows}, str[1] = {cols * 2};
        cuuint32_t box[2] = {64, 64}, bn[2] = {16, 256}, es[2] = {1, 1};
        enc(&P.tm[i < 3 ? i : 4], CU_TENSOR_MAP_DATA_TYPE_BFLOAT16, 2, d_in[9 + i], d2, str, box, es, CU_TENSOR_MAP_INTERLEAVE_NONE, CU_TENSOR_MAP_SWIZZLE_128B,
            CU_TENSOR_MAP_L2_PROMOTION_L2_128B, CU_TENSOR_MAP_FLOAT_OOB_FILL_NONE);
        if (i < 2) enc(&P.tn[i], CU_TENSOR_MAP_DATA_TYPE_BFLOAT16, 2, d_in[9 + i], d2, str, bn, es, CU_TENSOR_MAP_INTERLEAVE_NONE, CU_TENSOR_MAP_SWIZZLE_32B,
                       CU_TENSOR_MAP_L2_PROMOTION_L2_128B, CU_TENSOR_MAP_FLOAT_OOB_FILL_NONE);
    }
    {
        cuuint64_t dims[2] = {512, 2048}, str[1] = {1024};
        cuuint32_t box[2] = {8, 256}, es[2] = {1, 1};
        enc(&P.tm[3], CU_TENSOR_MAP_DATA_TYPE_BFLOAT16, 2, d_in[0], dims, str, box, es, CU_TENSOR_MAP_INTERLEAVE_NONE, CU_TENSOR_MAP_SWIZZLE_NONE,
            CU_TENSOR_MAP_L2_PROMOTION_NONE, CU_TENSOR_MAP_FLOAT_OOB_FILL_NONE);
    }
    P.mem0 = (BP)d_in[8]; P.Wo = (BP)d_in[12]; P.Dskip = (BP)d_in[6]; P.out = (__nv_bfloat16*)d_out;
    cudaStream_t s = cudaStreamPerThread;
    P.pa = {(BP)d_in[0], (BP)d_in[1], (BP)d_in[2], (BP)d_in[3], (BP)d_in[4], (BP)d_in[5], (BP)d_in[6], {(BP)d_in[9], (BP)d_in[10], (BP)d_in[11], (BP)d_in[12]}};
    plan(P);
    TK(); main_kernel<<<2 * NCL, 384, SMEM_BYTES, s>>>(P); TK();
}
```

```cpp
#include <cuda_runtime.h>
#include <cuda_bf16.h>
#include <cuda.h>
#include <stdint.h>
#include <string.h>
#include <math.h>

namespace {

constexpr int NCL = 66;
constexpr int NQ = 43;
constexpr int V_REC = 8, V_OP = 72, V_QKV = 88;

__device__ uint4 g_x[2 * 128 * 1024];
__device__ uint4 g_xn[64 * 4096];
__device__ uint4 g_st[64 * 256];
__device__ uint4 g_qkv[128 * 32 * 1536];
__device__ uint4 g_o[64 * 64 * 512];
__device__ uint4 g_pp[64 * 4 * 4096];
__device__ uint4 g_xch[133 * 512];
__device__ unsigned g_sel[64];
__device__ unsigned g_side[96];
__device__ unsigned g_probe[4096];
__device__ unsigned g_gate[32];
__device__ __align__(16) uint32_t g_P[512 * 272];
__device__ uint4 g_W[512 * 784];
__device__ __align__(16) uint32_t g_u[512 * 1152];
__device__ uint2 g_carry[512 * 40 * 32];
__device__ uint2 g_far[512 * 8 * 32];
__device__ unsigned g_cnt[900 * 8];
__device__ uint32_t g_ln0[2048];

enum { C_XN = 0  , C_QKV = 64  , C_O = 128  , C_PP = 384  , C_FAR = 896 };
__device__ __forceinline__ unsigned* cnt_ptr(int i) { return g_cnt + i * 8; }

struct ProArgs { const __nv_bfloat16 *x, *lAr, *Ai, *Cr, *Ci, *ldt, *Dk, *W[4]; };
struct Params {
    CUtensorMap tm[5];
    CUtensorMap tn[2];
    ProArgs pa;
    int dopro;
    const __nv_bfloat16* mem0;
    const __nv_bfloat16* Wo;
    const __nv_bfloat16* Dskip;
    __nv_bfloat16* out;
    int roles;
    int chains;
    int lag;
    int zero;
    int nl[2];
    uint8_t list[2][64];
};

__device__ __forceinline__ uint32_t smem_u32(const void* p) { return (uint32_t)__cvta_generic_to_shared(p); }
__device__ __forceinline__ uint32_t mapa(uint32_t a, uint32_t r) {
    uint32_t o; asm("mapa.shared::cluster.u32 %0,%1,%2;" : "=r"(o) : "r"(a), "r"(r)); return o;
}
__device__ __forceinline__ void mbar_init(uint32_t b, int c) { asm volatile("mbarrier.init.shared::cta.b64 [%0],%1;" ::"r"(b), "r"(c) : "memory"); }
__device__ __forceinline__ void mbar_expect(uint32_t b, int bytes) { asm volatile("mbarrier.arrive.expect_tx.shared::cta.b64 _,[%0],%1;" ::"r"(b), "r"(bytes) : "memory"); }
__device__ __forceinline__ void mbar_arrive(uint32_t b) { asm volatile("mbarrier.arrive.shared::cta.b64 _,[%0];" ::"r"(b) : "memory"); }
__device__ __forceinline__ void mbar_arrive_cluster(uint32_t b) { asm volatile("mbarrier.arrive.shared::cluster.b64 _,[%0];" ::"r"(b) : "memory"); }
__device__ __forceinline__ void mbar_wait(uint32_t b, uint32_t ph) {
    asm volatile(
        "{.reg .pred p; .reg .u32 n; mov.u32 n,0;\n"
        "W%=: mbarrier.try_wait.parity.shared::cta.b64 p,[%0],%1;\n"
        "@p bra D%=;\n"
        "add.u32 n,n,1; setp.lt.u32 p,n,2000000; @p bra W%=;\n"
        "trap;\n"
        "D%=: }" ::"r"(b), "r"(ph) : "memory");
}
__device__ __forceinline__ bool wait_lds128(uint32_t b, uint32_t ph, uint32_t a, uint4& v) {
    uint32_t ok;
    asm volatile("{.reg .pred p; mbarrier.try_wait.parity.shared::cta.b64 p,[%5],%6,20000; ld.shared.v4.u32 {%0,%1,%2,%3},[%7]; selp.u32 %4,1,0,p;}"
                 : "=r"(v.x), "=r"(v.y), "=r"(v.z), "=r"(v.w), "=r"(ok) : "r"(b), "r"(ph), "r"(a) : "memory");
    return ok;
}
__device__ __forceinline__ bool wait_lds64(uint32_t b, uint32_t ph, uint32_t a, uint2& v) {
    uint32_t ok;
    asm volatile("{.reg .pred p; mbarrier.try_wait.parity.shared::cta.b64 p,[%3],%4,20000; ld.shared.v2.u32 {%0,%1},[%5]; selp.u32 %2,1,0,p;}"
                 : "=r"(v.x), "=r"(v.y), "=r"(ok) : "r"(b), "r"(ph), "r"(a) : "memory");
    return ok;
}
template <int PH> __device__ __forceinline__ void mbar_wait_c(uint32_t b) {
    asm volatile(
        "{.reg .pred p; .reg .u32 n; mov.u32 n,%2;\n"
        "W%=: mbarrier.try_wait.parity.shared::cta.b64 p,[%0],%1;\n"
        "@p bra D%=;\n"
        "add.u32 n,n,1; setp.lt.u32 p,n,2000000; @p bra W%=;\n"
        "trap;\n"
        "D%=: }" ::"r"(b), "n"(PH), "n"(PH) : "memory");
}
__device__ __forceinline__ bool elect() {
    uint32_t r; asm volatile("{.reg .pred p; elect.sync _|p,0xffffffff; selp.u32 %0,1,0,p;}" : "=r"(r)); return r;
}
__device__ __forceinline__ void bar_sync(int id, int n) { asm volatile("bar.sync %0,%1;" ::"r"(id), "r"(n) : "memory"); }
__device__ __forceinline__ void bar_arrive(int id, int n) { asm volatile("bar.arrive %0,%1;" ::"r"(id), "r"(n) : "memory"); }
__device__ __forceinline__ void cluster_sync() { asm volatile("barrier.cluster.arrive.relaxed.aligned; barrier.cluster.wait.aligned;" ::: "memory"); }
__device__ __forceinline__ void fence_async() { asm volatile("fence.proxy.async;" ::: "memory"); }
__device__ __forceinline__ void fence_async_smem() { asm volatile("fence.proxy.async.shared::cta;" ::: "memory"); }
#define EFR 1
#define EFW 2
constexpr uint64_t POL_N = 0x1000000000000000ull, POL_F = 0x12F0000000000000ull;
constexpr uint64_t POL_LAST = EFR ? POL_F : POL_N  , POL_LATE = EFW ? POL_F : POL_N  , POL_SOON = EFW > 1 ? POL_F : POL_N;
__device__ __forceinline__ void bulk_g2s(uint32_t dst, const void* src, int bytes, uint32_t bar, uint64_t pol) {
    asm volatile("cp.async.bulk.shared::cluster.global.mbarrier::complete_tx::bytes.L2::cache_hint [%0],[%1],%2,[%3],%4;" ::"r"(dst), "l"(src), "r"(bytes), "r"(bar), "l"(pol) : "memory");
}
__device__ __forceinline__ void bulk_g2s_mc(uint32_t dst, const void* src, int bytes, uint32_t bar, uint64_t pol) {
    asm volatile("cp.async.bulk.shared::cluster.global.mbarrier::complete_tx::bytes.multicast::cluster.L2::cache_hint [%0],[%1],%2,[%3],%4,%5;" ::"r"(dst), "l"(src), "r"(bytes), "r"(bar), "h"((uint16_t)3), "l"(pol) : "memory");
}
__device__ __forceinline__ void stg128(uint4* p, uint4 v, uint64_t pol) {
    asm volatile("st.global.L2::cache_hint.v4.u32 [%0],{%1,%2,%3,%4},%5;" ::"l"(p), "r"(v.x), "r"(v.y), "r"(v.z), "r"(v.w), "l"(pol));
}
__device__ __forceinline__ void stg32(uint32_t* p, uint32_t v, uint64_t pol) { asm volatile("st.global.L2::cache_hint.u32 [%0],%1,%2;" ::"l"(p), "r"(v), "l"(pol)); }
__device__ __forceinline__ uint4 ldcg128_last(const uint4* p) {
    uint4 v; asm volatile("ld.global.cg.L2::cache_hint.v4.u32 {%0,%1,%2,%3},[%4],%5;" : "=r"(v.x), "=r"(v.y), "=r"(v.z), "=r"(v.w) : "l"(p), "l"(POL_LAST) : "memory"); return v;
}
__device__ __forceinline__ void tma2d(uint32_t dst, const CUtensorMap* tm, int x, int y, uint32_t bar) {
    asm volatile("cp.async.bulk.tensor.2d.shared::cluster.global.mbarrier::complete_tx::bytes [%0],[%1,{%2,%3}],[%4];" ::"r"(dst), "l"(tm), "r"(x), "r"(y), "r"(bar) : "memory");
}
__device__ __forceinline__ void tma3d(uint32_t dst, const CUtensorMap* tm, int y, int z, uint32_t bar) {
    asm volatile("cp.async.bulk.tensor.3d.shared::cluster.global.mbarrier::complete_tx::bytes [%0],[%1,{0,%2,%3}],[%4];" ::"r"(dst), "l"(tm), "r"(y), "r"(z), "r"(bar) : "memory");
}
__device__ __forceinline__ void st_async4(uint32_t a, uint32_t x, uint32_t y, uint32_t z, uint32_t w, uint32_t mb) {
    asm volatile("st.async.shared::cluster.mbarrier::complete_tx::bytes.v4.b32 [%0],{%1,%2,%3,%4},[%5];" ::"r"(a), "r"(x), "r"(y), "r"(z), "r"(w), "r"(mb) : "memory");
}
__device__ __forceinline__ void st_async2(uint32_t a, uint32_t x, uint32_t y, uint32_t mb) {
    asm volatile("st.async.shared::cluster.mbarrier::complete_tx::bytes.v2.b32 [%0],{%1,%2},[%3];" ::"r"(a), "r"(x), "r"(y), "r"(mb) : "memory");
}
#define LDSQ "ld.shared"
__device__ __forceinline__ uint4 lds128(uint32_t a) { uint4 v; asm volatile(LDSQ ".v4.u32 {%0,%1,%2,%3},[%4];" : "=r"(v.x), "=r"(v.y), "=r"(v.z), "=r"(v.w) : "r"(a) : "memory"); return v; }
__device__ __forceinline__ uint4 lds128v(uint32_t a) { uint4 v; asm volatile("ld.volatile.shared.v4.u32 {%0,%1,%2,%3},[%4];" : "=r"(v.x), "=r"(v.y), "=r"(v.z), "=r"(v.w) : "r"(a) : "memory"); return v; }
__device__ __forceinline__ uint2 lds64(uint32_t a) { uint2 v; asm volatile(LDSQ ".v2.u32 {%0,%1},[%2];" : "=r"(v.x), "=r"(v.y) : "r"(a) : "memory"); return v; }
__device__ __forceinline__ uint32_t lds32(uint32_t a) { uint32_t v; asm volatile(LDSQ ".u32 %0,[%1];" : "=r"(v) : "r"(a) : "memory"); return v; }
__device__ __forceinline__ void sts128(uint32_t a, uint32_t x, uint32_t y, uint32_t z, uint32_t w) { asm volatile("st.shared.v4.u32 [%0],{%1,%2,%3,%4};" ::"r"(a), "r"(x), "r"(y), "r"(z), "r"(w) : "memory"); }
__device__ __forceinline__ void sts64(uint32_t a, uint32_t x, uint32_t y) { asm volatile("st.shared.v2.u32 [%0],{%1,%2};" ::"r"(a), "r"(x), "r"(y) : "memory"); }
__device__ __forceinline__ void sts32(uint32_t a, uint32_t x) { asm volatile("st.shared.u32 [%0],%1;" ::"r"(a), "r"(x) : "memory"); }
__device__ __forceinline__ uint4 ldsm4(uint32_t a) { uint4 v; asm volatile("ldmatrix.sync.aligned.m8n8.x4.shared.b16 {%0,%1,%2,%3},[%4];" : "=r"(v.x), "=r"(v.y), "=r"(v.z), "=r"(v.w) : "r"(a) : "memory"); return v; }
__device__ __forceinline__ uint4 ldsm4t(uint32_t a) { uint4 v; asm volatile("ldmatrix.sync.aligned.m8n8.x4.trans.shared.b16 {%0,%1,%2,%3},[%4];" : "=r"(v.x), "=r"(v.y), "=r"(v.z), "=r"(v.w) : "r"(a) : "memory"); return v; }
__device__ __forceinline__ uint32_t movm(uint32_t a) { uint32_t d; asm volatile("movmatrix.sync.aligned.m8n8.trans.b16 %0,%1;" : "=r"(d) : "r"(a)); return d; }
__device__ __forceinline__ uint32_t pack2(float lo, float hi) { uint32_t d; asm("cvt.rn.bf16x2.f32 %0,%1,%2;" : "=r"(d) : "f"(hi), "f"(lo)); return d; }
__device__ __forceinline__ uint32_t hadd2(uint32_t a, uint32_t b) { uint32_t d; asm("add.rn.bf16x2 %0,%1,%2;" : "=r"(d) : "r"(a), "r"(b)); return d; }
__device__ __forceinline__ uint32_t hmul2(uint32_t a, uint32_t b) { uint32_t d; asm("mul.rn.bf16x2 %0,%1,%2;" : "=r"(d) : "r"(a), "r"(b)); return d; }
__device__ __forceinline__ float blo(uint32_t v) { return __uint_as_float(v << 16); }
__device__ __forceinline__ float bhi(uint32_t v) { return __uint_as_float(v & 0xffff0000u); }
__device__ __forceinline__ float rbf(float x) { return __uint_as_float(pack2(0.f, x)); }
__device__ __forceinline__ float ex2(float x) { float y; asm("ex2.approx.ftz.f32 %0,%1;" : "=f"(y) : "f"(x)); return y; }
__device__ __forceinline__ float rcp(float x) { float y; asm("rcp.approx.ftz.f32 %0,%1;" : "=f"(y) : "f"(x)); return y; }
__device__ __forceinline__ void mma16(float* c, uint32_t a0, uint32_t a1, uint32_t a2, uint32_t a3, uint32_t b0, uint32_t b1) {
    asm volatile("mma.sync.aligned.m16n8k16.row.col.f32.bf16.bf16.f32 {%0,%1,%2,%3},{%4,%5,%6,%7},{%8,%9},{%0,%1,%2,%3};"
                 : "+f"(c[0]), "+f"(c[1]), "+f"(c[2]), "+f"(c[3]) : "r"(a0), "r"(a1), "r"(a2), "r"(a3), "r"(b0), "r"(b1));
}
__device__ __forceinline__ void mma16_top(float& d0, float& d1, uint32_t a0, uint32_t a2, uint32_t b0, uint32_t b1) {
    asm volatile("{.reg .b32 j; .reg .f32 e,f; mma.sync.aligned.m16n8k16.row.col.f32.bf16.bf16.f32 {%0,%1,e,f},{%2,j,%3,j},{%4,%5},{0f00000000,0f00000000,0f00000000,0f00000000};}"
                 : "=f"(d0), "=f"(d1) : "r"(a0), "r"(a2), "r"(b0), "r"(b1));
}
__device__ __forceinline__ void mma8(float* c, uint32_t a0, uint32_t a1, uint32_t b0) {
    asm volatile("mma.sync.aligned.m16n8k8.row.col.f32.bf16.bf16.f32 {%0,%1,%2,%3},{%4,%5},{%6},{%0,%1,%2,%3};"
                 : "+f"(c[0]), "+f"(c[1]), "+f"(c[2]), "+f"(c[3]) : "r"(a0), "r"(a1), "r"(b0));
}
__device__ __forceinline__ uint4 ld_rlx128(const uint4* p) {
    uint4 v;
    asm volatile("{.reg .b128 t; ld.relaxed.gpu.global.b128 t,[%4]; mov.b128 {%0,%1,%2,%3},t;}" : "=r"(v.x), "=r"(v.y), "=r"(v.z), "=r"(v.w) : "l"(p) : "memory");
    return v;
}
__device__ __forceinline__ void st_rlx128(uint4* p, uint32_t x, uint32_t y, uint32_t z, uint32_t w) {
    asm volatile("{.reg .b128 t; mov.b128 t,{%1,%2,%3,%4}; st.relaxed.gpu.global.b128 [%0],t;}" ::"l"(p), "r"(x), "r"(y), "r"(z), "r"(w) : "memory");
}
__device__ __forceinline__ uint4 ldcg128(const uint4* p) { uint4 v; asm volatile("ld.global.cg.v4.u32 {%0,%1,%2,%3},[%4];" : "=r"(v.x), "=r"(v.y), "=r"(v.z), "=r"(v.w) : "l"(p) : "memory"); return v; }
__device__ __forceinline__ void red_release(unsigned* p, unsigned v) {
    asm volatile("fence.proxy.async; red.relaxed.gpu.global.add.u32 [%0],%1;" ::"l"(p), "r"(v) : "memory");
}
__device__ __forceinline__ void wait_cnt(const unsigned* p, unsigned target) {
    asm volatile(
        "{.reg .pred p; .reg .u32 n,v; mov.u32 n,0;\n"
        "W%=: ld.acquire.gpu.global.u32 v,[%0]; setp.ge.u32 p,v,%1; @p bra D%=;\n"
        "nanosleep.u32 20; add.u32 n,n,1; setp.lt.u32 p,n,4000000; @p bra W%=;\n"
        "trap;\n"
        "D%=: }" ::"l"(p), "r"(target) : "memory");
}
__device__ __forceinline__ void wait_cnt_warp(const unsigned* p, unsigned target) {
    asm volatile(
        "{.reg .pred p; .reg .u32 n,v; mov.u32 n,0;\n"
        "W%=: ld.acquire.gpu.global.u32 v,[%0]; setp.ge.u32 p,v,%1; vote.sync.all.pred p,p,0xffffffff; @p bra.uni D%=;\n"
        "nanosleep.u32 20; add.u32 n,n,1; setp.lt.u32 p,n,4000000; @p bra.uni W%=;\n"
        "trap;\n"
        "D%=: }" ::"l"(p), "r"(target) : "memory");
}
__device__ __forceinline__ void wait_flag_warp(const unsigned* p, unsigned target) {
    asm volatile(
        "{.reg .pred p; .reg .u32 n,v; mov.u32 n,0;\n"
        "W%=: ld.relaxed.gpu.global.u32 v,[%0]; setp.ge.u32 p,v,%1; vote.sync.all.pred p,p,0xffffffff; @p bra.uni D%=;\n"
        "add.u32 n,n,1; setp.lt.u32 p,n,10000000; @p bra.uni W%=;\n"
        "trap;\n"
        "D%=: }" ::"l"(p), "r"(target) : "memory");
}
__device__ __forceinline__ uint64_t mkdesc(uint32_t addr, uint32_t lbo, uint32_t sbo, uint32_t sw) {
    return (uint64_t)((addr & 0x3FFFF) >> 4) | ((uint64_t)(lbo >> 4) << 16) | ((uint64_t)(sbo >> 4) << 32) | ((uint64_t)sw << 62);
}
__device__ __forceinline__ void wg_fence() { asm volatile("wgmma.fence.sync.aligned;" ::: "memory"); }
__device__ __forceinline__ void wg_commit() { asm volatile("wgmma.commit_group.sync.aligned;" ::: "memory"); }
template <int N> __device__ __forceinline__ void wg_wait() { asm volatile("wgmma.wait_group.sync.aligned %0;" ::"n"(N) : "memory"); }
#define R8(c, o) "+f"(c[o]), "+f"(c[o + 1]), "+f"(c[o + 2]), "+f"(c[o + 3]), "+f"(c[o + 4]), "+f"(c[o + 5]), "+f"(c[o + 6]), "+f"(c[o + 7])
#define R32(c, o) R8(c, o), R8(c, o + 8), R8(c, o + 16), R8(c, o + 24)
#define S32A "%0,%1,%2,%3,%4,%5,%6,%7,%8,%9,%10,%11,%12,%13,%14,%15,%16,%17,%18,%19,%20,%21,%22,%23,%24,%25,%26,%27,%28,%29,%30,%31"
template <int ACC> __device__ __forceinline__ void wgmma64_rs(float* c, const uint32_t* a, uint64_t db) {
    asm volatile("wgmma.mma_async.sync.aligned.m64n64k16.f32.bf16.bf16 {" S32A "},{%32,%33,%34,%35},%36,%37,1,1,0;"
                 : R32(c, 0) : "r"(a[0]), "r"(a[1]), "r"(a[2]), "r"(a[3]), "l"(db), "n"(ACC));
}
template <int ACC> __device__ __forceinline__ void wgmma64_ta(float* c, uint64_t da, uint64_t db) {
    asm volatile("wgmma.mma_async.sync.aligned.m64n64k16.f32.bf16.bf16 {" S32A "},%32,%33,%34,1,1,1,0;" : R32(c, 0) : "l"(da), "l"(db), "n"(ACC));
}
template <int ACC> __device__ __forceinline__ void wgmma80_tb(float* c, uint64_t da, uint64_t db) {
    asm volatile("wgmma.mma_async.sync.aligned.m64n80k16.f32.bf16.bf16 {" S32A ",%32,%33,%34,%35,%36,%37,%38,%39},%40,%41,%42,1,1,0,1;"
                 : R32(c, 0), R8(c, 32) : "l"(da), "l"(db), "n"(ACC));
}
template <int N> __device__ __forceinline__ void reg_inc() { asm volatile("setmaxnreg.inc.sync.aligned.u32 %0;" ::"n"(N)); }
template <int N> __device__ __forceinline__ void reg_dec() { asm volatile("setmaxnreg.dec.sync.aligned.u32 %0;" ::"n"(N)); }

#define PROF(cond, idx) do {} while (0)
#define CPROF(k) do {} while (0)

constexpr int S_GATE = 232440, S_XBAR = 232432, S_VCL = 232444, B_BAR = 231936;
#define RCB 136
#define RCU 184
#define NFP 2
#define UFE 0
#define PFM 0
#define NFE 2
#define QLAG 3
constexpr float SC_LOG2E = 0.08838834764831845f * 1.4426950408889634f;

__device__ __forceinline__ float2 ln_finish(float mean, float var) {
    float sd; asm("sqrt.approx.f32 %0,%1;" : "=f"(sd) : "f"(rbf(rbf(var) + 1e-5f)));
    sd = rbf(sd);
    return make_float2(rbf(mean), sd);
}

__device__ __forceinline__ float2 row_stats512(uint4* v, const uint4* src, int s1, int s2) {
    const int g = (threadIdx.x & 31) >> 2;
#pragma unroll
    for (int i = 0; i < 16; i++) v[i] = ldcg128(src + (i >> 1) * s1 + (i & 1) * s2);
    float a[4] = {0, 0, 0, 0}, q0[4] = {0, 0, 0, 0}, q1[4] = {0, 0, 0, 0};
#pragma unroll
    for (int i = 0; i < 16; i++) {
        mma16(a, v[i].x, v[i].y, v[i].z, v[i].w, 0x3f803f80u, 0x3f803f80u);
        mma8(q0, v[i].x, v[i].y, v[i].x); mma8(q1, v[i].x, v[i].y, v[i].y);
        mma8(q0, v[i].z, v[i].w, v[i].z); mma8(q1, v[i].z, v[i].w, v[i].w);
    }
    const float sum = a[0] + a[2], sq = (g & 1) ? q0[1] + q1[3] : q0[0] + q1[2];
    return make_float2(sum, fmaxf(sq - sum * sum * (1.f / 512.f), 0.f));
}
__device__ __forceinline__ void x1_norm(const uint2* src, int r, bool on) {
    const int lane = threadIdx.x & 31, g = lane >> 2, t = r * 4 + (lane & 3);
    uint2 v[16];
#pragma unroll
    for (int i = 0; i < 16; i++) asm volatile("ld.global.cg.v2.u32 {%0,%1},[%2];" : "=r"(v[i].x), "=r"(v[i].y) : "l"(src + (g * 4096 + t) + ((i >> 1) * 16 + (i & 1)) * 2048) : "memory");
    float s = 0, q = 0;
#pragma unroll
    for (int i = 0; i < 32; i++) {
        const uint32_t w = (i & 1) ? v[i >> 1].y : v[i >> 1].x;
        s += blo(w) + bhi(w); q = fmaf(blo(w), blo(w), fmaf(bhi(w), bhi(w), q));
    }
#pragma unroll
    for (int d = 4; d < 32; d *= 2) { s += __shfl_xor_sync(0xffffffffu, s, d); q += __shfl_xor_sync(0xffffffffu, q, d); }
    if (g == 0 && on) g_ln0[t] = 0;
    s *= 1.f / 512.f;
    const float2 l = ln_finish(s, fmaxf(fmaf(q, 1.f / 512.f, -s * s), 0.f));
    const float rs = rcp(l.y);
    const uint32_t mm = pack2(-l.x, -l.x);
    uint4* dst = g_xn + ((t >> 6) * 4096 + ((t >> 3) & 7) * 64 + g * 8 + (t & 7));
#define NRM(w) pack2(blo(hadd2(w, mm)) * rs, bhi(hadd2(w, mm)) * rs)
#pragma unroll
    for (int i = 0; i < 8; i++)
        asm volatile("{.reg .pred p; setp.ne.u32 p,%5,0; @p st.global.v4.u32 [%0],{%1,%2,%3,%4};}" ::"l"(dst + i * 512), "r"(NRM(v[2 * i].x)), "r"(NRM(v[2 * i].y)),
                     "r"(NRM(v[2 * i + 1].x)), "r"(NRM(v[2 * i + 1].y)), "r"((uint32_t)on) : "memory");
}

#define NWO 10
#define VMASK 0x4444
#define VQ 16
#define VPRE 2
#define MPRE 1
#define NPM NPX
#define SCHED(i) do {} while (0)
#define VPX 0
#define OA 0
#define QA 0
#define NPX 2
#define NPF 4
constexpr int SLOT = 24576, SL_V = 8192, SL_Q = 16384, SL_KM = 20480, SL_VM = 22528;
constexpr int R_WV = 0, R_SL = 65536, R_WO = R_SL + 4 * SLOT, R_M = 196608  , R_U = R_M + 8192  ,
              R_OS = R_U + 8192  , R_SB = R_OS + 8192  , R_OB = R_SB + 5248  , R_PB = R_OB + 2048  ,
              R_IL = R_PB + 1024  , R_SEL = 231680, R_BAR = R_SEL + 256, R_STQ = 65536, R_STK = 131072;
static_assert(R_WO + (16 - NWO) * 4096 <= R_M && R_IL + 64 <= R_SEL && R_BAR + 512 <= 232448, "smem map");
enum { RB_XFULL = 0  , RB_GO = 4  , RB_QK = 8  , RB_INIT = 24, RB_SV = 25  , RB_N = 29 };
#define GATE 1
enum { NB_MFULL = 1  , NB_PART = 3  , NB_S = 5, NB_P = 6, NB_O = 7, NB_W = 10 };
#define WDEP 1
#define RH 56
#define RW0 224
#define D1 300
#define D2 300
#define DX 0
__device__ __forceinline__ uint32_t clk32() { uint32_t c; asm volatile("mov.u32 %0,%%clock;" : "=r"(c)::"memory"); return c; }
__device__ __forceinline__ void spin(int cycles) {
    if (cycles <= 0) return;
    const uint32_t t0 = clk32();
    while (clk32() - t0 < (uint32_t)cycles) {}
}
__device__ __forceinline__ uint4* xregion(int X, int r) { return (uint4*)(((size_t)g_xch + 8191) & ~(size_t)8191) + (X * 66 + r) * 512; }

struct RecW { uint32_t po, dp, lw, swr, pwr, w, wv; };

template <int X>
__device__ __forceinline__ void rec_step(const RecW& k, uint32_t sb, int s, uint32_t z, uint32_t gate, const uint32_t (*wq)[4], const uint32_t (*wk)[4], uint4* wv, uint4* wo) {
    const uint32_t wz = k.w + z, w5 = wz * 512, so = (s & 1) * SLOT + w5;
    constexpr int SL = R_SL + X * 2 * SLOT;
    const uint32_t qb = sb + R_BAR + (RB_QK + X * 8) * 8 + wz * 8;
    const uint32_t l8 = ((k.lw + z) >> 1) + (sb - (sb >> 1) + SL + (s & 1) * SLOT + wz * 256);
    uint4 mk[8];
#define WVF(ks) wv[ks]
#define WVL(a, b) _Pragma("unroll") for (int ks_ = (a); ks_ < (b); ks_++) if (ks_ < 16 && !((VMASK >> ks_) & 1)) wv[ks_] = ldsm4t(k.wv + ks_ * 2048)
    WVL(0, VPRE);
    bar_sync(NB_MFULL + X, 288);
    uint32_t x[4], vv[2];
    float av[2][4] = {{0, 0, 0, 0}, {0, 0, 0, 0}};
    {
        float aq[2][4] = {{0, 0, 0, 0}, {0, 0, 0, 0}}, ak[2][4] = {{0, 0, 0, 0}, {0, 0, 0, 0}};
#pragma unroll
        for (int i = 0; i < MPRE; i++) mk[i] = ldsm4(k.lw + X * 4096 + R_M + i * 512);
#pragma unroll
        for (int i = 0; i < 8; i++) {
            if (i + MPRE < 8) mk[i + MPRE] = ldsm4(k.lw + X * 4096 + R_M + (i + MPRE) * 512);
            if (2 * i < VQ) { WVL(2 * i + VPRE, min(2 * i + 2 + VPRE, VQ + VPX)); }
            SCHED(i);
            const uint4 mf = mk[i];
            mma16(aq[0], wq[2 * i][0], wq[2 * i][1], wq[2 * i][2], wq[2 * i][3], mf.x, mf.y);
            mma16(ak[0], wk[2 * i][0], wk[2 * i][1], wk[2 * i][2], wk[2 * i][3], mf.x, mf.y);
            if (2 * i < VQ) mma16(av[0], WVF(2 * i).x, WVF(2 * i).y, WVF(2 * i).z, WVF(2 * i).w, mf.x, mf.y);
            mma16(aq[QA & 1], wq[2 * i + 1][0], wq[2 * i + 1][1], wq[2 * i + 1][2], wq[2 * i + 1][3], mf.z, mf.w);
            mma16(ak[(QA >> 1) & 1], wk[2 * i + 1][0], wk[2 * i + 1][1], wk[2 * i + 1][2], wk[2 * i + 1][3], mf.z, mf.w);
            if (2 * i < VQ) mma16(av[QA >> 2], WVF(2 * i + 1).x, WVF(2 * i + 1).y, WVF(2 * i + 1).z, WVF(2 * i + 1).w, mf.z, mf.w);
        }
        if (QA) {
#pragma unroll
            for (int i = 0; i < 4; i++) { if (QA & 1) aq[0][i] += aq[1][i]; if (QA & 2) ak[0][i] += ak[1][i]; }
        }
        x[0] = movm(pack2(aq[0][0], aq[0][1])); x[1] = movm(pack2(aq[0][2], aq[0][3]));
        x[2] = movm(pack2(ak[0][0], ak[0][1])); x[3] = movm(pack2(ak[0][2], ak[0][3]));
        st_async4(k.lw + (R_U + X * 4096 + w5 + k.dp), x[0], x[1], x[2], x[3], qb + k.dp);
    }
    {
#pragma unroll
        for (int i = VQ / 2; i < 8; i++) {
            const uint4 mf = mk[i];
            WVL(2 * i + VPX, 2 * i + 2 + VPX);
            mma16(av[0], WVF(2 * i).x, WVF(2 * i).y, WVF(2 * i).z, WVF(2 * i).w, mf.x, mf.y);
            mma16(av[1], WVF(2 * i + 1).x, WVF(2 * i + 1).y, WVF(2 * i + 1).z, WVF(2 * i + 1).w, mf.z, mf.w);
        }
        if (VQ < 16 || QA >= 4) {
#pragma unroll
            for (int i = 0; i < 4; i++) av[0][i] += av[1][i];
        }
        vv[0] = pack2(av[0][0], av[0][1]); vv[1] = pack2(av[0][2], av[0][3]);
        st_async2(l8 + (SL_VM + k.dp), vv[0], vv[1], qb + k.dp);
        asm volatile("{.reg .pred p; setp.eq.u32 p,%1,%2; @p mbarrier.arrive.shared::cta.b64 _,[%0];}" ::"r"(gate), "r"(k.swr), "r"(gate ? sb + R_SB : 0) : "memory");
        const uint4 k0 = lds128(k.lw + so + SL), k1 = lds128(k.lw + so + SL + 4096);
#pragma unroll
        for (int i = 0; i < NPX; i++) wo[i] = lds128(k.lw + w5 + R_WO + i * 4096);
        mbar_wait(qb, s & 1);
        const uint4 u = lds128(k.lw + w5 + R_U + X * 4096);
        const uint32_t q0 = hadd2(x[0], u.x), q1 = hadd2(x[1], u.y);
        x[2] = hadd2(x[2], u.z); x[3] = hadd2(x[3], u.w);
        float sa[4] = {0, 0, 0, 0}, sc[4] = {0, 0, 0, 0}, sm0, sm1;
        mma16(sa, k0.x, k0.y, k0.z, k0.w, q0, q1);
        mma16(sc, k1.x, k1.y, k1.z, k1.w, q0, q1);
        mma16_top(sm0, sm1, x[2], x[3], q0, q1);
        asm volatile("stmatrix.sync.aligned.m8n8.x4.trans.shared.b16 [%0],{%1,%2,%3,%4};" ::"r"(k.swr), "r"(pack2(sa[0], sa[1])), "r"(pack2(sa[2], sa[3])),
                     "r"(pack2(sc[0], sc[1])), "r"(pack2(sc[2], sc[3])) : "memory");
        asm volatile("stmatrix.sync.aligned.m8n8.x1.trans.shared.b16 [%0],{%1};" ::"r"(k.swr + 512), "r"(pack2(sm0, sm1)) : "memory");
    }
    bar_sync(NB_S, 256);
    uint4 v0, v1;
    uint32_t ls;
    {
        const uint4 y = ldsm4t(k.lw + wz * 656 + R_SB);
        uint32_t y4; asm volatile("ldmatrix.sync.aligned.m8n8.x1.trans.shared.b16 {%0},[%1];" : "=r"(y4) : "r"(k.lw + wz * 656 + R_SB + 512) : "memory");
        const uint2 vp = lds64(l8 + SL_VM);
        sts64(l8 + SL_KM, x[2], x[3]);
        v0 = lds128(k.lw + so + SL + SL_V); v1 = lds128(k.lw + so + SL + SL_V + 4096);
        vv[0] = hadd2(vv[0], vp.x); vv[1] = hadd2(vv[1], vp.y);
        sts64(l8 + SL_VM, vv[0], vv[1]);
#pragma unroll
        for (int i = NPX; i < NPM; i++) wo[i] = lds128(k.lw + w5 + R_WO + i * 4096);
        const uint32_t ONE = 0x3f803f80u + z;
        float a[4] = {0, 0, 0, 0}, b[4] = {0, 0, 0, 0}, e[4] = {0, 0, 0, 0};
        mma8(e, ONE, z, y4); mma16(a, ONE, z, z, ONE, y.x, y.y); mma16(b, ONE, z, z, ONE, y.z, y.w);
        float s0, s1;
        asm("{.reg .pred p1,p2,p4; .reg .f32 t0,t1,u0,u1; .reg .b32 m; and.b32 m,%12,64; setp.ne.u32 p1,m,0; and.b32 m,%12,128; setp.ne.u32 p2,m,0; and.b32 m,%12,256; setp.ne.u32 p4,m,0;"
            "selp.f32 t0,%4,%2,p1; selp.f32 t1,%5,%3,p1; selp.f32 u0,%8,%6,p1; selp.f32 u1,%9,%7,p1; selp.f32 t0,u0,t0,p2; selp.f32 t1,u1,t1,p2; selp.f32 %0,%10,t0,p4; selp.f32 %1,%11,t1,p4;}"
            : "=f"(s0), "=f"(s1) : "f"(a[0]), "f"(a[1]), "f"(a[2]), "f"(a[3]), "f"(b[0]), "f"(b[1]), "f"(b[2]), "f"(b[3]), "f"(e[0]), "f"(e[1]), "r"(k.lw));
        const int mi = __float_as_int(fmaxf(s0, s1));
        const int mp = __reduce_max_sync(0xffffffffu, mi), mn = (int)__reduce_min_sync(0xffffffffu, (unsigned)mi);
        const float mo = -__int_as_float(mp >= 0 ? mp : mn) * SC_LOG2E;
        s0 = ex2(fmaf(s0, SC_LOG2E, mo)); s1 = ex2(fmaf(s1, SC_LOG2E, mo));
        sts32(k.pwr, pack2(s0, s1));
        ls = k.lw < sb + 320 ? __float2uint_rn((s0 + s1) * 16777216.f) : 0;
    }
    bar_sync(NB_P, 256);
    {
        const uint4 pp = lds128(k.lw + R_PB);
        const uint32_t pm = lds32(((k.lw + z) >> 2) + (sb - (sb >> 2) + R_PB + 512));
        sts32(sb + R_IL + (wz >> 1) * 16 + (wz & 1) * 4, __float_as_uint(rcp(__uint2float_rn(__reduce_add_sync(0xffffffffu, ls)) * (1.f / 16777216.f))));
        float o0[4] = {0, 0, 0, 0}, o1[4] = {0, 0, 0, 0}, o2[4] = {0, 0, 0, 0};
        mma16(o0, v0.x, v0.y, v0.z, v0.w, pp.x, pp.y);
        mma16(o1, v1.x, v1.y, v1.z, v1.w, pp.z, pp.w);
        mma8(o2, vv[0], vv[1], pm);
        asm volatile("stmatrix.sync.aligned.m8n8.x2.trans.shared.b16 [%0],{%1,%2};" ::"r"(k.lw + wz * 256 + R_OB),
                     "r"(pack2(o0[0] + o1[0] + o2[0], o0[1] + o1[1] + o2[1])), "r"(pack2(o0[2] + o1[2] + o2[2], o0[3] + o1[3] + o2[3])) : "memory");
#pragma unroll
        for (int i = NPM; i < NPF; i++) wo[i] = lds128(k.lw + w5 + R_WO + i * 4096);
    }
    bar_sync(NB_O, 256);
    {
        const uint32_t po = k.po + z, tag = (s + 1) & 1;
        float r0[2][4] = {{0, 0, 0, 0}, {0, 0, 0, 0}}, r1[2][4] = {{0, 0, 0, 0}, {0, 0, 0, 0}};
        uint4 b[4];
#pragma unroll
        for (int i = 0; i < 4; i++) b[i] = ldsm4(k.lw + R_OB + i * 512);
        SCHED(8);
#pragma unroll
        for (int m = NWO + NPF; m < 16; m++) wo[m] = lds128(k.lw + w5 + R_WO + (m - NWO) * 4096);
        const uint2 il = lds64(sb + R_IL + (po & 48));
        const float i0 = __uint_as_float(il.x), i1 = __uint_as_float(il.y);
#pragma unroll
        for (int i = 0; i < 4; i++) {
            mma16(r0[0], wo[4 * i].x, wo[4 * i].y, wo[4 * i].z, wo[4 * i].w, b[i].x, b[i].y);
            mma16(r1[0], wo[4 * i + 1].x, wo[4 * i + 1].y, wo[4 * i + 1].z, wo[4 * i + 1].w, b[i].x, b[i].y);
            mma16(r0[OA], wo[4 * i + 2].x, wo[4 * i + 2].y, wo[4 * i + 2].z, wo[4 * i + 2].w, b[i].z, b[i].w);
            mma16(r1[OA], wo[4 * i + 3].x, wo[4 * i + 3].y, wo[4 * i + 3].z, wo[4 * i + 3].w, b[i].z, b[i].w);
        }
#pragma unroll
        for (int i = 0; i < 4; i++) { r0[0][i] = (OA ? r0[0][i] + r0[1][i] : r0[0][i]) * ((i & 1) ? i1 : i0); r1[0][i] = (OA ? r1[0][i] + r1[1][i] : r1[0][i]) * ((i & 1) ? i1 : i0); }
        st_rlx128((uint4*)((char*)xregion(X, 0) + ((po & ~1u) ^ ((po & X) << 12))), (pack2(r0[0][0], r0[0][2]) & ~1u) | tag,
                  pack2(r1[0][0], r1[0][2]), pack2(r0[0][1], r0[0][3]), pack2(r1[0][1], r1[0][3]));
        bar_arrive(NB_PART + X, 288);
    }
}

__device__ __forceinline__ void rec_fetch(const Params& p, uint32_t sb, int head, uint32_t rank, int which, int dst) {
#pragma unroll 1
    for (int j = 0; j < 8; j++) tma2d(sb + dst + j * 8192, &p.tm[which], head * 128 + (j >> 2) * 64, rank * 256 + (j & 3) * 64, sb + R_BAR + RB_INIT * 8);
}

__device__ __forceinline__ void rec_weights(const Params& p, uint32_t sb, int head, uint32_t rank, int w) {
    const int lane = threadIdx.x & 31, g = lane >> 2, c = lane & 3;
    const int t = w & 3, WG = w >> 2;
    uint32_t wq[16][4], wk[16][4];
    uint4 wo[16], wv[16];
    const uint32_t woff = sb + WG * 32768 + (((lane >> 4) << 3) + (lane & 7)) * 128 + (((2 * t + ((lane >> 3) & 1)) ^ (lane & 7)) << 4);
    const uint32_t lw = sb + lane * 16;
    PROF(threadIdx.x == 0, 3501);
    PROF(threadIdx.x == 0, 3502);
    mbar_wait(sb + R_BAR + RB_INIT * 8, 0);
    PROF(threadIdx.x == 0, 3503);
#pragma unroll
    for (int ks = 0; ks < 16; ks++) {
        uint4 a = ldsm4t(woff + R_STQ + ks * 2048), b = ldsm4t(woff + R_STK + ks * 2048);
        wq[ks][0] = a.x; wq[ks][1] = a.y; wq[ks][2] = a.z; wq[ks][3] = a.w;
        wk[ks][0] = b.x; wk[ks][1] = b.y; wk[ks][2] = b.z; wk[ks][3] = b.w;
    }
    bar_sync(NB_W, 256);
    {
        const __nv_bfloat16* wp = p.Wo + (size_t)(head * 128 + 2 * c) * 512 + rank * 256 + w * 32 + g * 4;
#pragma unroll
        for (int ks = 0; ks < 8; ks++) {
            const uint2 r0 = *(const uint2*)(wp + (ks * 16) * 512), r1 = *(const uint2*)(wp + (ks * 16 + 1) * 512);
            const uint2 r2 = *(const uint2*)(wp + (ks * 16 + 8) * 512), r3 = *(const uint2*)(wp + (ks * 16 + 9) * 512);
            const uint4 f[2] = {make_uint4(__byte_perm(r0.x, r1.x, 0x5410), __byte_perm(r0.x, r1.x, 0x7632), __byte_perm(r2.x, r3.x, 0x5410), __byte_perm(r2.x, r3.x, 0x7632)),
                                make_uint4(__byte_perm(r0.y, r1.y, 0x5410), __byte_perm(r0.y, r1.y, 0x7632), __byte_perm(r2.y, r3.y, 0x5410), __byte_perm(r2.y, r3.y, 0x7632))};
#pragma unroll
            for (int h = 0; h < 2; h++) {
                const int m = 2 * ks + h;
                if (m >= NPF && m < NPF + NWO) wo[m] = f[h];
                else sts128(lw + w * 512 + R_WO + (m < NPF ? m : m - NWO) * 4096, f[h].x, f[h].y, f[h].z, f[h].w);
            }
        }
    }
    fence_async_smem();
    PROF(threadIdx.x == 0, 3504);
    __syncthreads();
#pragma unroll
    for (int i = 0; i < 16; i++) if ((VMASK >> i) & 1) wv[i] = ldsm4t(woff + R_WV + i * 2048);
    cluster_sync();
    PROF(threadIdx.x == 0, 3505);
    RecW k;
    {
        const int r = (w * 4 + (lane >> 3)) * 2 + rank;
        const uint32_t sl = lds32(sb + R_SEL + r * 4);
        const int slot = head * 8 + (lane & 7);
        k.po = (r * 512 + slot + (sl & 1) * 256) * 16 + (((sl >> 1) ^ sl) & 1);
    }
    k.dp = mapa(sb, rank ^ 1) - sb;
    k.lw = __shfl_sync(0xffffffffu, lw, lane);
    k.swr = __shfl_sync(0xffffffffu, sb + R_SB + (lane & 7) * 656 + (lane >> 3) * 128 + w * 16, lane);
    k.pwr = __shfl_sync(0xffffffffu, sb + R_PB + (g < 4 ? (w * 4 + c) * 16 + g * 4 : 512 + (w * 4 + c) * 4), lane);
    k.w = w;
    k.wv = __shfl_sync(0xffffffffu, woff + R_WV, lane);
    const int e0 = (p.chains & 1) ? 64 : 0, o1 = (p.chains & 2) ? p.lag : 1000, nit = (p.chains & 2) ? p.lag + 64 : e0;
    const uint32_t zero = p.zero;
#pragma unroll 1
    for (int it = 0; it < nit; it++) {
        const uint32_t g0 = sb + R_BAR + (RB_GO + (it & 1)) * 8, g1 = sb + R_BAR + (RB_GO + 2 + ((it - o1) & 1)) * 8;
        if (it < e0) {
            rec_step<0>(k, sb, it, it & zero, GATE && it > o1 ? g1 ^ 8 : 0, wq, wk, wv, wo);
            if ((!GATE || it < o1) && threadIdx.x == 0) mbar_arrive(g0);
        }
        if (it >= o1) {
            rec_step<1>(k, sb, it - o1, it & zero, GATE && it < e0 ? g0 : 0, wq, wk, wv, wo);
            if ((!GATE || it + 1 >= e0) && threadIdx.x == 0) mbar_arrive(g1);
        }
    }
}

__device__ __forceinline__ uint32_t mism(uint32_t a, uint32_t b, uint32_t t) {
    uint32_t d; asm("lop3.b32 %0,%1,%2,%3,0x7e;" : "=r"(d) : "r"(a), "r"(b), "r"(t)); return d;
}
template <bool TWO>
__device__ __forceinline__ void poll8(uint4* x, const uint4* src, uint32_t tag) {
#pragma unroll
    for (int j = 0; j < 8; j++) x[j] = ld_rlx128(src + j * 32);
    int n = 0;
    while (true) {
        uint32_t bad = 0;
#pragma unroll
        for (int j = 0; j < 8; j += 2) bad |= TWO ? mism(x[j].x, x[j].z, tag) | mism(x[j + 1].x, x[j + 1].z, tag) : mism(x[j].x, x[j + 1].x, tag);
        if (!__any_sync(0xffffffffu, bad & 1)) break;
#pragma unroll
        for (int j = 0; j < 8; j++)
            asm volatile("{.reg .pred p; .reg .b128 t; setp.ne.u32 p,%5,0; mov.b128 t,{%0,%1,%2,%3}; @p ld.relaxed.gpu.global.b128 t,[%4]; mov.b128 {%0,%1,%2,%3},t;}"
                         : "+r"(x[j].x), "+r"(x[j].y), "+r"(x[j].z), "+r"(x[j].w) : "l"(src + j * 32), "r"((TWO ? mism(x[j].x, x[j].z, tag) : x[j].x ^ tag) & 1) : "memory");
        if (++n > 2000000) __trap();
    }
}

__device__ __forceinline__ void rec_comm(const Params& p, uint32_t sb, int X, int head, uint32_t rank) {
    const int lane = threadIdx.x & 31, g = lane >> 2, c = lane & 3;
    const int me = head * 2 + rank;
    const uint32_t mb = sb + R_M + X * 4096 + lane * 16;
    uint4 x[8];
#pragma unroll
    for (int j = 0; j < 8; j++) x[j] = *(const uint4*)(p.mem0 + (lane & 7) * 512 + rank * 256 + (j * 4 + (lane >> 3)) * 8);
    const uint32_t sl = lds32(sb + R_SEL + me * 4);
    const uint4* src1 = xregion(X, me) + ((sl >> X) & 1) * 256 + c * 8 + g;
    const uint4* src2 = xregion(X, 64 + rank) + ((sl >> (2 + X)) & 1) * 256 + lane;
    uint2* mdst = (uint2*)(xregion(X, 64 + rank) + (c >> 1) * 256 + head * 8 + (g & 3) * 2 + (c & 1)) + (g >> 2);
    const uint32_t one = (g & 1) ? 0x3f800000u : 0x00003f80u, selA = (g & 2) ? 0u : one, selB = (g & 2) ? one : 0u;
    const uint32_t qb = sb + R_BAR + (RB_QK + X * 8 + lane) * 8;
    if (lane < 8) mbar_expect(qb, 768);
    mbar_wait(sb + R_BAR + (RB_XFULL + X * 2) * 8, 0);
#pragma unroll 1
    for (int s = 0;; s++) {
#pragma unroll
        for (int j = 0; j < 8; j++) sts128(mb + j * 512, x[j].x, x[j].y, x[j].z, x[j].w);
        bar_arrive(NB_MFULL + X, 288);
        PROF(lane == 0, X * 64 + s);
        bar_sync(NB_PART + X, 288);
        if (s == 63) break;
        const uint32_t tag = (s + 1) & 1;
        if (lane < 8) mbar_expect(qb, 768);
        spin(D1 + (lds32(sb + R_SEL) >> 20));
        poll8<false>(x, src1, tag);
        float a[4][4];
#pragma unroll
        for (int j = 0; j < 4; j++) {
            a[j][0] = a[j][1] = a[j][2] = a[j][3] = 0;
            mma16(a[j], x[j].x, x[j].y, x[j].z, x[j].w, selA, selB);
        }
#pragma unroll
        for (int j = 0; j < 4; j++) mma16(a[j], x[j + 4].x, x[j + 4].y, x[j + 4].z, x[j + 4].w, selA, selB);
#pragma unroll
        for (int i = 0; i < 4; i++) a[0][i] = (a[0][i] + a[1][i]) + (a[2][i] + a[3][i]);
        asm volatile("st.relaxed.gpu.global.b64 [%0],%1;" ::"l"(mdst), "l"(((uint64_t)pack2(a[0][2], a[0][3]) << 32) | ((pack2(a[0][0], a[0][1]) & ~1u) | tag)) : "memory");
        const uint32_t t2 = clk32();
        mbar_wait(sb + R_BAR + (RB_XFULL + X * 2 + tag) * 8, ((s + 1) >> 1) & 1);
        while (clk32() - t2 < D2) {}
        poll8<true>(x, src2, tag);
    }
}

template <int MT>
__device__ __forceinline__ void xattn(uint32_t l16, uint32_t l8, uint32_t os, int g, int c) {
    constexpr int NT = 3 + 2 * MT;
    float S[NT][4];
#pragma unroll
    for (int i = 0; i < NT; i++) S[i][0] = S[i][1] = S[i][2] = S[i][3] = 0;
#pragma unroll 2
    for (int ks = 0; ks < 8; ks++) {
        const uint4 q = lds128(l16 + SL_Q + ks * 512);
        const uint2 u = lds64(l8 + SL_KM + ks * 256);
        mma16(S[0], q.x, q.y, q.z, q.w, u.x, u.y);
#pragma unroll
        for (int m = 0; m <= MT; m++) {
            const uint4 kk = lds128(l16 + m * 4096 + ks * 512);
            mma16(S[1 + 2 * m], q.x, q.y, q.z, q.w, kk.x, kk.z); mma16(S[2 + 2 * m], q.x, q.y, q.z, q.w, kk.y, kk.w);
        }
    }
    const float NEG = -__int_as_float(0x7f800000);
    if (2 * c > g) { S[NT - 2][0] = NEG; S[NT - 1][2] = NEG; }
    if (2 * c + 1 > g) { S[NT - 2][1] = NEG; S[NT - 1][3] = NEG; }
    S[NT - 1][0] = S[NT - 1][1] = NEG;
    float m0 = fmaxf(S[0][0], S[0][1]), m1 = fmaxf(S[0][2], S[0][3]);
#pragma unroll
    for (int i = 1; i < NT; i++) { if (i < NT - 1) m0 = fmaxf(m0, fmaxf(S[i][0], S[i][1])); m1 = fmaxf(m1, fmaxf(S[i][2], S[i][3])); }
    m0 = fmaxf(m0, __shfl_xor_sync(0xffffffffu, m0, 1)); m1 = fmaxf(m1, __shfl_xor_sync(0xffffffffu, m1, 1));
    m0 = fmaxf(m0, __shfl_xor_sync(0xffffffffu, m0, 2)); m1 = fmaxf(m1, __shfl_xor_sync(0xffffffffu, m1, 2));
    m0 *= -SC_LOG2E; m1 *= -SC_LOG2E;
    float l0 = 0, l1 = 0;
#pragma unroll
    for (int i = 0; i < NT; i++) {
        if (i < NT - 1) { S[i][0] = ex2(fmaf(S[i][0], SC_LOG2E, m0)); S[i][1] = ex2(fmaf(S[i][1], SC_LOG2E, m0)); l0 += S[i][0] + S[i][1]; }
        S[i][2] = ex2(fmaf(S[i][2], SC_LOG2E, m1)); S[i][3] = ex2(fmaf(S[i][3], SC_LOG2E, m1)); l1 += S[i][2] + S[i][3];
    }
    l0 += __shfl_xor_sync(0xffffffffu, l0, 1); l1 += __shfl_xor_sync(0xffffffffu, l1, 1);
    l0 += __shfl_xor_sync(0xffffffffu, l0, 2); l1 += __shfl_xor_sync(0xffffffffu, l1, 2);
    l0 = rcp(l0); l1 = rcp(l1);
    uint32_t P[NT][2];
#pragma unroll
    for (int i = 0; i < NT; i++) { P[i][0] = i < NT - 1 ? pack2(S[i][0] * l0, S[i][1] * l0) : 0u; P[i][1] = pack2(S[i][2] * l1, S[i][3] * l1); }
#pragma unroll 2
    for (int et = 0; et < 8; et++) {
        float a[4] = {0, 0, 0, 0}, b[4] = {0, 0, 0, 0};
        const uint2 vm = lds64(l8 + SL_VM + et * 256);
        mma8(a, vm.x, vm.y, P[0][0]); mma8(b, vm.x, vm.y, P[0][1]);
#pragma unroll
        for (int m = 0; m <= MT; m++) {
            const uint4 v = lds128(l16 + SL_V + m * 4096 + et * 512);
            mma16(a, v.x, v.y, v.z, v.w, P[1 + 2 * m][0], P[2 + 2 * m][0]); mma16(b, v.x, v.y, v.z, v.w, P[1 + 2 * m][1], P[2 + 2 * m][1]);
        }
        asm volatile("stmatrix.sync.aligned.m8n8.x4.trans.shared.b16 [%0],{%1,%2,%3,%4};" ::"r"(os + (et >> 2) * 2048 + (et & 3) * 256),
                     "r"(pack2(a[0], a[1])), "r"(pack2(a[2], a[3])), "r"(pack2(b[0], b[1])), "r"(pack2(b[2], b[3])) : "memory");
    }
}

__device__ __forceinline__ void rec_tiles(uint32_t sb, int X, int head, uint32_t rank, int& nxt, int lim, int need) {
#pragma unroll 1
    while (nxt <= lim) {
        if ((nxt & 1) == 0) {
            unsigned v; int n = 0;
            while (true) {
                asm volatile("ld.relaxed.gpu.global.u32 %0,[%1];" : "=r"(v) : "l"(cnt_ptr(C_QKV + X * 32 + (nxt >> 1))) : "memory");
                if (__all_sync(0xffffffffu, v >= 2 * NQ)) break;
                if (nxt > need) return;
                if (++n > 3000000) __trap();
            }
        }
        if (elect()) {
            const uint32_t bar = sb + R_BAR + (RB_XFULL + X * 2 + (nxt & 1)) * 8, dst = sb + R_SL + (X * 2 + (nxt & 1)) * SLOT;
            const uint4* src = g_qkv + (size_t)((X * 64 + nxt) * 32 + head) * 1536;
            mbar_expect(bar, 20480);
            bulk_g2s_mc(dst + rank * 8192, src + 512 + rank * 512, 8192, bar, POL_LAST);
            bulk_g2s(dst + SL_Q, src + (rank ^ X) * 256, 4096, bar, POL_LAST);
        }
        __syncwarp();
        nxt++;
    }
}

__device__ __forceinline__ void rec_attn(const Params& p, uint32_t sb, int X, int head, uint32_t rank) {
    const int lane = threadIdx.x & 31, g = lane >> 2, c = lane & 3;
    const int mt = rank ^ X;
    const uint32_t dp = mapa(sb, rank ^ 1) - sb;
    int nxt = 0;
    rec_tiles(sb, X, head, rank, nxt, 1, 0);
#pragma unroll 1
    for (int s = 0; s < 64; s++) {
        const uint32_t so = sb + R_SL + (X * 2 + (s & 1)) * SLOT;
        mbar_wait(sb + R_BAR + (RB_GO + X * 2 + (s & 1)) * 8, (s >> 1) & 1);
        rec_tiles(sb, X, head, rank, nxt, min(s + 1, 63), -1);
        spin(DX);
        mbar_wait(sb + R_BAR + (RB_XFULL + X * 2 + (s & 1)) * 8, (s >> 1) & 1);
        if (elect()) asm volatile("cp.async.bulk.wait_group.read 0;" ::: "memory");
        __syncwarp();
        const uint32_t os = sb + R_OS + X * 4096 + (lane >> 4) * 1024 + (lane & 15) * 16;
        if (mt) xattn<1>(so + lane * 16, so + lane * 8, os, g, c); else xattn<0>(so + lane * 16, so + lane * 8, os, g, c);
        fence_async_smem();
        __syncwarp();
        const uint32_t svb = sb + R_BAR + (RB_SV + X * 2 + (s & 1)) * 8;
        if (elect()) {
            mbar_arrive(svb); mbar_arrive_cluster(svb + dp);
            const uint64_t pol = POL_SOON;
#pragma unroll
            for (int kb = 0; kb < 2; kb++)
                asm volatile("cp.async.bulk.global.shared::cta.bulk_group.L2::cache_hint [%0],[%1],%2,%3;" ::"l"(g_o + ((X * 32 + (s >> 1)) * 64 + head * 2 + kb) * 512 + ((s & 1) * 4 + mt * 2) * 64),
                             "r"(sb + R_OS + X * 4096 + kb * 2048), "r"(2048), "l"(pol) : "memory");
            asm volatile("cp.async.bulk.commit_group;" ::: "memory");
            if (s & 1) { asm volatile("cp.async.bulk.wait_group 0;" ::: "memory"); red_release(cnt_ptr(C_O + (X * 32 + (s >> 1)) * 4 + (head >> 3)), 1); }
        }
        __syncwarp();
        rec_tiles(sb, X, head, rank, nxt, min(s + 1, 63), s + 1);
        mbar_wait(svb, (s >> 1) & 1);
        rec_tiles(sb, X, head, rank, nxt, min(s + 2, 63), -1);
    }
}

__device__ __forceinline__ uint32_t probe1(unsigned* r, int lane) {
    uint32_t v = 0;
    const uint32_t t0 = clk32();
    asm volatile("{.reg .pred p; setp.eq.u32 p,%2,0; @p atom.relaxed.gpu.global.or.b32 %0,[%1],0;}" : "+r"(v) : "l"(r), "r"(lane) : "memory");
    v = __shfl_sync(0xffffffffu, v, 0);
    asm volatile("{.reg .pred p; setp.eq.u32 p,%0,0x5a5a5a5b; @p nanosleep.u32 1;}" ::"r"(v) : "memory");
    return clk32() - t0;
}
__device__ __forceinline__ void rec_probe(uint32_t sb, int me, int w) {
    const int lane = threadIdx.x & 31;
    unsigned* r = (unsigned*)xregion(w & 1, (w & 2) ? 64 + (me & 1) : me) + ((w & 2) ? (me >> 1) * 32 : 0);
    uint32_t b0 = ~0u, b1 = ~0u;
#pragma unroll 1
    for (int i = 0; i < 3; i++) { b0 = min(b0, probe1(r, lane)); b1 = min(b1, probe1(r + 1024, lane)); }
    sts32(sb + R_BAR + 480 + w * 4, b1 < b0);
}
__device__ __forceinline__ void rec_sides(uint32_t sb, int me, int w) {
    const int lane = threadIdx.x & 31;
    if (lane == 0) asm volatile("red.relaxed.gpu.global.add.u32 [%0],%1;" ::"l"(g_sel + me), "r"((lds32(sb + R_BAR + 480 + w * 4) << w) + 256u) : "memory");
    __syncwarp();
    if (w < 2) {
        unsigned v; int n = 0;
        while (true) {
            asm volatile("ld.relaxed.gpu.global.u32 %0,[%1];" : "=r"(v) : "l"(g_sel + w * 32 + lane) : "memory");
            if (__all_sync(0xffffffffu, v >= 1024)) break;
            if (++n > 2000000) __trap();
        }
        sts32(sb + R_SEL + (w * 32 + lane) * 4, v);
    }
}

__device__ __forceinline__ void rec_init(uint32_t sb) {
    const uint32_t b = sb + R_BAR;
    const int i = threadIdx.x & 31;
    mbar_init(b + i * 8, i >= RB_SV ? 2 : 1);
    if (i == RB_INIT) mbar_expect(b + RB_INIT * 8, 196608);
    asm volatile("fence.mbarrier_init.release.cluster;" ::: "memory");
}
constexpr int G_BAR = B_BAR;
enum { GB_FULL = 0  , GB_EMPTY = 8  , GB_RS = 16, GB_SS = 17, GB_LAG = 18, GB_FREE = 19, GB_DONE = 20  , GB_N = 24 };
constexpr int Q_PRE = 8;
constexpr int NQRS = 2 * NQ - 64;
__device__ __forceinline__ void gemm_init(uint32_t sb, bool op) {
    const int i = threadIdx.x & 31;
    if (i < GB_N) mbar_init(sb + G_BAR + i * 8, i >= GB_DONE ? 4 : i == GB_FREE ? 8 : (i >= GB_EMPTY && i < GB_RS) ? 2 : 1);
    if (i == GB_RS) mbar_expect(sb + G_BAR + i * 8, op ? 131072 : 98304);
    if (i == GB_SS) mbar_expect(sb + G_BAR + i * 8, op ? 131072 : 163840);
    asm volatile("fence.mbarrier_init.release.cluster;" ::: "memory");
}
__device__ __forceinline__ int qkv_blk(int id, int j) { return NQRS * 4 + id * 10 + j; }
__device__ __forceinline__ void qkv_fetch(const Params& p, uint32_t sb, int id, int j0, int j1) {
#pragma unroll 1
    for (int j = j0 * 2; j < j1 * 2; j++) {
        const int blk = min(qkv_blk(id, j >> 1), 511);
        tma2d(sb + j * 8192, &p.tn[blk >> 8], (blk & 255) * 16, (j & 1) * 256, sb + G_BAR + GB_SS * 8);
    }
}
__device__ __forceinline__ void qkv_stage(const Params& p, uint32_t dst, uint32_t bar, int id, int k0, int nk) {
#pragma unroll 1
    for (int j = 0; j < 2 * nk; j++) {
        const int u = id * 2 + (j >= nk);
        tma2d(dst + j * 8192, &p.tm[u < 64 ? 2 : 0], (u & 63) * 64, (k0 + (j >= nk ? j - nk : j)) * 64, bar);
    }
}
__device__ __forceinline__ void op_fetch(const Params& p, uint32_t sb, int id, int half) {
#pragma unroll 1
    for (int j = 0; j < 16; j++) tma2d(sb + j * 8192, &p.tm[4], ((id * 2 + (j >> 3)) & 7) * 64, (id >> 2) * 1024 + (j & 7) * 128 + half * 64, sb + G_BAR + (GB_RS + half) * 8);
}
template <bool OP>
__device__ __forceinline__ void gemm_producer(const Params& p, uint32_t sb, int id) {
    constexpr int NS = OP ? 6 : 8, SB = OP ? 16384 : 8192, RING = OP ? 131072 : 163840;
    if (!elect()) return;
    mbar_wait(sb + G_BAR + GB_FREE * 8, 0);
    if (OP) op_fetch(p, sb, id, 1);
    else {
        mbar_expect(sb + G_BAR + GB_RS * 8, 32768);
        qkv_stage(p, sb + 196608, sb + G_BAR + GB_RS * 8, id, 6, 2);
        qkv_fetch(p, sb, id, Q_PRE, 10);
        mbar_wait(sb + G_BAR + GB_FREE * 8, 1);
    }
    wait_cnt(g_gate, lds32(sb + S_GATE));
    int st = 0; uint32_t ph = 1;
#pragma unroll 1
    for (int n = 0; n < p.nl[OP]; n++) {
        const int e = p.list[OP][n];
        wait_cnt(OP ? cnt_ptr(C_O + e * 4 + (id >> 2)) : cnt_ptr(C_XN + e), OP ? 16 : 8);
        PROF(true, 1024 + n * 4);
        const uint4* src = OP ? g_o + (e * 64 + (id >> 2) * 16) * 512 : g_xn + e * 4096;
#pragma unroll 1
        for (int s = 0; s < 8; s++) {
            mbar_wait(sb + G_BAR + (GB_EMPTY + st) * 8, ph);
            mbar_expect(sb + G_BAR + (GB_FULL + st) * 8, SB);
            bulk_g2s(sb + RING + st * SB, src + s * (SB / 16), SB, sb + G_BAR + (GB_FULL + st) * 8, POL_N);
            if (++st == NS) { st = 0; ph ^= 1; }
        }
    }
}
template <bool OP>
__device__ __forceinline__ void gemm_release(const Params& p, uint32_t sb, int id) {
    if (threadIdx.x != 288) return;
#pragma unroll 1
    for (int n = 0; n < 2 * p.nl[OP]; n++) {
        const int e = p.list[OP][n >> 1];
        mbar_wait(sb + G_BAR + (GB_DONE + (n & 3)) * 8, (n >> 2) & 1);
        red_release(OP ? cnt_ptr(C_PP + e * 8 + (id & 3) * 2 + (n & 1)) : cnt_ptr(C_QKV + e), 1);
        PROF(n & 1, 1024 + (n >> 1) * 4 + 3);
    }
}
__device__ __forceinline__ void op_permute(uint32_t sb) {
#pragma unroll 2
    for (int i = threadIdx.x; i < 4096; i += 256) {
        const uint32_t a = sb + i * 32 + ((i >> 2) & 1) * 16, b = a ^ 16;
        const uint4 x = lds128(a), y = lds128(b);
        sts128(a, __byte_perm(x.x, x.y, 0x5410), __byte_perm(x.z, x.w, 0x5410), __byte_perm(y.x, y.y, 0x5410), __byte_perm(y.z, y.w, 0x5410));
        sts128(b, __byte_perm(x.x, x.y, 0x7632), __byte_perm(x.z, x.w, 0x7632), __byte_perm(y.x, y.y, 0x7632), __byte_perm(y.z, y.w, 0x7632));
    }
    fence_async_smem();
    bar_sync(1, 256);
}
template <bool OP>
__device__ __forceinline__ void gemm_consumer(const Params& p, uint32_t sb, int id, int w) {
    constexpr int NS = OP ? 6 : 8, SB = OP ? 16384 : 8192, RING = OP ? 131072 : 163840;
    const int lane = threadIdx.x & 31, wg = w >> 2, t = w & 3, u = id * 2 + wg;
    uint32_t a[128];
    mbar_wait(sb + G_BAR + GB_RS * 8, 0);
    PROF(threadIdx.x == 0, 3501);
    if (OP) op_permute(sb);
    const uint32_t wo = sb + (((lane >> 4) << 3) + (lane & 7)) * 128 + (((2 * t + ((lane >> 3) & 1)) ^ (lane & 7)) << 4);
#pragma unroll
    for (int ks = 0; ks < 32; ks++) {
        const uint4 v = ldsm4t(wo + ks * 2048 + (OP ? wg * 65536 : ks < 24 ? 131072 + wg * 49152 : 196608 - 49152 + wg * 16384));
        a[ks * 4] = v.x; a[ks * 4 + 1] = v.y; a[ks * 4 + 2] = v.z; a[ks * 4 + 3] = v.w;
        if (ks == 31 || (!OP && ks == 23)) {
            fence_async_smem();
            __syncwarp();
            if (lane == 0) mbar_arrive(sb + G_BAR + GB_FREE * 8);
            if (ks == 23) mbar_wait(sb + G_BAR + GB_RS * 8, 1);
        }
    }
    PROF(threadIdx.x == 0, 3502);
    mbar_wait(sb + G_BAR + GB_SS * 8, 0);
    if (OP) op_permute(sb);
    PROF(threadIdx.x == 0, 3503);
    float c0[32], c1[OP ? 32 : 40];
    int st = 0; uint32_t ph = 0;
    const bool el = (threadIdx.x & 127) == 0;
#pragma unroll 1
    for (int n = 0; n < p.nl[OP]; n++) {
        int prev = 0;
        const uint32_t wb = sb + wg * (OP ? 65536 : 81920) + (n & p.zero);
        const uint64_t dw = OP ? mkdesc(wb, 0, 1024, 1) : mkdesc(wb, 16384, 256, 3);
        if (!OP && wg) mbar_wait(sb + G_BAR + GB_LAG * 8, n & 1);
#pragma unroll
        for (int s = 0; s < 8; s++) {
            mbar_wait(sb + G_BAR + (GB_FULL + st) * 8, ph);
            const uint64_t dx = mkdesc(sb + RING + st * SB, 128, 1024, 0);
            wg_fence();
#pragma unroll
            for (int kk = 0; kk < 4; kk++) {
                const int ks = s * 4 + kk;
                if (ks == 0) { wgmma64_rs<0>(c0, a, dx); if (OP) wgmma64_ta<0>(c1, dw, dx + 512); else wgmma80_tb<0>(c1, dx, dw); }
                else { wgmma64_rs<1>(c0, a + ks * 4, dx + kk * 16); if (OP) wgmma64_ta<1>(c1, dw + ks * 128, dx + 512 + kk * 16); else wgmma80_tb<1>(c1, dx + kk * 16, dw + ks * 32); }
            }
            wg_commit();
            if (s) {
                wg_wait<1>();
                if (el) { mbar_arrive(sb + G_BAR + (GB_EMPTY + prev) * 8); if (!OP && s == QLAG && !wg) mbar_arrive(sb + G_BAR + GB_LAG * 8); }
            }
            prev = st;
            if (++st == NS) { st = 0; ph ^= 1; }
        }
        const int e = p.list[OP][n];
        wg_wait<0>();
        if (el) mbar_arrive(sb + G_BAR + (GB_EMPTY + prev) * 8);
        PROF(threadIdx.x == 128, 1024 + n * 4 + 1);
        if (OP) {
            uint4* dst = g_pp + (e * 4 + (id >> 2)) * 4096 + ((u & 7) * 32 + t * 8) * 16 + (lane >> 2) * 16 + (lane & 3);
#pragma unroll
            for (int j = 0; j < 4; j++) {
                const float* x = c0 + j * 8; const float* y = c1 + j * 8;
                stg128(dst + j * 4, make_uint4(pack2(x[0] + y[0], x[1] + y[1]), pack2(x[2] + y[2], x[3] + y[3]), pack2(x[4] + y[4], x[5] + y[5]), pack2(x[6] + y[6], x[7] + y[7])), POL_SOON);
            }
        } else {
            uint4* dst = g_qkv + (size_t)e * 2 * 32 * 1536 + lane;
            const uint64_t pol = POL_SOON;
#pragma unroll
            for (int j = 0; j < 4; j++) {
                const float* x = c0 + j * 8;
                uint4 v = make_uint4(pack2(x[0], x[1]), pack2(x[2], x[3]), pack2(x[4], x[5]), pack2(x[6], x[7]));
                if (u >= 64) v = make_uint4(movm(v.x), movm(v.z), movm(v.y), movm(v.w));
                stg128(dst + (((j >> 1) * 32 + ((u & 63) >> 1)) * 1536 + (u < 64 ? 1024 : 0) + (j & 1) * 256 + ((u & 1) * 4 + t) * 32), v, pol);
            }
#pragma unroll
            for (int j = 0; j < 5; j++) {
                const float* x = c1 + (OP ? 0 : j * 8);
                const int blk = qkv_blk(id, wg * 5 + j);
                if (blk < 512) stg128(dst + (((t >> 1) * 32 + ((blk >> 3) & 31)) * 1536 + (blk >> 8) * 512 + (t & 1) * 256 + (blk & 7) * 32),
                                      make_uint4(pack2(x[0], x[1]), pack2(x[2], x[3]), pack2(x[4], x[5]), pack2(x[6], x[7])), pol);
            }
        }
        __syncwarp();
        if (lane == 0) mbar_arrive(sb + G_BAR + (GB_DONE + (n & 1) * 2 + wg) * 8);
        PROF(threadIdx.x == 128, 1024 + n * 4 + 2);
    }
}

template <int NP, bool MMA>
__device__ __forceinline__ void sum_partials(float* x, const uint2* src, const uint32_t* r0, const uint32_t* r1, uint32_t idm) {
    uint2 v[4][NP];
#pragma unroll
    for (int s = 0; s < 4; s++)
#pragma unroll
        for (int i = 0; i < NP; i++) asm volatile("ld.global.cg.L2::cache_hint.v2.u32 {%0,%1},[%2],%3;" : "=r"(v[s][i].x), "=r"(v[s][i].y) : "l"(src + s * 8192 + i * 32), "l"(POL_LAST) : "memory");
#pragma unroll
    for (int i = 0; i < NP; i++) {
        uint32_t a, b;
        if (MMA) {
            float t[4] = {0, 0, 0, 0};
            mma16(t, v[0][i].x, v[0][i].y, v[1][i].x, v[1][i].y, idm, idm); mma16(t, v[2][i].x, v[2][i].y, v[3][i].x, v[3][i].y, idm, idm);
            a = pack2(t[0], t[2]); b = pack2(t[1], t[3]);
        } else {
            a = pack2((blo(v[0][i].x) + blo(v[1][i].x)) + (blo(v[2][i].x) + blo(v[3][i].x)), (blo(v[0][i].y) + blo(v[1][i].y)) + (blo(v[2][i].y) + blo(v[3][i].y)));
            b = pack2((bhi(v[0][i].x) + bhi(v[1][i].x)) + (bhi(v[2][i].x) + bhi(v[3][i].x)), (bhi(v[0][i].y) + bhi(v[1][i].y)) + (bhi(v[2][i].y) + bhi(v[3][i].y)));
        }
        const uint32_t s0 = hadd2(a, r0[i]), s1 = hadd2(b, r1[i]);
        x[4 * i] = blo(s0); x[4 * i + 2] = bhi(s0); x[4 * i + 1] = blo(s1); x[4 * i + 3] = bhi(s1);
    }
}
__device__ __forceinline__ const uint2* pp_src(int e, int tile, int lane) { return (const uint2*)g_pp + e * 32768 + tile * 128 + (lane >> 3) * 8 + (lane & 3) * 2 + ((lane >> 2) & 1); }

__device__ __forceinline__ void fin_warp(const Params& p, uint32_t sb, int id) {
    const int tile = (id & ~1) + (threadIdx.x & 1), lane = (id & 1) * 16 + ((threadIdx.x & 31) >> 1);
    wait_cnt_warp(g_gate, lds32(sb + S_GATE));
#pragma unroll 1
    for (int e = 32; e < 64; e++) {
        wait_cnt_warp(cnt_ptr(C_PP + e * 8 + (id >> 3)), 4);
        const uint4* rp = g_x + ((127 + tile * 2) * 1024 + e * 32 + lane);
        uint32_t o0[4], o1[4];
#pragma unroll
        for (int h = 0; h < 2; h++) {
            const uint4 r = ldcg128(rp + h * 1024);
            const uint32_t a[2] = {r.x, r.y}, b[2] = {r.z, r.w};
            float x[8];
            sum_partials<2, false>(x, pp_src(e, tile, lane) + h * 64, a, b, 0);
#pragma unroll
            for (int i = 0; i < 2; i++) {
                o0[h * 2 + i] = __byte_perm(__float_as_uint(x[4 * i]), __float_as_uint(x[4 * i + 2]), 0x7632);
                o1[h * 2 + i] = __byte_perm(__float_as_uint(x[4 * i + 1]), __float_as_uint(x[4 * i + 3]), 0x7632);
            }
        }
        uint4* dst = (uint4*)p.out + ((e - 32) * 64 + lane * 2) * 64 + tile;
        dst[0] = make_uint4(o0[0], o0[1], o0[2], o0[3]); dst[64] = make_uint4(o1[0], o1[1], o1[2], o1[3]);
        PROF((threadIdx.x & 31) == 0, 1536 + e);
    }
}

constexpr int PROW = 272, UROW = 2304, UPRE = 256;
constexpr int C_UR = 0  , C_TB = 65536  , C_BG = C_TB + 51200,
              CB_M = 8960, CB_U = CB_M + 1792, CB_BIG = CB_U + 2560, C_ST = C_BG + 8 * CB_BIG  ;
static_assert(C_ST + 4736 <= B_BAR, "smem map");
enum { CB_TB = 0, CB_UF = 1  , CB_CF = 5  , CB_LD = 9   };
__device__ __forceinline__ void conv_init(uint32_t sb, bool spare) {
    const int i = threadIdx.x & 31;
    mbar_init(sb + B_BAR + i * 8, (i >= CB_UF && i < CB_CF && !spare) ? 2 : 1);
    if (i == CB_TB && !spare) mbar_expect(sb + B_BAR + i * 8, 51200);
    asm volatile("fence.mbarrier_init.release.cluster;" ::: "memory");
}
__device__ __forceinline__ void mma_q(float* c, const uint32_t* a, const uint4& q) {
    mma16(c, a[0], a[1], a[2], a[3], q.x, q.y); mma16(c, a[4], a[5], a[6], a[7], q.z, q.w);
}
__device__ __forceinline__ uint2 ld_acc(const uint2* p, bool on) {
    uint2 v = make_uint2(0, 0);
    asm volatile("{.reg .pred p; setp.ne.u32 p,%3,0; @p ld.global.cg.v2.u32 {%0,%1},[%2];}" : "+r"(v.x), "+r"(v.y) : "l"(p), "r"((uint32_t)on) : "memory");
    return v;
}
__device__ __forceinline__ void add_acc(float* c, uint2 v) { c[0] += blo(v.x); c[1] += bhi(v.x); c[2] += blo(v.y); c[3] += bhi(v.y); }
__device__ __forceinline__ void st_acc(uint2* p, const float* c) { *p = make_uint2(pack2(c[0], c[1]), pack2(c[2], c[3])); }
__device__ __forceinline__ float sum8(const uint4* v, int k) {
#define VK(i) __uint_as_float(k == 0 ? v[i].x : k == 1 ? v[i].y : k == 2 ? v[i].z : v[i].w)
    return ((VK(0) + VK(1)) + (VK(2) + VK(3))) + ((VK(4) + VK(5)) + (VK(6) + VK(7)));
}
template <int XW>
__device__ __forceinline__ void stats_send(uint32_t l16, const float* x, uint4* gs, int q, int w) {
    float s0 = 0, s1 = 0, m0 = 0, m1 = 0;
#pragma unroll
    for (int i = 0; i < 8; i++) { s0 += x[2 * i]; s1 += x[2 * i + 1]; m0 = fmaf(x[2 * i], x[2 * i], m0); m1 = fmaf(x[2 * i + 1], x[2 * i + 1], m1); }
    sts128(l16 + C_ST + w * 512, __float_as_uint(s0), __float_as_uint(m0), __float_as_uint(s1), __float_as_uint(m1));
    if (w == XW) {
        bar_sync(2, 256);
        uint4 v[8];
#pragma unroll
        for (int i = 0; i < 8; i++) v[i] = lds128(l16 + C_ST + i * 512);
        st_rlx128(gs + q * 32, __float_as_uint(sum8(v, 0)), __float_as_uint(sum8(v, 1)) & 0x7fffffffu, __float_as_uint(sum8(v, 2)), __float_as_uint(sum8(v, 3)));
    } else bar_arrive(2, 256);
}
template <int XW>
__device__ __forceinline__ float4 stats_recv(uint32_t l16, const uint4* gs, int w) {
    if (w == XW) {
        uint4 v[8];
        int n = 0;
        while (true) {
            uint32_t bad = 0;
#pragma unroll
            for (int i = 0; i < 8; i++) v[i] = ld_rlx128(gs + i * 32);
#pragma unroll
            for (int i = 0; i < 8; i++) bad |= v[i].y;
            if (!__any_sync(0xffffffffu, bad >> 31)) break;
            if (++n > 2000000) __trap();
        }
        const float s0 = sum8(v, 0) * (1.f / 512.f), s1 = sum8(v, 2) * (1.f / 512.f);
        const float2 l0 = ln_finish(s0, fmaxf(fmaf(sum8(v, 1), 1.f / 512.f, -s0 * s0), 0.f)), l1 = ln_finish(s1, fmaxf(fmaf(sum8(v, 3), 1.f / 512.f, -s1 * s1), 0.f));
        sts128(l16 + C_ST + 4096, __float_as_uint(l0.x), __float_as_uint(rcp(l0.y)), __float_as_uint(l1.x), __float_as_uint(rcp(l1.y)));
    }
    bar_sync(3, 256);
    const uint4 r = lds128(l16 + C_ST + 4096);
    return make_float4(__uint_as_float(r.x), __uint_as_float(r.y), __uint_as_float(r.z), __uint_as_float(r.w));
}

#define HOIST_STOP(k) asm volatile("{.reg .pred p; setp.eq.u32 p,%0,%1; @p nanosleep.u32 1;}" ::"r"(zero), "r"((k) + 1) : "memory")
__device__ __forceinline__ void conv_near(float (*acc)[4], uint32_t ta, uint32_t qa, uint32_t zero) {
#pragma unroll
    for (int k = 0; k < 8; k++) {
        uint32_t a[8];
#pragma unroll
        for (int j = 0; j < 8; j++) a[j] = lds32(ta + k * 800 + j * 32);
        mma_q(acc[k], a, ldsm4(qa + k * 1024));
        if (k % NFE == NFE - 1 && k < 7) HOIST_STOP(k);
    }
}
template <int K0>
__device__ __forceinline__ void conv_pair(float (*acc)[4], float (*pend)[4], uint32_t ta, uint32_t q0, uint32_t q1, uint32_t q2, uint32_t zero) {
#pragma unroll
    for (int i = 0; i < 4; i++) {
        const int k = K0 + i;
#pragma unroll
        for (int e = 0; e < 4; e++) { acc[4 - K0 + i][e] += pend[i][e]; pend[i][e] = 0; }
        uint32_t a[16];
#pragma unroll
        for (int j = 0; j < 16; j++) a[j] = lds32(ta + 256 + k * 800 + j * 32);
        const uint4 x1 = ldsm4(q1 + k * 1024);
        mma_q(acc[k], a, x1); mma_q(pend[i], a, ldsm4(q2 + k * 1024));
        mma_q(pend[i], a + 8, x1); mma_q(acc[k], a + 8, ldsm4(q0 + k * 1024));
        if (i % NFP == NFP - 1 && i < 3) HOIST_STOP(k);
    }
}

__device__ __forceinline__ void conv_tile(const Params& p, uint32_t sb, int q, int w) {
    const int lane = __shfl_sync(0xffffffffu, threadIdx.x & 31, threadIdx.x & 31), g = lane >> 2, c = lane & 3, tile = q * 8 + w;
    const uint32_t l16 = sb + lane * 16;
#pragma unroll
    for (int i = 0; i < 16; i++) sts128(l16 + C_UR + w * 8192 + i * 512, 0, 0, 0, 0);
    wait_cnt_warp(g_gate, lds32(sb + S_GATE));
    if (lane < 8) bulk_g2s(sb + C_TB + (w * 8 + lane) * 800, g_P + (tile * 8 + lane) * PROW + 72, 800, sb + B_BAR + CB_TB * 8, POL_N);
    uint32_t A[8][8];
#pragma unroll
    for (int k = 0; k < 8; k++)
#pragma unroll
        for (int j = 0; j < 8; j++) A[k][j] = __ldcg(g_P + (tile * 8 + k) * PROW + 16 + 8 * j + g - 2 * c);
    if (lane == 0) { const uint4 d = __ldg((const uint4*)p.Dskip + tile); sts128(sb + C_ST + 4608 + w * 16, d.x, d.y, d.z, d.w); }
    float acc[8][4], pend[4][4];
#pragma unroll
    for (int k = 0; k < 8; k++) acc[k][0] = acc[k][1] = acc[k][2] = acc[k][3] = pend[k & 3][k >> 2] = pend[k & 3][2 + (k >> 2)] = 0;
    const uint32_t row = sb + C_UR + w * 8192, ta = sb + C_TB + w * 6400 + (8 + g - 2 * c) * 4, zero = p.zero, qo = (lane & 7) * 16 - (lane >> 3) * 32;
    bar_sync(4, 384);
    mbar_wait(sb + B_BAR + CB_TB * 8, 0);
#pragma unroll 1
    for (int b = 0; b < 32; b++) {
        const int lz = lane + (b & p.zero);
        const uint4 r0 = ldcg128(g_x + (tile * 2048 + b * 32 + lz)), r1 = ldcg128(g_x + (tile * 2048 + b * 32 + lz) + 1024);
        const uint32_t q1 = row + ((qo + (b - 1) * 128) & 1023);
        if (w == 0) conv_near(acc, ta, q1, zero);
        PROF(threadIdx.x == 0, 2048 + b * 8);
        const uint2* pps = pp_src(b, tile, lz);
        asm volatile("" : "+l"(pps));
        wait_flag_warp(cnt_ptr(C_PP + b * 8 + q), 4);
        PROF(threadIdx.x == 0, 2048 + b * 8 + 1);
        float x[16];
        {
            const uint32_t a[4] = {r0.x, r0.y, r1.x, r1.y}, bb[4] = {r0.z, r0.w, r1.z, r1.w};
            sum_partials<4, true>(x, pps, a, bb, (2 * (lz & 3) == lz >> 2) ? 0x00003f80u : (2 * (lz & 3) + 1 == lz >> 2) ? 0x3f800000u : 0u);
        }
        stats_send<0>(l16, x, g_st + b * 256 + lz, q, w);
        {
            PROF(threadIdx.x == 0, 2048 + b * 8 + 2);
            if (b) mbar_wait(sb + B_BAR + (CB_CF + (w >> 1)) * 8, (b - 1) & 1);
            const uint2* cb = g_carry + ((tile * 320 + b) * 32 + lz);
            uint2 cr[8];
#pragma unroll
            for (int k = 0; k < 8; k++) cr[k] = ld_acc(cb + k * 1280, b >= 4);
            if (w) conv_near(acc, ta, q1, zero);
#pragma unroll
            for (int k = 0; k < 8; k++) add_acc(acc[k], cr[k]);
        }
        float4 ln = stats_recv<0>(l16, g_st + b * 256 + lz, w);
        PROF(threadIdx.x == 0, 2048 + b * 8 + 3);
        uint32_t u[8];
#pragma unroll
        for (int k = 0; k < 8; k++) {
            u[k] = pack2(rbf(x[2 * k] - ln.x) * ln.y, rbf(x[2 * k + 1] - ln.z) * ln.w);
            sts32(row + k * 1024 + (b & 7) * 128 + lane * 4, u[k]);
        }
        __syncwarp();
        if (UFE && lane == 0) mbar_arrive(sb + B_BAR + (CB_UF + (w >> 1)) * 8);
        const uint32_t qa = row + ((qo + b * 128) & 1023);
#pragma unroll
        for (int k = 0; k < 8; k++) mma_q(acc[k], A[k], ldsm4(qa + k * 1024));
        const uint4 dk = lds128(sb + C_ST + 4608 + w * 16);
#pragma unroll
        for (int k = 0; k < 8; k++) {
            const float t = __shfl_sync(0xffffffffu, acc[k][3], (lz & ~3) | ((lz - 1) & 3));
            const uint32_t y = movm(pack2(acc[k][0] + (c ? t : 0.f), acc[k][1] + acc[k][2]));
            acc[k][0] = c ? 0.f : t; acc[k][1] = acc[k][2] = acc[k][3] = 0;
            const uint32_t dw = k >> 1 == 0 ? dk.x : k >> 1 == 1 ? dk.y : k >> 1 == 2 ? dk.z : dk.w;
            const uint32_t s = hadd2(hadd2(y, hmul2(u[k], __byte_perm(dw, 0, (k & 1) ? 0x3232 : 0x1010))), __byte_perm(__float_as_uint(x[2 * k]), __float_as_uint(x[2 * k + 1]), 0x7632));
            x[2 * k] = blo(s); x[2 * k + 1] = bhi(s);
        }
        if (!UFE && lane == 0) mbar_arrive(sb + B_BAR + (CB_UF + (w >> 1)) * 8);
        stats_send<1>(l16, x, g_st + (32 + b) * 256 + lz, q, w);
        {
            PROF(threadIdx.x == 0, 2048 + b * 8 + 4);
            uint4* dst = g_x + (131072 + tile * 2048 + b * 32 + lz);
#pragma unroll
            for (int e = 0; e < 2; e++) {
                const float* y = x + e * 8;
                dst[e * 1024] = make_uint4(__byte_perm(__float_as_uint(y[0]), __float_as_uint(y[2]), 0x7632), __byte_perm(__float_as_uint(y[4]), __float_as_uint(y[6]), 0x7632),
                                           __byte_perm(__float_as_uint(y[1]), __float_as_uint(y[3]), 0x7632), __byte_perm(__float_as_uint(y[5]), __float_as_uint(y[7]), 0x7632));
            }
            uint32_t* du = g_u + (tile * 8 * (UROW / 2) + UPRE / 2 + b * 32 + lz);
#pragma unroll
            for (int k = 0; k < 8; k++) du[k * (UROW / 2)] = u[k];
        }
#pragma unroll 1
        for (int pass = 0; pass < 2; pass++) {
            if (pass == (w == 1)) {
                const uint32_t q0 = row + ((qo + (b - 2) * 128) & 1023);
                if (b & 1) conv_pair<4>(acc, pend, ta, q0, q1, qa, zero); else conv_pair<0>(acc, pend, ta, q0, q1, qa, zero);
            }
            if (pass) break;
            ln = stats_recv<1>(l16, g_st + (32 + b) * 256 + lz, w);
            PROF(threadIdx.x == 0, 2048 + b * 8 + 5);
            uint32_t o[2][4];
#pragma unroll
            for (int e = 0; e < 2; e++) {
                const float mu = e ? ln.z : ln.x, rs = e ? ln.w : ln.y;
#pragma unroll
                for (int i = 0; i < 4; i++) o[e][i] = pack2(rbf(x[4 * i + e] - mu) * rs, rbf(x[4 * i + 2 + e] - mu) * rs);
            }
#pragma unroll
            for (int i = 0; i < 4; i++) {
                const uint32_t t = __shfl_xor_sync(0xffffffffu, (lz & 1) ? o[0][i] : o[1][i], 1);
                if (lz & 1) o[0][i] = t; else o[1][i] = t;
            }
            uint4* dst = g_xn + ((32 + b) * 4096 + q * 512 + (lz >> 2) * 64 + w * 8 + (lz & 2) * 2 + (lz & 1));
            dst[0] = make_uint4(o[0][0], o[0][1], o[0][2], o[0][3]); dst[2] = make_uint4(o[1][0], o[1][1], o[1][2], o[1][3]);
            if (w == 7) {
                bar_sync(5, 256);
                if (elect()) red_release(cnt_ptr(C_XN + 32 + b), 1);
                PROF(lane == 0, 2048 + b * 8 + 6);
                __syncwarp();
            } else bar_arrive(5, 256);
        }
    }
}

template <int P0, bool TRI = false>
__device__ __forceinline__ void bg_half(float (*acc)[4], uint4* win, uint32_t ta, uint32_t qa, uint32_t mask, uint32_t row) {
#pragma unroll
    for (int i = 0; i < 4; i++) {
        win[P0 + i] = ldsm4(((qa + i * 128) & mask) + row);
        const uint4 a = lds128(ta + (3 - i) * 448), e = lds128(ta + (3 - i) * 448 + 224);
#pragma unroll
        for (int r = TRI ? 7 - P0 - i : 0; r < 8; r++) mma16(acc[r], a.x, a.y, a.z, a.w, win[(P0 + i + 1 + r) & 7].x, win[(P0 + i + 1 + r) & 7].y);
#pragma unroll
        for (int r = TRI ? 7 - P0 - i : 0; r < 8; r++) mma16(acc[r], e.x, e.y, e.z, e.w, win[(P0 + i + 1 + r) & 7].z, win[(P0 + i + 1 + r) & 7].w);
    }
}
__device__ __forceinline__ void bg_fetch(uint32_t sb, int q, int j, int n, int lane) {
    const int b0 = n >> 1, ch = q * 64 + j * 16 + (n & 1) * 8 + (b0 & 7), lo = max(b0 - 24, -4), nu = b0 > 4 ? (b0 - 4 - lo) * 128 : 0;
    const uint32_t bar = sb + B_BAR + (CB_LD + j * 2 + (n & 1)) * 8, buf = sb + C_BG + (j * 2 + (n & 1)) * CB_BIG;
    const int nt = min((b0 + 7) >> 2, 5) * 1792;
    if (elect()) {
        mbar_expect(bar, nt + nu + 1792);
        bulk_g2s(buf, g_W + ch * 784, nt, bar, POL_N);
        bulk_g2s(buf + CB_M, g_W + (ch ^ 4) * 784, 1792, bar, POL_N);
        if (nu) bulk_g2s(buf + CB_U + (lo - b0 + 24) * 128, g_u + ch * (UROW / 2) + UPRE / 2 + lo * 32, nu, bar, POL_N);
    }
    __syncwarp();
}
__device__ __forceinline__ void conv_back(uint32_t sb, int q, int j) {
    const int lane = __shfl_sync(0xffffffffu, threadIdx.x & 31, threadIdx.x & 31), g = lane >> 2, c = lane & 3;
    wait_cnt_warp(g_gate, lds32(sb + S_GATE));
    bg_fetch(sb, q, j, 2, lane);
    bar_sync(4, 384);
    const uint32_t to = (6 + g - 2 * c) * 16, qo = (lane & 7) * 16 - (lane >> 3) * 32;
#pragma unroll 1
    for (int n = 2; n < 64; n++) {
        const int b0 = n >> 1, i = n & 1, chl = j * 16 + i * 8 + (b0 & 7), hm = (b0 + 7) >> 2;
        const uint32_t buf = sb + C_BG + (j * 2 + i) * CB_BIG, ta = buf + to;
        float acc[8][4];
        uint4 win[8];
        if (n < 63) bg_fetch(sb, q, j, n + 1, lane);
        if (n == 34 || n == 42) wait_flag_warp(cnt_ptr(C_FAR + (n == 42)), 12);
        mbar_wait(sb + B_BAR + (CB_LD + j * 2 + i) * 8, (b0 - 1) & 1);
#pragma unroll
        for (int r = 0; r < 8; r++) {
            acc[r][0] = acc[r][1] = acc[r][2] = acc[r][3] = 0;
            win[r] = make_uint4(0, 0, 0, 0);
            if (r) asm volatile("{.reg .pred p; setp.ge.s32 p,%5,24; @p ldmatrix.sync.aligned.m8n8.x4.shared.b16 {%0,%1,%2,%3},[%4];}"
                                : "+r"(win[r].x), "+r"(win[r].y), "+r"(win[r].z), "+r"(win[r].w) : "r"(buf + CB_U + qo + r * 128), "r"(b0 + r) : "memory");
        }
        const uint2* fr = g_far + (((q * 64 + chl) * 8 + b0 - 24) * 32 + lane);
        uint2* cr = g_carry + (((q * 64 + chl) * 40 + b0) * 32 + lane);
        uint2* cm = g_carry + (((q * 64 + (chl ^ 4)) * 40 + b0) * 32 + lane);
        const uint32_t fm = 0xff000000u >> b0;
        uint2 pf[8], pm[4];
#pragma unroll
        for (int r = 0; r < 8; r++) pf[r] = ld_acc(fr + r * 32, (fm >> r) & 1);
#pragma unroll
        for (int r = 0; r < 4; r++) pm[r] = ld_acc(cm + r * 32, b0 > 4);
#pragma unroll 1
        for (int h = hm > 3 ? 5 : 3; h >= 3; h -= 2) {
            if (h <= hm) bg_half<0>(acc, win, ta + (h - 1) * 1792, qo + (28 - 4 * h) * 128, ~0u, buf + CB_U);
            if (h == 3 && i == 0) mbar_wait(sb + B_BAR + (CB_UF + j) * 8, (b0 - 1) & 1);
            bg_half<4>(acc, win, ta + (h - 2) * 1792, qo + (h == 3 ? b0 - 4 : 12) * 128, h == 3 ? 1023u : ~0u, h == 3 ? sb + C_UR + chl * 1024 : buf + CB_U);
        }
        uint4 wm[8];
#pragma unroll
        for (int r = 1; r < 8; r++) wm[r] = ldsm4(sb + C_UR + (chl ^ 4) * 1024 + ((qo + (b0 + r) * 128) & 1023));
#pragma unroll
        for (int r = 0; r < 8; r++) add_acc(acc[r], pf[r]);
#pragma unroll
        for (int r = 4; r < 8; r++) { st_acc(cr + r * 32, acc[r]); acc[r][0] = blo(pm[r - 4].x); acc[r][1] = bhi(pm[r - 4].x); acc[r][2] = blo(pm[r - 4].y); acc[r][3] = bhi(pm[r - 4].y); }
#pragma unroll
        for (int t = 7; t >= 0; t--) {
            const uint4 a = lds128(ta + t * 224), e = lds128(ta + CB_M + t * 224);
#pragma unroll
            for (int r = 0; r < 4; r++) { const uint4& x = win[4 + r - (t >> 1)]; mma16(acc[r], a.x, a.y, a.z, a.w, (t & 1) ? x.z : x.x, (t & 1) ? x.w : x.y); }
#pragma unroll
            for (int r = 0; r < 4; r++) { const uint4& x = wm[4 + r - (t >> 1)]; mma16(acc[4 + r], e.x, e.y, e.z, e.w, (t & 1) ? x.z : x.x, (t & 1) ? x.w : x.y); }
        }
#pragma unroll
        for (int r = 0; r < 4; r++) { st_acc(cr + r * 32, acc[r]); st_acc(cm + r * 32, acc[4 + r]); }
        __syncwarp();
        if (lane == 0 && i) mbar_arrive(sb + B_BAR + (CB_CF + j) * 8);
        PROF(j == 0 && lane == 0 && i, 2048 + b0 * 8 + 7);
    }
}
__device__ __forceinline__ void conv_far(uint32_t sb, int w) {
    const int lane = __shfl_sync(0xffffffffu, threadIdx.x & 31, threadIdx.x & 31), g = lane >> 2, c = lane & 3;
    wait_cnt_warp(g_gate, lds32(sb + S_GATE));
    wait_cnt_warp(cnt_ptr(C_XN + 39), 8);
    const uint32_t to = (6 + g - 2 * c) * 16, qo = (lane & 7) * 16 - (lane >> 3) * 32;
#pragma unroll 1
    for (int n = -1; n * 12 + w < 512; n++) {
        const int t = n * 12 + w, ch = (t & 63) * 8 + (((t >> 6) + 1) & 7), cn = ((t + 12) & 63) * 8 + ((((t + 12) >> 6) + 1) & 7);
        const uint32_t bar = sb + B_BAR + (w * 2 + (n & 1)) * 8, buf = sb + (w * 2 + (n & 1)) * 5120;
        if (t + 12 < 512 && elect()) {
            const uint32_t nb = sb + (w * 2 + (~n & 1)) * 5120;
            mbar_expect(bar ^ 8, 3584 + 1152);
            bulk_g2s(nb, g_W + cn * 784 + 560, 3584, bar ^ 8, POL_N);
            bulk_g2s(nb + 3584, g_u + cn * (UROW / 2) + UPRE / 2 - 32, 1152, bar ^ 8, POL_N);
        }
        __syncwarp();
        if (n < 0) continue;
        float acc[8][4];
        uint4 win[8];
#pragma unroll
        for (int r = 0; r < 8; r++) { acc[r][0] = acc[r][1] = acc[r][2] = acc[r][3] = 0; win[r] = make_uint4(0, 0, 0, 0); }
        mbar_wait(bar, (n >> 1) & 1);
        bg_half<0, true>(acc, win, buf + to + 1792, qo + 128, ~0u, buf + 3584);
        bg_half<4, true>(acc, win, buf + to, qo + 640, ~0u, buf + 3584);
#pragma unroll
        for (int r = 0; r < 8; r++) st_acc(g_far + (ch * 256 + lane) + r * 32, acc[r]);
        __syncwarp();
        if (((t + 12) ^ t) >= 256 && elect()) red_release(cnt_ptr(C_FAR + (t >> 8)), 1);
        __syncwarp();
    }
    PROF(threadIdx.x == 0, 2048);
}

constexpr int P_X = 131072  , P_K6 = P_X + 32768  , P_P = P_K6 + 10496  , P_U = P_P + 33280  ,
              P_END = P_U + 17408, P_PRM = P_P + 8192  , P_Y = P_P  ;
static_assert(P_END <= B_BAR && P_END <= R_SEL, "prologue scratch");
#define KGUN 2
constexpr int KGU = KGUN;
__device__ __forceinline__ void csq(float& r, float& i) { const float t = r * i; r = fmaf(r, r, -(i * i)); i = t + t; }
__device__ __forceinline__ void cpow(float ar, float ph, float p, float& r, float& i) {
    const float e = ex2(ar * p);
    const float u = ph * p, n = fabsf(u) < 4194304.f ? (u + 12582912.f) - 12582912.f : u;
    const float t = (u - n) * 6.283185307179586f;
    r = e * __cosf(t); i = e * __sinf(t);
}
__device__ __forceinline__ void mma_tf32(float* c, float a0, float a1, float a2, float a3, float b0, float b1) {
    asm volatile("mma.sync.aligned.m16n8k8.row.col.f32.tf32.tf32.f32 {%0,%1,%2,%3},{%4,%5,%6,%7},{%8,%9},{%0,%1,%2,%3};"
                 : "+f"(c[0]), "+f"(c[1]), "+f"(c[2]), "+f"(c[3])
                 : "r"(__float_as_uint(a0)), "r"(__float_as_uint(a1)), "r"(__float_as_uint(a2)), "r"(__float_as_uint(a3)), "r"(__float_as_uint(b0)), "r"(__float_as_uint(b1)));
}

__device__ __forceinline__ void early_fetch(const Params& p, uint32_t sb) {
    const int v = lds32(sb + S_VCL);
    if (elect()) {
        if (v >= V_QKV) { if (v < V_QKV + NQ && (p.roles & 8)) qkv_fetch(p, sb, v - V_QKV, 0, Q_PRE); }
        else if (v >= V_OP) { if (p.roles & 4) op_fetch(p, sb, v - V_OP, 0); }
        else if (v >= V_REC && (p.roles & 2)) { rec_fetch(p, sb, (v - V_REC) >> 1, v & 1, 0, R_STQ); rec_fetch(p, sb, (v - V_REC) >> 1, v & 1, 2, R_WV); }
    }
    __syncwarp();
}
struct ProRegs { uint32_t v[2][4], ldt[2]; };
__device__ __forceinline__ void prologue_load(const ProArgs& a, int b, ProRegs& pr) {
    const int w = threadIdx.x >> 5;
#pragma unroll
    for (int i = 0; i < 2; i++) {
        const int gi = b * 512 + (w & 3) * 128 + ((w >> 2) & 1) * 64 + i * 32 + (threadIdx.x & 31);
        pr.ldt[i] = __ldg((const uint16_t*)a.ldt + b * 4 + (w & 3));
        pr.v[i][0] = __ldg((const uint16_t*)a.lAr + gi); pr.v[i][1] = __ldg((const uint16_t*)a.Ai + gi);
        pr.v[i][2] = __ldg((const uint16_t*)a.Cr + gi); pr.v[i][3] = __ldg((const uint16_t*)a.Ci + gi);
    }
}
__device__ __forceinline__ void prologue(const Params& p, uint32_t sb, int b, int w, const ProRegs& pr) {
    const ProArgs& a = p.pa;
    const int tid = threadIdx.x, lane = tid & 31, g = lane >> 2, c = lane & 3;
    const int d0 = b * 4;
    if (w >= 8) {
        const int t2 = tid - 256;
        if (w < 10) {
            const int row = b * 16 + (w - 8) * 8 + g;
            uint4 v[16];
            const float2 r = row_stats512(v, (const uint4*)(a.x + (size_t)row * 512) + c, 8, 4);
            const float2 l = ln_finish(r.x * (1.f / 512.f), r.y * (1.f / 512.f));
            if (c == (g >> 1)) asm volatile("st.relaxed.gpu.global.u32 [%0],%1;" ::"l"(g_ln0 + row), "r"(pack2(l.x, l.y)) : "memory");
        }
        PROF(t2 == 0, 3516);
        const int gi = b * 128 + t2;
#pragma unroll 1
        for (int k = gi; k < 133 * 512; k += 16384) g_xch[k] = make_uint4(0, 0, 0, 0);
        g_st[gi] = make_uint4(~0u, ~0u, ~0u, ~0u);
        if (gi < 900 * 8) g_cnt[gi] = 0;
        if (gi < 64) g_sel[gi] = 0;
        bar_sync(6, 384);
        if (lane < 4 && ((PFM >> (w - 8)) & 1)) asm volatile("cp.async.bulk.prefetch.L2.global [%0],%1;" ::"l"(a.W[w - 8] + (b * 4 + lane) * 4096), "r"(8192) : "memory");
        bar_sync(9, 384);
        if (w == 10) early_fetch(p, sb);
#pragma unroll 2
        for (int i = t2; i < 4 * 784; i += 128) {
            const int ch = i / 784, k = i - ch * 784;
            const uint32_t o = sb + P_P + (ch * 2080 + 266 + (k / 14) * 18 + k) * 4;
            g_W[d0 * 784 + i] = make_uint4(lds32(o), lds32(o + 32), lds32(o + 64), lds32(o + 96));
        }
        bar_arrive(10, 384);
        PROF(t2 == 0, 3517);
        return;
    }
#pragma unroll
    for (int i = 0; i < 2; i++) {
        const float dt = rbf(expf(blo(pr.ldt[i])));
        const float ar = -rbf(expf(blo(pr.v[i][0]))) * dt, ai = blo(pr.v[i][1]) * dt;
        sts128(sb + P_PRM + (w * 64 + i * 32 + lane) * 16, __float_as_uint(ar * 1.4426950408889634f), __float_as_uint(ai * 0.15915494309189535f),
               __float_as_uint(2.f * (blo(pr.v[i][2]) * dt)), __float_as_uint(2.f * (blo(pr.v[i][3]) * dt)));
    }
    if (tid < 64) sts128(sb + P_U + (tid >> 3) * 2176 + (tid & 7) * 16, 0, 0, 0, 0);
    bar_arrive(6, 384);
    __syncwarp();
    PROF(tid == 0, 3510);
    const int ch = w & 3, hf = w >> 2;
    {
        float k0[4] = {0, 0, 0, 0}, k1[4] = {0, 0, 0, 0}, k2[4] = {0, 0, 0, 0}, k3[4] = {0, 0, 0, 0}, k4[4] = {0, 0, 0, 0}, kl = 0;
#pragma unroll KGU
        for (int j = 0; j < 16; j++) {
            const uint4 q = lds128(sb + P_PRM + (w * 64 + j * 4 + c) * 16);
            const float cr = __uint_as_float(q.z), ci = __uint_as_float(q.w);
            float wr[4], wi[4], vr[4], vi[4];
            cpow(__uint_as_float(q.x), __uint_as_float(q.y), (float)g, wr[0], wi[0]);
            cpow(__uint_as_float(q.x), __uint_as_float(q.y), (float)(g + 8), vr[0], vi[0]);
#pragma unroll
            for (int i = 1; i < 4; i++) { wr[i] = wr[i - 1]; wi[i] = wi[i - 1]; csq(wr[i], wi[i]); vr[i] = vr[i - 1]; vi[i] = vi[i - 1]; csq(vr[i], vi[i]); }
            float hr = wr[3], hi = wi[3];
            csq(hr, hi);
            mma_tf32(k0, wr[0], vr[0], wi[0], vi[0], cr * hr - ci * hi, -(cr * hi + ci * hr));
            hr = vr[3]; hi = vi[3]; csq(hr, hi);
            mma_tf32(k1, wr[0], vr[0], wi[0], vi[0], cr * hr - ci * hi, -(cr * hi + ci * hr));
            csq(hr, hi);
            mma_tf32(k2, wr[1], vr[1], wi[1], vi[1], cr * hr - ci * hi, -(cr * hi + ci * hr));
            csq(hr, hi);
            mma_tf32(k3, wr[2], vr[2], wi[2], vi[2], cr * hr - ci * hi, -(cr * hi + ci * hr));
            csq(hr, hi);
            mma_tf32(k4, wr[3], vr[3], wi[3], vi[3], cr * hr - ci * hi, -(cr * hi + ci * hr));
            csq(hr, hi);
            kl += cr * hr - ci * hi;
        }
        kl += __shfl_xor_sync(0xffffffffu, kl, 1); kl += __shfl_xor_sync(0xffffffffu, kl, 2);
        const uint32_t o = sb + P_K6 + (ch * 656 + c * 32 + g) * 4, ol = sb + P_K6 + (ch * 656 + 640) * 4;
#define KST(k, base) sts32(o + (base) * 4, __float_as_uint(k[0])); sts32(o + (base) * 4 + 64, __float_as_uint(k[1])); \
                     sts32(o + (base) * 4 + 32, __float_as_uint(k[2])); sts32(o + (base) * 4 + 96, __float_as_uint(k[3]))
#define KAD(k, base) k[0] += __uint_as_float(lds32(o + (base) * 4)); k[1] += __uint_as_float(lds32(o + (base) * 4 + 64)); \
                     k[2] += __uint_as_float(lds32(o + (base) * 4 + 32)); k[3] += __uint_as_float(lds32(o + (base) * 4 + 96))
        if (hf == 0) {
            bar_sync(2 + ch, 64);
            KAD(k0, 0); KAD(k1, 128); KAD(k2, 256); KAD(k3, 384); KAD(k4, 512);
            kl += __uint_as_float(lds32(ol));
            __syncwarp();
        }
        KST(k0, 0); KST(k1, 128); KST(k2, 256); KST(k3, 384); KST(k4, 512);
        if (lane == 0) sts32(ol, __float_as_uint(kl));
        if (hf == 1) { __syncwarp(); bar_arrive(2 + ch, 64); }
    }
    PROF(tid == 0, 3511);
    {
        uint4 l0, l1;
        int n = 0;
        while (true) {
            l0 = ld_rlx128((const uint4*)g_ln0 + tid * 2); l1 = ld_rlx128((const uint4*)g_ln0 + tid * 2 + 1);
            if (__all_sync(0xffffffffu, l0.x && l0.y && l0.z && l0.w && l1.x && l1.y && l1.z && l1.w)) break;
            if (++n > 2000000) __trap();
        }
        sts128(sb + P_P + tid * 32, l0.x, l0.y, l0.z, l0.w); sts128(sb + P_P + tid * 32 + 16, l1.x, l1.y, l1.z, l1.w);
        bar_sync(8, 384);
        mbar_wait(sb + S_XBAR, 0);
        __syncwarp();
#pragma unroll 2
        for (int i = 0; i < 8; i++) {
            const int t = w * 256 + i * 32 + lane;
            const uint32_t ln = lds32(sb + P_P + t * 4);
            const uint2 x = lds64(sb + P_X + t * 16 + (b & 1) * 8);
            const float m = blo(ln), rs = rcp(bhi(ln));
            const uint32_t u0 = pack2(rbf(blo(x.x) - m) * rs, rbf(bhi(x.x) - m) * rs), u1 = pack2(rbf(blo(x.y) - m) * rs, rbf(bhi(x.y) - m) * rs);
            sts128(sb + P_X + t * 16, x.x, x.y, u0, u1);
            const uint32_t o = sb + P_U + ((t >> 3) & 1) * 2176 + ((t >> 4) + 8) * 16 + (t & 7) * 2;
            asm volatile("st.shared.u16 [%0],%1;" ::"r"(o), "h"((uint16_t)u0) : "memory");
            asm volatile("st.shared.u16 [%0],%1;" ::"r"(o + 4352), "h"((uint16_t)(u0 >> 16)) : "memory");
            asm volatile("st.shared.u16 [%0],%1;" ::"r"(o + 8704), "h"((uint16_t)u1) : "memory");
            asm volatile("st.shared.u16 [%0],%1;" ::"r"(o + 13056), "h"((uint16_t)(u1 >> 16)) : "memory");
        }
    }
    bar_sync(1, 256);
    PROF(tid == 0, 3512);
    if (tid < 64) sts32(sb + P_P + ((tid >> 4) * 2080 + (tid & 15)) * 4, 0);
#pragma unroll 1
    for (int x = tid; x < 2048; x += 512) {
        uint32_t pw[2][4];
#pragma unroll
        for (int h = 0; h < 2; h++) {
            const int y = x + h * 256;
            const int i0 = y <= 256 ? y : 256 + (int)((pack2((float)y, 0.f) & 0xffff) - 0x4380);
            const int i1 = y <= 256 ? max(y - 1, 0) : 256 + (int)((pack2((float)(y - 1), 0.f) & 0xffff) - 0x4380);
#pragma unroll
            for (int k = 0; k < 4; k++) {
                const float lo = __uint_as_float(lds32(sb + P_K6 + k * 2624 + i0 * 4)), hi = __uint_as_float(lds32(sb + P_K6 + k * 2624 + i1 * 4));
                pw[h][k] = pack2(lo, y ? hi : 0.f);
            }
        }
#pragma unroll
        for (int h = 0; h < 2; h++)
#pragma unroll
            for (int k = 0; k < 4; k++) sts32(sb + P_P + (k * 2080 + x + h * 256 + 16) * 4, pw[h][k]);
    }
    fence_async_smem();
    bar_arrive(9, 384);
    bar_sync(1, 256);
    if (tid < 4) {
        asm volatile("cp.async.bulk.global.shared::cta.bulk_group [%0],[%1],%2;" ::"l"(g_P + (d0 + tid) * PROW), "r"(sb + P_P + tid * 8320), "r"(PROW * 4) : "memory");
        asm volatile("cp.async.bulk.commit_group;" ::: "memory");
    }
    __syncwarp();
    PROF(tid == 0, 3513);
    {
        float acc[16][4];
#pragma unroll
        for (int j = 0; j < 16; j++) acc[j][0] = acc[j][1] = acc[j][2] = acc[j][3] = 0;
#pragma unroll 1
        for (int e = hf * 4; e < hf * 4 + 4; e++) {
            uint32_t B[16][2];
            const uint32_t ua = sb + P_U + ch * 4352 + ((lane >> 3) & 1) * 2176 + (8 + (lane >> 4) * 8 + (lane & 7) - e) * 16;
#pragma unroll
            for (int j = 0; j < 8; j++) { const uint4 v = ldsm4(ua + j * 256); B[2 * j][0] = v.x; B[2 * j][1] = v.y; B[2 * j + 1][0] = v.z; B[2 * j + 1][1] = v.w; }
            const uint32_t pa = sb + P_P + (ch * 2080 + 16 + e * 16 + g - 2 * c) * 4;
#pragma unroll
            for (int d = 0; d < 16; d++) {
                const uint32_t a0 = lds32(pa + d * 512), a1 = lds32(pa + d * 512 + 32), a2 = lds32(pa + d * 512 - 32);
#pragma unroll
                for (int j = d; j < 16; j++) mma16(acc[j], a0, a1, a2, a0, B[j - d][0], B[j - d][1]);
            }
        }
        PROF(tid == 0, 3514);
        const uint32_t o = sb + P_Y + (ch * 2560 + c * 40 + g) * 4;
        if (tid < 4) asm volatile("cp.async.bulk.wait_group 0;" ::: "memory");
        __syncwarp();
        bar_sync(10, 384);
        if (hf == 0) {
            bar_sync(2 + ch, 64);
#pragma unroll
            for (int j = 0; j < 16; j++) {
                acc[j][0] += __uint_as_float(lds32(o + j * 640)); acc[j][1] += __uint_as_float(lds32(o + j * 640 + 80));
                acc[j][2] += __uint_as_float(lds32(o + j * 640 + 32)); acc[j][3] += __uint_as_float(lds32(o + j * 640 + 112));
            }
        }
#pragma unroll
        for (int j = 0; j < 16; j++) {
            sts32(o + j * 640, __float_as_uint(acc[j][0])); sts32(o + j * 640 + 80, __float_as_uint(acc[j][1]));
            sts32(o + j * 640 + 32, __float_as_uint(acc[j][2])); sts32(o + j * 640 + 112, __float_as_uint(acc[j][3]));
        }
        if (hf == 1) bar_arrive(2 + ch, 64);
    }
    const uint2 dk = __ldg((const uint2*)(a.Dk + d0));
    bar_sync(1, 256);
#pragma unroll 2
    for (int i = 0; i < 8; i++) {
        const int t = i * 256 + tid;
        const uint32_t o = sb + P_Y + (t + 4 * (t >> 4)) * 4;
        const uint4 xu = lds128(sb + P_X + t * 16);
        float y[4];
#pragma unroll
        for (int k = 0; k < 4; k++) y[k] = rbf(__uint_as_float(lds32(o + k * 10240)));
        uint2 r;
        r.x = pack2(blo(xu.x) + rbf(y[0] + rbf(blo(xu.z) * blo(dk.x))), bhi(xu.x) + rbf(y[1] + rbf(bhi(xu.z) * bhi(dk.x))));
        r.y = pack2(blo(xu.y) + rbf(y[2] + rbf(blo(xu.w) * blo(dk.y))), bhi(xu.y) + rbf(y[3] + rbf(bhi(xu.w) * bhi(dk.y))));
        ((uint2*)g_x)[b * 2048 + t] = r;
    }
    PROF(tid == 0, 3515);
}

__device__ __forceinline__ int pick_role(int cl, uint32_t rank, int rec0) {
    const int lane = threadIdx.x & 31;
    unsigned ep;
    asm volatile("ld.relaxed.gpu.global.u32 %0,[%1];" : "=r"(ep) : "l"(g_gate) : "memory");
    ep = (ep / (4 * NCL) + 1) * 2;
    if (rank == 0) {
        unsigned* r = (unsigned*)(((size_t)g_probe + 8191) & ~(size_t)8191) + cl * 8;
        uint32_t b0 = ~0u, b1 = ~0u;
#pragma unroll 1
        for (int i = 0; i < 6; i++) { b0 = min(b0, probe1(r, lane)); b1 = min(b1, probe1(r + 1024, lane)); }
        if (lane == 0) asm volatile("st.relaxed.gpu.global.u32 [%0],%1;" ::"l"(g_side + cl), "r"(ep + (b1 < b0)) : "memory");
    }
    uint32_t m[3];
#pragma unroll
    for (int i = 0; i < 3; i++) {
        unsigned v; int n = 0;
        const bool on = i * 32 + lane < NCL;
        while (true) {
            asm volatile("ld.relaxed.gpu.global.u32 %0,[%1];" : "=r"(v) : "l"(g_side + i * 32 + lane) : "memory");
            if (__all_sync(0xffffffffu, !on || (v & ~1u) == ep)) break;
            if (++n > 2000000) __trap();
        }
        m[i] = __ballot_sync(0xffffffffu, on && (v & 1));
    }
    if (__popc(m[0]) + __popc(m[1]) + __popc(m[2]) < NCL / 2) { m[0] = ~m[0]; m[1] = ~m[1]; m[2] = ~m[2] & 3; }
    const int tot = __popc(m[0]) + __popc(m[1]) + __popc(m[2]);
    int below = 0;
#pragma unroll
    for (int i = 0; i < 3; i++) below += __popc(m[i] & (cl >= i * 32 + 32 ? ~0u : cl <= i * 32 ? 0u : (1u << (cl - i * 32)) - 1));
    const bool mine = ((cl < 32 ? m[0] : cl < 64 ? m[1] : m[2]) >> (cl & 31)) & 1;
    const int skip = tot - 32;
    if (mine && below >= skip) return rec0 + below - skip;
    const int j = cl - max(below - skip, 0);
    return j < rec0 ? j : j + 32;
}

__global__ void __cluster_dims__(2, 1, 1) __launch_bounds__(384, 1) main_kernel(const __grid_constant__ Params p) {
    extern __shared__ __align__(1024) uint8_t smem[];
    const uint32_t sb = smem_u32(smem);
    uint32_t rank; asm("mov.u32 %0,%%cluster_ctarank;" : "=r"(rank));
    const int wi = __shfl_sync(0xffffffffu, threadIdx.x >> 5, 0);
    const int cl = blockIdx.x >> 1, wg = wi >> 2;
    PROF(threadIdx.x == 0, 3500);
    ProRegs pr;
    prologue_load(p.pa, max((int)blockIdx.x - 4, 0), pr);
    if (wi == 11 && p.dopro && cl >= 2 && elect()) {
        mbar_init(sb + S_XBAR, 1);
        asm volatile("fence.mbarrier_init.release.cluster;" ::: "memory");
        mbar_expect(sb + S_XBAR, 32768);
        for (int j = 0; j < 8; j++) tma2d(sb + P_X + j * 4096, &p.tm[3], ((blockIdx.x - 4) >> 1) * 8, j * 256, sb + S_XBAR);
    }
    if (threadIdx.x == 320) {
        unsigned v = 0;
        if (p.dopro) {
            asm volatile("ld.relaxed.gpu.global.u32 %0,[%1];" : "=r"(v) : "l"(g_gate) : "memory");
            v = (v / (4 * NCL) + 1) * (4 * NCL);
        }
        sts32(sb + S_GATE, v);
    }
    __syncwarp();
    if (wg == 2) bar_arrive(8, 384);
    if (wi == 10) {
        const int v = blockIdx.x;
        sts32(sb + S_VCL, v);
        if (v < V_REC || v == 131) conv_init(sb, v == 131); else if (v < V_OP) rec_init(sb); else gemm_init(sb, v < V_QKV);
        __syncwarp();
        asm volatile("barrier.cluster.arrive.aligned;" ::: "memory");
    } else asm volatile("barrier.cluster.arrive.relaxed.aligned;" ::: "memory");
    if (p.dopro && cl >= 2) prologue(p, sb, blockIdx.x - 4, wi, pr); else if (wg < 2) bar_sync(8, 384); else if (wi == 10) early_fetch(p, sb);
    asm volatile("barrier.cluster.wait.aligned;" ::: "memory");
    const int v = __shfl_sync(0xffffffffu, lds32(sb + S_VCL), 0);
    const int role = (v < V_REC ? 1 : v < V_OP ? 2 : v < V_QKV ? 4 : v < V_QKV + NQ ? 24 : 1) & p.roles;
    fence_async_smem();
    bar_sync(wg == 2 ? 7 : 1, wg == 2 ? 128 : 256);
    if (p.dopro && (threadIdx.x == 32 || threadIdx.x == 352)) red_release(g_gate, 1);
    PROF(threadIdx.x == 32, 3509);
    if (wi == 0 && (role & 8) && elect()) qkv_stage(p, sb + 131072, sb + G_BAR + GB_RS * 8, v - V_QKV, 0, 6);
    PROF(threadIdx.x == 0, 3506);
    __syncwarp();
    if (role == 2) {
        const int head = (v - V_REC) >> 1;
        if (wi == 0 && elect()) rec_fetch(p, sb, head, rank, 1, R_STK);
        __syncwarp();
        if (p.dopro && wi < 9) {
            if (wi < 8) { if (wi == 2) wait_flag_warp(g_gate, lds32(sb + S_GATE)); PROF(threadIdx.x == 64, 3507); bar_sync(3, 256); }
            x1_norm(wi < 8 ? (const uint2*)g_x : (const uint2*)p.pa.x, (v - V_REC) * 8 + (wi & 7), wi < 8);
            if (wi == 7) { bar_sync(2, 256); if (elect()) red_release(cnt_ptr(C_XN + head), 4); __syncwarp(); } else if (wi < 7) bar_arrive(2, 256);
            PROF(threadIdx.x == 224, 3508);
            PROF(threadIdx.x == 256, 3499);
        }
        if (wg == 2) {
            reg_dec<RH>();
            const int w = wi & 3;
            wait_cnt_warp(g_gate, lds32(sb + S_GATE));
            wait_cnt_warp(cnt_ptr(C_XN + head), 8);
            rec_probe(sb, head * 2 + rank, w);
            rec_sides(sb, head * 2 + rank, w);
            __syncthreads();
            cluster_sync();
            if ((p.chains >> (w & 1)) & 1) { if (w < 2) rec_comm(p, sb, w, head, rank); else rec_attn(p, sb, w & 1, head, rank); }
        } else {
            reg_inc<RW0>();
            rec_weights(p, sb, head, rank, wi);
        }
    } else if (role == 1) {
        if (v == 131) conv_far(sb, wi); else if (wg == 2) { reg_dec<RCB>(); conv_back(sb, v, wi & 3); } else { reg_inc<RCU>(); conv_tile(p, sb, v, wi); }
    } else if (role == 4) {
        if (wg == 2) {
            reg_dec<40>();
            if (wi == 8) gemm_producer<true>(p, sb, v - V_OP); else if (wi == 9) gemm_release<true>(p, sb, v - V_OP);
        } else { reg_inc<232>(); gemm_consumer<true>(p, sb, v - V_OP, wi); }
    } else if (role) {
        if (wg == 2) {
            reg_dec<40>();
            if (wi < 10) {
                if (role & 8) { if (wi == 8) gemm_producer<false>(p, sb, v - V_QKV); else gemm_release<false>(p, sb, v - V_QKV); }
            } else if (v < V_QKV + 32 && (role & 16)) fin_warp(p, sb, (v - V_QKV) * 2 + wi - 10);
        } else { reg_inc<232>(); if (role & 8) gemm_consumer<false>(p, sb, v - V_QKV, wi); }
    }
    __syncwarp();
    cluster_sync();
}

typedef CUresult (*EncFn)(CUtensorMap*, CUtensorMapDataType, cuuint32_t, void*, const cuuint64_t*, const cuuint64_t*, const cuuint32_t*, const cuuint32_t*,
                          CUtensorMapInterleave, CUtensorMapSwizzle, CUtensorMapL2promotion, CUtensorMapFloatOOBfill);
constexpr int SMEM_BYTES = 232448;
#define LAG 8
#define QLEAD 6
#define OLEAD (LAG / 2 + 2)
void plan(Params& P) {
    P.roles = 31; P.chains = 3; P.lag = LAG; P.dopro = 1;
    for (int r = 0; r < 2; r++) {
        const int lead = r ? OLEAD : QLEAD;
        int n = 0;
        for (int i = 0; i < 32 + lead; i++) {
            if (i >= lead) P.list[r][n++] = 32 + i - lead;
            if (i < 32) P.list[r][n++] = i;
        }
        P.nl[r] = n;
    }
}

#define TK() do {} while (0)
}

extern "C" void kernel_launch(void* const* d_in, const int* in_sizes, int n_in, void* d_out, int out_size) {
    typedef const __nv_bfloat16* BP;
    static EncFn enc = nullptr;
    if (!enc) {
        void* fn = nullptr; cudaDriverEntryPointQueryResult qr;
        cudaGetDriverEntryPoint("cuTensorMapEncodeTiled", &fn, cudaEnableDefault, &qr);
        enc = (EncFn)fn;
        cudaFuncSetAttribute(main_kernel, cudaFuncAttributeMaxDynamicSharedMemorySize, SMEM_BYTES);
    }
    static Params P;
    for (int i = 0; i < 4; i++) {
        const cuuint64_t cols = i < 3 ? 4096 : 512, rows = i < 3 ? 512 : 4096;
        cuuint64_t d2[2] = {cols, rows}, str[1] = {cols * 2};
        cuuint32_t box[2] = {64, 64}, bn[2] = {16, 256}, es[2] = {1, 1};
        enc(&P.tm[i < 3 ? i : 4], CU_TENSOR_MAP_DATA_TYPE_BFLOAT16, 2, d_in[9 + i], d2, str, box, es, CU_TENSOR_MAP_INTERLEAVE_NONE, CU_TENSOR_MAP_SWIZZLE_128B,
            CU_TENSOR_MAP_L2_PROMOTION_L2_128B, CU_TENSOR_MAP_FLOAT_OOB_FILL_NONE);
        if (i < 2) enc(&P.tn[i], CU_TENSOR_MAP_DATA_TYPE_BFLOAT16, 2, d_in[9 + i], d2, str, bn, es, CU_TENSOR_MAP_INTERLEAVE_NONE, CU_TENSOR_MAP_SWIZZLE_32B,
                       CU_TENSOR_MAP_L2_PROMOTION_L2_128B, CU_TENSOR_MAP_FLOAT_OOB_FILL_NONE);
    }
    {
        cuuint64_t dims[2] = {512, 2048}, str[1] = {1024};
        cuuint32_t box[2] = {8, 256}, es[2] = {1, 1};
        enc(&P.tm[3], CU_TENSOR_MAP_DATA_TYPE_BFLOAT16, 2, d_in[0], dims, str, box, es, CU_TENSOR_MAP_INTERLEAVE_NONE, CU_TENSOR_MAP_SWIZZLE_NONE,
            CU_TENSOR_MAP_L2_PROMOTION_NONE, CU_TENSOR_MAP_FLOAT_OOB_FILL_NONE);
    }
    P.mem0 = (BP)d_in[8]; P.Wo = (BP)d_in[12]; P.Dskip = (BP)d_in[6]; P.out = (__nv_bfloat16*)d_out;
    cudaStream_t s = cudaStreamPerThread;
    P.pa = {(BP)d_in[0], (BP)d_in[1], (BP)d_in[2], (BP)d_in[3], (BP)d_in[4], (BP)d_in[5], (BP)d_in[6], {(BP)d_in[9], (BP)d_in[10], (BP)d_in[11], (BP)d_in[12]}};
    plan(P);
    TK(); main_kernel<<<2 * NCL, 384, SMEM_BYTES, s>>>(P); TK();
}
```

```cpp
#include <cuda_runtime.h>
#include <cuda_bf16.h>
#include <cuda.h>
#include <stdint.h>
#include <string.h>
#include <math.h>

namespace {

constexpr int NCL = 66;
constexpr int NQ = 43;
constexpr int V_REC = 8, V_OP = 72, V_QKV = 88;

#define XP 1024
__device__ uint4 g_x[2 * 128 * XP];
__device__ uint4 g_xn[64 * 4096];
__device__ uint4 g_st[64 * 256];
__device__ uint4 g_qkv[128 * 32 * 1536];
__device__ uint4 g_o[64 * 64 * 512];
__device__ uint4 g_pp[64 * 4 * 4096];
__device__ uint4 g_xch[133 * 512];
__device__ unsigned g_sel[64];
__device__ unsigned g_gate[32];
__device__ __align__(16) uint32_t g_P[512 * 272];
__device__ uint4 g_W[512 * 784];
__device__ __align__(16) uint32_t g_u[512 * 1152];
__device__ uint2 g_carry[512 * 40 * 32];
__device__ uint2 g_far[512 * 8 * 32];
__device__ unsigned g_cnt[900 * 8];
__device__ uint32_t g_ln0[2048];

enum { C_XN = 0  , C_QKV = 64  , C_O = 128  , C_PP = 384  , C_FAR = 896 };
__device__ __forceinline__ unsigned* cnt_ptr(int i) { return g_cnt + i * 8; }

struct ProArgs { const __nv_bfloat16 *x, *lAr, *Ai, *Cr, *Ci, *ldt, *Dk, *W[4]; };
struct Params {
    CUtensorMap tm[5];
    CUtensorMap tn[2];
    ProArgs pa;
    int dopro;
    const __nv_bfloat16* mem0;
    const __nv_bfloat16* Wo;
    const __nv_bfloat16* Dskip;
    __nv_bfloat16* out;
    int roles;
    int chains;
    int lag;
    int zero;
    int nl[2];
    uint8_t list[2][64];
};

__device__ __forceinline__ uint32_t smem_u32(const void* p) { return (uint32_t)__cvta_generic_to_shared(p); }
__device__ __forceinline__ uint32_t mapa(uint32_t a, uint32_t r) {
    uint32_t o; asm("mapa.shared::cluster.u32 %0,%1,%2;" : "=r"(o) : "r"(a), "r"(r)); return o;
}
__device__ __forceinline__ void mbar_init(uint32_t b, int c) { asm volatile("mbarrier.init.shared::cta.b64 [%0],%1;" ::"r"(b), "r"(c) : "memory"); }
__device__ __forceinline__ void mbar_expect(uint32_t b, int bytes) { asm volatile("mbarrier.arrive.expect_tx.shared::cta.b64 _,[%0],%1;" ::"r"(b), "r"(bytes) : "memory"); }
__device__ __forceinline__ void mbar_arrive(uint32_t b) { asm volatile("mbarrier.arrive.shared::cta.b64 _,[%0];" ::"r"(b) : "memory"); }
__device__ __forceinline__ void mbar_arrive_cluster(uint32_t b) { asm volatile("mbarrier.arrive.shared::cluster.b64 _,[%0];" ::"r"(b) : "memory"); }
__device__ __forceinline__ void mbar_wait(uint32_t b, uint32_t ph) {
    asm volatile(
        "{.reg .pred p; .reg .u32 n; mov.u32 n,0;\n"
        "W%=: mbarrier.try_wait.parity.shared::cta.b64 p,[%0],%1;\n"
        "@p bra D%=;\n"
        "add.u32 n,n,1; setp.lt.u32 p,n,2000000; @p bra W%=;\n"
        "trap;\n"
        "D%=: }" ::"r"(b), "r"(ph) : "memory");
}
__device__ __forceinline__ bool wait_lds128(uint32_t b, uint32_t ph, uint32_t a, uint4& v) {
    uint32_t ok;
    asm volatile("{.reg .pred p; mbarrier.try_wait.parity.shared::cta.b64 p,[%5],%6,20000; ld.shared.v4.u32 {%0,%1,%2,%3},[%7]; selp.u32 %4,1,0,p;}"
                 : "=r"(v.x), "=r"(v.y), "=r"(v.z), "=r"(v.w), "=r"(ok) : "r"(b), "r"(ph), "r"(a) : "memory");
    return ok;
}
__device__ __forceinline__ bool wait_lds64(uint32_t b, uint32_t ph, uint32_t a, uint2& v) {
    uint32_t ok;
    asm volatile("{.reg .pred p; mbarrier.try_wait.parity.shared::cta.b64 p,[%3],%4,20000; ld.shared.v2.u32 {%0,%1},[%5]; selp.u32 %2,1,0,p;}"
                 : "=r"(v.x), "=r"(v.y), "=r"(ok) : "r"(b), "r"(ph), "r"(a) : "memory");
    return ok;
}
template <int PH> __device__ __forceinline__ void mbar_wait_c(uint32_t b) {
    asm volatile(
        "{.reg .pred p; .reg .u32 n; mov.u32 n,%2;\n"
        "W%=: mbarrier.try_wait.parity.shared::cta.b64 p,[%0],%1;\n"
        "@p bra D%=;\n"
        "add.u32 n,n,1; setp.lt.u32 p,n,2000000; @p bra W%=;\n"
        "trap;\n"
        "D%=: }" ::"r"(b), "n"(PH), "n"(PH) : "memory");
}
__device__ __forceinline__ bool elect() {
    uint32_t r; asm volatile("{.reg .pred p; elect.sync _|p,0xffffffff; selp.u32 %0,1,0,p;}" : "=r"(r)); return r;
}
__device__ __forceinline__ void bar_sync(int id, int n) { asm volatile("bar.sync %0,%1;" ::"r"(id), "r"(n) : "memory"); }
__device__ __forceinline__ void bar_arrive(int id, int n) { asm volatile("bar.arrive %0,%1;" ::"r"(id), "r"(n) : "memory"); }
__device__ __forceinline__ void cluster_sync() { asm volatile("barrier.cluster.arrive.relaxed.aligned; barrier.cluster.wait.aligned;" ::: "memory"); }
__device__ __forceinline__ void fence_async() { asm volatile("fence.proxy.async;" ::: "memory"); }
__device__ __forceinline__ void fence_async_smem() { asm volatile("fence.proxy.async.shared::cta;" ::: "memory"); }
#define EFR 1
#define EFW 2
constexpr uint64_t POL_N = 0x1000000000000000ull, POL_F = 0x12F0000000000000ull;
constexpr uint64_t POL_LAST = EFR ? POL_F : POL_N  , POL_LATE = EFW ? POL_F : POL_N  , POL_SOON = EFW > 1 ? POL_F : POL_N;
__device__ __forceinline__ void bulk_g2s(uint32_t dst, const void* src, int bytes, uint32_t bar, uint64_t pol) {
    asm volatile("cp.async.bulk.shared::cluster.global.mbarrier::complete_tx::bytes.L2::cache_hint [%0],[%1],%2,[%3],%4;" ::"r"(dst), "l"(src), "r"(bytes), "r"(bar), "l"(pol) : "memory");
}
__device__ __forceinline__ void bulk_g2s_mc(uint32_t dst, const void* src, int bytes, uint32_t bar, uint64_t pol) {
    asm volatile("cp.async.bulk.shared::cluster.global.mbarrier::complete_tx::bytes.multicast::cluster.L2::cache_hint [%0],[%1],%2,[%3],%4,%5;" ::"r"(dst), "l"(src), "r"(bytes), "r"(bar), "h"((uint16_t)3), "l"(pol) : "memory");
}
__device__ __forceinline__ void stg128(uint4* p, uint4 v, uint64_t pol) {
    asm volatile("st.global.L2::cache_hint.v4.u32 [%0],{%1,%2,%3,%4},%5;" ::"l"(p), "r"(v.x), "r"(v.y), "r"(v.z), "r"(v.w), "l"(pol));
}
__device__ __forceinline__ void stg32(uint32_t* p, uint32_t v, uint64_t pol) { asm volatile("st.global.L2::cache_hint.u32 [%0],%1,%2;" ::"l"(p), "r"(v), "l"(pol)); }
__device__ __forceinline__ uint4 ldcg128_last(const uint4* p) {
    uint4 v; asm volatile("ld.global.cg.L2::cache_hint.v4.u32 {%0,%1,%2,%3},[%4],%5;" : "=r"(v.x), "=r"(v.y), "=r"(v.z), "=r"(v.w) : "l"(p), "l"(POL_LAST) : "memory"); return v;
}
__device__ __forceinline__ void tma2d(uint32_t dst, const CUtensorMap* tm, int x, int y, uint32_t bar) {
    asm volatile("cp.async.bulk.tensor.2d.shared::cluster.global.mbarrier::complete_tx::bytes [%0],[%1,{%2,%3}],[%4];" ::"r"(dst), "l"(tm), "r"(x), "r"(y), "r"(bar) : "memory");
}
__device__ __forceinline__ void tma3d(uint32_t dst, const CUtensorMap* tm, int y, int z, uint32_t bar) {
    asm volatile("cp.async.bulk.tensor.3d.shared::cluster.global.mbarrier::complete_tx::bytes [%0],[%1,{0,%2,%3}],[%4];" ::"r"(dst), "l"(tm), "r"(y), "r"(z), "r"(bar) : "memory");
}
__device__ __forceinline__ void st_async4(uint32_t a, uint32_t x, uint32_t y, uint32_t z, uint32_t w, uint32_t mb) {
    asm volatile("st.async.shared::cluster.mbarrier::complete_tx::bytes.v4.b32 [%0],{%1,%2,%3,%4},[%5];" ::"r"(a), "r"(x), "r"(y), "r"(z), "r"(w), "r"(mb) : "memory");
}
__device__ __forceinline__ void st_async2(uint32_t a, uint32_t x, uint32_t y, uint32_t mb) {
    asm volatile("st.async.shared::cluster.mbarrier::complete_tx::bytes.v2.b32 [%0],{%1,%2},[%3];" ::"r"(a), "r"(x), "r"(y), "r"(mb) : "memory");
}
#define LDSQ "ld.shared"
__device__ __forceinline__ uint4 lds128(uint32_t a) { uint4 v; asm volatile(LDSQ ".v4.u32 {%0,%1,%2,%3},[%4];" : "=r"(v.x), "=r"(v.y), "=r"(v.z), "=r"(v.w) : "r"(a) : "memory"); return v; }
__device__ __forceinline__ uint4 lds128v(uint32_t a) { uint4 v; asm volatile("ld.volatile.shared.v4.u32 {%0,%1,%2,%3},[%4];" : "=r"(v.x), "=r"(v.y), "=r"(v.z), "=r"(v.w) : "r"(a) : "memory"); return v; }
__device__ __forceinline__ uint2 lds64(uint32_t a) { uint2 v; asm volatile(LDSQ ".v2.u32 {%0,%1},[%2];" : "=r"(v.x), "=r"(v.y) : "r"(a) : "memory"); return v; }
__device__ __forceinline__ uint32_t lds32(uint32_t a) { uint32_t v; asm volatile(LDSQ ".u32 %0,[%1];" : "=r"(v) : "r"(a) : "memory"); return v; }
__device__ __forceinline__ void sts128(uint32_t a, uint32_t x, uint32_t y, uint32_t z, uint32_t w) { asm volatile("st.shared.v4.u32 [%0],{%1,%2,%3,%4};" ::"r"(a), "r"(x), "r"(y), "r"(z), "r"(w) : "memory"); }
__device__ __forceinline__ void sts64(uint32_t a, uint32_t x, uint32_t y) { asm volatile("st.shared.v2.u32 [%0],{%1,%2};" ::"r"(a), "r"(x), "r"(y) : "memory"); }
__device__ __forceinline__ void sts32(uint32_t a, uint32_t x) { asm volatile("st.shared.u32 [%0],%1;" ::"r"(a), "r"(x) : "memory"); }
__device__ __forceinline__ uint4 ldsm4(uint32_t a) { uint4 v; asm volatile("ldmatrix.sync.aligned.m8n8.x4.shared.b16 {%0,%1,%2,%3},[%4];" : "=r"(v.x), "=r"(v.y), "=r"(v.z), "=r"(v.w) : "r"(a) : "memory"); return v; }
__device__ __forceinline__ uint4 ldsm4t(uint32_t a) { uint4 v; asm volatile("ldmatrix.sync.aligned.m8n8.x4.trans.shared.b16 {%0,%1,%2,%3},[%4];" : "=r"(v.x), "=r"(v.y), "=r"(v.z), "=r"(v.w) : "r"(a) : "memory"); return v; }
__device__ __forceinline__ uint32_t movm(uint32_t a) { uint32_t d; asm volatile("movmatrix.sync.aligned.m8n8.trans.b16 %0,%1;" : "=r"(d) : "r"(a)); return d; }
__device__ __forceinline__ uint32_t pack2(float lo, float hi) { uint32_t d; asm("cvt.rn.bf16x2.f32 %0,%1,%2;" : "=r"(d) : "f"(hi), "f"(lo)); return d; }
__device__ __forceinline__ uint32_t hadd2(uint32_t a, uint32_t b) { uint32_t d; asm("add.rn.bf16x2 %0,%1,%2;" : "=r"(d) : "r"(a), "r"(b)); return d; }
__device__ __forceinline__ uint32_t hmul2(uint32_t a, uint32_t b) { uint32_t d; asm("mul.rn.bf16x2 %0,%1,%2;" : "=r"(d) : "r"(a), "r"(b)); return d; }
__device__ __forceinline__ float blo(uint32_t v) { return __uint_as_float(v << 16); }
__device__ __forceinline__ float bhi(uint32_t v) { return __uint_as_float(v & 0xffff0000u); }
__device__ __forceinline__ float rbf(float x) { return __uint_as_float(pack2(0.f, x)); }
__device__ __forceinline__ float ex2(float x) { float y; asm("ex2.approx.ftz.f32 %0,%1;" : "=f"(y) : "f"(x)); return y; }
__device__ __forceinline__ float rcp(float x) { float y; asm("rcp.approx.ftz.f32 %0,%1;" : "=f"(y) : "f"(x)); return y; }
__device__ __forceinline__ void mma16(float* c, uint32_t a0, uint32_t a1, uint32_t a2, uint32_t a3, uint32_t b0, uint32_t b1) {
    asm volatile("mma.sync.aligned.m16n8k16.row.col.f32.bf16.bf16.f32 {%0,%1,%2,%3},{%4,%5,%6,%7},{%8,%9},{%0,%1,%2,%3};"
                 : "+f"(c[0]), "+f"(c[1]), "+f"(c[2]), "+f"(c[3]) : "r"(a0), "r"(a1), "r"(a2), "r"(a3), "r"(b0), "r"(b1));
}
__device__ __forceinline__ void mma16_top(float& d0, float& d1, uint32_t a0, uint32_t a2, uint32_t b0, uint32_t b1) {
    asm volatile("{.reg .b32 j; .reg .f32 e,f; mma.sync.aligned.m16n8k16.row.col.f32.bf16.bf16.f32 {%0,%1,e,f},{%2,j,%3,j},{%4,%5},{0f00000000,0f00000000,0f00000000,0f00000000};}"
                 : "=f"(d0), "=f"(d1) : "r"(a0), "r"(a2), "r"(b0), "r"(b1));
}
__device__ __forceinline__ void mma8(float* c, uint32_t a0, uint32_t a1, uint32_t b0) {
    asm volatile("mma.sync.aligned.m16n8k8.row.col.f32.bf16.bf16.f32 {%0,%1,%2,%3},{%4,%5},{%6},{%0,%1,%2,%3};"
                 : "+f"(c[0]), "+f"(c[1]), "+f"(c[2]), "+f"(c[3]) : "r"(a0), "r"(a1), "r"(b0));
}
__device__ __forceinline__ uint4 ld_rlx128(const uint4* p) {
    uint4 v;
    asm volatile("{.reg .b128 t; ld.relaxed.gpu.global.b128 t,[%4]; mov.b128 {%0,%1,%2,%3},t;}" : "=r"(v.x), "=r"(v.y), "=r"(v.z), "=r"(v.w) : "l"(p) : "memory");
    return v;
}
__device__ __forceinline__ void st_rlx128(uint4* p, uint32_t x, uint32_t y, uint32_t z, uint32_t w) {
    asm volatile("{.reg .b128 t; mov.b128 t,{%1,%2,%3,%4}; st.relaxed.gpu.global.b128 [%0],t;}" ::"l"(p), "r"(x), "r"(y), "r"(z), "r"(w) : "memory");
}
__device__ __forceinline__ uint4 ldcg128(const uint4* p) { uint4 v; asm volatile("ld.global.cg.v4.u32 {%0,%1,%2,%3},[%4];" : "=r"(v.x), "=r"(v.y), "=r"(v.z), "=r"(v.w) : "l"(p) : "memory"); return v; }
__device__ __forceinline__ void red_release(unsigned* p, unsigned v) {
    asm volatile("fence.proxy.async; red.relaxed.gpu.global.add.u32 [%0],%1;" ::"l"(p), "r"(v) : "memory");
}
__device__ __forceinline__ void wait_cnt(const unsigned* p, unsigned target) {
    asm volatile(
        "{.reg .pred p; .reg .u32 n,v; mov.u32 n,0;\n"
        "W%=: ld.acquire.gpu.global.u32 v,[%0]; setp.ge.u32 p,v,%1; @p bra D%=;\n"
        "nanosleep.u32 20; add.u32 n,n,1; setp.lt.u32 p,n,4000000; @p bra W%=;\n"
        "trap;\n"
        "D%=: }" ::"l"(p), "r"(target) : "memory");
}
__device__ __forceinline__ void wait_cnt_warp(const unsigned* p, unsigned target) {
    asm volatile(
        "{.reg .pred p; .reg .u32 n,v; mov.u32 n,0;\n"
        "W%=: ld.acquire.gpu.global.u32 v,[%0]; setp.ge.u32 p,v,%1; vote.sync.all.pred p,p,0xffffffff; @p bra.uni D%=;\n"
        "nanosleep.u32 20; add.u32 n,n,1; setp.lt.u32 p,n,4000000; @p bra.uni W%=;\n"
        "trap;\n"
        "D%=: }" ::"l"(p), "r"(target) : "memory");
}
__device__ __forceinline__ void wait_flag_warp(const unsigned* p, unsigned target) {
    asm volatile(
        "{.reg .pred p; .reg .u32 n,v; mov.u32 n,0;\n"
        "W%=: ld.relaxed.gpu.global.u32 v,[%0]; setp.ge.u32 p,v,%1; vote.sync.all.pred p,p,0xffffffff; @p bra.uni D%=;\n"
        "add.u32 n,n,1; setp.lt.u32 p,n,10000000; @p bra.uni W%=;\n"
        "trap;\n"
        "D%=: }" ::"l"(p), "r"(target) : "memory");
}
__device__ __forceinline__ uint64_t mkdesc(uint32_t addr, uint32_t lbo, uint32_t sbo, uint32_t sw) {
    return (uint64_t)((addr & 0x3FFFF) >> 4) | ((uint64_t)(lbo >> 4) << 16) | ((uint64_t)(sbo >> 4) << 32) | ((uint64_t)sw << 62);
}
__device__ __forceinline__ void wg_fence() { asm volatile("wgmma.fence.sync.aligned;" ::: "memory"); }
__device__ __forceinline__ void wg_commit() { asm volatile("wgmma.commit_group.sync.aligned;" ::: "memory"); }
template <int N> __device__ __forceinline__ void wg_wait() { asm volatile("wgmma.wait_group.sync.aligned %0;" ::"n"(N) : "memory"); }
#define R8(c, o) "+f"(c[o]), "+f"(c[o + 1]), "+f"(c[o + 2]), "+f"(c[o + 3]), "+f"(c[o + 4]), "+f"(c[o + 5]), "+f"(c[o + 6]), "+f"(c[o + 7])
#define R32(c, o) R8(c, o), R8(c, o + 8), R8(c, o + 16), R8(c, o + 24)
#define S32A "%0,%1,%2,%3,%4,%5,%6,%7,%8,%9,%10,%11,%12,%13,%14,%15,%16,%17,%18,%19,%20,%21,%22,%23,%24,%25,%26,%27,%28,%29,%30,%31"
template <int ACC> __device__ __forceinline__ void wgmma64_rs(float* c, const uint32_t* a, uint64_t db) {
    asm volatile("wgmma.mma_async.sync.aligned.m64n64k16.f32.bf16.bf16 {" S32A "},{%32,%33,%34,%35},%36,%37,1,1,0;"
                 : R32(c, 0) : "r"(a[0]), "r"(a[1]), "r"(a[2]), "r"(a[3]), "l"(db), "n"(ACC));
}
template <int ACC> __device__ __forceinline__ void wgmma64_ta(float* c, uint64_t da, uint64_t db) {
    asm volatile("wgmma.mma_async.sync.aligned.m64n64k16.f32.bf16.bf16 {" S32A "},%32,%33,%34,1,1,1,0;" : R32(c, 0) : "l"(da), "l"(db), "n"(ACC));
}
template <int ACC> __device__ __forceinline__ void wgmma80_tb(float* c, uint64_t da, uint64_t db) {
    asm volatile("wgmma.mma_async.sync.aligned.m64n80k16.f32.bf16.bf16 {" S32A ",%32,%33,%34,%35,%36,%37,%38,%39},%40,%41,%42,1,1,0,1;"
                 : R32(c, 0), R8(c, 32) : "l"(da), "l"(db), "n"(ACC));
}
template <int N> __device__ __forceinline__ void reg_inc() { asm volatile("setmaxnreg.inc.sync.aligned.u32 %0;" ::"n"(N)); }
template <int N> __device__ __forceinline__ void reg_dec() { asm volatile("setmaxnreg.dec.sync.aligned.u32 %0;" ::"n"(N)); }

#define PROF(cond, idx) do {} while (0)
#define CPROF(k) do {} while (0)

constexpr int S_GATE = 232440, S_XBAR = 232432, B_BAR = 231936;
#define RCB 136
#define RCU 184
#define NFP 2
#define UFE 0
#define PFM 8
#define NFE 2
#define QLAG 3
constexpr float SC_LOG2E = 0.08838834764831845f * 1.4426950408889634f;

__device__ __forceinline__ float2 ln_finish(float mean, float var) {
    float sd; asm("sqrt.approx.f32 %0,%1;" : "=f"(sd) : "f"(rbf(rbf(var) + 1e-5f)));
    sd = rbf(sd);
    return make_float2(rbf(mean), sd);
}

__device__ __forceinline__ float2 row_stats512(uint4* v, const uint4* src, int s1, int s2) {
    const int g = (threadIdx.x & 31) >> 2;
#pragma unroll
    for (int i = 0; i < 16; i++) v[i] = ldcg128(src + (i >> 1) * s1 + (i & 1) * s2);
    float a[4] = {0, 0, 0, 0}, q0[4] = {0, 0, 0, 0}, q1[4] = {0, 0, 0, 0};
#pragma unroll
    for (int i = 0; i < 16; i++) {
        mma16(a, v[i].x, v[i].y, v[i].z, v[i].w, 0x3f803f80u, 0x3f803f80u);
        mma8(q0, v[i].x, v[i].y, v[i].x); mma8(q1, v[i].x, v[i].y, v[i].y);
        mma8(q0, v[i].z, v[i].w, v[i].z); mma8(q1, v[i].z, v[i].w, v[i].w);
    }
    const float sum = a[0] + a[2], sq = (g & 1) ? q0[1] + q1[3] : q0[0] + q1[2];
    return make_float2(sum, fmaxf(sq - sum * sum * (1.f / 512.f), 0.f));
}
__device__ __forceinline__ void x1_norm(const uint2* src, int r, bool on) {
    const int lane = threadIdx.x & 31, g = lane >> 2, t = r * 4 + (lane & 3);
    constexpr int xp = XP;
    uint2 v[16];
#pragma unroll
    for (int i = 0; i < 16; i++) asm volatile("ld.global.cg.v2.u32 {%0,%1},[%2];" : "=r"(v[i].x), "=r"(v[i].y) : "l"(src + (g * 4 * xp + t) + ((i >> 1) * 16 + (i & 1)) * 2 * xp) : "memory");
    float s = 0, q = 0;
#pragma unroll
    for (int i = 0; i < 32; i++) {
        const uint32_t w = (i & 1) ? v[i >> 1].y : v[i >> 1].x;
        s += blo(w) + bhi(w); q = fmaf(blo(w), blo(w), fmaf(bhi(w), bhi(w), q));
    }
#pragma unroll
    for (int d = 4; d < 32; d *= 2) { s += __shfl_xor_sync(0xffffffffu, s, d); q += __shfl_xor_sync(0xffffffffu, q, d); }
    if (g == 0 && on) g_ln0[t] = 0;
    s *= 1.f / 512.f;
    const float2 l = ln_finish(s, fmaxf(fmaf(q, 1.f / 512.f, -s * s), 0.f));
    const float rs = rcp(l.y);
    const uint32_t mm = pack2(-l.x, -l.x);
    uint4* dst = g_xn + ((t >> 6) * 4096 + ((t >> 3) & 7) * 64 + g * 8 + (t & 7));
#define NRM(w) pack2(blo(hadd2(w, mm)) * rs, bhi(hadd2(w, mm)) * rs)
#pragma unroll
    for (int i = 0; i < 8; i++)
        asm volatile("{.reg .pred p; setp.ne.u32 p,%5,0; @p st.global.v4.u32 [%0],{%1,%2,%3,%4};}" ::"l"(dst + i * 512), "r"(NRM(v[2 * i].x)), "r"(NRM(v[2 * i].y)),
                     "r"(NRM(v[2 * i + 1].x)), "r"(NRM(v[2 * i + 1].y)), "r"((uint32_t)on) : "memory");
}

#define NWO 10
#define VMASK 0x4444
#define VQ 16
#define VPRE 2
#define MPRE 1
#define NPM NPX
#define SCHED(i) do {} while (0)
#define VPX 0
#define OA 0
#define QA 0
#define NPX 2
#define NPF 4
constexpr int SLOT = 24576, SL_V = 8192, SL_Q = 16384, SL_KM = 20480, SL_VM = 22528;
constexpr int R_WV = 0, R_SL = 65536, R_WO = R_SL + 4 * SLOT, R_M = 196608  , R_U = R_M + 8192  ,
              R_OS = R_U + 8192  , R_SB = R_OS + 8192  , R_OB = R_SB + 5248  , R_PB = R_OB + 2048  ,
              R_IL = R_PB + 1024  , R_SEL = 231680, R_BAR = R_SEL + 256, R_STQ = 65536, R_STK = 131072;
static_assert(R_WO + (16 - NWO) * 4096 <= R_M && R_IL + 64 <= R_SEL && R_BAR + 512 <= 232448, "smem map");
enum { RB_XFULL = 0  , RB_GO = 4  , RB_QK = 8  , RB_INIT = 24, RB_SV = 25  , RB_N = 29 };
#define GATE 1
enum { NB_MFULL = 1  , NB_PART = 3  , NB_S = 5, NB_P = 6, NB_O = 7, NB_W = 10 };
#define WDEP 1
#define RH 56
#define RW0 224
#define D1 300
#define D2 300
#define DX 0
__device__ __forceinline__ uint32_t clk32() { uint32_t c; asm volatile("mov.u32 %0,%%clock;" : "=r"(c)::"memory"); return c; }
__device__ __forceinline__ void spin(int cycles) {
    if (cycles <= 0) return;
    const uint32_t t0 = clk32();
    while (clk32() - t0 < (uint32_t)cycles) {}
}
__device__ __forceinline__ uint4* xregion(int X, int r) { return (uint4*)(((size_t)g_xch + 8191) & ~(size_t)8191) + (X * 66 + r) * 512; }

struct RecW { uint32_t po, dp, lw, swr, pwr, w, wv; };

template <int X>
__device__ __forceinline__ void rec_step(const RecW& k, uint32_t sb, int s, uint32_t z, uint32_t gate, const uint32_t (*wq)[4], const uint32_t (*wk)[4], uint4* wv, uint4* wo) {
    const uint32_t wz = k.w + z, w5 = wz * 512, so = (s & 1) * SLOT + w5;
    constexpr int SL = R_SL + X * 2 * SLOT;
    const uint32_t qb = sb + R_BAR + (RB_QK + X * 8) * 8 + wz * 8;
    const uint32_t l8 = ((k.lw + z) >> 1) + (sb - (sb >> 1) + SL + (s & 1) * SLOT + wz * 256);
    uint4 mk[8];
#define WVF(ks) wv[ks]
#define WVL(a, b) _Pragma("unroll") for (int ks_ = (a); ks_ < (b); ks_++) if (ks_ < 16 && !((VMASK >> ks_) & 1)) wv[ks_] = ldsm4t(k.wv + ks_ * 2048)
    WVL(0, VPRE);
    bar_sync(NB_MFULL + X, 288);
    uint32_t x[4], vv[2];
    float av[2][4] = {{0, 0, 0, 0}, {0, 0, 0, 0}};
    {
        float aq[2][4] = {{0, 0, 0, 0}, {0, 0, 0, 0}}, ak[2][4] = {{0, 0, 0, 0}, {0, 0, 0, 0}};
#pragma unroll
        for (int i = 0; i < MPRE; i++) mk[i] = ldsm4(k.lw + X * 4096 + R_M + i * 512);
#pragma unroll
        for (int i = 0; i < 8; i++) {
            if (i + MPRE < 8) mk[i + MPRE] = ldsm4(k.lw + X * 4096 + R_M + (i + MPRE) * 512);
            if (2 * i < VQ) { WVL(2 * i + VPRE, min(2 * i + 2 + VPRE, VQ + VPX)); }
            SCHED(i);
            const uint4 mf = mk[i];
            mma16(aq[0], wq[2 * i][0], wq[2 * i][1], wq[2 * i][2], wq[2 * i][3], mf.x, mf.y);
            mma16(ak[0], wk[2 * i][0], wk[2 * i][1], wk[2 * i][2], wk[2 * i][3], mf.x, mf.y);
            if (2 * i < VQ) mma16(av[0], WVF(2 * i).x, WVF(2 * i).y, WVF(2 * i).z, WVF(2 * i).w, mf.x, mf.y);
            mma16(aq[QA & 1], wq[2 * i + 1][0], wq[2 * i + 1][1], wq[2 * i + 1][2], wq[2 * i + 1][3], mf.z, mf.w);
            mma16(ak[(QA >> 1) & 1], wk[2 * i + 1][0], wk[2 * i + 1][1], wk[2 * i + 1][2], wk[2 * i + 1][3], mf.z, mf.w);
            if (2 * i < VQ) mma16(av[QA >> 2], WVF(2 * i + 1).x, WVF(2 * i + 1).y, WVF(2 * i + 1).z, WVF(2 * i + 1).w, mf.z, mf.w);
        }
        if (QA) {
#pragma unroll
            for (int i = 0; i < 4; i++) { if (QA & 1) aq[0][i] += aq[1][i]; if (QA & 2) ak[0][i] += ak[1][i]; }
        }
        x[0] = movm(pack2(aq[0][0], aq[0][1])); x[1] = movm(pack2(aq[0][2], aq[0][3]));
        x[2] = movm(pack2(ak[0][0], ak[0][1])); x[3] = movm(pack2(ak[0][2], ak[0][3]));
        st_async4(k.lw + (R_U + X * 4096 + w5 + k.dp), x[0], x[1], x[2], x[3], qb + k.dp);
    }
    {
#pragma unroll
        for (int i = VQ / 2; i < 8; i++) {
            const uint4 mf = mk[i];
            WVL(2 * i + VPX, 2 * i + 2 + VPX);
            mma16(av[0], WVF(2 * i).x, WVF(2 * i).y, WVF(2 * i).z, WVF(2 * i).w, mf.x, mf.y);
            mma16(av[1], WVF(2 * i + 1).x, WVF(2 * i + 1).y, WVF(2 * i + 1).z, WVF(2 * i + 1).w, mf.z, mf.w);
        }
        if (VQ < 16 || QA >= 4) {
#pragma unroll
            for (int i = 0; i < 4; i++) av[0][i] += av[1][i];
        }
        vv[0] = pack2(av[0][0], av[0][1]); vv[1] = pack2(av[0][2], av[0][3]);
        st_async2(l8 + (SL_VM + k.dp), vv[0], vv[1], qb + k.dp);
        asm volatile("{.reg .pred p; setp.eq.u32 p,%1,%2; @p mbarrier.arrive.shared::cta.b64 _,[%0];}" ::"r"(gate), "r"(k.swr), "r"(gate ? sb + R_SB : 0) : "memory");
        const uint4 k0 = lds128(k.lw + so + SL), k1 = lds128(k.lw + so + SL + 4096);
#pragma unroll
        for (int i = 0; i < NPX; i++) wo[i] = lds128(k.lw + w5 + R_WO + i * 4096);
        mbar_wait(qb, s & 1);
        const uint4 u = lds128(k.lw + w5 + R_U + X * 4096);
        const uint32_t q0 = hadd2(x[0], u.x), q1 = hadd2(x[1], u.y);
        x[2] = hadd2(x[2], u.z); x[3] = hadd2(x[3], u.w);
        float sa[4] = {0, 0, 0, 0}, sc[4] = {0, 0, 0, 0}, sm0, sm1;
        mma16(sa, k0.x, k0.y, k0.z, k0.w, q0, q1);
        mma16(sc, k1.x, k1.y, k1.z, k1.w, q0, q1);
        mma16_top(sm0, sm1, x[2], x[3], q0, q1);
        asm volatile("stmatrix.sync.aligned.m8n8.x4.trans.shared.b16 [%0],{%1,%2,%3,%4};" ::"r"(k.swr), "r"(pack2(sa[0], sa[1])), "r"(pack2(sa[2], sa[3])),
                     "r"(pack2(sc[0], sc[1])), "r"(pack2(sc[2], sc[3])) : "memory");
        asm volatile("stmatrix.sync.aligned.m8n8.x1.trans.shared.b16 [%0],{%1};" ::"r"(k.swr + 512), "r"(pack2(sm0, sm1)) : "memory");
    }
    bar_sync(NB_S, 256);
    uint4 v0, v1;
    uint32_t ls;
    {
        const uint4 y = ldsm4t(k.lw + wz * 656 + R_SB);
        uint32_t y4; asm volatile("ldmatrix.sync.aligned.m8n8.x1.trans.shared.b16 {%0},[%1];" : "=r"(y4) : "r"(k.lw + wz * 656 + R_SB + 512) : "memory");
        const uint2 vp = lds64(l8 + SL_VM);
        sts64(l8 + SL_KM, x[2], x[3]);
        v0 = lds128(k.lw + so + SL + SL_V); v1 = lds128(k.lw + so + SL + SL_V + 4096);
        vv[0] = hadd2(vv[0], vp.x); vv[1] = hadd2(vv[1], vp.y);
        sts64(l8 + SL_VM, vv[0], vv[1]);
#pragma unroll
        for (int i = NPX; i < NPM; i++) wo[i] = lds128(k.lw + w5 + R_WO + i * 4096);
        const uint32_t ONE = 0x3f803f80u + z;
        float a[4] = {0, 0, 0, 0}, b[4] = {0, 0, 0, 0}, e[4] = {0, 0, 0, 0};
        mma8(e, ONE, z, y4); mma16(a, ONE, z, z, ONE, y.x, y.y); mma16(b, ONE, z, z, ONE, y.z, y.w);
        float s0, s1;
        asm("{.reg .pred p1,p2,p4; .reg .f32 t0,t1,u0,u1; .reg .b32 m; and.b32 m,%12,64; setp.ne.u32 p1,m,0; and.b32 m,%12,128; setp.ne.u32 p2,m,0; and.b32 m,%12,256; setp.ne.u32 p4,m,0;"
            "selp.f32 t0,%4,%2,p1; selp.f32 t1,%5,%3,p1; selp.f32 u0,%8,%6,p1; selp.f32 u1,%9,%7,p1; selp.f32 t0,u0,t0,p2; selp.f32 t1,u1,t1,p2; selp.f32 %0,%10,t0,p4; selp.f32 %1,%11,t1,p4;}"
            : "=f"(s0), "=f"(s1) : "f"(a[0]), "f"(a[1]), "f"(a[2]), "f"(a[3]), "f"(b[0]), "f"(b[1]), "f"(b[2]), "f"(b[3]), "f"(e[0]), "f"(e[1]), "r"(k.lw));
        const int mi = __float_as_int(fmaxf(s0, s1));
        const int mp = __reduce_max_sync(0xffffffffu, mi), mn = (int)__reduce_min_sync(0xffffffffu, (unsigned)mi);
        const float mo = -__int_as_float(mp >= 0 ? mp : mn) * SC_LOG2E;
        s0 = ex2(fmaf(s0, SC_LOG2E, mo)); s1 = ex2(fmaf(s1, SC_LOG2E, mo));
        sts32(k.pwr, pack2(s0, s1));
        ls = k.lw < sb + 320 ? __float2uint_rn((s0 + s1) * 16777216.f) : 0;
    }
    bar_sync(NB_P, 256);
    {
        const uint4 pp = lds128(k.lw + R_PB);
        const uint32_t pm = lds32(((k.lw + z) >> 2) + (sb - (sb >> 2) + R_PB + 512));
        sts32(sb + R_IL + (wz >> 1) * 16 + (wz & 1) * 4, __float_as_uint(rcp(__uint2float_rn(__reduce_add_sync(0xffffffffu, ls)) * (1.f / 16777216.f))));
        float o0[4] = {0, 0, 0, 0}, o1[4] = {0, 0, 0, 0}, o2[4] = {0, 0, 0, 0};
        mma16(o0, v0.x, v0.y, v0.z, v0.w, pp.x, pp.y);
        mma16(o1, v1.x, v1.y, v1.z, v1.w, pp.z, pp.w);
        mma8(o2, vv[0], vv[1], pm);
        asm volatile("stmatrix.sync.aligned.m8n8.x2.trans.shared.b16 [%0],{%1,%2};" ::"r"(k.lw + wz * 256 + R_OB),
                     "r"(pack2(o0[0] + o1[0] + o2[0], o0[1] + o1[1] + o2[1])), "r"(pack2(o0[2] + o1[2] + o2[2], o0[3] + o1[3] + o2[3])) : "memory");
#pragma unroll
        for (int i = NPM; i < NPF; i++) wo[i] = lds128(k.lw + w5 + R_WO + i * 4096);
    }
    bar_sync(NB_O, 256);
    {
        const uint32_t po = k.po + z, tag = (s + 1) & 1;
        float r0[2][4] = {{0, 0, 0, 0}, {0, 0, 0, 0}}, r1[2][4] = {{0, 0, 0, 0}, {0, 0, 0, 0}};
        uint4 b[4];
#pragma unroll
        for (int i = 0; i < 4; i++) b[i] = ldsm4(k.lw + R_OB + i * 512);
        SCHED(8);
#pragma unroll
        for (int m = NWO + NPF; m < 16; m++) wo[m] = lds128(k.lw + w5 + R_WO + (m - NWO) * 4096);
        const uint2 il = lds64(sb + R_IL + (po & 48));
        const float i0 = __uint_as_float(il.x), i1 = __uint_as_float(il.y);
#pragma unroll
        for (int i = 0; i < 4; i++) {
            mma16(r0[0], wo[4 * i].x, wo[4 * i].y, wo[4 * i].z, wo[4 * i].w, b[i].x, b[i].y);
            mma16(r1[0], wo[4 * i + 1].x, wo[4 * i + 1].y, wo[4 * i + 1].z, wo[4 * i + 1].w, b[i].x, b[i].y);
            mma16(r0[OA], wo[4 * i + 2].x, wo[4 * i + 2].y, wo[4 * i + 2].z, wo[4 * i + 2].w, b[i].z, b[i].w);
            mma16(r1[OA], wo[4 * i + 3].x, wo[4 * i + 3].y, wo[4 * i + 3].z, wo[4 * i + 3].w, b[i].z, b[i].w);
        }
#pragma unroll
        for (int i = 0; i < 4; i++) { r0[0][i] = (OA ? r0[0][i] + r0[1][i] : r0[0][i]) * ((i & 1) ? i1 : i0); r1[0][i] = (OA ? r1[0][i] + r1[1][i] : r1[0][i]) * ((i & 1) ? i1 : i0); }
        st_rlx128((uint4*)((char*)xregion(X, 0) + ((po & ~1u) ^ ((po & X) << 12))), (pack2(r0[0][0], r0[0][2]) & ~1u) | tag,
                  pack2(r1[0][0], r1[0][2]), pack2(r0[0][1], r0[0][3]), pack2(r1[0][1], r1[0][3]));
        bar_arrive(NB_PART + X, 288);
    }
}

__device__ __forceinline__ void rec_fetch(const Params& p, uint32_t sb, int head, uint32_t rank, int which, int dst) {
#pragma unroll 1
    for (int j = 0; j < 8; j++) tma2d(sb + dst + j * 8192, &p.tm[which], head * 128 + (j >> 2) * 64, rank * 256 + (j & 3) * 64, sb + R_BAR + RB_INIT * 8);
}

__device__ __forceinline__ void rec_weights(const Params& p, uint32_t sb, int head, uint32_t rank, int w) {
    const int lane = threadIdx.x & 31, g = lane >> 2, c = lane & 3;
    const int t = w & 3, WG = w >> 2;
    uint32_t wq[16][4], wk[16][4];
    uint4 wo[16], wv[16];
    const uint32_t woff = sb + WG * 32768 + (((lane >> 4) << 3) + (lane & 7)) * 128 + (((2 * t + ((lane >> 3) & 1)) ^ (lane & 7)) << 4);
    const uint32_t lw = sb + lane * 16;
    PROF(threadIdx.x == 0, 3501);
    {
        const __nv_bfloat16* wp = p.Wo + (size_t)(head * 128 + 2 * c) * 512 + rank * 256 + w * 32 + g * 4;
#pragma unroll
        for (int ks = 0; ks < 8; ks++) {
            const uint2 r0 = *(const uint2*)(wp + (ks * 16) * 512), r1 = *(const uint2*)(wp + (ks * 16 + 1) * 512);
            const uint2 r2 = *(const uint2*)(wp + (ks * 16 + 8) * 512), r3 = *(const uint2*)(wp + (ks * 16 + 9) * 512);
            const uint4 f[2] = {make_uint4(__byte_perm(r0.x, r1.x, 0x5410), __byte_perm(r0.x, r1.x, 0x7632), __byte_perm(r2.x, r3.x, 0x5410), __byte_perm(r2.x, r3.x, 0x7632)),
                                make_uint4(__byte_perm(r0.y, r1.y, 0x5410), __byte_perm(r0.y, r1.y, 0x7632), __byte_perm(r2.y, r3.y, 0x5410), __byte_perm(r2.y, r3.y, 0x7632))};
#pragma unroll
            for (int h = 0; h < 2; h++) {
                const int m = 2 * ks + h;
                wo[m] = f[h];
            }
        }
    }
    PROF(threadIdx.x == 0, 3502);
    mbar_wait(sb + R_BAR + RB_INIT * 8, 0);
    PROF(threadIdx.x == 0, 3503);
#pragma unroll
    for (int ks = 0; ks < 16; ks++) {
        uint4 a = ldsm4t(woff + R_STQ + ks * 2048), b = ldsm4t(woff + R_STK + ks * 2048);
        wq[ks][0] = a.x; wq[ks][1] = a.y; wq[ks][2] = a.z; wq[ks][3] = a.w;
        wk[ks][0] = b.x; wk[ks][1] = b.y; wk[ks][2] = b.z; wk[ks][3] = b.w;
    }
    bar_sync(NB_W, 256);
#pragma unroll
    for (int m = 0; m < 16; m++)
        if (m < NPF || m >= NPF + NWO) sts128(lw + w * 512 + R_WO + (m < NPF ? m : m - NWO) * 4096, wo[m].x, wo[m].y, wo[m].z, wo[m].w);
    fence_async_smem();
    PROF(threadIdx.x == 0, 3504);
    __syncthreads();
#pragma unroll
    for (int i = 0; i < 16; i++) if ((VMASK >> i) & 1) wv[i] = ldsm4t(woff + R_WV + i * 2048);
    cluster_sync();
    PROF(threadIdx.x == 0, 3505);
    RecW k;
    {
        const int r = (w * 4 + (lane >> 3)) * 2 + rank;
        const uint32_t sl = lds32(sb + R_SEL + r * 4);
        const int slot = head * 8 + (lane & 7);
        k.po = (r * 512 + slot + (sl & 1) * 256) * 16 + (((sl >> 1) ^ sl) & 1);
    }
    k.dp = mapa(sb, rank ^ 1) - sb;
    k.lw = __shfl_sync(0xffffffffu, lw, lane);
    k.swr = __shfl_sync(0xffffffffu, sb + R_SB + (lane & 7) * 656 + (lane >> 3) * 128 + w * 16, lane);
    k.pwr = __shfl_sync(0xffffffffu, sb + R_PB + (g < 4 ? (w * 4 + c) * 16 + g * 4 : 512 + (w * 4 + c) * 4), lane);
    k.w = w;
    k.wv = __shfl_sync(0xffffffffu, woff + R_WV, lane);
    const int e0 = (p.chains & 1) ? 64 : 0, o1 = (p.chains & 2) ? p.lag : 1000, nit = (p.chains & 2) ? p.lag + 64 : e0;
    const uint32_t zero = p.zero;
#pragma unroll 1
    for (int it = 0; it < nit; it++) {
        const uint32_t g0 = sb + R_BAR + (RB_GO + (it & 1)) * 8, g1 = sb + R_BAR + (RB_GO + 2 + ((it - o1) & 1)) * 8;
        if (it < e0) {
            rec_step<0>(k, sb, it, it & zero, GATE && it > o1 ? g1 ^ 8 : 0, wq, wk, wv, wo);
            if ((!GATE || it < o1) && threadIdx.x == 0) mbar_arrive(g0);
        }
        if (it >= o1) {
            rec_step<1>(k, sb, it - o1, it & zero, GATE && it < e0 ? g0 : 0, wq, wk, wv, wo);
            if ((!GATE || it + 1 >= e0) && threadIdx.x == 0) mbar_arrive(g1);
        }
    }
}

__device__ __forceinline__ uint32_t mism(uint32_t a, uint32_t b, uint32_t t) {
    uint32_t d; asm("lop3.b32 %0,%1,%2,%3,0x7e;" : "=r"(d) : "r"(a), "r"(b), "r"(t)); return d;
}
template <bool TWO>
__device__ __forceinline__ void poll8(uint4* x, const uint4* src, uint32_t tag) {
#pragma unroll
    for (int j = 0; j < 8; j++) x[j] = ld_rlx128(src + j * 32);
    int n = 0;
    while (true) {
        uint32_t bad = 0;
#pragma unroll
        for (int j = 0; j < 8; j += 2) bad |= TWO ? mism(x[j].x, x[j].z, tag) | mism(x[j + 1].x, x[j + 1].z, tag) : mism(x[j].x, x[j + 1].x, tag);
        if (!__any_sync(0xffffffffu, bad & 1)) break;
#pragma unroll
        for (int j = 0; j < 8; j++)
            asm volatile("{.reg .pred p; .reg .b128 t; setp.ne.u32 p,%5,0; mov.b128 t,{%0,%1,%2,%3}; @p ld.relaxed.gpu.global.b128 t,[%4]; mov.b128 {%0,%1,%2,%3},t;}"
                         : "+r"(x[j].x), "+r"(x[j].y), "+r"(x[j].z), "+r"(x[j].w) : "l"(src + j * 32), "r"((TWO ? mism(x[j].x, x[j].z, tag) : x[j].x ^ tag) & 1) : "memory");
        if (++n > 2000000) __trap();
    }
}

__device__ __forceinline__ void rec_comm(const Params& p, uint32_t sb, int X, int head, uint32_t rank) {
    const int lane = threadIdx.x & 31, g = lane >> 2, c = lane & 3;
    const int me = head * 2 + rank;
    const uint32_t mb = sb + R_M + X * 4096 + lane * 16;
    uint4 x[8];
#pragma unroll
    for (int j = 0; j < 8; j++) x[j] = *(const uint4*)(p.mem0 + (lane & 7) * 512 + rank * 256 + (j * 4 + (lane >> 3)) * 8);
    const uint32_t sl = lds32(sb + R_SEL + me * 4);
    const uint4* src1 = xregion(X, me) + ((sl >> X) & 1) * 256 + c * 8 + g;
    const uint4* src2 = xregion(X, 64 + rank) + ((sl >> (2 + X)) & 1) * 256 + lane;
    uint2* mdst = (uint2*)(xregion(X, 64 + rank) + (c >> 1) * 256 + head * 8 + (g & 3) * 2 + (c & 1)) + (g >> 2);
    const uint32_t one = (g & 1) ? 0x3f800000u : 0x00003f80u, selA = (g & 2) ? 0u : one, selB = (g & 2) ? one : 0u;
    const uint32_t qb = sb + R_BAR + (RB_QK + X * 8 + lane) * 8;
    if (lane < 8) mbar_expect(qb, 768);
    mbar_wait(sb + R_BAR + (RB_XFULL + X * 2) * 8, 0);
#pragma unroll 1
    for (int s = 0;; s++) {
#pragma unroll
        for (int j = 0; j < 8; j++) sts128(mb + j * 512, x[j].x, x[j].y, x[j].z, x[j].w);
        bar_arrive(NB_MFULL + X, 288);
        PROF(lane == 0, X * 64 + s);
        bar_sync(NB_PART + X, 288);
        if (s == 63) break;
        const uint32_t tag = (s + 1) & 1;
        if (lane < 8) mbar_expect(qb, 768);
        spin(D1 + (lds32(sb + R_SEL) >> 20));
        poll8<false>(x, src1, tag);
        float a[4][4];
#pragma unroll
        for (int j = 0; j < 4; j++) {
            a[j][0] = a[j][1] = a[j][2] = a[j][3] = 0;
            mma16(a[j], x[j].x, x[j].y, x[j].z, x[j].w, selA, selB);
        }
#pragma unroll
        for (int j = 0; j < 4; j++) mma16(a[j], x[j + 4].x, x[j + 4].y, x[j + 4].z, x[j + 4].w, selA, selB);
#pragma unroll
        for (int i = 0; i < 4; i++) a[0][i] = (a[0][i] + a[1][i]) + (a[2][i] + a[3][i]);
        asm volatile("st.relaxed.gpu.global.b64 [%0],%1;" ::"l"(mdst), "l"(((uint64_t)pack2(a[0][2], a[0][3]) << 32) | ((pack2(a[0][0], a[0][1]) & ~1u) | tag)) : "memory");
        const uint32_t t2 = clk32();
        mbar_wait(sb + R_BAR + (RB_XFULL + X * 2 + tag) * 8, ((s + 1) >> 1) & 1);
        while (clk32() - t2 < D2) {}
        poll8<true>(x, src2, tag);
    }
}

template <int MT>
__device__ __forceinline__ void xattn(uint32_t l16, uint32_t l8, uint32_t os, int g, int c) {
    constexpr int NT = 3 + 2 * MT;
    float S[NT][4];
#pragma unroll
    for (int i = 0; i < NT; i++) S[i][0] = S[i][1] = S[i][2] = S[i][3] = 0;
#pragma unroll 2
    for (int ks = 0; ks < 8; ks++) {
        const uint4 q = lds128(l16 + SL_Q + ks * 512);
        const uint2 u = lds64(l8 + SL_KM + ks * 256);
        mma16(S[0], q.x, q.y, q.z, q.w, u.x, u.y);
#pragma unroll
        for (int m = 0; m <= MT; m++) {
            const uint4 kk = lds128(l16 + m * 4096 + ks * 512);
            mma16(S[1 + 2 * m], q.x, q.y, q.z, q.w, kk.x, kk.z); mma16(S[2 + 2 * m], q.x, q.y, q.z, q.w, kk.y, kk.w);
        }
    }
    const float NEG = -__int_as_float(0x7f800000);
    if (2 * c > g) { S[NT - 2][0] = NEG; S[NT - 1][2] = NEG; }
    if (2 * c + 1 > g) { S[NT - 2][1] = NEG; S[NT - 1][3] = NEG; }
    S[NT - 1][0] = S[NT - 1][1] = NEG;
    float m0 = fmaxf(S[0][0], S[0][1]), m1 = fmaxf(S[0][2], S[0][3]);
#pragma unroll
    for (int i = 1; i < NT; i++) { if (i < NT - 1) m0 = fmaxf(m0, fmaxf(S[i][0], S[i][1])); m1 = fmaxf(m1, fmaxf(S[i][2], S[i][3])); }
    m0 = fmaxf(m0, __shfl_xor_sync(0xffffffffu, m0, 1)); m1 = fmaxf(m1, __shfl_xor_sync(0xffffffffu, m1, 1));
    m0 = fmaxf(m0, __shfl_xor_sync(0xffffffffu, m0, 2)); m1 = fmaxf(m1, __shfl_xor_sync(0xffffffffu, m1, 2));
    m0 *= -SC_LOG2E; m1 *= -SC_LOG2E;
    float l0 = 0, l1 = 0;
#pragma unroll
    for (int i = 0; i < NT; i++) {
        if (i < NT - 1) { S[i][0] = ex2(fmaf(S[i][0], SC_LOG2E, m0)); S[i][1] = ex2(fmaf(S[i][1], SC_LOG2E, m0)); l0 += S[i][0] + S[i][1]; }
        S[i][2] = ex2(fmaf(S[i][2], SC_LOG2E, m1)); S[i][3] = ex2(fmaf(S[i][3], SC_LOG2E, m1)); l1 += S[i][2] + S[i][3];
    }
    l0 += __shfl_xor_sync(0xffffffffu, l0, 1); l1 += __shfl_xor_sync(0xffffffffu, l1, 1);
    l0 += __shfl_xor_sync(0xffffffffu, l0, 2); l1 += __shfl_xor_sync(0xffffffffu, l1, 2);
    l0 = rcp(l0); l1 = rcp(l1);
    uint32_t P[NT][2];
#pragma unroll
    for (int i = 0; i < NT; i++) { P[i][0] = i < NT - 1 ? pack2(S[i][0] * l0, S[i][1] * l0) : 0u; P[i][1] = pack2(S[i][2] * l1, S[i][3] * l1); }
#pragma unroll 2
    for (int et = 0; et < 8; et++) {
        float a[4] = {0, 0, 0, 0}, b[4] = {0, 0, 0, 0};
        const uint2 vm = lds64(l8 + SL_VM + et * 256);
        mma8(a, vm.x, vm.y, P[0][0]); mma8(b, vm.x, vm.y, P[0][1]);
#pragma unroll
        for (int m = 0; m <= MT; m++) {
            const uint4 v = lds128(l16 + SL_V + m * 4096 + et * 512);
            mma16(a, v.x, v.y, v.z, v.w, P[1 + 2 * m][0], P[2 + 2 * m][0]); mma16(b, v.x, v.y, v.z, v.w, P[1 + 2 * m][1], P[2 + 2 * m][1]);
        }
        asm volatile("stmatrix.sync.aligned.m8n8.x4.trans.shared.b16 [%0],{%1,%2,%3,%4};" ::"r"(os + (et >> 2) * 2048 + (et & 3) * 256),
                     "r"(pack2(a[0], a[1])), "r"(pack2(a[2], a[3])), "r"(pack2(b[0], b[1])), "r"(pack2(b[2], b[3])) : "memory");
    }
}

__device__ __forceinline__ void rec_tiles(uint32_t sb, int X, int head, uint32_t rank, int& nxt, int lim, int need) {
#pragma unroll 1
    while (nxt <= lim) {
        if ((nxt & 1) == 0) {
            unsigned v; int n = 0;
            while (true) {
                asm volatile("ld.relaxed.gpu.global.u32 %0,[%1];" : "=r"(v) : "l"(cnt_ptr(C_QKV + X * 32 + (nxt >> 1))) : "memory");
                if (__all_sync(0xffffffffu, v >= 2 * NQ)) break;
                if (nxt > need) return;
                if (++n > 3000000) __trap();
            }
        }
        if (elect()) {
            const uint32_t bar = sb + R_BAR + (RB_XFULL + X * 2 + (nxt & 1)) * 8, dst = sb + R_SL + (X * 2 + (nxt & 1)) * SLOT;
            const uint4* src = g_qkv + (size_t)((X * 64 + nxt) * 32 + head) * 1536;
            mbar_expect(bar, 20480);
            bulk_g2s_mc(dst + rank * 8192, src + 512 + rank * 512, 8192, bar, POL_LAST);
            bulk_g2s(dst + SL_Q, src + (rank ^ X) * 256, 4096, bar, POL_LAST);
        }
        __syncwarp();
        nxt++;
    }
}

__device__ __forceinline__ void rec_attn(const Params& p, uint32_t sb, int X, int head, uint32_t rank) {
    const int lane = threadIdx.x & 31, g = lane >> 2, c = lane & 3;
    const int mt = rank ^ X;
    const uint32_t dp = mapa(sb, rank ^ 1) - sb;
    int nxt = 0;
    rec_tiles(sb, X, head, rank, nxt, 1, 0);
#pragma unroll 1
    for (int s = 0; s < 64; s++) {
        const uint32_t so = sb + R_SL + (X * 2 + (s & 1)) * SLOT;
        mbar_wait(sb + R_BAR + (RB_GO + X * 2 + (s & 1)) * 8, (s >> 1) & 1);
        rec_tiles(sb, X, head, rank, nxt, min(s + 1, 63), -1);
        spin(DX);
        mbar_wait(sb + R_BAR + (RB_XFULL + X * 2 + (s & 1)) * 8, (s >> 1) & 1);
        if (elect()) asm volatile("cp.async.bulk.wait_group.read 0;" ::: "memory");
        __syncwarp();
        const uint32_t os = sb + R_OS + X * 4096 + (lane >> 4) * 1024 + (lane & 15) * 16;
        if (mt) xattn<1>(so + lane * 16, so + lane * 8, os, g, c); else xattn<0>(so + lane * 16, so + lane * 8, os, g, c);
        fence_async_smem();
        __syncwarp();
        const uint32_t svb = sb + R_BAR + (RB_SV + X * 2 + (s & 1)) * 8;
        if (elect()) {
            mbar_arrive(svb); mbar_arrive_cluster(svb + dp);
            const uint64_t pol = POL_SOON;
#pragma unroll
            for (int kb = 0; kb < 2; kb++)
                asm volatile("cp.async.bulk.global.shared::cta.bulk_group.L2::cache_hint [%0],[%1],%2,%3;" ::"l"(g_o + ((X * 32 + (s >> 1)) * 64 + head * 2 + kb) * 512 + ((s & 1) * 4 + mt * 2) * 64),
                             "r"(sb + R_OS + X * 4096 + kb * 2048), "r"(2048), "l"(pol) : "memory");
            asm volatile("cp.async.bulk.commit_group;" ::: "memory");
            if (s & 1) { asm volatile("cp.async.bulk.wait_group 0;" ::: "memory"); red_release(cnt_ptr(C_O + (X * 32 + (s >> 1)) * 4 + (head >> 3)), 1); }
        }
        __syncwarp();
        rec_tiles(sb, X, head, rank, nxt, min(s + 1, 63), s + 1);
        mbar_wait(svb, (s >> 1) & 1);
        rec_tiles(sb, X, head, rank, nxt, min(s + 2, 63), -1);
    }
}

__device__ __forceinline__ uint32_t timed_clear(unsigned* r, int lane) {
    uint32_t v = 0;
    const uint32_t t0 = clk32();
    asm volatile("{.reg .pred p; setp.eq.u32 p,%2,0; @p atom.relaxed.gpu.global.exch.b32 %0,[%1],0;}" : "+r"(v) : "l"(r), "r"(lane) : "memory");
    v = __shfl_sync(0xffffffffu, v, 0);
    asm volatile("{.reg .pred p; setp.eq.u32 p,%0,0x5a5a5a5b; @p nanosleep.u32 1;}" ::"r"(v) : "memory");
    return clk32() - t0;
}
__device__ __forceinline__ void rec_slots(int me, int X) {
    const int lane = threadIdx.x & 31;
#pragma unroll 1
    for (int i = lane; i < 512; i += 32) xregion(X, me)[i] = make_uint4(0, 0, 0, 0);
    if (lane < 16) xregion(X, 64 + (me & 1))[(lane >> 3) * 256 + (me >> 1) * 8 + (lane & 7)] = make_uint4(0, 0, 0, 0);
    __syncwarp();
    uint32_t sel = 0;
#pragma unroll 1
    for (int k = 0; k < 2; k++) {
        unsigned* r = (unsigned*)xregion(X, k ? 64 + (me & 1) : me) + k * (me >> 1) * 32;
        uint32_t b0 = ~0u, b1 = ~0u;
#pragma unroll 1
        for (int i = 0; i < 4; i++) { b0 = min(b0, timed_clear(r, lane)); b1 = min(b1, timed_clear(r + 1024, lane)); }
        sel |= (b1 < b0) << (2 * k + X);
    }
    if (lane == 0) ((uint16_t*)g_sel)[me * 2 + X] = sel;
}

__device__ __forceinline__ void rec_init(uint32_t sb) {
    const uint32_t b = sb + R_BAR;
    const int i = threadIdx.x & 31;
    mbar_init(b + i * 8, i >= RB_SV ? 2 : 1);
    if (i == RB_INIT) mbar_expect(b + RB_INIT * 8, 196608);
    asm volatile("fence.mbarrier_init.release.cluster;" ::: "memory");
}
constexpr int G_BAR = B_BAR;
enum { GB_FULL = 0  , GB_EMPTY = 8  , GB_RS = 16, GB_SS = 17, GB_LAG = 18, GB_FREE = 19, GB_DONE = 20  , GB_N = 24 };
constexpr int Q_PRE = 8;
constexpr int NQRS = 2 * NQ - 64;
__device__ __forceinline__ void gemm_init(uint32_t sb, bool op) {
    const int i = threadIdx.x & 31;
    if (i < GB_N) mbar_init(sb + G_BAR + i * 8, i >= GB_DONE ? 4 : i == GB_FREE ? 8 : (i >= GB_EMPTY && i < GB_RS) ? 2 : 1);
    if (i == GB_RS) mbar_expect(sb + G_BAR + i * 8, op ? 131072 : 98304);
    if (i == GB_SS) mbar_expect(sb + G_BAR + i * 8, op ? 131072 : 163840);
    asm volatile("fence.mbarrier_init.release.cluster;" ::: "memory");
}
__device__ __forceinline__ int qkv_blk(int id, int j) { return NQRS * 4 + id * 10 + j; }
__device__ __forceinline__ void qkv_fetch(const Params& p, uint32_t sb, int id, int j0, int j1) {
#pragma unroll 1
    for (int j = j0 * 2; j < j1 * 2; j++) {
        const int blk = min(qkv_blk(id, j >> 1), 511);
        tma2d(sb + j * 8192, &p.tn[blk >> 8], (blk & 255) * 16, (j & 1) * 256, sb + G_BAR + GB_SS * 8);
    }
}
__device__ __forceinline__ void qkv_stage(const Params& p, uint32_t dst, uint32_t bar, int id, int k0, int nk) {
#pragma unroll 1
    for (int j = 0; j < 2 * nk; j++) {
        const int u = id * 2 + (j >= nk);
        tma2d(dst + j * 8192, &p.tm[u < 64 ? 2 : 0], (u & 63) * 64, (k0 + (j >= nk ? j - nk : j)) * 64, bar);
    }
}
__device__ __forceinline__ void op_fetch(const Params& p, uint32_t sb, int id, int half) {
#pragma unroll 1
    for (int j = 0; j < 16; j++) tma2d(sb + j * 8192, &p.tm[4], ((id * 2 + (j >> 3)) & 7) * 64, (id >> 2) * 1024 + (j & 7) * 128 + half * 64, sb + G_BAR + (GB_RS + half) * 8);
}
template <bool OP>
__device__ __forceinline__ void gemm_producer(const Params& p, uint32_t sb, int id) {
    constexpr int NS = OP ? 6 : 8, SB = OP ? 16384 : 8192, RING = OP ? 131072 : 163840;
    if (!elect()) return;
    mbar_wait(sb + G_BAR + GB_FREE * 8, 0);
    if (OP) op_fetch(p, sb, id, 1);
    else {
        mbar_expect(sb + G_BAR + GB_RS * 8, 32768);
        qkv_stage(p, sb + 196608, sb + G_BAR + GB_RS * 8, id, 6, 2);
        qkv_fetch(p, sb, id, Q_PRE, 10);
        mbar_wait(sb + G_BAR + GB_FREE * 8, 1);
    }
    wait_cnt(g_gate, lds32(sb + S_GATE));
    int st = 0; uint32_t ph = 1;
#pragma unroll 1
    for (int n = 0; n < p.nl[OP]; n++) {
        const int e = p.list[OP][n];
        wait_cnt(OP ? cnt_ptr(C_O + e * 4 + (id >> 2)) : cnt_ptr(C_XN + e), 16);
        PROF(true, 1024 + n * 4);
        const uint4* src = OP ? g_o + (e * 64 + (id >> 2) * 16) * 512 : g_xn + e * 4096;
#pragma unroll 1
        for (int s = 0; s < 8; s++) {
            mbar_wait(sb + G_BAR + (GB_EMPTY + st) * 8, ph);
            mbar_expect(sb + G_BAR + (GB_FULL + st) * 8, SB);
            bulk_g2s(sb + RING + st * SB, src + s * (SB / 16), SB, sb + G_BAR + (GB_FULL + st) * 8, POL_N);
            if (++st == NS) { st = 0; ph ^= 1; }
        }
    }
}
template <bool OP>
__device__ __forceinline__ void gemm_release(const Params& p, uint32_t sb, int id) {
    if (threadIdx.x != 288) return;
#pragma unroll 1
    for (int n = 0; n < 2 * p.nl[OP]; n++) {
        const int e = p.list[OP][n >> 1];
        mbar_wait(sb + G_BAR + (GB_DONE + (n & 3)) * 8, (n >> 2) & 1);
        red_release(OP ? cnt_ptr(C_PP + e * 8 + (id & 3) * 2 + (n & 1)) : cnt_ptr(C_QKV + e), 1);
        PROF(n & 1, 1024 + (n >> 1) * 4 + 3);
    }
}
__device__ __forceinline__ void op_permute(uint32_t sb) {
#pragma unroll 2
    for (int i = threadIdx.x; i < 4096; i += 256) {
        const uint32_t a = sb + i * 32 + ((i >> 2) & 1) * 16, b = a ^ 16;
        const uint4 x = lds128(a), y = lds128(b);
        sts128(a, __byte_perm(x.x, x.y, 0x5410), __byte_perm(x.z, x.w, 0x5410), __byte_perm(y.x, y.y, 0x5410), __byte_perm(y.z, y.w, 0x5410));
        sts128(b, __byte_perm(x.x, x.y, 0x7632), __byte_perm(x.z, x.w, 0x7632), __byte_perm(y.x, y.y, 0x7632), __byte_perm(y.z, y.w, 0x7632));
    }
    fence_async_smem();
    bar_sync(1, 256);
}
template <bool OP>
__device__ __forceinline__ void gemm_consumer(const Params& p, uint32_t sb, int id, int w) {
    constexpr int NS = OP ? 6 : 8, SB = OP ? 16384 : 8192, RING = OP ? 131072 : 163840;
    const int lane = threadIdx.x & 31, wg = w >> 2, t = w & 3, u = id * 2 + wg;
    uint32_t a[128];
    mbar_wait(sb + G_BAR + GB_RS * 8, 0);
    PROF(threadIdx.x == 0, 3501);
    if (OP) op_permute(sb);
    const uint32_t wo = sb + (((lane >> 4) << 3) + (lane & 7)) * 128 + (((2 * t + ((lane >> 3) & 1)) ^ (lane & 7)) << 4);
#pragma unroll
    for (int ks = 0; ks < 32; ks++) {
        const uint4 v = ldsm4t(wo + ks * 2048 + (OP ? wg * 65536 : ks < 24 ? 131072 + wg * 49152 : 196608 - 49152 + wg * 16384));
        a[ks * 4] = v.x; a[ks * 4 + 1] = v.y; a[ks * 4 + 2] = v.z; a[ks * 4 + 3] = v.w;
        if (ks == 31 || (!OP && ks == 23)) {
            fence_async_smem();
            __syncwarp();
            if (lane == 0) mbar_arrive(sb + G_BAR + GB_FREE * 8);
            if (ks == 23) mbar_wait(sb + G_BAR + GB_RS * 8, 1);
        }
    }
    PROF(threadIdx.x == 0, 3502);
    mbar_wait(sb + G_BAR + GB_SS * 8, 0);
    if (OP) op_permute(sb);
    PROF(threadIdx.x == 0, 3503);
    float c0[32], c1[OP ? 32 : 40];
    int st = 0; uint32_t ph = 0;
    const bool el = (threadIdx.x & 127) == 0;
#pragma unroll 1
    for (int n = 0; n < p.nl[OP]; n++) {
        int prev = 0;
        const uint32_t wb = sb + wg * (OP ? 65536 : 81920) + (n & p.zero);
        const uint64_t dw = OP ? mkdesc(wb, 0, 1024, 1) : mkdesc(wb, 16384, 256, 3);
        if (!OP && wg) mbar_wait(sb + G_BAR + GB_LAG * 8, n & 1);
#pragma unroll
        for (int s = 0; s < 8; s++) {
            mbar_wait(sb + G_BAR + (GB_FULL + st) * 8, ph);
            const uint64_t dx = mkdesc(sb + RING + st * SB, 128, 1024, 0);
            wg_fence();
#pragma unroll
            for (int kk = 0; kk < 4; kk++) {
                const int ks = s * 4 + kk;
                if (ks == 0) { wgmma64_rs<0>(c0, a, dx); if (OP) wgmma64_ta<0>(c1, dw, dx + 512); else wgmma80_tb<0>(c1, dx, dw); }
                else { wgmma64_rs<1>(c0, a + ks * 4, dx + kk * 16); if (OP) wgmma64_ta<1>(c1, dw + ks * 128, dx + 512 + kk * 16); else wgmma80_tb<1>(c1, dx + kk * 16, dw + ks * 32); }
            }
            wg_commit();
            if (s) {
                wg_wait<1>();
                if (el) { mbar_arrive(sb + G_BAR + (GB_EMPTY + prev) * 8); if (!OP && s == QLAG && !wg) mbar_arrive(sb + G_BAR + GB_LAG * 8); }
            }
            prev = st;
            if (++st == NS) { st = 0; ph ^= 1; }
        }
        const int e = p.list[OP][n];
        wg_wait<0>();
        if (el) mbar_arrive(sb + G_BAR + (GB_EMPTY + prev) * 8);
        PROF(threadIdx.x == 128, 1024 + n * 4 + 1);
        if (OP) {
            uint4* dst = g_pp + (e * 4 + (id >> 2)) * 4096 + ((u & 7) * 32 + t * 8) * 16 + (lane >> 2) * 16 + (lane & 3);
#pragma unroll
            for (int j = 0; j < 4; j++) {
                const float* x = c0 + j * 8; const float* y = c1 + j * 8;
                stg128(dst + j * 4, make_uint4(pack2(x[0] + y[0], x[1] + y[1]), pack2(x[2] + y[2], x[3] + y[3]), pack2(x[4] + y[4], x[5] + y[5]), pack2(x[6] + y[6], x[7] + y[7])), POL_SOON);
            }
        } else {
            uint4* dst = g_qkv + (size_t)e * 2 * 32 * 1536 + lane;
            const uint64_t pol = POL_SOON;
#pragma unroll
            for (int j = 0; j < 4; j++) {
                const float* x = c0 + j * 8;
                uint4 v = make_uint4(pack2(x[0], x[1]), pack2(x[2], x[3]), pack2(x[4], x[5]), pack2(x[6], x[7]));
                if (u >= 64) v = make_uint4(movm(v.x), movm(v.z), movm(v.y), movm(v.w));
                stg128(dst + (((j >> 1) * 32 + ((u & 63) >> 1)) * 1536 + (u < 64 ? 1024 : 0) + (j & 1) * 256 + ((u & 1) * 4 + t) * 32), v, pol);
            }
#pragma unroll
            for (int j = 0; j < 5; j++) {
                const float* x = c1 + (OP ? 0 : j * 8);
                const int blk = qkv_blk(id, wg * 5 + j);
                if (blk < 512) stg128(dst + (((t >> 1) * 32 + ((blk >> 3) & 31)) * 1536 + (blk >> 8) * 512 + (t & 1) * 256 + (blk & 7) * 32),
                                      make_uint4(pack2(x[0], x[1]), pack2(x[2], x[3]), pack2(x[4], x[5]), pack2(x[6], x[7])), pol);
            }
        }
        __syncwarp();
        if (lane == 0) mbar_arrive(sb + G_BAR + (GB_DONE + (n & 1) * 2 + wg) * 8);
        PROF(threadIdx.x == 128, 1024 + n * 4 + 2);
    }
}

template <int NP, bool MMA>
__device__ __forceinline__ void sum_partials(float* x, const uint2* src, const uint32_t* r0, const uint32_t* r1, uint32_t idm) {
    uint2 v[4][NP];
#pragma unroll
    for (int s = 0; s < 4; s++)
#pragma unroll
        for (int i = 0; i < NP; i++) asm volatile("ld.global.cg.L2::cache_hint.v2.u32 {%0,%1},[%2],%3;" : "=r"(v[s][i].x), "=r"(v[s][i].y) : "l"(src + s * 8192 + i * 32), "l"(POL_LAST) : "memory");
#pragma unroll
    for (int i = 0; i < NP; i++) {
        uint32_t a, b;
        if (MMA) {
            float t[4] = {0, 0, 0, 0};
            mma16(t, v[0][i].x, v[0][i].y, v[1][i].x, v[1][i].y, idm, idm); mma16(t, v[2][i].x, v[2][i].y, v[3][i].x, v[3][i].y, idm, idm);
            a = pack2(t[0], t[2]); b = pack2(t[1], t[3]);
        } else {
            a = pack2((blo(v[0][i].x) + blo(v[1][i].x)) + (blo(v[2][i].x) + blo(v[3][i].x)), (blo(v[0][i].y) + blo(v[1][i].y)) + (blo(v[2][i].y) + blo(v[3][i].y)));
            b = pack2((bhi(v[0][i].x) + bhi(v[1][i].x)) + (bhi(v[2][i].x) + bhi(v[3][i].x)), (bhi(v[0][i].y) + bhi(v[1][i].y)) + (bhi(v[2][i].y) + bhi(v[3][i].y)));
        }
        const uint32_t s0 = hadd2(a, r0[i]), s1 = hadd2(b, r1[i]);
        x[4 * i] = blo(s0); x[4 * i + 2] = bhi(s0); x[4 * i + 1] = blo(s1); x[4 * i + 3] = bhi(s1);
    }
}
__device__ __forceinline__ const uint2* pp_src(int e, int tile, int lane) { return (const uint2*)g_pp + e * 32768 + tile * 128 + (lane >> 3) * 8 + (lane & 3) * 2 + ((lane >> 2) & 1); }

__device__ __forceinline__ void fin_warp(const Params& p, uint32_t sb, int id) {
    const int tile = (id & ~1) + (threadIdx.x & 1), lane = (id & 1) * 16 + ((threadIdx.x & 31) >> 1);
    wait_cnt_warp(g_gate, lds32(sb + S_GATE));
#pragma unroll 1
    for (int e = 32; e < 64; e++) {
        wait_cnt_warp(cnt_ptr(C_PP + e * 8 + (id >> 3)), 4);
        const uint4* rp = g_x + ((128 + tile * 2) * XP + (e - 32) * 32 + lane);
        uint32_t o0[4], o1[4];
#pragma unroll
        for (int h = 0; h < 2; h++) {
            const uint4 r = ldcg128(rp + h * XP);
            const uint32_t a[2] = {r.x, r.y}, b[2] = {r.z, r.w};
            float x[8];
            sum_partials<2, false>(x, pp_src(e, tile, lane) + h * 64, a, b, 0);
#pragma unroll
            for (int i = 0; i < 2; i++) {
                o0[h * 2 + i] = __byte_perm(__float_as_uint(x[4 * i]), __float_as_uint(x[4 * i + 2]), 0x7632);
                o1[h * 2 + i] = __byte_perm(__float_as_uint(x[4 * i + 1]), __float_as_uint(x[4 * i + 3]), 0x7632);
            }
        }
        uint4* dst = (uint4*)p.out + ((e - 32) * 64 + lane * 2) * 64 + tile;
        dst[0] = make_uint4(o0[0], o0[1], o0[2], o0[3]); dst[64] = make_uint4(o1[0], o1[1], o1[2], o1[3]);
        PROF((threadIdx.x & 31) == 0, 1536 + e);
    }
}

constexpr int PROW = 272, UROW = 2304, UPRE = 256;
constexpr int C_UR = 0  , C_TB = 65536  , C_BG = C_TB + 51200,
              CB_M = 8960, CB_U = CB_M + 1792, CB_BIG = CB_U + 2560, C_ST = C_BG + 8 * CB_BIG  ;
static_assert(C_ST + 4736 <= B_BAR, "smem map");
enum { CB_TB = 0, CB_UF = 1  , CB_CF = 5  , CB_LD = 9   };
__device__ __forceinline__ void conv_init(uint32_t sb, bool spare) {
    const int i = threadIdx.x & 31;
    mbar_init(sb + B_BAR + i * 8, (i >= CB_UF && i < CB_CF && !spare) ? 2 : 1);
    if (i == CB_TB && !spare) mbar_expect(sb + B_BAR + i * 8, 51200);
    asm volatile("fence.mbarrier_init.release.cluster;" ::: "memory");
}
__device__ __forceinline__ void mma_q(float* c, const uint32_t* a, const uint4& q) {
    mma16(c, a[0], a[1], a[2], a[3], q.x, q.y); mma16(c, a[4], a[5], a[6], a[7], q.z, q.w);
}
__device__ __forceinline__ uint2 ld_acc(const uint2* p, bool on) {
    uint2 v = make_uint2(0, 0);
    asm volatile("{.reg .pred p; setp.ne.u32 p,%3,0; @p ld.global.cg.v2.u32 {%0,%1},[%2];}" : "+r"(v.x), "+r"(v.y) : "l"(p), "r"((uint32_t)on) : "memory");
    return v;
}
__device__ __forceinline__ void add_acc(float* c, uint2 v) { c[0] += blo(v.x); c[1] += bhi(v.x); c[2] += blo(v.y); c[3] += bhi(v.y); }
__device__ __forceinline__ void st_acc(uint2* p, const float* c) { *p = make_uint2(pack2(c[0], c[1]), pack2(c[2], c[3])); }
__device__ __forceinline__ float sum8(const uint4* v, int k) {
#define VK(i) __uint_as_float(k == 0 ? v[i].x : k == 1 ? v[i].y : k == 2 ? v[i].z : v[i].w)
    return ((VK(0) + VK(1)) + (VK(2) + VK(3))) + ((VK(4) + VK(5)) + (VK(6) + VK(7)));
}
template <int XW>
__device__ __forceinline__ void stats_send(uint32_t l16, const float* x, uint4* gs, int q, int w) {
    float s0 = 0, s1 = 0, m0 = 0, m1 = 0;
#pragma unroll
    for (int i = 0; i < 8; i++) { s0 += x[2 * i]; s1 += x[2 * i + 1]; m0 = fmaf(x[2 * i], x[2 * i], m0); m1 = fmaf(x[2 * i + 1], x[2 * i + 1], m1); }
    sts128(l16 + C_ST + w * 512, __float_as_uint(s0), __float_as_uint(m0), __float_as_uint(s1), __float_as_uint(m1));
    if (w == XW) {
        bar_sync(2, 256);
        uint4 v[8];
#pragma unroll
        for (int i = 0; i < 8; i++) v[i] = lds128(l16 + C_ST + i * 512);
        st_rlx128(gs + q * 32, __float_as_uint(sum8(v, 0)), __float_as_uint(sum8(v, 1)) & 0x7fffffffu, __float_as_uint(sum8(v, 2)), __float_as_uint(sum8(v, 3)));
    } else bar_arrive(2, 256);
}
template <int XW>
__device__ __forceinline__ float4 stats_recv(uint32_t l16, const uint4* gs, int w) {
    if (w == XW) {
        uint4 v[8];
        int n = 0;
        while (true) {
            uint32_t bad = 0;
#pragma unroll
            for (int i = 0; i < 8; i++) v[i] = ld_rlx128(gs + i * 32);
#pragma unroll
            for (int i = 0; i < 8; i++) bad |= v[i].y;
            if (!__any_sync(0xffffffffu, bad >> 31)) break;
            if (++n > 2000000) __trap();
        }
        const float s0 = sum8(v, 0) * (1.f / 512.f), s1 = sum8(v, 2) * (1.f / 512.f);
        const float2 l0 = ln_finish(s0, fmaxf(fmaf(sum8(v, 1), 1.f / 512.f, -s0 * s0), 0.f)), l1 = ln_finish(s1, fmaxf(fmaf(sum8(v, 3), 1.f / 512.f, -s1 * s1), 0.f));
        sts128(l16 + C_ST + 4096, __float_as_uint(l0.x), __float_as_uint(rcp(l0.y)), __float_as_uint(l1.x), __float_as_uint(rcp(l1.y)));
    }
    bar_sync(3, 256);
    const uint4 r = lds128(l16 + C_ST + 4096);
    return make_float4(__uint_as_float(r.x), __uint_as_float(r.y), __uint_as_float(r.z), __uint_as_float(r.w));
}

#define HOIST_STOP(k) asm volatile("{.reg .pred p; setp.eq.u32 p,%0,%1; @p nanosleep.u32 1;}" ::"r"(zero), "r"((k) + 1) : "memory")
__device__ __forceinline__ void conv_near(float (*acc)[4], uint32_t ta, uint32_t qa, uint32_t zero) {
#pragma unroll
    for (int k = 0; k < 8; k++) {
        uint32_t a[8];
#pragma unroll
        for (int j = 0; j < 8; j++) a[j] = lds32(ta + k * 800 + j * 32);
        mma_q(acc[k], a, ldsm4(qa + k * 1024));
        if (k % NFE == NFE - 1 && k < 7) HOIST_STOP(k);
    }
}
template <int K0>
__device__ __forceinline__ void conv_pair(float (*acc)[4], float (*pend)[4], uint32_t ta, uint32_t q0, uint32_t q1, uint32_t q2, uint32_t zero) {
#pragma unroll
    for (int i = 0; i < 4; i++) {
        const int k = K0 + i;
#pragma unroll
        for (int e = 0; e < 4; e++) { acc[4 - K0 + i][e] += pend[i][e]; pend[i][e] = 0; }
        uint32_t a[16];
#pragma unroll
        for (int j = 0; j < 16; j++) a[j] = lds32(ta + 256 + k * 800 + j * 32);
        const uint4 x1 = ldsm4(q1 + k * 1024);
        mma_q(acc[k], a, x1); mma_q(pend[i], a, ldsm4(q2 + k * 1024));
        mma_q(pend[i], a + 8, x1); mma_q(acc[k], a + 8, ldsm4(q0 + k * 1024));
        if (i % NFP == NFP - 1 && i < 3) HOIST_STOP(k);
    }
}

__device__ __forceinline__ void conv_tile(const Params& p, uint32_t sb, int q, int w) {
    const int lane = __shfl_sync(0xffffffffu, threadIdx.x & 31, threadIdx.x & 31), g = lane >> 2, c = lane & 3, tile = q * 8 + w;
    const uint32_t l16 = sb + lane * 16;
#pragma unroll
    for (int i = 0; i < 16; i++) sts128(l16 + C_UR + w * 8192 + i * 512, 0, 0, 0, 0);
    wait_cnt_warp(g_gate, lds32(sb + S_GATE));
    if (lane < 8) bulk_g2s(sb + C_TB + (w * 8 + lane) * 800, g_P + (tile * 8 + lane) * PROW + 72, 800, sb + B_BAR + CB_TB * 8, POL_N);
    uint32_t A[8][8];
#pragma unroll
    for (int k = 0; k < 8; k++)
#pragma unroll
        for (int j = 0; j < 8; j++) A[k][j] = __ldcg(g_P + (tile * 8 + k) * PROW + 16 + 8 * j + g - 2 * c);
    if (lane == 0) { const uint4 d = __ldg((const uint4*)p.Dskip + tile); sts128(sb + C_ST + 4608 + w * 16, d.x, d.y, d.z, d.w); }
    float acc[8][4], pend[4][4];
#pragma unroll
    for (int k = 0; k < 8; k++) acc[k][0] = acc[k][1] = acc[k][2] = acc[k][3] = pend[k & 3][k >> 2] = pend[k & 3][2 + (k >> 2)] = 0;
    const uint32_t row = sb + C_UR + w * 8192, ta = sb + C_TB + w * 6400 + (8 + g - 2 * c) * 4, zero = p.zero, qo = (lane & 7) * 16 - (lane >> 3) * 32;
    bar_sync(4, 384);
    mbar_wait(sb + B_BAR + CB_TB * 8, 0);
#pragma unroll 1
    for (int b = 0; b < 32; b++) {
        const int lz = lane + (b & p.zero);
        const uint4 r0 = ldcg128(g_x + (tile * 2 * XP + b * 32 + lz)), r1 = ldcg128(g_x + (tile * 2 * XP + b * 32 + lz) + XP);
        const uint32_t q1 = row + ((qo + (b - 1) * 128) & 1023);
        if (w == 0) conv_near(acc, ta, q1, zero);
        PROF(threadIdx.x == 0, 2048 + b * 8);
        const uint2* pps = pp_src(b, tile, lz);
        asm volatile("" : "+l"(pps));
        wait_flag_warp(cnt_ptr(C_PP + b * 8 + q), 4);
        PROF(threadIdx.x == 0, 2048 + b * 8 + 1);
        float x[16];
        {
            const uint32_t a[4] = {r0.x, r0.y, r1.x, r1.y}, bb[4] = {r0.z, r0.w, r1.z, r1.w};
            sum_partials<4, true>(x, pps, a, bb, (2 * (lz & 3) == lz >> 2) ? 0x00003f80u : (2 * (lz & 3) + 1 == lz >> 2) ? 0x3f800000u : 0u);
        }
        stats_send<0>(l16, x, g_st + b * 256 + lz, q, w);
        {
            PROF(threadIdx.x == 0, 2048 + b * 8 + 2);
            if (b) mbar_wait(sb + B_BAR + (CB_CF + (w >> 1)) * 8, (b - 1) & 1);
            const uint2* cb = g_carry + ((tile * 320 + b) * 32 + lz);
            uint2 cr[8];
#pragma unroll
            for (int k = 0; k < 8; k++) cr[k] = ld_acc(cb + k * 1280, b >= 4);
            if (w) conv_near(acc, ta, q1, zero);
#pragma unroll
            for (int k = 0; k < 8; k++) add_acc(acc[k], cr[k]);
        }
        float4 ln = stats_recv<0>(l16, g_st + b * 256 + lz, w);
        PROF(threadIdx.x == 0, 2048 + b * 8 + 3);
        uint32_t u[8];
#pragma unroll
        for (int k = 0; k < 8; k++) {
            u[k] = pack2(rbf(x[2 * k] - ln.x) * ln.y, rbf(x[2 * k + 1] - ln.z) * ln.w);
            sts32(row + k * 1024 + (b & 7) * 128 + lane * 4, u[k]);
        }
        __syncwarp();
        if (UFE && lane == 0) mbar_arrive(sb + B_BAR + (CB_UF + (w >> 1)) * 8);
        const uint32_t qa = row + ((qo + b * 128) & 1023);
#pragma unroll
        for (int k = 0; k < 8; k++) mma_q(acc[k], A[k], ldsm4(qa + k * 1024));
        const uint4 dk = lds128(sb + C_ST + 4608 + w * 16);
#pragma unroll
        for (int k = 0; k < 8; k++) {
            const float t = __shfl_sync(0xffffffffu, acc[k][3], (lz & ~3) | ((lz - 1) & 3));
            const uint32_t y = movm(pack2(acc[k][0] + (c ? t : 0.f), acc[k][1] + acc[k][2]));
            acc[k][0] = c ? 0.f : t; acc[k][1] = acc[k][2] = acc[k][3] = 0;
            const uint32_t dw = k >> 1 == 0 ? dk.x : k >> 1 == 1 ? dk.y : k >> 1 == 2 ? dk.z : dk.w;
            const uint32_t s = hadd2(hadd2(y, hmul2(u[k], __byte_perm(dw, 0, (k & 1) ? 0x3232 : 0x1010))), __byte_perm(__float_as_uint(x[2 * k]), __float_as_uint(x[2 * k + 1]), 0x7632));
            x[2 * k] = blo(s); x[2 * k + 1] = bhi(s);
        }
        if (!UFE && lane == 0) mbar_arrive(sb + B_BAR + (CB_UF + (w >> 1)) * 8);
        stats_send<1>(l16, x, g_st + (32 + b) * 256 + lz, q, w);
        {
            PROF(threadIdx.x == 0, 2048 + b * 8 + 4);
            uint4* dst = g_x + ((128 + tile * 2) * XP + b * 32 + lz);
#pragma unroll
            for (int e = 0; e < 2; e++) {
                const float* y = x + e * 8;
                dst[e * XP] = make_uint4(__byte_perm(__float_as_uint(y[0]), __float_as_uint(y[2]), 0x7632), __byte_perm(__float_as_uint(y[4]), __float_as_uint(y[6]), 0x7632),
                                           __byte_perm(__float_as_uint(y[1]), __float_as_uint(y[3]), 0x7632), __byte_perm(__float_as_uint(y[5]), __float_as_uint(y[7]), 0x7632));
            }
            uint32_t* du = g_u + (tile * 8 * (UROW / 2) + UPRE / 2 + b * 32 + lz);
#pragma unroll
            for (int k = 0; k < 8; k++) du[k * (UROW / 2)] = u[k];
        }
#pragma unroll 1
        for (int pass = 0; pass < 2; pass++) {
            if (pass == (w == 1)) {
                const uint32_t q0 = row + ((qo + (b - 2) * 128) & 1023);
                if (b & 1) conv_pair<4>(acc, pend, ta, q0, q1, qa, zero); else conv_pair<0>(acc, pend, ta, q0, q1, qa, zero);
            }
            if (pass) break;
            ln = stats_recv<1>(l16, g_st + (32 + b) * 256 + lz, w);
            PROF(threadIdx.x == 0, 2048 + b * 8 + 5);
            uint32_t o[2][4];
#pragma unroll
            for (int e = 0; e < 2; e++) {
                const float mu = e ? ln.z : ln.x, rs = e ? ln.w : ln.y;
#pragma unroll
                for (int i = 0; i < 4; i++) o[e][i] = pack2(rbf(x[4 * i + e] - mu) * rs, rbf(x[4 * i + 2 + e] - mu) * rs);
            }
#pragma unroll
            for (int i = 0; i < 4; i++) {
                const uint32_t t = __shfl_xor_sync(0xffffffffu, (lz & 1) ? o[0][i] : o[1][i], 1);
                if (lz & 1) o[0][i] = t; else o[1][i] = t;
            }
            uint4* dst = g_xn + ((32 + b) * 4096 + q * 512 + (lz >> 2) * 64 + w * 8 + (lz & 2) * 2 + (lz & 1));
            dst[0] = make_uint4(o[0][0], o[0][1], o[0][2], o[0][3]); dst[2] = make_uint4(o[1][0], o[1][1], o[1][2], o[1][3]);
            if (w == 7) {
                bar_sync(5, 256);
                if (elect()) red_release(cnt_ptr(C_XN + 32 + b), 2);
                PROF(lane == 0, 2048 + b * 8 + 6);
                __syncwarp();
            } else bar_arrive(5, 256);
        }
    }
}

template <int P0, bool TRI = false>
__device__ __forceinline__ void bg_half(float (*acc)[4], uint4* win, uint32_t ta, uint32_t qa, uint32_t mask, uint32_t row) {
#pragma unroll
    for (int i = 0; i < 4; i++) {
        win[P0 + i] = ldsm4(((qa + i * 128) & mask) + row);
        const uint4 a = lds128(ta + (3 - i) * 448), e = lds128(ta + (3 - i) * 448 + 224);
#pragma unroll
        for (int r = TRI ? 7 - P0 - i : 0; r < 8; r++) mma16(acc[r], a.x, a.y, a.z, a.w, win[(P0 + i + 1 + r) & 7].x, win[(P0 + i + 1 + r) & 7].y);
#pragma unroll
        for (int r = TRI ? 7 - P0 - i : 0; r < 8; r++) mma16(acc[r], e.x, e.y, e.z, e.w, win[(P0 + i + 1 + r) & 7].z, win[(P0 + i + 1 + r) & 7].w);
    }
}
__device__ __forceinline__ void bg_fetch(uint32_t sb, int q, int j, int n, int lane) {
    const int b0 = n >> 1, ch = q * 64 + j * 16 + (n & 1) * 8 + (b0 & 7), lo = max(b0 - 24, -4), nu = b0 > 4 ? (b0 - 4 - lo) * 128 : 0;
    const uint32_t bar = sb + B_BAR + (CB_LD + j * 2 + (n & 1)) * 8, buf = sb + C_BG + (j * 2 + (n & 1)) * CB_BIG;
    const int nt = min((b0 + 7) >> 2, 5) * 1792;
    if (elect()) {
        mbar_expect(bar, nt + nu + 1792);
        bulk_g2s(buf, g_W + ch * 784, nt, bar, POL_N);
        bulk_g2s(buf + CB_M, g_W + (ch ^ 4) * 784, 1792, bar, POL_N);
        if (nu) bulk_g2s(buf + CB_U + (lo - b0 + 24) * 128, g_u + ch * (UROW / 2) + UPRE / 2 + lo * 32, nu, bar, POL_N);
    }
    __syncwarp();
}
__device__ __forceinline__ void conv_back(uint32_t sb, int q, int j) {
    const int lane = __shfl_sync(0xffffffffu, threadIdx.x & 31, threadIdx.x & 31), g = lane >> 2, c = lane & 3;
    wait_cnt_warp(g_gate, lds32(sb + S_GATE));
    bg_fetch(sb, q, j, 2, lane);
    bar_sync(4, 384);
    const uint32_t to = (6 + g - 2 * c) * 16, qo = (lane & 7) * 16 - (lane >> 3) * 32;
#pragma unroll 1
    for (int n = 2; n < 64; n++) {
        const int b0 = n >> 1, i = n & 1, chl = j * 16 + i * 8 + (b0 & 7), hm = (b0 + 7) >> 2;
        const uint32_t buf = sb + C_BG + (j * 2 + i) * CB_BIG, ta = buf + to;
        float acc[8][4];
        uint4 win[8];
        if (n < 63) bg_fetch(sb, q, j, n + 1, lane);
        if (n == 34 || n == 42) wait_flag_warp(cnt_ptr(C_FAR + (n == 42)), 12);
        mbar_wait(sb + B_BAR + (CB_LD + j * 2 + i) * 8, (b0 - 1) & 1);
#pragma unroll
        for (int r = 0; r < 8; r++) {
            acc[r][0] = acc[r][1] = acc[r][2] = acc[r][3] = 0;
            win[r] = make_uint4(0, 0, 0, 0);
            if (r) asm volatile("{.reg .pred p; setp.ge.s32 p,%5,24; @p ldmatrix.sync.aligned.m8n8.x4.shared.b16 {%0,%1,%2,%3},[%4];}"
                                : "+r"(win[r].x), "+r"(win[r].y), "+r"(win[r].z), "+r"(win[r].w) : "r"(buf + CB_U + qo + r * 128), "r"(b0 + r) : "memory");
        }
        const uint2* fr = g_far + (((q * 64 + chl) * 8 + b0 - 24) * 32 + lane);
        uint2* cr = g_carry + (((q * 64 + chl) * 40 + b0) * 32 + lane);
        uint2* cm = g_carry + (((q * 64 + (chl ^ 4)) * 40 + b0) * 32 + lane);
        const uint32_t fm = 0xff000000u >> b0;
        uint2 pf[8], pm[4];
#pragma unroll
        for (int r = 0; r < 8; r++) pf[r] = ld_acc(fr + r * 32, (fm >> r) & 1);
#pragma unroll
        for (int r = 0; r < 4; r++) pm[r] = ld_acc(cm + r * 32, b0 > 4);
#pragma unroll 1
        for (int h = hm > 3 ? 5 : 3; h >= 3; h -= 2) {
            if (h <= hm) bg_half<0>(acc, win, ta + (h - 1) * 1792, qo + (28 - 4 * h) * 128, ~0u, buf + CB_U);
            if (h == 3 && i == 0) mbar_wait(sb + B_BAR + (CB_UF + j) * 8, (b0 - 1) & 1);
            bg_half<4>(acc, win, ta + (h - 2) * 1792, qo + (h == 3 ? b0 - 4 : 12) * 128, h == 3 ? 1023u : ~0u, h == 3 ? sb + C_UR + chl * 1024 : buf + CB_U);
        }
        uint4 wm[8];
#pragma unroll
        for (int r = 1; r < 8; r++) wm[r] = ldsm4(sb + C_UR + (chl ^ 4) * 1024 + ((qo + (b0 + r) * 128) & 1023));
#pragma unroll
        for (int r = 0; r < 8; r++) add_acc(acc[r], pf[r]);
#pragma unroll
        for (int r = 4; r < 8; r++) { st_acc(cr + r * 32, acc[r]); acc[r][0] = blo(pm[r - 4].x); acc[r][1] = bhi(pm[r - 4].x); acc[r][2] = blo(pm[r - 4].y); acc[r][3] = bhi(pm[r - 4].y); }
#pragma unroll
        for (int t = 7; t >= 0; t--) {
            const uint4 a = lds128(ta + t * 224), e = lds128(ta + CB_M + t * 224);
#pragma unroll
            for (int r = 0; r < 4; r++) { const uint4& x = win[4 + r - (t >> 1)]; mma16(acc[r], a.x, a.y, a.z, a.w, (t & 1) ? x.z : x.x, (t & 1) ? x.w : x.y); }
#pragma unroll
            for (int r = 0; r < 4; r++) { const uint4& x = wm[4 + r - (t >> 1)]; mma16(acc[4 + r], e.x, e.y, e.z, e.w, (t & 1) ? x.z : x.x, (t & 1) ? x.w : x.y); }
        }
#pragma unroll
        for (int r = 0; r < 4; r++) { st_acc(cr + r * 32, acc[r]); st_acc(cm + r * 32, acc[4 + r]); }
        __syncwarp();
        if (lane == 0 && i) mbar_arrive(sb + B_BAR + (CB_CF + j) * 8);
        PROF(j == 0 && lane == 0 && i, 2048 + b0 * 8 + 7);
    }
}
__device__ __forceinline__ void conv_far(uint32_t sb, int w) {
    const int lane = __shfl_sync(0xffffffffu, threadIdx.x & 31, threadIdx.x & 31), g = lane >> 2, c = lane & 3;
    wait_cnt_warp(g_gate, lds32(sb + S_GATE));
    wait_cnt_warp(cnt_ptr(C_XN + 39), 16);
    const uint32_t to = (6 + g - 2 * c) * 16, qo = (lane & 7) * 16 - (lane >> 3) * 32;
#pragma unroll 1
    for (int n = -1; n * 12 + w < 512; n++) {
        const int t = n * 12 + w, ch = (t & 63) * 8 + (((t >> 6) + 1) & 7), cn = ((t + 12) & 63) * 8 + ((((t + 12) >> 6) + 1) & 7);
        const uint32_t bar = sb + B_BAR + (w * 2 + (n & 1)) * 8, buf = sb + (w * 2 + (n & 1)) * 5120;
        if (t + 12 < 512 && elect()) {
            const uint32_t nb = sb + (w * 2 + (~n & 1)) * 5120;
            mbar_expect(bar ^ 8, 3584 + 1152);
            bulk_g2s(nb, g_W + cn * 784 + 560, 3584, bar ^ 8, POL_N);
            bulk_g2s(nb + 3584, g_u + cn * (UROW / 2) + UPRE / 2 - 32, 1152, bar ^ 8, POL_N);
        }
        __syncwarp();
        if (n < 0) continue;
        float acc[8][4];
        uint4 win[8];
#pragma unroll
        for (int r = 0; r < 8; r++) { acc[r][0] = acc[r][1] = acc[r][2] = acc[r][3] = 0; win[r] = make_uint4(0, 0, 0, 0); }
        mbar_wait(bar, (n >> 1) & 1);
        bg_half<0, true>(acc, win, buf + to + 1792, qo + 128, ~0u, buf + 3584);
        bg_half<4, true>(acc, win, buf + to, qo + 640, ~0u, buf + 3584);
#pragma unroll
        for (int r = 0; r < 8; r++) st_acc(g_far + (ch * 256 + lane) + r * 32, acc[r]);
        __syncwarp();
        if (((t + 12) ^ t) >= 256 && elect()) red_release(cnt_ptr(C_FAR + (t >> 8)), 1);
        __syncwarp();
    }
    PROF(threadIdx.x == 0, 2048);
}

constexpr int P_X = 131072  , P_K6 = P_X + 32768  , P_P = P_K6 + 10496  , P_U = P_P + 33280  ,
              P_END = P_U + 17408, P_PRM = P_P + 8192  , P_Y = P_P  ;
static_assert(P_END <= B_BAR && P_END <= R_SEL, "prologue scratch");
#define KGUN 2
constexpr int KGU = KGUN;
__device__ __forceinline__ void csq(float& r, float& i) { const float t = r * i; r = fmaf(r, r, -(i * i)); i = t + t; }
__device__ __forceinline__ void cpow(float ar, float ph, float p, float& r, float& i) {
    const float e = ex2(ar * p);
    const float u = ph * p, n = fabsf(u) < 4194304.f ? (u + 12582912.f) - 12582912.f : u;
    const float t = (u - n) * 6.283185307179586f;
    r = e * __cosf(t); i = e * __sinf(t);
}
__device__ __forceinline__ void mma_tf32(float* c, float a0, float a1, float a2, float a3, float b0, float b1) {
    asm volatile("mma.sync.aligned.m16n8k8.row.col.f32.tf32.tf32.f32 {%0,%1,%2,%3},{%4,%5,%6,%7},{%8,%9},{%0,%1,%2,%3};"
                 : "+f"(c[0]), "+f"(c[1]), "+f"(c[2]), "+f"(c[3])
                 : "r"(__float_as_uint(a0)), "r"(__float_as_uint(a1)), "r"(__float_as_uint(a2)), "r"(__float_as_uint(a3)), "r"(__float_as_uint(b0)), "r"(__float_as_uint(b1)));
}

__device__ __forceinline__ void early_fetch(const Params& p, uint32_t sb) {
    const int v = blockIdx.x;
    if (elect()) {
        if (v >= V_QKV) { if (v < V_QKV + NQ && (p.roles & 8)) qkv_fetch(p, sb, v - V_QKV, 0, Q_PRE); }
        else if (v >= V_OP) { if (p.roles & 4) op_fetch(p, sb, v - V_OP, 0); }
        else if (v >= V_REC && (p.roles & 2)) { rec_fetch(p, sb, (v - V_REC) >> 1, v & 1, 0, R_STQ); rec_fetch(p, sb, (v - V_REC) >> 1, v & 1, 2, R_WV); }
    }
    __syncwarp();
}
struct ProRegs { uint32_t v[2][4], ldt[2]; };
__device__ __forceinline__ void prologue_load(const ProArgs& a, int b, ProRegs& pr) {
    const int w = threadIdx.x >> 5;
#pragma unroll
    for (int i = 0; i < 2; i++) {
        const int gi = b * 512 + (w & 3) * 128 + ((w >> 2) & 1) * 64 + i * 32 + (threadIdx.x & 31);
        pr.ldt[i] = __ldg((const uint16_t*)a.ldt + b * 4 + (w & 3));
        pr.v[i][0] = __ldg((const uint16_t*)a.lAr + gi); pr.v[i][1] = __ldg((const uint16_t*)a.Ai + gi);
        pr.v[i][2] = __ldg((const uint16_t*)a.Cr + gi); pr.v[i][3] = __ldg((const uint16_t*)a.Ci + gi);
    }
}
__device__ __forceinline__ void prologue(const Params& p, uint32_t sb, int b, int w, const ProRegs& pr) {
    const ProArgs& a = p.pa;
    const int tid = threadIdx.x, lane = tid & 31, g = lane >> 2, c = lane & 3;
    const int d0 = b * 4;
    if (w >= 8) {
        const int t2 = tid - 256;
        if (w < 10) {
            const int row = b * 16 + (w - 8) * 8 + g;
            uint4 v[16];
            const float2 r = row_stats512(v, (const uint4*)(a.x + (size_t)row * 512) + c, 8, 4);
            const float2 l = ln_finish(r.x * (1.f / 512.f), r.y * (1.f / 512.f));
            if (c == (g >> 1)) asm volatile("st.relaxed.gpu.global.u32 [%0],%1;" ::"l"(g_ln0 + row), "r"(pack2(l.x, l.y)) : "memory");
        }
        else if (b + 4 >= V_REC && b + 4 < V_OP) rec_slots(b + 4 - V_REC, w - 10);
        PROF(t2 == 0, 3516);
        const int gi = b * 128 + t2;
        g_st[gi] = make_uint4(~0u, ~0u, ~0u, ~0u);
        if (gi < 900 * 8) g_cnt[gi] = 0;
        bar_sync(6, 384);
        if (lane < 4 && ((PFM >> (w - 8)) & 1)) asm volatile("cp.async.bulk.prefetch.L2.global [%0],%1;" ::"l"(a.W[w - 8] + (b * 4 + lane) * 4096), "r"(8192) : "memory");
        bar_sync(9, 384);
        if (w == 10) early_fetch(p, sb);
#pragma unroll 2
        for (int i = t2; i < 4 * 784; i += 128) {
            const int ch = i / 784, k = i - ch * 784;
            const uint32_t o = sb + P_P + (ch * 2080 + 266 + (k / 14) * 18 + k) * 4;
            g_W[d0 * 784 + i] = make_uint4(lds32(o), lds32(o + 32), lds32(o + 64), lds32(o + 96));
        }
        bar_arrive(10, 384);
        PROF(t2 == 0, 3517);
        return;
    }
#pragma unroll
    for (int i = 0; i < 2; i++) {
        const float dt = rbf(expf(blo(pr.ldt[i])));
        const float ar = -rbf(expf(blo(pr.v[i][0]))) * dt, ai = blo(pr.v[i][1]) * dt;
        sts128(sb + P_PRM + (w * 64 + i * 32 + lane) * 16, __float_as_uint(ar * 1.4426950408889634f), __float_as_uint(ai * 0.15915494309189535f),
               __float_as_uint(2.f * (blo(pr.v[i][2]) * dt)), __float_as_uint(2.f * (blo(pr.v[i][3]) * dt)));
    }
    if (tid < 64) sts128(sb + P_U + (tid >> 3) * 2176 + (tid & 7) * 16, 0, 0, 0, 0);
    bar_arrive(6, 384);
    __syncwarp();
    PROF(tid == 0, 3510);
    const int ch = w & 3, hf = w >> 2;
    {
        float k0[4] = {0, 0, 0, 0}, k1[4] = {0, 0, 0, 0}, k2[4] = {0, 0, 0, 0}, k3[4] = {0, 0, 0, 0}, k4[4] = {0, 0, 0, 0}, kl = 0;
#pragma unroll KGU
        for (int j = 0; j < 16; j++) {
            const uint4 q = lds128(sb + P_PRM + (w * 64 + j * 4 + c) * 16);
            const float cr = __uint_as_float(q.z), ci = __uint_as_float(q.w);
            float wr[4], wi[4], vr[4], vi[4];
            cpow(__uint_as_float(q.x), __uint_as_float(q.y), (float)g, wr[0], wi[0]);
            cpow(__uint_as_float(q.x), __uint_as_float(q.y), (float)(g + 8), vr[0], vi[0]);
#pragma unroll
            for (int i = 1; i < 4; i++) { wr[i] = wr[i - 1]; wi[i] = wi[i - 1]; csq(wr[i], wi[i]); vr[i] = vr[i - 1]; vi[i] = vi[i - 1]; csq(vr[i], vi[i]); }
            float hr = wr[3], hi = wi[3];
            csq(hr, hi);
            mma_tf32(k0, wr[0], vr[0], wi[0], vi[0], cr * hr - ci * hi, -(cr * hi + ci * hr));
            hr = vr[3]; hi = vi[3]; csq(hr, hi);
            mma_tf32(k1, wr[0], vr[0], wi[0], vi[0], cr * hr - ci * hi, -(cr * hi + ci * hr));
            csq(hr, hi);
            mma_tf32(k2, wr[1], vr[1], wi[1], vi[1], cr * hr - ci * hi, -(cr * hi + ci * hr));
            csq(hr, hi);
            mma_tf32(k3, wr[2], vr[2], wi[2], vi[2], cr * hr - ci * hi, -(cr * hi + ci * hr));
            csq(hr, hi);
            mma_tf32(k4, wr[3], vr[3], wi[3], vi[3], cr * hr - ci * hi, -(cr * hi + ci * hr));
            csq(hr, hi);
            kl += cr * hr - ci * hi;
        }
        kl += __shfl_xor_sync(0xffffffffu, kl, 1); kl += __shfl_xor_sync(0xffffffffu, kl, 2);
        const uint32_t o = sb + P_K6 + (ch * 656 + c * 32 + g) * 4, ol = sb + P_K6 + (ch * 656 + 640) * 4;
#define KST(k, base) sts32(o + (base) * 4, __float_as_uint(k[0])); sts32(o + (base) * 4 + 64, __float_as_uint(k[1])); \
                     sts32(o + (base) * 4 + 32, __float_as_uint(k[2])); sts32(o + (base) * 4 + 96, __float_as_uint(k[3]))
#define KAD(k, base) k[0] += __uint_as_float(lds32(o + (base) * 4)); k[1] += __uint_as_float(lds32(o + (base) * 4 + 64)); \
                     k[2] += __uint_as_float(lds32(o + (base) * 4 + 32)); k[3] += __uint_as_float(lds32(o + (base) * 4 + 96))
        if (hf == 0) {
            bar_sync(2 + ch, 64);
            KAD(k0, 0); KAD(k1, 128); KAD(k2, 256); KAD(k3, 384); KAD(k4, 512);
            kl += __uint_as_float(lds32(ol));
            __syncwarp();
        }
        KST(k0, 0); KST(k1, 128); KST(k2, 256); KST(k3, 384); KST(k4, 512);
        if (lane == 0) sts32(ol, __float_as_uint(kl));
        if (hf == 1) { __syncwarp(); bar_arrive(2 + ch, 64); }
    }
    PROF(tid == 0, 3511);
    {
        uint4 l0, l1;
        int n = 0;
        while (true) {
            l0 = ld_rlx128((const uint4*)g_ln0 + tid * 2); l1 = ld_rlx128((const uint4*)g_ln0 + tid * 2 + 1);
            if (__all_sync(0xffffffffu, l0.x && l0.y && l0.z && l0.w && l1.x && l1.y && l1.z && l1.w)) break;
            if (++n > 2000000) __trap();
        }
        sts128(sb + P_P + tid * 32, l0.x, l0.y, l0.z, l0.w); sts128(sb + P_P + tid * 32 + 16, l1.x, l1.y, l1.z, l1.w);
        bar_sync(8, 384);
        mbar_wait(sb + S_XBAR, 0);
        __syncwarp();
#pragma unroll 2
        for (int i = 0; i < 8; i++) {
            const int t = w * 256 + i * 32 + lane;
            const uint32_t ln = lds32(sb + P_P + t * 4);
            const uint2 x = lds64(sb + P_X + t * 16 + (b & 1) * 8);
            const float m = blo(ln), rs = rcp(bhi(ln));
            const uint32_t u0 = pack2(rbf(blo(x.x) - m) * rs, rbf(bhi(x.x) - m) * rs), u1 = pack2(rbf(blo(x.y) - m) * rs, rbf(bhi(x.y) - m) * rs);
            sts128(sb + P_X + t * 16, x.x, x.y, u0, u1);
            const uint32_t o = sb + P_U + ((t >> 3) & 1) * 2176 + ((t >> 4) + 8) * 16 + (t & 7) * 2;
            asm volatile("st.shared.u16 [%0],%1;" ::"r"(o), "h"((uint16_t)u0) : "memory");
            asm volatile("st.shared.u16 [%0],%1;" ::"r"(o + 4352), "h"((uint16_t)(u0 >> 16)) : "memory");
            asm volatile("st.shared.u16 [%0],%1;" ::"r"(o + 8704), "h"((uint16_t)u1) : "memory");
            asm volatile("st.shared.u16 [%0],%1;" ::"r"(o + 13056), "h"((uint16_t)(u1 >> 16)) : "memory");
        }
    }
    bar_sync(1, 256);
    PROF(tid == 0, 3512);
    if (tid < 64) sts32(sb + P_P + ((tid >> 4) * 2080 + (tid & 15)) * 4, 0);
#pragma unroll 1
    for (int x = tid; x < 2048; x += 512) {
        uint32_t pw[2][4];
#pragma unroll
        for (int h = 0; h < 2; h++) {
            const int y = x + h * 256;
            const int i0 = y <= 256 ? y : 256 + (int)((pack2((float)y, 0.f) & 0xffff) - 0x4380);
            const int i1 = y <= 256 ? max(y - 1, 0) : 256 + (int)((pack2((float)(y - 1), 0.f) & 0xffff) - 0x4380);
#pragma unroll
            for (int k = 0; k < 4; k++) {
                const float lo = __uint_as_float(lds32(sb + P_K6 + k * 2624 + i0 * 4)), hi = __uint_as_float(lds32(sb + P_K6 + k * 2624 + i1 * 4));
                pw[h][k] = pack2(lo, y ? hi : 0.f);
            }
        }
#pragma unroll
        for (int h = 0; h < 2; h++)
#pragma unroll
            for (int k = 0; k < 4; k++) sts32(sb + P_P + (k * 2080 + x + h * 256 + 16) * 4, pw[h][k]);
    }
    fence_async_smem();
    bar_arrive(9, 384);
    bar_sync(1, 256);
    if (tid < 4) {
        asm volatile("cp.async.bulk.global.shared::cta.bulk_group [%0],[%1],%2;" ::"l"(g_P + (d0 + tid) * PROW), "r"(sb + P_P + tid * 8320), "r"(PROW * 4) : "memory");
        asm volatile("cp.async.bulk.commit_group;" ::: "memory");
    }
    __syncwarp();
    PROF(tid == 0, 3513);
    {
        float acc[16][4];
#pragma unroll
        for (int j = 0; j < 16; j++) acc[j][0] = acc[j][1] = acc[j][2] = acc[j][3] = 0;
#pragma unroll 1
        for (int e = hf * 4; e < hf * 4 + 4; e++) {
            uint32_t B[16][2];
            const uint32_t ua = sb + P_U + ch * 4352 + ((lane >> 3) & 1) * 2176 + (8 + (lane >> 4) * 8 + (lane & 7) - e) * 16;
#pragma unroll
            for (int j = 0; j < 8; j++) { const uint4 v = ldsm4(ua + j * 256); B[2 * j][0] = v.x; B[2 * j][1] = v.y; B[2 * j + 1][0] = v.z; B[2 * j + 1][1] = v.w; }
            const uint32_t pa = sb + P_P + (ch * 2080 + 16 + e * 16 + g - 2 * c) * 4;
#pragma unroll
            for (int d = 0; d < 16; d++) {
                const uint32_t a0 = lds32(pa + d * 512), a1 = lds32(pa + d * 512 + 32), a2 = lds32(pa + d * 512 - 32);
#pragma unroll
                for (int j = d; j < 16; j++) mma16(acc[j], a0, a1, a2, a0, B[j - d][0], B[j - d][1]);
            }
        }
        PROF(tid == 0, 3514);
        const uint32_t o = sb + P_Y + (ch * 2560 + c * 40 + g) * 4;
        if (tid < 4) asm volatile("cp.async.bulk.wait_group 0;" ::: "memory");
        __syncwarp();
        bar_sync(10, 384);
        if (hf == 0) {
            bar_sync(2 + ch, 64);
#pragma unroll
            for (int j = 0; j < 16; j++) {
                acc[j][0] += __uint_as_float(lds32(o + j * 640)); acc[j][1] += __uint_as_float(lds32(o + j * 640 + 80));
                acc[j][2] += __uint_as_float(lds32(o + j * 640 + 32)); acc[j][3] += __uint_as_float(lds32(o + j * 640 + 112));
            }
        }
#pragma unroll
        for (int j = 0; j < 16; j++) {
            sts32(o + j * 640, __float_as_uint(acc[j][0])); sts32(o + j * 640 + 80, __float_as_uint(acc[j][1]));
            sts32(o + j * 640 + 32, __float_as_uint(acc[j][2])); sts32(o + j * 640 + 112, __float_as_uint(acc[j][3]));
        }
        if (hf == 1) bar_arrive(2 + ch, 64);
    }
    const uint2 dk = __ldg((const uint2*)(a.Dk + d0));
    bar_sync(1, 256);
#pragma unroll 2
    for (int i = 0; i < 8; i++) {
        const int t = i * 256 + tid;
        const uint32_t o = sb + P_Y + (t + 4 * (t >> 4)) * 4;
        const uint4 xu = lds128(sb + P_X + t * 16);
        float y[4];
#pragma unroll
        for (int k = 0; k < 4; k++) y[k] = rbf(__uint_as_float(lds32(o + k * 10240)));
        uint2 r;
        r.x = pack2(blo(xu.x) + rbf(y[0] + rbf(blo(xu.z) * blo(dk.x))), bhi(xu.x) + rbf(y[1] + rbf(bhi(xu.z) * bhi(dk.x))));
        r.y = pack2(blo(xu.y) + rbf(y[2] + rbf(blo(xu.w) * blo(dk.y))), bhi(xu.y) + rbf(y[3] + rbf(bhi(xu.w) * bhi(dk.y))));
        ((uint2*)g_x)[b * 2 * XP + t] = r;
    }
    PROF(tid == 0, 3515);
}

__global__ void __cluster_dims__(2, 1, 1) __launch_bounds__(384, 1) main_kernel(const __grid_constant__ Params p) {
    extern __shared__ __align__(1024) uint8_t smem[];
    const uint32_t sb = smem_u32(smem);
    uint32_t rank; asm("mov.u32 %0,%%cluster_ctarank;" : "=r"(rank));
    const int wi = __shfl_sync(0xffffffffu, threadIdx.x >> 5, 0);
    const int v = blockIdx.x, cl = v >> 1, wg = wi >> 2;
    PROF(threadIdx.x == 0, 3500);
    ProRegs pr;
    prologue_load(p.pa, max((int)blockIdx.x - 4, 0), pr);
    if (wi == 11 && p.dopro && cl >= 2 && elect()) {
        mbar_init(sb + S_XBAR, 1);
        asm volatile("fence.mbarrier_init.release.cluster;" ::: "memory");
        mbar_expect(sb + S_XBAR, 32768);
        for (int j = 0; j < 8; j++) tma2d(sb + P_X + j * 4096, &p.tm[3], ((blockIdx.x - 4) >> 1) * 8, j * 256, sb + S_XBAR);
    }
    if (threadIdx.x == 320) {
        unsigned v = 0;
        if (p.dopro) {
            asm volatile("ld.relaxed.gpu.global.u32 %0,[%1];" : "=r"(v) : "l"(g_gate) : "memory");
            v = (v / (4 * NCL) + 1) * (4 * NCL);
        }
        sts32(sb + S_GATE, v);
    }
    __syncwarp();
    if (wi == 10) {
        if (v < V_REC || v == 131) conv_init(sb, v == 131); else if (v < V_OP) rec_init(sb); else gemm_init(sb, v < V_QKV);
        __syncwarp();
    }
    if (wg == 2) bar_arrive(8, 384);
    asm volatile("barrier.cluster.arrive.relaxed.aligned;" ::: "memory");
    if (p.dopro && cl >= 2) prologue(p, sb, blockIdx.x - 4, wi, pr); else if (wg < 2) bar_sync(8, 384); else if (wi == 10) early_fetch(p, sb);
    asm volatile("barrier.cluster.wait.aligned;" ::: "memory");
    const int role = (v < V_REC ? 1 : v < V_OP ? 2 : v < V_QKV ? 4 : v < V_QKV + NQ ? 24 : 1) & p.roles;
    fence_async_smem();
    bar_sync(wg == 2 ? 7 : 1, wg == 2 ? 128 : 256);
    if (p.dopro && (threadIdx.x == 32 || threadIdx.x == 352)) red_release(g_gate, 1);
    PROF(threadIdx.x == 32, 3509);
    if (wi == 0 && (role & 8) && elect()) qkv_stage(p, sb + 131072, sb + G_BAR + GB_RS * 8, v - V_QKV, 0, 6);
    PROF(threadIdx.x == 0, 3506);
    __syncwarp();
    if (p.dopro && v >= V_REC && v < V_QKV && (v < V_OP ? wi == 8 : wi < 8)) {
        bool on = v >= V_OP;
#pragma unroll 1
        for (int r = on ? 64 + (v - V_OP) * 8 + wi : v - V_REC; r < 512;) {
            if (on) wait_flag_warp(g_gate, lds32(sb + S_GATE));
            PROF(threadIdx.x == 256 && on, 3507);
            x1_norm(on ? (const uint2*)g_x : (const uint2*)p.pa.W[0], r, on);
            __syncwarp();
            if (on && elect()) red_release(cnt_ptr(C_XN + (r >> 4)), 1);
            __syncwarp();
            PROF(threadIdx.x == 256, on ? 3508 : 3499);
            if (on) r += v < V_OP ? 512 : 128;
            on = true;
        }
    }
    if (role == 2) {
        const int head = (v - V_REC) >> 1;
        if (wi == 0 && elect()) rec_fetch(p, sb, head, rank, 1, R_STK);
        __syncwarp();
        if (wg == 2) {
            reg_dec<RH>();
            const int w = wi & 3;
            wait_cnt_warp(g_gate, lds32(sb + S_GATE));
            if (w < 2) { const uint32_t x = __ldcg(g_sel + (threadIdx.x & 63)); sts32(sb + R_SEL + (threadIdx.x & 63) * 4, (x | x >> 16) & 15); }
            __syncthreads();
            cluster_sync();
            if ((p.chains >> (w & 1)) & 1) { if (w < 2) rec_comm(p, sb, w, head, rank); else rec_attn(p, sb, w & 1, head, rank); }
        } else {
            reg_inc<RW0>();
            rec_weights(p, sb, head, rank, wi);
        }
    } else if (role == 1) {
        if (v == 131) conv_far(sb, wi); else if (wg == 2) { reg_dec<RCB>(); conv_back(sb, v, wi & 3); } else { reg_inc<RCU>(); conv_tile(p, sb, v, wi); }
    } else if (role == 4) {
        if (wg == 2) {
            reg_dec<40>();
            if (wi == 8) gemm_producer<true>(p, sb, v - V_OP); else if (wi == 9) gemm_release<true>(p, sb, v - V_OP);
        } else { reg_inc<232>(); gemm_consumer<true>(p, sb, v - V_OP, wi); }
    } else if (role) {
        if (wg == 2) {
            reg_dec<40>();
            if (wi < 10) {
                if (role & 8) { if (wi == 8) gemm_producer<false>(p, sb, v - V_QKV); else gemm_release<false>(p, sb, v - V_QKV); }
            } else if (v < V_QKV + 32 && (role & 16)) fin_warp(p, sb, (v - V_QKV) * 2 + wi - 10);
        } else { reg_inc<232>(); if (role & 8) gemm_consumer<false>(p, sb, v - V_QKV, wi); }
    }
    __syncwarp();
    cluster_sync();
}

typedef CUresult (*EncFn)(CUtensorMap*, CUtensorMapDataType, cuuint32_t, void*, const cuuint64_t*, const cuuint64_t*, const cuuint32_t*, const cuuint32_t*,
                          CUtensorMapInterleave, CUtensorMapSwizzle, CUtensorMapL2promotion, CUtensorMapFloatOOBfill);
constexpr int SMEM_BYTES = 232448;
#define LAG 8
#define QLEAD 6
#define OLEAD (LAG / 2 + 2)
void plan(Params& P) {
    P.roles = 31; P.chains = 3; P.lag = LAG; P.dopro = 1;
    for (int r = 0; r < 2; r++) {
        const int lead = r ? OLEAD : QLEAD;
        int n = 0;
        for (int i = 0; i < 32 + lead; i++) {
            if (i >= lead) P.list[r][n++] = 32 + i - lead;
            if (i < 32) P.list[r][n++] = i;
        }
        P.nl[r] = n;
    }
}

#define TK() do {} while (0)
}

extern "C" void kernel_launch(void* const* d_in, const int* in_sizes, int n_in, void* d_out, int out_size) {
    typedef const __nv_bfloat16* BP;
    static EncFn enc = nullptr;
    if (!enc) {
        void* fn = nullptr; cudaDriverEntryPointQueryResult qr;
        cudaGetDriverEntryPoint("cuTensorMapEncodeTiled", &fn, cudaEnableDefault, &qr);
        enc = (EncFn)fn;
        cudaFuncSetAttribute(main_kernel, cudaFuncAttributeMaxDynamicSharedMemorySize, SMEM_BYTES);
    }
    static Params P;
    for (int i = 0; i < 4; i++) {
        const cuuint64_t cols = i < 3 ? 4096 : 512, rows = i < 3 ? 512 : 4096;
        cuuint64_t d2[2] = {cols, rows}, str[1] = {cols * 2};
        cuuint32_t box[2] = {64, 64}, bn[2] = {16, 256}, es[2] = {1, 1};
        enc(&P.tm[i < 3 ? i : 4], CU_TENSOR_MAP_DATA_TYPE_BFLOAT16, 2, d_in[9 + i], d2, str, box, es, CU_TENSOR_MAP_INTERLEAVE_NONE, CU_TENSOR_MAP_SWIZZLE_128B,
            CU_TENSOR_MAP_L2_PROMOTION_L2_128B, CU_TENSOR_MAP_FLOAT_OOB_FILL_NONE);
        if (i < 2) enc(&P.tn[i], CU_TENSOR_MAP_DATA_TYPE_BFLOAT16, 2, d_in[9 + i], d2, str, bn, es, CU_TENSOR_MAP_INTERLEAVE_NONE, CU_TENSOR_MAP_SWIZZLE_32B,
                       CU_TENSOR_MAP_L2_PROMOTION_L2_128B, CU_TENSOR_MAP_FLOAT_OOB_FILL_NONE);
    }
    {
        cuuint64_t dims[2] = {512, 2048}, str[1] = {1024};
        cuuint32_t box[2] = {8, 256}, es[2] = {1, 1};
        enc(&P.tm[3], CU_TENSOR_MAP_DATA_TYPE_BFLOAT16, 2, d_in[0], dims, str, box, es, CU_TENSOR_MAP_INTERLEAVE_NONE, CU_TENSOR_MAP_SWIZZLE_NONE,
            CU_TENSOR_MAP_L2_PROMOTION_NONE, CU_TENSOR_MAP_FLOAT_OOB_FILL_NONE);
    }
    P.mem0 = (BP)d_in[8]; P.Wo = (BP)d_in[12]; P.Dskip = (BP)d_in[6]; P.out = (__nv_bfloat16*)d_out;
    cudaStream_t s = cudaStreamPerThread;
    P.pa = {(BP)d_in[0], (BP)d_in[1], (BP)d_in[2], (BP)d_in[3], (BP)d_in[4], (BP)d_in[5], (BP)d_in[6], {(BP)d_in[9], (BP)d_in[10], (BP)d_in[11], (BP)d_in[12]}};
    plan(P);
    TK(); main_kernel<<<2 * NCL, 384, SMEM_BYTES, s>>>(P); TK();
}
```

```cpp
#include <cuda_runtime.h>
#include <cuda_bf16.h>
#include <cuda.h>
#include <stdint.h>
#include <string.h>
#include <math.h>

namespace {

constexpr int NCL = 66;
constexpr int NQ = 43;
constexpr int V_REC = 8, V_OP = 72, V_QKV = 88;

#define XP 1024
__device__ uint4 g_x[2 * 128 * XP];
__device__ uint4 g_xn[64 * 4096];
__device__ uint4 g_st[64 * 256];
__device__ uint4 g_qkv[128 * 32 * 1536];
__device__ uint4 g_o[64 * 64 * 512];
__device__ uint4 g_pp[64 * 4 * 4096];
__device__ uint4 g_xch[133 * 512];
__device__ unsigned g_sel[64];
__device__ unsigned g_gate[32];
__device__ __align__(16) uint32_t g_P[512 * 272];
__device__ uint4 g_W[512 * 784];
__device__ __align__(16) uint32_t g_u[512 * 1152];
__device__ uint2 g_carry[512 * 40 * 32];
__device__ uint2 g_far[512 * 8 * 32];
__device__ unsigned g_cnt[900 * 8];
__device__ uint32_t g_ln0[2048];

enum { C_XN = 0  , C_QKV = 64  , C_O = 128  , C_PP = 384  , C_FAR = 896 };
__device__ __forceinline__ unsigned* cnt_ptr(int i) { return g_cnt + i * 8; }

struct ProArgs { const __nv_bfloat16 *x, *lAr, *Ai, *Cr, *Ci, *ldt, *Dk, *W[4]; };
struct Params {
    CUtensorMap tm[5];
    CUtensorMap tn[2];
    ProArgs pa;
    int dopro;
    const __nv_bfloat16* mem0;
    const __nv_bfloat16* Wo;
    const __nv_bfloat16* Dskip;
    __nv_bfloat16* out;
    int roles;
    int chains;
    int lag;
    int zero;
    int nl[2];
    uint8_t list[2][64];
};

__device__ __forceinline__ uint32_t smem_u32(const void* p) { return (uint32_t)__cvta_generic_to_shared(p); }
__device__ __forceinline__ uint32_t mapa(uint32_t a, uint32_t r) {
    uint32_t o; asm("mapa.shared::cluster.u32 %0,%1,%2;" : "=r"(o) : "r"(a), "r"(r)); return o;
}
__device__ __forceinline__ void mbar_init(uint32_t b, int c) { asm volatile("mbarrier.init.shared::cta.b64 [%0],%1;" ::"r"(b), "r"(c) : "memory"); }
__device__ __forceinline__ void mbar_expect(uint32_t b, int bytes) { asm volatile("mbarrier.arrive.expect_tx.shared::cta.b64 _,[%0],%1;" ::"r"(b), "r"(bytes) : "memory"); }
__device__ __forceinline__ void mbar_arrive(uint32_t b) { asm volatile("mbarrier.arrive.shared::cta.b64 _,[%0];" ::"r"(b) : "memory"); }
__device__ __forceinline__ void mbar_arrive_cluster(uint32_t b) { asm volatile("mbarrier.arrive.shared::cluster.b64 _,[%0];" ::"r"(b) : "memory"); }
__device__ __forceinline__ void mbar_wait(uint32_t b, uint32_t ph) {
    asm volatile(
        "{.reg .pred p; .reg .u32 n; mov.u32 n,0;\n"
        "W%=: mbarrier.try_wait.parity.shared::cta.b64 p,[%0],%1;\n"
        "@p bra D%=;\n"
        "add.u32 n,n,1; setp.lt.u32 p,n,2000000; @p bra W%=;\n"
        "trap;\n"
        "D%=: }" ::"r"(b), "r"(ph) : "memory");
}
__device__ __forceinline__ bool wait_lds128(uint32_t b, uint32_t ph, uint32_t a, uint4& v) {
    uint32_t ok;
    asm volatile("{.reg .pred p; mbarrier.try_wait.parity.shared::cta.b64 p,[%5],%6,20000; ld.shared.v4.u32 {%0,%1,%2,%3},[%7]; selp.u32 %4,1,0,p;}"
                 : "=r"(v.x), "=r"(v.y), "=r"(v.z), "=r"(v.w), "=r"(ok) : "r"(b), "r"(ph), "r"(a) : "memory");
    return ok;
}
__device__ __forceinline__ bool wait_lds64(uint32_t b, uint32_t ph, uint32_t a, uint2& v) {
    uint32_t ok;
    asm volatile("{.reg .pred p; mbarrier.try_wait.parity.shared::cta.b64 p,[%3],%4,20000; ld.shared.v2.u32 {%0,%1},[%5]; selp.u32 %2,1,0,p;}"
                 : "=r"(v.x), "=r"(v.y), "=r"(ok) : "r"(b), "r"(ph), "r"(a) : "memory");
    return ok;
}
template <int PH> __device__ __forceinline__ void mbar_wait_c(uint32_t b) {
    asm volatile(
        "{.reg .pred p; .reg .u32 n; mov.u32 n,%2;\n"
        "W%=: mbarrier.try_wait.parity.shared::cta.b64 p,[%0],%1;\n"
        "@p bra D%=;\n"
        "add.u32 n,n,1; setp.lt.u32 p,n,2000000; @p bra W%=;\n"
        "trap;\n"
        "D%=: }" ::"r"(b), "n"(PH), "n"(PH) : "memory");
}
__device__ __forceinline__ bool elect() {
    uint32_t r; asm volatile("{.reg .pred p; elect.sync _|p,0xffffffff; selp.u32 %0,1,0,p;}" : "=r"(r)); return r;
}
__device__ __forceinline__ void bar_sync(int id, int n) { asm volatile("bar.sync %0,%1;" ::"r"(id), "r"(n) : "memory"); }
__device__ __forceinline__ void bar_arrive(int id, int n) { asm volatile("bar.arrive %0,%1;" ::"r"(id), "r"(n) : "memory"); }
__device__ __forceinline__ void cluster_sync() { asm volatile("barrier.cluster.arrive.relaxed.aligned; barrier.cluster.wait.aligned;" ::: "memory"); }
__device__ __forceinline__ void fence_async() { asm volatile("fence.proxy.async;" ::: "memory"); }
__device__ __forceinline__ void fence_async_smem() { asm volatile("fence.proxy.async.shared::cta;" ::: "memory"); }
#define EFR 1
#define EFW 2
constexpr uint64_t POL_N = 0x1000000000000000ull, POL_F = 0x12F0000000000000ull;
constexpr uint64_t POL_LAST = EFR ? POL_F : POL_N  , POL_LATE = EFW ? POL_F : POL_N  , POL_SOON = EFW > 1 ? POL_F : POL_N;
__device__ __forceinline__ void bulk_g2s(uint32_t dst, const void* src, int bytes, uint32_t bar, uint64_t pol) {
    asm volatile("cp.async.bulk.shared::cluster.global.mbarrier::complete_tx::bytes.L2::cache_hint [%0],[%1],%2,[%3],%4;" ::"r"(dst), "l"(src), "r"(bytes), "r"(bar), "l"(pol) : "memory");
}
__device__ __forceinline__ void bulk_g2s_mc(uint32_t dst, const void* src, int bytes, uint32_t bar, uint64_t pol) {
    asm volatile("cp.async.bulk.shared::cluster.global.mbarrier::complete_tx::bytes.multicast::cluster.L2::cache_hint [%0],[%1],%2,[%3],%4,%5;" ::"r"(dst), "l"(src), "r"(bytes), "r"(bar), "h"((uint16_t)3), "l"(pol) : "memory");
}
__device__ __forceinline__ void stg128(uint4* p, uint4 v, uint64_t pol) {
    asm volatile("st.global.L2::cache_hint.v4.u32 [%0],{%1,%2,%3,%4},%5;" ::"l"(p), "r"(v.x), "r"(v.y), "r"(v.z), "r"(v.w), "l"(pol));
}
__device__ __forceinline__ void stg32(uint32_t* p, uint32_t v, uint64_t pol) { asm volatile("st.global.L2::cache_hint.u32 [%0],%1,%2;" ::"l"(p), "r"(v), "l"(pol)); }
__device__ __forceinline__ uint4 ldcg128_last(const uint4* p) {
    uint4 v; asm volatile("ld.global.cg.L2::cache_hint.v4.u32 {%0,%1,%2,%3},[%4],%5;" : "=r"(v.x), "=r"(v.y), "=r"(v.z), "=r"(v.w) : "l"(p), "l"(POL_LAST) : "memory"); return v;
}
__device__ __forceinline__ void tma2d(uint32_t dst, const CUtensorMap* tm, int x, int y, uint32_t bar) {
    asm volatile("cp.async.bulk.tensor.2d.shared::cluster.global.mbarrier::complete_tx::bytes [%0],[%1,{%2,%3}],[%4];" ::"r"(dst), "l"(tm), "r"(x), "r"(y), "r"(bar) : "memory");
}
__device__ __forceinline__ void tma3d(uint32_t dst, const CUtensorMap* tm, int y, int z, uint32_t bar) {
    asm volatile("cp.async.bulk.tensor.3d.shared::cluster.global.mbarrier::complete_tx::bytes [%0],[%1,{0,%2,%3}],[%4];" ::"r"(dst), "l"(tm), "r"(y), "r"(z), "r"(bar) : "memory");
}
__device__ __forceinline__ void st_async4(uint32_t a, uint32_t x, uint32_t y, uint32_t z, uint32_t w, uint32_t mb) {
    asm volatile("st.async.shared::cluster.mbarrier::complete_tx::bytes.v4.b32 [%0],{%1,%2,%3,%4},[%5];" ::"r"(a), "r"(x), "r"(y), "r"(z), "r"(w), "r"(mb) : "memory");
}
__device__ __forceinline__ void st_async2(uint32_t a, uint32_t x, uint32_t y, uint32_t mb) {
    asm volatile("st.async.shared::cluster.mbarrier::complete_tx::bytes.v2.b32 [%0],{%1,%2},[%3];" ::"r"(a), "r"(x), "r"(y), "r"(mb) : "memory");
}
#define LDSQ "ld.shared"
__device__ __forceinline__ uint4 lds128(uint32_t a) { uint4 v; asm volatile(LDSQ ".v4.u32 {%0,%1,%2,%3},[%4];" : "=r"(v.x), "=r"(v.y), "=r"(v.z), "=r"(v.w) : "r"(a) : "memory"); return v; }
__device__ __forceinline__ uint4 lds128v(uint32_t a) { uint4 v; asm volatile("ld.volatile.shared.v4.u32 {%0,%1,%2,%3},[%4];" : "=r"(v.x), "=r"(v.y), "=r"(v.z), "=r"(v.w) : "r"(a) : "memory"); return v; }
__device__ __forceinline__ uint2 lds64(uint32_t a) { uint2 v; asm volatile(LDSQ ".v2.u32 {%0,%1},[%2];" : "=r"(v.x), "=r"(v.y) : "r"(a) : "memory"); return v; }
__device__ __forceinline__ uint32_t lds32(uint32_t a) { uint32_t v; asm volatile(LDSQ ".u32 %0,[%1];" : "=r"(v) : "r"(a) : "memory"); return v; }
__device__ __forceinline__ void sts128(uint32_t a, uint32_t x, uint32_t y, uint32_t z, uint32_t w) { asm volatile("st.shared.v4.u32 [%0],{%1,%2,%3,%4};" ::"r"(a), "r"(x), "r"(y), "r"(z), "r"(w) : "memory"); }
__device__ __forceinline__ void sts64(uint32_t a, uint32_t x, uint32_t y) { asm volatile("st.shared.v2.u32 [%0],{%1,%2};" ::"r"(a), "r"(x), "r"(y) : "memory"); }
__device__ __forceinline__ void sts32(uint32_t a, uint32_t x) { asm volatile("st.shared.u32 [%0],%1;" ::"r"(a), "r"(x) : "memory"); }
__device__ __forceinline__ uint4 ldsm4(uint32_t a) { uint4 v; asm volatile("ldmatrix.sync.aligned.m8n8.x4.shared.b16 {%0,%1,%2,%3},[%4];" : "=r"(v.x), "=r"(v.y), "=r"(v.z), "=r"(v.w) : "r"(a) : "memory"); return v; }
__device__ __forceinline__ uint4 ldsm4t(uint32_t a) { uint4 v; asm volatile("ldmatrix.sync.aligned.m8n8.x4.trans.shared.b16 {%0,%1,%2,%3},[%4];" : "=r"(v.x), "=r"(v.y), "=r"(v.z), "=r"(v.w) : "r"(a) : "memory"); return v; }
__device__ __forceinline__ uint32_t movm(uint32_t a) { uint32_t d; asm volatile("movmatrix.sync.aligned.m8n8.trans.b16 %0,%1;" : "=r"(d) : "r"(a)); return d; }
__device__ __forceinline__ uint32_t pack2(float lo, float hi) { uint32_t d; asm("cvt.rn.bf16x2.f32 %0,%1,%2;" : "=r"(d) : "f"(hi), "f"(lo)); return d; }
__device__ __forceinline__ uint32_t hadd2(uint32_t a, uint32_t b) { uint32_t d; asm("add.rn.bf16x2 %0,%1,%2;" : "=r"(d) : "r"(a), "r"(b)); return d; }
__device__ __forceinline__ uint32_t hmul2(uint32_t a, uint32_t b) { uint32_t d; asm("mul.rn.bf16x2 %0,%1,%2;" : "=r"(d) : "r"(a), "r"(b)); return d; }
__device__ __forceinline__ float blo(uint32_t v) { return __uint_as_float(v << 16); }
__device__ __forceinline__ float bhi(uint32_t v) { return __uint_as_float(v & 0xffff0000u); }
__device__ __forceinline__ float rbf(float x) { return __uint_as_float(pack2(0.f, x)); }
__device__ __forceinline__ float ex2(float x) { float y; asm("ex2.approx.ftz.f32 %0,%1;" : "=f"(y) : "f"(x)); return y; }
__device__ __forceinline__ float rcp(float x) { float y; asm("rcp.approx.ftz.f32 %0,%1;" : "=f"(y) : "f"(x)); return y; }
__device__ __forceinline__ void mma16(float* c, uint32_t a0, uint32_t a1, uint32_t a2, uint32_t a3, uint32_t b0, uint32_t b1) {
    asm volatile("mma.sync.aligned.m16n8k16.row.col.f32.bf16.bf16.f32 {%0,%1,%2,%3},{%4,%5,%6,%7},{%8,%9},{%0,%1,%2,%3};"
                 : "+f"(c[0]), "+f"(c[1]), "+f"(c[2]), "+f"(c[3]) : "r"(a0), "r"(a1), "r"(a2), "r"(a3), "r"(b0), "r"(b1));
}
__device__ __forceinline__ void mma16_top(float& d0, float& d1, uint32_t a0, uint32_t a2, uint32_t b0, uint32_t b1) {
    asm volatile("{.reg .b32 j; .reg .f32 e,f; mma.sync.aligned.m16n8k16.row.col.f32.bf16.bf16.f32 {%0,%1,e,f},{%2,j,%3,j},{%4,%5},{0f00000000,0f00000000,0f00000000,0f00000000};}"
                 : "=f"(d0), "=f"(d1) : "r"(a0), "r"(a2), "r"(b0), "r"(b1));
}
__device__ __forceinline__ void mma8(float* c, uint32_t a0, uint32_t a1, uint32_t b0) {
    asm volatile("mma.sync.aligned.m16n8k8.row.col.f32.bf16.bf16.f32 {%0,%1,%2,%3},{%4,%5},{%6},{%0,%1,%2,%3};"
                 : "+f"(c[0]), "+f"(c[1]), "+f"(c[2]), "+f"(c[3]) : "r"(a0), "r"(a1), "r"(b0));
}
__device__ __forceinline__ uint4 ld_rlx128(const uint4* p) {
    uint4 v;
    asm volatile("{.reg .b128 t; ld.relaxed.gpu.global.b128 t,[%4]; mov.b128 {%0,%1,%2,%3},t;}" : "=r"(v.x), "=r"(v.y), "=r"(v.z), "=r"(v.w) : "l"(p) : "memory");
    return v;
}
__device__ __forceinline__ void st_rlx128(uint4* p, uint32_t x, uint32_t y, uint32_t z, uint32_t w) {
    asm volatile("{.reg .b128 t; mov.b128 t,{%1,%2,%3,%4}; st.relaxed.gpu.global.b128 [%0],t;}" ::"l"(p), "r"(x), "r"(y), "r"(z), "r"(w) : "memory");
}
__device__ __forceinline__ uint4 ldcg128(const uint4* p) { uint4 v; asm volatile("ld.global.cg.v4.u32 {%0,%1,%2,%3},[%4];" : "=r"(v.x), "=r"(v.y), "=r"(v.z), "=r"(v.w) : "l"(p) : "memory"); return v; }
__device__ __forceinline__ void red_release(unsigned* p, unsigned v) {
    asm volatile("fence.proxy.async; red.relaxed.gpu.global.add.u32 [%0],%1;" ::"l"(p), "r"(v) : "memory");
}
__device__ __forceinline__ void red_relaxed(unsigned* p, unsigned v) { asm volatile("red.relaxed.gpu.global.add.u32 [%0],%1;" ::"l"(p), "r"(v) : "memory"); }
__device__ __forceinline__ void wait_cnt(const unsigned* p, unsigned target) {
    asm volatile(
        "{.reg .pred p; .reg .u32 n,v; mov.u32 n,0;\n"
        "W%=: ld.acquire.gpu.global.u32 v,[%0]; setp.ge.u32 p,v,%1; @p bra D%=;\n"
        "nanosleep.u32 20; add.u32 n,n,1; setp.lt.u32 p,n,4000000; @p bra W%=;\n"
        "trap;\n"
        "D%=: }" ::"l"(p), "r"(target) : "memory");
}
__device__ __forceinline__ void wait_cnt_warp(const unsigned* p, unsigned target) {
    asm volatile(
        "{.reg .pred p; .reg .u32 n,v; mov.u32 n,0;\n"
        "W%=: ld.acquire.gpu.global.u32 v,[%0]; setp.ge.u32 p,v,%1; vote.sync.all.pred p,p,0xffffffff; @p bra.uni D%=;\n"
        "nanosleep.u32 20; add.u32 n,n,1; setp.lt.u32 p,n,4000000; @p bra.uni W%=;\n"
        "trap;\n"
        "D%=: }" ::"l"(p), "r"(target) : "memory");
}
__device__ __forceinline__ void wait_flag_warp(const unsigned* p, unsigned target) {
    asm volatile(
        "{.reg .pred p; .reg .u32 n,v; mov.u32 n,0;\n"
        "W%=: ld.relaxed.gpu.global.u32 v,[%0]; setp.ge.u32 p,v,%1; vote.sync.all.pred p,p,0xffffffff; @p bra.uni D%=;\n"
        "add.u32 n,n,1; setp.lt.u32 p,n,10000000; @p bra.uni W%=;\n"
        "trap;\n"
        "D%=: }" ::"l"(p), "r"(target) : "memory");
}
__device__ __forceinline__ uint64_t mkdesc(uint32_t addr, uint32_t lbo, uint32_t sbo, uint32_t sw) {
    return (uint64_t)((addr & 0x3FFFF) >> 4) | ((uint64_t)(lbo >> 4) << 16) | ((uint64_t)(sbo >> 4) << 32) | ((uint64_t)sw << 62);
}
__device__ __forceinline__ void wg_fence() { asm volatile("wgmma.fence.sync.aligned;" ::: "memory"); }
__device__ __forceinline__ void wg_commit() { asm volatile("wgmma.commit_group.sync.aligned;" ::: "memory"); }
template <int N> __device__ __forceinline__ void wg_wait() { asm volatile("wgmma.wait_group.sync.aligned %0;" ::"n"(N) : "memory"); }
#define R8(c, o) "+f"(c[o]), "+f"(c[o + 1]), "+f"(c[o + 2]), "+f"(c[o + 3]), "+f"(c[o + 4]), "+f"(c[o + 5]), "+f"(c[o + 6]), "+f"(c[o + 7])
#define R32(c, o) R8(c, o), R8(c, o + 8), R8(c, o + 16), R8(c, o + 24)
#define S32A "%0,%1,%2,%3,%4,%5,%6,%7,%8,%9,%10,%11,%12,%13,%14,%15,%16,%17,%18,%19,%20,%21,%22,%23,%24,%25,%26,%27,%28,%29,%30,%31"
template <int ACC> __device__ __forceinline__ void wgmma64_rs(float* c, const uint32_t* a, uint64_t db) {
    asm volatile("wgmma.mma_async.sync.aligned.m64n64k16.f32.bf16.bf16 {" S32A "},{%32,%33,%34,%35},%36,%37,1,1,0;"
                 : R32(c, 0) : "r"(a[0]), "r"(a[1]), "r"(a[2]), "r"(a[3]), "l"(db), "n"(ACC));
}
template <int ACC> __device__ __forceinline__ void wgmma64_ta(float* c, uint64_t da, uint64_t db) {
    asm volatile("wgmma.mma_async.sync.aligned.m64n64k16.f32.bf16.bf16 {" S32A "},%32,%33,%34,1,1,1,0;" : R32(c, 0) : "l"(da), "l"(db), "n"(ACC));
}
template <int ACC> __device__ __forceinline__ void wgmma80_tb(float* c, uint64_t da, uint64_t db) {
    asm volatile("wgmma.mma_async.sync.aligned.m64n80k16.f32.bf16.bf16 {" S32A ",%32,%33,%34,%35,%36,%37,%38,%39},%40,%41,%42,1,1,0,1;"
                 : R32(c, 0), R8(c, 32) : "l"(da), "l"(db), "n"(ACC));
}
template <int N> __device__ __forceinline__ void reg_inc() { asm volatile("setmaxnreg.inc.sync.aligned.u32 %0;" ::"n"(N)); }
template <int N> __device__ __forceinline__ void reg_dec() { asm volatile("setmaxnreg.dec.sync.aligned.u32 %0;" ::"n"(N)); }

#define PROF(cond, idx) do {} while (0)
#define CPROF(k) do {} while (0)

constexpr int S_GATE = 232440, S_XBAR = 232432, B_BAR = 231936;
#define RCB 136
#define RCU 184
#define NFP 2
#define UFE 0
#define PFM 8
#define NFE 2
#define QLAG 3
constexpr float SC_LOG2E = 0.08838834764831845f * 1.4426950408889634f;

__device__ __forceinline__ float2 ln_finish(float mean, float var) {
    float sd; asm("sqrt.approx.f32 %0,%1;" : "=f"(sd) : "f"(rbf(rbf(var) + 1e-5f)));
    sd = rbf(sd);
    return make_float2(rbf(mean), sd);
}

__device__ __forceinline__ float2 row_stats512(uint4* v, const uint4* src, int s1, int s2) {
    const int g = (threadIdx.x & 31) >> 2;
#pragma unroll
    for (int i = 0; i < 16; i++) v[i] = ldcg128(src + (i >> 1) * s1 + (i & 1) * s2);
    float a[4] = {0, 0, 0, 0}, q0[4] = {0, 0, 0, 0}, q1[4] = {0, 0, 0, 0};
#pragma unroll
    for (int i = 0; i < 16; i++) {
        mma16(a, v[i].x, v[i].y, v[i].z, v[i].w, 0x3f803f80u, 0x3f803f80u);
        mma8(q0, v[i].x, v[i].y, v[i].x); mma8(q1, v[i].x, v[i].y, v[i].y);
        mma8(q0, v[i].z, v[i].w, v[i].z); mma8(q1, v[i].z, v[i].w, v[i].w);
    }
    const float sum = a[0] + a[2], sq = (g & 1) ? q0[1] + q1[3] : q0[0] + q1[2];
    return make_float2(sum, fmaxf(sq - sum * sum * (1.f / 512.f), 0.f));
}
__device__ __forceinline__ void x1_norm(const uint2* src, int r, bool on) {
    const int lane = threadIdx.x & 31, g = lane >> 2, t = r * 4 + (lane & 3);
    constexpr int xp = XP;
    uint2 v[16];
#pragma unroll
    for (int i = 0; i < 16; i++) asm volatile("ld.global.cg.v2.u32 {%0,%1},[%2];" : "=r"(v[i].x), "=r"(v[i].y) : "l"(src + (g * 4 * xp + t) + ((i >> 1) * 16 + (i & 1)) * 2 * xp) : "memory");
    float s = 0, q = 0;
#pragma unroll
    for (int i = 0; i < 32; i++) {
        const uint32_t w = (i & 1) ? v[i >> 1].y : v[i >> 1].x;
        s += blo(w) + bhi(w); q = fmaf(blo(w), blo(w), fmaf(bhi(w), bhi(w), q));
    }
#pragma unroll
    for (int d = 4; d < 32; d *= 2) { s += __shfl_xor_sync(0xffffffffu, s, d); q += __shfl_xor_sync(0xffffffffu, q, d); }
    if (g == 0 && on) g_ln0[t] = 0;
    s *= 1.f / 512.f;
    const float2 l = ln_finish(s, fmaxf(fmaf(q, 1.f / 512.f, -s * s), 0.f));
    const float rs = rcp(l.y);
    const uint32_t mm = pack2(-l.x, -l.x);
    uint4* dst = g_xn + ((t >> 6) * 4096 + ((t >> 3) & 7) * 64 + g * 8 + (t & 7));
#define NRM(w) pack2(blo(hadd2(w, mm)) * rs, bhi(hadd2(w, mm)) * rs)
#pragma unroll
    for (int i = 0; i < 8; i++)
        asm volatile("{.reg .pred p; setp.ne.u32 p,%5,0; @p st.global.v4.u32 [%0],{%1,%2,%3,%4};}" ::"l"(dst + i * 512), "r"(NRM(v[2 * i].x)), "r"(NRM(v[2 * i].y)),
                     "r"(NRM(v[2 * i + 1].x)), "r"(NRM(v[2 * i + 1].y)), "r"((uint32_t)on) : "memory");
}

#define NWO 10
#define VMASK 0x4444
#define VPRE 2
#define VFIRST 1
#define OA 0
#define OL 0x16
#define PINS 0xae1
#define NPX 2
#define NPF 2
constexpr int SLOT = 24576, SL_V = 8192, SL_Q = 16384, SL_KM = 20480, SL_VM = 22528;
constexpr int R_SL = 0, R_WV = 4 * SLOT  , R_WO = R_WV + 65536, R_M = 196608  , R_U = R_M + 8192  ,
              R_OS = R_U + 8192  , R_SB = R_OS + 8192  , R_OB = R_SB + 5248  , R_PB = R_OB + 2048  ,
              R_IL = R_PB + 1024  , R_SEL = 231680, R_BAR = R_SEL + 256, R_STV = 0, R_STQ = 65536, R_STK = 131072;
static_assert(R_WO + (16 - NWO) * 4096 <= R_M && R_IL + 64 <= R_SEL && R_BAR + 512 <= 232448, "smem map");
enum { RB_XFULL = 0  , RB_GO = 4  , RB_QK = 8  , RB_INIT = 24, RB_SV = 25   };

enum { NB_MFULL = 1  , NB_PART = 3  , NB_S = 5, NB_P = 6, NB_O = 7, NB_W = 10 };
#define HL 2
#define XU 8
#define TFIRST 0
#define RELO red_release
#define RACC 2
#define WDEP 1
#define RH 56
#define RW0 224
#define D1 400
#define D2 400
#define DX 0
__device__ __forceinline__ uint32_t clk32() { uint32_t c; asm volatile("mov.u32 %0,%%clock;" : "=r"(c)::"memory"); return c; }
__device__ __forceinline__ void spin(int cycles) {
    if (cycles <= 0) return;
    asm volatile("{.reg .pred p; .reg .u32 a,b; mov.u32 a,%%clock; add.u32 a,a,%0;\nS%=: mov.u32 b,%%clock; sub.u32 b,b,a; setp.lt.s32 p,b,0; @p bra.uni S%=;}" ::"r"(cycles) : "memory");
}
__device__ __forceinline__ uint4* xregion(int X, int r) { return (uint4*)(((size_t)g_xch + 8191) & ~(size_t)8191) + (X * 66 + r) * 512; }

__device__ __forceinline__ void arrive_if(uint32_t bar, uint32_t a, uint32_t b) {
    asm volatile("{.reg .pred p; setp.eq.u32 p,%1,%2; @p mbarrier.arrive.shared::cta.b64 _,[%0];}" ::"r"(bar), "r"(a), "r"(b) : "memory");
}
struct RecW { uint32_t po, dp, lw, sp  , w; };
#define PIN(n) if ((PINS >> (n)) & 1) asm volatile("griddepcontrol.launch_dependents;" ::: "memory")
constexpr int v_stream(int n) {
    int ks = 0;
    for (; ks < 16; ks++) if (!((VMASK >> ks) & 1) && n-- == 0) break;
    return ks;
}
constexpr uint64_t v_next() {
    uint64_t r = 0;
    for (int n = 0; v_stream(n + VPRE) < 16; n++) r |= (uint64_t)v_stream(n + VPRE) << (4 * v_stream(n));
    return r;
}
constexpr uint64_t V_NEXT = v_next();
constexpr int V_PRE = v_stream(VPRE);

template <int X>
__device__ __forceinline__ void rec_step(const RecW& k, uint32_t sb, int s, uint32_t zero, int lo, int hi, int d, const uint32_t (*wq)[4], const uint32_t (*wk)[4], uint4* wv, uint4* wo) {
    constexpr int SL = R_SL + X * 2 * SLOT;
    uint4 mk[8];
    bar_sync(NB_MFULL + X, 288);
    mk[0] = ldsm4(k.lw + X * 4096 + R_M);
    PIN(0);
    mk[1] = ldsm4(k.lw + X * 4096 + R_M + 512);
    PIN(0);
    asm volatile("" : "+r"(s));
    const uint32_t z = s & zero, wz = k.w + z, w5 = wz * 512, so = (s & 1) * SLOT + w5;
    const uint32_t qb = sb + R_BAR + (RB_QK + X * 8) * 8 + wz * 8;
    uint32_t x[4], vv[2], l8;
    {
        float aq[4] = {0, 0, 0, 0}, ak[4] = {0, 0, 0, 0}, av[4] = {0, 0, 0, 0};
#pragma unroll
        for (int t = 0; t < 16; t++) {
            const uint32_t b0 = (t & 1) ? mk[t >> 1].z : mk[t >> 1].x, b1 = (t & 1) ? mk[t >> 1].w : mk[t >> 1].y;
            mma16(aq, wq[t][0], wq[t][1], wq[t][2], wq[t][3], b0, b1);
            PIN(8);
            mma16(ak, wk[t][0], wk[t][1], wk[t][2], wk[t][3], b0, b1);
            PIN(9);
            mma16(av, wv[t].x, wv[t].y, wv[t].z, wv[t].w, b0, b1);
            PIN(10);
            if ((t & 1) && t < 13) mk[(t >> 1) + 2] = ldsm4(k.lw + X * 4096 + R_M + (t >> 1) * 512 + 1024);
            const int nx = (V_NEXT >> (4 * t)) & 15;
            if (nx) wv[nx] = lds128(k.lw + w5 + R_WV + nx * 4096);
            if (t == 14) l8 = ((k.lw + z) >> 1) + (sb - (sb >> 1) + SL + (s & 1) * SLOT + wz * 256);
            if (t < 15) PIN(1);
        }
        x[0] = movm(pack2(aq[0], aq[1])); x[1] = movm(pack2(aq[2], aq[3]));
        x[2] = movm(pack2(ak[0], ak[1])); x[3] = movm(pack2(ak[2], ak[3]));
        vv[0] = pack2(av[0], av[1]); vv[1] = pack2(av[2], av[3]);
        if (VFIRST) st_async2(l8 + (SL_VM + k.dp), vv[0], vv[1], qb + k.dp);
        st_async4(k.lw + (R_U + X * 4096 + w5 + k.dp), x[0], x[1], x[2], x[3], qb + k.dp);
        if (!VFIRST) st_async2(l8 + (SL_VM + k.dp), vv[0], vv[1], qb + k.dp);
    }
    {
        arrive_if(sb + R_BAR + (RB_GO + 2 - 2 * X + ((s + d) & 1)) * 8, k.sp, X ? s >= hi : s <= lo);
        const uint32_t swr = ((k.sp + z) & 0xffff) + (sb + R_SB);
        const uint4 k0 = lds128(k.lw + so + SL), k1 = lds128(k.lw + so + SL + 4096);
#pragma unroll
        for (int i = 0; i < NPX; i++) wo[i] = lds128(k.lw + w5 + R_WO + i * 4096);
        mbar_wait(qb, s & 1);
        const uint4 u = lds128(k.lw + w5 + R_U + X * 4096);
        const uint32_t q0 = hadd2(x[0], u.x), q1 = hadd2(x[1], u.y);
        x[2] = hadd2(x[2], u.z); x[3] = hadd2(x[3], u.w);
        float sa[4] = {0, 0, 0, 0}, sc[4] = {0, 0, 0, 0}, sm0, sm1;
        mma16(sa, k0.x, k0.y, k0.z, k0.w, q0, q1);
        mma16(sc, k1.x, k1.y, k1.z, k1.w, q0, q1);
        mma16_top(sm0, sm1, x[2], x[3], q0, q1);
        asm volatile("stmatrix.sync.aligned.m8n8.x4.trans.shared.b16 [%0],{%1,%2,%3,%4};" ::"r"(swr), "r"(pack2(sa[0], sa[1])), "r"(pack2(sa[2], sa[3])),
                     "r"(pack2(sc[0], sc[1])), "r"(pack2(sc[2], sc[3])) : "memory");
        asm volatile("stmatrix.sync.aligned.m8n8.x1.trans.shared.b16 [%0],{%1};" ::"r"(swr + 512), "r"(pack2(sm0, sm1)) : "memory");
    }
    bar_sync(NB_S, 256);
    uint4 v0, v1;
    uint32_t ls;
    {
        const uint4 y = ldsm4t(k.lw + wz * 656 + R_SB);
        PIN(2);
        uint32_t y4; asm volatile("ldmatrix.sync.aligned.m8n8.x1.trans.shared.b16 {%0},[%1];" : "=r"(y4) : "r"(k.lw + wz * 656 + R_SB + 512) : "memory");
        PIN(2);
        const uint2 vp = lds64(l8 + SL_VM);
        sts64(l8 + SL_KM, x[2], x[3]);
        const uint32_t ONE = 0x3f803f80u + z;
        float a[4] = {0, 0, 0, 0}, b[4] = {0, 0, 0, 0}, e[4] = {0, 0, 0, 0};
        mma16(a, ONE, z, z, ONE, y.x, y.y); mma16(b, ONE, z, z, ONE, y.z, y.w); mma8(e, ONE, z, y4);
        vv[0] = hadd2(vv[0], vp.x); vv[1] = hadd2(vv[1], vp.y);
        sts64(l8 + SL_VM, vv[0], vv[1]);
        float s0, s1;
        asm("{.reg .pred p1,p2,p4; .reg .f32 t0,t1,u0,u1; .reg .b32 m; and.b32 m,%12,64; setp.ne.u32 p1,m,0; and.b32 m,%12,128; setp.ne.u32 p2,m,0; and.b32 m,%12,256; setp.ne.u32 p4,m,0;"
            "selp.f32 t0,%4,%2,p1; selp.f32 t1,%5,%3,p1; selp.f32 u0,%8,%6,p1; selp.f32 u1,%9,%7,p1; selp.f32 t0,u0,t0,p2; selp.f32 t1,u1,t1,p2; selp.f32 %0,%10,t0,p4; selp.f32 %1,%11,t1,p4;}"
            : "=f"(s0), "=f"(s1) : "f"(a[0]), "f"(a[1]), "f"(a[2]), "f"(a[3]), "f"(b[0]), "f"(b[1]), "f"(b[2]), "f"(b[3]), "f"(e[0]), "f"(e[1]), "r"(k.lw));
        const int mi = __float_as_int(fmaxf(s0, s1));
        const int mp = __reduce_max_sync(0xffffffffu, mi), mn = (int)__reduce_min_sync(0xffffffffu, (unsigned)mi);
        PIN(3);
        v0 = lds128(k.lw + so + SL + SL_V); v1 = lds128(k.lw + so + SL + SL_V + 4096);
#pragma unroll
        for (int i = NPX; i < NPF; i++) wo[i] = lds128(k.lw + w5 + R_WO + i * 4096);
        PIN(4);
        const float mo = -__int_as_float(mp >= 0 ? mp : mn) * SC_LOG2E;
        s0 = ex2(fmaf(s0, SC_LOG2E, mo)); s1 = ex2(fmaf(s1, SC_LOG2E, mo));
        sts32(((k.sp + z) >> 16) + (sb + R_PB), pack2(s0, s1));
        ls = k.lw < sb + 320 ? __float_as_uint((s0 + s1) + 4.f) : 0;
    }
    bar_sync(NB_P, 256);
    {
        const uint4 pp = lds128(k.lw + R_PB);
        PIN(5);
        const uint32_t pm = lds32(((k.lw + z) >> 2) + (sb - (sb >> 2) + R_PB + 512));
        PIN(5);
        sts32(sb + R_IL + (wz >> 1) * 16 + (wz & 1) * 4, __reduce_add_sync(0xffffffffu, ls) - 20u * 0x40800000u);
        float o0[4] = {0, 0, 0, 0}, o1[4] = {0, 0, 0, 0}, o2[4] = {0, 0, 0, 0};
        mma16(o0, v0.x, v0.y, v0.z, v0.w, pp.x, pp.y);
        mma16(o1, v1.x, v1.y, v1.z, v1.w, pp.z, pp.w);
        mma8(o2, vv[0], vv[1], pm);
        asm volatile("stmatrix.sync.aligned.m8n8.x2.trans.shared.b16 [%0],{%1,%2};" ::"r"(k.lw + wz * 256 + R_OB),
                     "r"(pack2(o0[0] + o1[0] + o2[0], o0[1] + o1[1] + o2[1])), "r"(pack2(o0[2] + o1[2] + o2[2], o0[3] + o1[3] + o2[3])) : "memory");
    }
    bar_sync(NB_O, 256);
    {
        float r0[2][4] = {{0, 0, 0, 0}, {0, 0, 0, 0}}, r1[2][4] = {{0, 0, 0, 0}, {0, 0, 0, 0}};
        uint4 b[4];
        b[0] = ldsm4(k.lw + R_OB);
        PIN(6);
        b[1] = ldsm4(k.lw + R_OB + 512);
        PIN(6);
#pragma unroll
        for (int m = NWO + NPF; m < 16; m++) if (((OL >> (2 * (15 - m))) & 3) == 3) wo[m] = lds128(k.lw + w5 + R_WO + (m - NWO) * 4096);
        const uint2 il = lds64(sb + R_IL + ((k.lw + z) & 48));
        PIN(6);
        float i0, i1;
        uint4* dst;
#pragma unroll
        for (int i = 0; i < 4; i++) {
            mma16(r0[0], wo[4 * i].x, wo[4 * i].y, wo[4 * i].z, wo[4 * i].w, b[i].x, b[i].y);
            mma16(r1[0], wo[4 * i + 1].x, wo[4 * i + 1].y, wo[4 * i + 1].z, wo[4 * i + 1].w, b[i].x, b[i].y);
            mma16(r0[OA], wo[4 * i + 2].x, wo[4 * i + 2].y, wo[4 * i + 2].z, wo[4 * i + 2].w, b[i].z, b[i].w);
            mma16(r1[OA], wo[4 * i + 3].x, wo[4 * i + 3].y, wo[4 * i + 3].z, wo[4 * i + 3].w, b[i].z, b[i].w);
            if (i < 2) b[i + 2] = ldsm4(k.lw + R_OB + (i + 2) * 512);
#pragma unroll
            for (int m = NWO + NPF; m < 16; m++) if (i < 3 && i == ((OL >> (2 * (15 - m))) & 3)) wo[m] = lds128(k.lw + w5 + R_WO + (m - NWO) * 4096);
            if (i == 1) { i0 = rcp(__uint2float_rn(il.x)) * 2097152.f; i1 = rcp(__uint2float_rn(il.y)) * 2097152.f; }
            if (i == 2) {
                const uint32_t po = k.po + z;
                dst = (uint4*)((char*)xregion(X, 0) + ((po & ~1u) ^ ((po & X) << 12)));
                asm volatile("" : "+l"(dst));
            }
            PIN(7);
        }
        const uint32_t tag = (s + 1) & 1;
#pragma unroll
        for (int i = 0; i < 4; i++) { r0[0][i] = (OA ? r0[0][i] + r0[1][i] : r0[0][i]) * ((i & 1) ? i1 : i0); r1[0][i] = (OA ? r1[0][i] + r1[1][i] : r1[0][i]) * ((i & 1) ? i1 : i0); }
        st_rlx128(dst, (pack2(r0[0][0], r0[0][2]) & ~1u) | tag,
                  pack2(r1[0][0], r1[0][2]), pack2(r0[0][1], r0[0][3]), pack2(r1[0][1], r1[0][3]));
        bar_arrive(NB_PART + X, 288);
#pragma unroll
        for (int t = 0; t < V_PRE; t++) if (!((VMASK >> t) & 1)) wv[t] = lds128(k.lw + w5 + R_WV + t * 4096);
        arrive_if(sb + R_BAR + (RB_GO + 2 * X + (s & 1)) * 8, k.sp, X ? s + 1 < hi : s >= lo);
    }
}

__device__ __forceinline__ void rec_fetch(const Params& p, uint32_t sb, int head, uint32_t rank, int which, int dst) {
#pragma unroll 1
    for (int j = 0; j < 8; j++) tma2d(sb + dst + j * 8192, &p.tm[which], head * 128 + (j >> 2) * 64, rank * 256 + (j & 3) * 64, sb + R_BAR + RB_INIT * 8);
}

__device__ __forceinline__ void rec_weights(const Params& p, uint32_t sb, int head, uint32_t rank, int w) {
    const int lane = threadIdx.x & 31, g = lane >> 2, c = lane & 3;
    const int t = w & 3, WG = w >> 2;
    uint32_t wq[16][4], wk[16][4];
    uint4 wo[16], wv[16];
    const uint32_t woff = sb + WG * 32768 + (((lane >> 4) << 3) + (lane & 7)) * 128 + (((2 * t + ((lane >> 3) & 1)) ^ (lane & 7)) << 4);
    const uint32_t lw = sb + lane * 16;
    PROF(threadIdx.x == 0, 3501);
    {
        const __nv_bfloat16* wp = p.Wo + (size_t)(head * 128 + 2 * c) * 512 + rank * 256 + w * 32 + g * 4;
#pragma unroll
        for (int ks = 0; ks < 8; ks++) {
            const uint2 r0 = *(const uint2*)(wp + (ks * 16) * 512), r1 = *(const uint2*)(wp + (ks * 16 + 1) * 512);
            const uint2 r2 = *(const uint2*)(wp + (ks * 16 + 8) * 512), r3 = *(const uint2*)(wp + (ks * 16 + 9) * 512);
            const uint4 f[2] = {make_uint4(__byte_perm(r0.x, r1.x, 0x5410), __byte_perm(r0.x, r1.x, 0x7632), __byte_perm(r2.x, r3.x, 0x5410), __byte_perm(r2.x, r3.x, 0x7632)),
                                make_uint4(__byte_perm(r0.y, r1.y, 0x5410), __byte_perm(r0.y, r1.y, 0x7632), __byte_perm(r2.y, r3.y, 0x5410), __byte_perm(r2.y, r3.y, 0x7632))};
#pragma unroll
            for (int h = 0; h < 2; h++) {
                const int m = 2 * ks + h;
                wo[m] = f[h];
            }
        }
    }
    PROF(threadIdx.x == 0, 3502);
    mbar_wait(sb + R_BAR + RB_INIT * 8, 0);
    PROF(threadIdx.x == 0, 3503);
#pragma unroll
    for (int ks = 0; ks < 16; ks++) {
        uint4 a = ldsm4t(woff + R_STQ + ks * 2048), b = ldsm4t(woff + R_STK + ks * 2048);
        wq[ks][0] = a.x; wq[ks][1] = a.y; wq[ks][2] = a.z; wq[ks][3] = a.w;
        wk[ks][0] = b.x; wk[ks][1] = b.y; wk[ks][2] = b.z; wk[ks][3] = b.w;
    }
    bar_sync(NB_W, 256);
#pragma unroll
    for (int m = 0; m < 16; m++)
        if (m < NPF || m >= NPF + NWO) sts128(lw + w * 512 + R_WO + (m < NPF ? m : m - NWO) * 4096, wo[m].x, wo[m].y, wo[m].z, wo[m].w);
#pragma unroll
    for (int i = 0; i < 16; i++) {
        wv[i] = ldsm4t(woff + R_STV + i * 2048);
        if (!((VMASK >> i) & 1)) sts128(lw + w * 512 + R_WV + i * 4096, wv[i].x, wv[i].y, wv[i].z, wv[i].w);
    }
    fence_async_smem();
    PROF(threadIdx.x == 0, 3504);
    __syncthreads();
    cluster_sync();
    PROF(threadIdx.x == 0, 3505);
    RecW k;
    {
        const int r = (w * 4 + (lane >> 3)) * 2 + rank;
        const uint32_t sl = lds32(sb + R_SEL + r * 4);
        const int slot = HL == 0 ? head * 8 + (lane & 7) : HL == 1 ? (head >> 2) * 32 + ((lane & 7) >> 1) * 8 + (head & 3) * 2 + (lane & 1) : (head >> 1) * 16 + ((lane & 7) >> 2) * 8 + (head & 1) * 4 + (lane & 3);
        k.po = (r * 512 + slot + (sl & 1) * 256) * 16 + (((sl >> 1) ^ sl) & 1);
    }
    k.dp = mapa(sb, rank ^ 1) - sb;
    k.lw = __shfl_sync(0xffffffffu, lw, lane);
    k.sp = __shfl_sync(0xffffffffu, (lane & 7) * 656 + (lane >> 3) * 128 + w * 16 + ((g < 4 ? (w * 4 + c) * 16 + g * 4 : 512 + (w * 4 + c) * 4) << 16), lane);
    k.w = w;
    const int e0 = (p.chains & 1) ? 64 : 0, o1 = (p.chains & 2) ? p.lag : 1000, nit = (p.chains & 2) ? p.lag + 64 : e0;
    const uint32_t zero = p.zero;
#pragma unroll 1
    for (int it = 0; it < nit; it++) {
        if (it < e0) rec_step<0>(k, sb, it, zero, o1, 0, o1 + 1, wq, wk, wv, wo);
        if (it >= o1) rec_step<1>(k, sb, it - o1, zero, 0, e0 - o1, o1, wq, wk, wv, wo);
    }
}

__device__ __forceinline__ uint32_t mism(uint32_t a, uint32_t b, uint32_t t) {
    uint32_t d; asm("lop3.b32 %0,%1,%2,%3,0x7e;" : "=r"(d) : "r"(a), "r"(b), "r"(t)); return d;
}
__device__ __forceinline__ uint32_t or3(uint32_t a, uint32_t b, uint32_t c) {
    uint32_t d; asm("lop3.b32 %0,%1,%2,%3,0xfe;" : "=r"(d) : "r"(a), "r"(b), "r"(c)); return d;
}
template <bool TWO, class F>
__device__ __forceinline__ void poll8(uint4* x, const uint4* src, uint32_t tag, F&& use) {
#pragma unroll
    for (int j = 0; j < 8; j++) x[j] = ld_rlx128(src + j * 32);
    int n = 0;
    while (true) {
        use();
        uint32_t bad = or3(mism(x[0].x, x[1].x, tag), mism(x[2].x, x[3].x, tag), mism(x[4].x, x[5].x, tag));
        if (TWO) bad = or3(bad, or3(mism(x[0].z, x[1].z, tag), mism(x[2].z, x[3].z, tag), mism(x[4].z, x[5].z, tag)), mism(x[6].z, x[7].z, tag));
        if (!__any_sync(0xffffffffu, (bad | mism(x[6].x, x[7].x, tag)) & 1)) break;
#pragma unroll
        for (int j = 0; j < 8; j++)
            asm volatile("{.reg .pred p; .reg .b128 t; .reg .b32 m; lop3.b32 m,%0,%6,%5,0x7e; and.b32 m,m,1; setp.ne.u32 p,m,0; mov.b128 t,{%0,%1,%2,%3};"
                         "@p ld.relaxed.gpu.global.b128 t,[%4]; mov.b128 {%0,%1,%2,%3},t;}"
                         : "+r"(x[j].x), "+r"(x[j].y), "+r"(x[j].z), "+r"(x[j].w) : "l"(src + j * 32), "r"(tag), "r"(TWO ? x[j].z : tag) : "memory");
        if (++n > 2000000) __trap();
    }
}

__device__ __forceinline__ void rec_comm(const Params& p, uint32_t sb, int X, int head, uint32_t rank) {
    const int lane = threadIdx.x & 31, g = lane >> 2, c = lane & 3;
    const int me = head * 2 + rank;
    const uint32_t mb = sb + R_M + X * 4096 + lane * 16;
    uint4 x[8];
#pragma unroll
    for (int j = 0; j < 8; j++) x[j] = *(const uint4*)(p.mem0 + (lane & 7) * 512 + rank * 256 + (j * 4 + (lane >> 3)) * 8);
    const uint32_t sl = lds32(sb + R_SEL + me * 4);
    const uint4* src1 = xregion(X, me) + ((sl >> X) & 1) * 256 + (HL == 0 ? c * 8 + g : HL == 1 ? (g >> 1) * 8 + c * 2 + (g & 1) : (c >> 1) * 16 + (g >> 2) * 8 + (c & 1) * 4 + (g & 3));
    const uint4* src2 = xregion(X, 64 + rank) + ((sl >> (2 + X)) & 1) * 256 + lane;
    uint2* mdst = (uint2*)(xregion(X, 64 + rank) + (c >> 1) * 256 + head * 8 + (g & 3) * 2 + (c & 1)) + (g >> 2);
    const uint32_t one = (g & 1) ? 0x3f800000u : 0x00003f80u, selA = (g & 2) ? 0u : one, selB = (g & 2) ? one : 0u;
    const uint32_t qb = sb + R_BAR + (RB_QK + X * 8 + lane) * 8;
    if (lane < 8) mbar_expect(qb, 768);
    mbar_wait(sb + R_BAR + (RB_XFULL + X * 2) * 8, 0);
#pragma unroll
    for (int j = 0; j < 8; j++) sts128(mb + j * 512, x[j].x, x[j].y, x[j].z, x[j].w);
#pragma unroll 1
    for (int s = 0;; s++) {
        bar_arrive(NB_MFULL + X, 288);
        PROF(lane == 0, X * 64 + s);
        bar_sync(NB_PART + X, 288);
        if (s == 63) break;
        const uint32_t tag = (s + 1) & 1;
        if (lane < 8) mbar_expect(qb, 768);
        spin(D1);
        uint32_t m0, m1;
        poll8<false>(x, src1, tag, [&]() {
            float a[RACC][4];
#pragma unroll
            for (int j = 0; j < 8; j++) {
                if (j < RACC) a[j][0] = a[j][1] = a[j][2] = a[j][3] = 0;
                mma16(a[j % RACC], x[j].x, x[j].y, x[j].z, x[j].w, selA, selB);
            }
#pragma unroll
            for (int i = 0; i < 4; i++) a[0][i] = RACC == 3 ? a[0][i] + a[1][i] + a[2 % RACC][i] : a[0][i] + a[1][i];
            m0 = (pack2(a[0][0], a[0][1]) & ~1u) | tag; m1 = pack2(a[0][2], a[0][3]);
        });
        asm volatile("st.relaxed.gpu.global.b64 [%0],%1;" ::"l"(mdst), "l"(((uint64_t)m1 << 32) | m0) : "memory");
        const uint32_t t2 = clk32();
        mbar_wait(sb + R_BAR + (RB_XFULL + X * 2 + tag) * 8, ((s + 1) >> 1) & 1);
        while (clk32() - t2 < D2) {}
        poll8<true>(x, src2, tag, [&]() {
#pragma unroll
            for (int j = 0; j < 8; j++) sts128(mb + j * 512, x[j].x, x[j].y, x[j].z, x[j].w);
        });
    }
}

template <int MT>
__device__ __forceinline__ void xattn(uint32_t l16, uint32_t l8, uint32_t os, int g, int c) {
    constexpr int NT = 3 + 2 * MT, XUN = XU;
    float S[NT][4];
#pragma unroll
    for (int i = 0; i < NT; i++) S[i][0] = S[i][1] = S[i][2] = S[i][3] = 0;
#pragma unroll XUN
    for (int ks = 0; ks < 8; ks++) {
        const uint4 q = lds128(l16 + SL_Q + ks * 512);
        const uint2 u = lds64(l8 + SL_KM + ks * 256);
        mma16(S[0], q.x, q.y, q.z, q.w, u.x, u.y);
#pragma unroll
        for (int m = 0; m <= MT; m++) {
            const uint4 kk = lds128(l16 + m * 4096 + ks * 512);
            mma16(S[1 + 2 * m], q.x, q.y, q.z, q.w, kk.x, kk.z); mma16(S[2 + 2 * m], q.x, q.y, q.z, q.w, kk.y, kk.w);
        }
    }
    const float NEG = -__int_as_float(0x7f800000);
    if (2 * c > g) { S[NT - 2][0] = NEG; S[NT - 1][2] = NEG; }
    if (2 * c + 1 > g) { S[NT - 2][1] = NEG; S[NT - 1][3] = NEG; }
    S[NT - 1][0] = S[NT - 1][1] = NEG;
    float m0 = fmaxf(S[0][0], S[0][1]), m1 = fmaxf(S[0][2], S[0][3]);
#pragma unroll
    for (int i = 1; i < NT; i++) { if (i < NT - 1) m0 = fmaxf(m0, fmaxf(S[i][0], S[i][1])); m1 = fmaxf(m1, fmaxf(S[i][2], S[i][3])); }
    m0 = fmaxf(m0, __shfl_xor_sync(0xffffffffu, m0, 1)); m1 = fmaxf(m1, __shfl_xor_sync(0xffffffffu, m1, 1));
    m0 = fmaxf(m0, __shfl_xor_sync(0xffffffffu, m0, 2)); m1 = fmaxf(m1, __shfl_xor_sync(0xffffffffu, m1, 2));
    m0 *= -SC_LOG2E; m1 *= -SC_LOG2E;
    float l0 = 0, l1 = 0;
#pragma unroll
    for (int i = 0; i < NT; i++) {
        if (i < NT - 1) { S[i][0] = ex2(fmaf(S[i][0], SC_LOG2E, m0)); S[i][1] = ex2(fmaf(S[i][1], SC_LOG2E, m0)); l0 += S[i][0] + S[i][1]; }
        S[i][2] = ex2(fmaf(S[i][2], SC_LOG2E, m1)); S[i][3] = ex2(fmaf(S[i][3], SC_LOG2E, m1)); l1 += S[i][2] + S[i][3];
    }
    l0 += __shfl_xor_sync(0xffffffffu, l0, 1); l1 += __shfl_xor_sync(0xffffffffu, l1, 1);
    l0 += __shfl_xor_sync(0xffffffffu, l0, 2); l1 += __shfl_xor_sync(0xffffffffu, l1, 2);
    uint2 vm = lds64(l8 + SL_VM);
    uint4 v[2];
#pragma unroll
    for (int m = 0; m <= MT; m++) v[m] = lds128(l16 + SL_V + m * 4096);
    l0 = rcp(l0); l1 = rcp(l1);
    uint32_t P[NT][2];
#pragma unroll
    for (int i = 0; i < NT; i++) { P[i][0] = i < NT - 1 ? pack2(S[i][0] * l0, S[i][1] * l0) : 0u; P[i][1] = pack2(S[i][2] * l1, S[i][3] * l1); }
#pragma unroll
    for (int et = 0; et < 8; et++) {
        float a[4] = {0, 0, 0, 0}, b[4] = {0, 0, 0, 0};
        const uint2 um = vm;
        const uint4 u[2] = {v[0], v[MT]};
        if (et < 7) {
            vm = lds64(l8 + SL_VM + et * 256 + 256);
#pragma unroll
            for (int m = 0; m <= MT; m++) v[m] = lds128(l16 + SL_V + m * 4096 + et * 512 + 512);
            PIN(11);
        }
        mma8(a, um.x, um.y, P[0][0]); mma8(b, um.x, um.y, P[0][1]);
#pragma unroll
        for (int m = 0; m <= MT; m++) {
            mma16(a, u[m].x, u[m].y, u[m].z, u[m].w, P[1 + 2 * m][0], P[2 + 2 * m][0]); mma16(b, u[m].x, u[m].y, u[m].z, u[m].w, P[1 + 2 * m][1], P[2 + 2 * m][1]);
        }
        asm volatile("stmatrix.sync.aligned.m8n8.x4.trans.shared.b16 [%0],{%1,%2,%3,%4};" ::"r"(os + (et >> 2) * 2048 + (et & 3) * 256),
                     "r"(pack2(a[0], a[1])), "r"(pack2(a[2], a[3])), "r"(pack2(b[0], b[1])), "r"(pack2(b[2], b[3])) : "memory");
    }
}

__device__ __forceinline__ void rec_tiles(uint32_t sb, int X, int head, uint32_t rank, int& nxt, int lim, int need) {
#pragma unroll 1
    while (nxt <= lim) {
        if ((nxt & 1) == 0) {
            unsigned v; int n = 0;
            while (true) {
                asm volatile("ld.relaxed.gpu.global.u32 %0,[%1];" : "=r"(v) : "l"(cnt_ptr(C_QKV + X * 32 + (nxt >> 1))) : "memory");
                if (__all_sync(0xffffffffu, v >= 2 * NQ)) break;
                if (nxt > need) return;
                if (++n > 3000000) __trap();
            }
        }
        if (elect()) {
            const uint32_t bar = sb + R_BAR + (RB_XFULL + X * 2 + (nxt & 1)) * 8, dst = sb + R_SL + (X * 2 + (nxt & 1)) * SLOT;
            const uint4* src = g_qkv + (size_t)((X * 64 + nxt) * 32 + head) * 1536;
            mbar_expect(bar, 20480);
            bulk_g2s_mc(dst + rank * 8192, src + 512 + rank * 512, 8192, bar, POL_LAST);
            bulk_g2s(dst + SL_Q, src + (rank ^ X) * 256, 4096, bar, POL_LAST);
        }
        __syncwarp();
        nxt++;
    }
}

__device__ __forceinline__ void rec_attn(const Params& p, uint32_t sb, int X, int head, uint32_t rank) {
    const int lane = __shfl_sync(0xffffffffu, threadIdx.x & 31, threadIdx.x & 31), g = lane >> 2, c = lane & 3;
    const int mt = rank ^ X;
    const uint32_t dp = mapa(sb, rank ^ 1) - sb;
    int nxt = 0;
    rec_tiles(sb, X, head, rank, nxt, 1, 0);
#pragma unroll 1
    for (int s = 0; s < 64; s++) {
        const uint32_t so = sb + R_SL + (X * 2 + (s & 1)) * SLOT;
        mbar_wait(sb + R_BAR + (RB_GO + X * 2 + (s & 1)) * 8, (s >> 1) & 1);
        rec_tiles(sb, X, head, rank, nxt, min(s + 1, 63), -1);
        spin(DX);
        mbar_wait(sb + R_BAR + (RB_XFULL + X * 2 + (s & 1)) * 8, (s >> 1) & 1);
        if (elect()) asm volatile("cp.async.bulk.wait_group.read 0;" ::: "memory");
        __syncwarp();
        const uint32_t os = sb + R_OS + X * 4096 + (lane >> 4) * 1024 + (lane & 15) * 16;
        if (mt) xattn<1>(so + lane * 16, so + lane * 8, os, g, c); else xattn<0>(so + lane * 16, so + lane * 8, os, g, c);
        fence_async_smem();
        __syncwarp();
        const uint32_t svb = sb + R_BAR + (RB_SV + X * 2 + (s & 1)) * 8;
        if (elect()) {
            mbar_arrive(svb); mbar_arrive_cluster(svb + dp);
            const uint64_t pol = POL_SOON;
#pragma unroll
            for (int kb = 0; kb < 2; kb++)
                asm volatile("cp.async.bulk.global.shared::cta.bulk_group.L2::cache_hint [%0],[%1],%2,%3;" ::"l"(g_o + ((X * 32 + (s >> 1)) * 64 + head * 2 + kb) * 512 + ((s & 1) * 4 + mt * 2) * 64),
                             "r"(sb + R_OS + X * 4096 + kb * 2048), "r"(2048), "l"(pol) : "memory");
            asm volatile("cp.async.bulk.commit_group;" ::: "memory");
        }
        __syncwarp();
        if (s & 1) {
            if (TFIRST && nxt == s + 2) { mbar_wait(svb, (s >> 1) & 1); rec_tiles(sb, X, head, rank, nxt, min(s + 2, 63), -1); }
            if (elect()) { asm volatile("cp.async.bulk.wait_group 0;" ::: "memory"); RELO(cnt_ptr(C_O + (X * 32 + (s >> 1)) * 4 + (head >> 3)), 1); }
            __syncwarp();
        }
        rec_tiles(sb, X, head, rank, nxt, min(s + 1, 63), s + 1);
        mbar_wait(svb, (s >> 1) & 1);
        rec_tiles(sb, X, head, rank, nxt, min(s + 2, 63), -1);
    }
}

__device__ __forceinline__ uint32_t timed_clear(unsigned* r, int lane) {
    uint32_t v = 0;
    const uint32_t t0 = clk32();
    asm volatile("{.reg .pred p; setp.eq.u32 p,%2,0; @p atom.relaxed.gpu.global.exch.b32 %0,[%1],0;}" : "+r"(v) : "l"(r), "r"(lane) : "memory");
    v = __shfl_sync(0xffffffffu, v, 0);
    asm volatile("{.reg .pred p; setp.eq.u32 p,%0,0x5a5a5a5b; @p nanosleep.u32 1;}" ::"r"(v) : "memory");
    return clk32() - t0;
}
__device__ __forceinline__ void rec_slots(int me, int X) {
    const int lane = threadIdx.x & 31;
#pragma unroll 1
    for (int i = lane; i < 512; i += 32) xregion(X, me)[i] = make_uint4(0, 0, 0, 0);
    if (lane < 16) xregion(X, 64 + (me & 1))[(lane >> 3) * 256 + (me >> 1) * 8 + (lane & 7)] = make_uint4(0, 0, 0, 0);
    __syncwarp();
    uint32_t sel = 0;
#pragma unroll 1
    for (int k = 0; k < 2; k++) {
        unsigned* r = (unsigned*)xregion(X, k ? 64 + (me & 1) : me) + k * (me >> 1) * 32;
        uint32_t b0 = ~0u, b1 = ~0u;
#pragma unroll 1
        for (int i = 0; i < 4; i++) { b0 = min(b0, timed_clear(r, lane)); b1 = min(b1, timed_clear(r + 1024, lane)); }
        sel |= (b1 < b0) << (2 * k + X);
    }
    if (lane == 0) ((uint16_t*)g_sel)[me * 2 + X] = sel;
}

__device__ __forceinline__ void rec_init(uint32_t sb) {
    const uint32_t b = sb + R_BAR;
    const int i = threadIdx.x & 31;
    mbar_init(b + i * 8, i >= RB_SV ? 2 : 1);
    if (i == RB_INIT) mbar_expect(b + RB_INIT * 8, 196608);
    asm volatile("fence.mbarrier_init.release.cluster;" ::: "memory");
}
constexpr int G_BAR = B_BAR;
enum { GB_FULL = 0  , GB_EMPTY = 8  , GB_RS = 16, GB_SS = 17, GB_LAG = 18, GB_FREE = 19, GB_DONE = 20  , GB_N = 24 };
constexpr int Q_PRE = 8;
constexpr int NQRS = 2 * NQ - 64;
__device__ __forceinline__ void gemm_init(uint32_t sb, bool op) {
    const int i = threadIdx.x & 31;
    if (i < GB_N) mbar_init(sb + G_BAR + i * 8, i >= GB_DONE ? 4 : i == GB_FREE ? 8 : (i >= GB_EMPTY && i < GB_RS) ? 2 : 1);
    if (i == GB_RS) mbar_expect(sb + G_BAR + i * 8, op ? 131072 : 98304);
    if (i == GB_SS) mbar_expect(sb + G_BAR + i * 8, op ? 131072 : 163840);
    asm volatile("fence.mbarrier_init.release.cluster;" ::: "memory");
}
__device__ __forceinline__ int qkv_blk(int id, int j) { return NQRS * 4 + id * 10 + j; }
__device__ __forceinline__ void qkv_fetch(const Params& p, uint32_t sb, int id, int j0, int j1) {
#pragma unroll 1
    for (int j = j0 * 2; j < j1 * 2; j++) {
        const int blk = min(qkv_blk(id, j >> 1), 511);
        tma2d(sb + j * 8192, &p.tn[blk >> 8], (blk & 255) * 16, (j & 1) * 256, sb + G_BAR + GB_SS * 8);
    }
}
__device__ __forceinline__ void qkv_stage(const Params& p, uint32_t dst, uint32_t bar, int id, int k0, int nk) {
#pragma unroll 1
    for (int j = 0; j < 2 * nk; j++) {
        const int u = id * 2 + (j >= nk);
        tma2d(dst + j * 8192, &p.tm[u < 64 ? 2 : 0], (u & 63) * 64, (k0 + (j >= nk ? j - nk : j)) * 64, bar);
    }
}
__device__ __forceinline__ void op_fetch(const Params& p, uint32_t sb, int id, int half) {
#pragma unroll 1
    for (int j = 0; j < 16; j++) tma2d(sb + j * 8192, &p.tm[4], ((id * 2 + (j >> 3)) & 7) * 64, (id >> 2) * 1024 + (j & 7) * 128 + half * 64, sb + G_BAR + (GB_RS + half) * 8);
}
template <bool OP>
__device__ __forceinline__ void gemm_producer(const Params& p, uint32_t sb, int id) {
    constexpr int NS = OP ? 6 : 8, SB = OP ? 16384 : 8192, RING = OP ? 131072 : 163840;
    if (!elect()) return;
    mbar_wait(sb + G_BAR + GB_FREE * 8, 0);
    if (OP) op_fetch(p, sb, id, 1);
    else {
        mbar_expect(sb + G_BAR + GB_RS * 8, 32768);
        qkv_stage(p, sb + 196608, sb + G_BAR + GB_RS * 8, id, 6, 2);
        qkv_fetch(p, sb, id, Q_PRE, 10);
        mbar_wait(sb + G_BAR + GB_FREE * 8, 1);
    }
    wait_cnt(g_gate, lds32(sb + S_GATE));
    int st = 0; uint32_t ph = 1;
#pragma unroll 1
    for (int n = 0; n < p.nl[OP]; n++) {
        const int e = p.list[OP][n];
        wait_cnt(OP ? cnt_ptr(C_O + e * 4 + (id >> 2)) : cnt_ptr(C_XN + e), 16);
        PROF(true, 1024 + n * 4);
        const uint4* src = OP ? g_o + (e * 64 + (id >> 2) * 16) * 512 : g_xn + e * 4096;
#pragma unroll 1
        for (int s = 0; s < 8; s++) {
            mbar_wait(sb + G_BAR + (GB_EMPTY + st) * 8, ph);
            mbar_expect(sb + G_BAR + (GB_FULL + st) * 8, SB);
            bulk_g2s(sb + RING + st * SB, src + s * (SB / 16), SB, sb + G_BAR + (GB_FULL + st) * 8, POL_N);
            if (++st == NS) { st = 0; ph ^= 1; }
        }
    }
}
template <bool OP>
__device__ __forceinline__ void gemm_release(const Params& p, uint32_t sb, int id) {
    if (threadIdx.x != 288) return;
#pragma unroll 1
    for (int n = 0; n < 2 * p.nl[OP]; n++) {
        const int e = p.list[OP][n >> 1];
        mbar_wait(sb + G_BAR + (GB_DONE + (n & 3)) * 8, (n >> 2) & 1);
        red_release(OP ? cnt_ptr(C_PP + e * 8 + (id & 3) * 2 + (n & 1)) : cnt_ptr(C_QKV + e), 1);
        PROF(n & 1, 1024 + (n >> 1) * 4 + 3);
    }
}
__device__ __forceinline__ void op_permute(uint32_t sb) {
#pragma unroll 2
    for (int i = threadIdx.x; i < 4096; i += 256) {
        const uint32_t a = sb + i * 32 + ((i >> 2) & 1) * 16, b = a ^ 16;
        const uint4 x = lds128(a), y = lds128(b);
        sts128(a, __byte_perm(x.x, x.y, 0x5410), __byte_perm(x.z, x.w, 0x5410), __byte_perm(y.x, y.y, 0x5410), __byte_perm(y.z, y.w, 0x5410));
        sts128(b, __byte_perm(x.x, x.y, 0x7632), __byte_perm(x.z, x.w, 0x7632), __byte_perm(y.x, y.y, 0x7632), __byte_perm(y.z, y.w, 0x7632));
    }
    fence_async_smem();
    bar_sync(1, 256);
}
template <bool OP>
__device__ __forceinline__ void gemm_consumer(const Params& p, uint32_t sb, int id, int w) {
    constexpr int NS = OP ? 6 : 8, SB = OP ? 16384 : 8192, RING = OP ? 131072 : 163840;
    const int lane = threadIdx.x & 31, wg = w >> 2, t = w & 3, u = id * 2 + wg;
    uint32_t a[128];
    mbar_wait(sb + G_BAR + GB_RS * 8, 0);
    PROF(threadIdx.x == 0, 3501);
    if (OP) op_permute(sb);
    const uint32_t wo = sb + (((lane >> 4) << 3) + (lane & 7)) * 128 + (((2 * t + ((lane >> 3) & 1)) ^ (lane & 7)) << 4);
#pragma unroll
    for (int ks = 0; ks < 32; ks++) {
        const uint4 v = ldsm4t(wo + ks * 2048 + (OP ? wg * 65536 : ks < 24 ? 131072 + wg * 49152 : 196608 - 49152 + wg * 16384));
        a[ks * 4] = v.x; a[ks * 4 + 1] = v.y; a[ks * 4 + 2] = v.z; a[ks * 4 + 3] = v.w;
        if (ks == 31 || (!OP && ks == 23)) {
            fence_async_smem();
            __syncwarp();
            if (lane == 0) mbar_arrive(sb + G_BAR + GB_FREE * 8);
            if (ks == 23) mbar_wait(sb + G_BAR + GB_RS * 8, 1);
        }
    }
    PROF(threadIdx.x == 0, 3502);
    mbar_wait(sb + G_BAR + GB_SS * 8, 0);
    if (OP) op_permute(sb);
    PROF(threadIdx.x == 0, 3503);
    float c0[32], c1[OP ? 32 : 40];
    int st = 0; uint32_t ph = 0;
    const bool el = (threadIdx.x & 127) == 0;
#pragma unroll 1
    for (int n = 0; n < p.nl[OP]; n++) {
        int prev = 0;
        const uint32_t wb = sb + wg * (OP ? 65536 : 81920) + (n & p.zero);
        const uint64_t dw = OP ? mkdesc(wb, 0, 1024, 1) : mkdesc(wb, 16384, 256, 3);
        if (!OP && wg) mbar_wait(sb + G_BAR + GB_LAG * 8, n & 1);
#pragma unroll
        for (int s = 0; s < 8; s++) {
            mbar_wait(sb + G_BAR + (GB_FULL + st) * 8, ph);
            const uint64_t dx = mkdesc(sb + RING + st * SB, 128, 1024, 0);
            wg_fence();
#pragma unroll
            for (int kk = 0; kk < 4; kk++) {
                const int ks = s * 4 + kk;
                if (ks == 0) { wgmma64_rs<0>(c0, a, dx); if (OP) wgmma64_ta<0>(c1, dw, dx + 512); else wgmma80_tb<0>(c1, dx, dw); }
                else { wgmma64_rs<1>(c0, a + ks * 4, dx + kk * 16); if (OP) wgmma64_ta<1>(c1, dw + ks * 128, dx + 512 + kk * 16); else wgmma80_tb<1>(c1, dx + kk * 16, dw + ks * 32); }
            }
            wg_commit();
            if (s) {
                wg_wait<1>();
                if (el) { mbar_arrive(sb + G_BAR + (GB_EMPTY + prev) * 8); if (!OP && s == QLAG && !wg) mbar_arrive(sb + G_BAR + GB_LAG * 8); }
            }
            prev = st;
            if (++st == NS) { st = 0; ph ^= 1; }
        }
        const int e = p.list[OP][n];
        wg_wait<0>();
        if (el) mbar_arrive(sb + G_BAR + (GB_EMPTY + prev) * 8);
        PROF(threadIdx.x == 128, 1024 + n * 4 + 1);
        if (OP) {
            uint4* dst = g_pp + (e * 4 + (id >> 2)) * 4096 + ((u & 7) * 32 + t * 8) * 16 + (lane >> 2) * 16 + (lane & 3);
#pragma unroll
            for (int j = 0; j < 4; j++) {
                const float* x = c0 + j * 8; const float* y = c1 + j * 8;
                stg128(dst + j * 4, make_uint4(pack2(x[0] + y[0], x[1] + y[1]), pack2(x[2] + y[2], x[3] + y[3]), pack2(x[4] + y[4], x[5] + y[5]), pack2(x[6] + y[6], x[7] + y[7])), POL_SOON);
            }
        } else {
            uint4* dst = g_qkv + (size_t)e * 2 * 32 * 1536 + lane;
            const uint64_t pol = POL_SOON;
#pragma unroll
            for (int j = 0; j < 4; j++) {
                const float* x = c0 + j * 8;
                uint4 v = make_uint4(pack2(x[0], x[1]), pack2(x[2], x[3]), pack2(x[4], x[5]), pack2(x[6], x[7]));
                if (u >= 64) v = make_uint4(movm(v.x), movm(v.z), movm(v.y), movm(v.w));
                stg128(dst + (((j >> 1) * 32 + ((u & 63) >> 1)) * 1536 + (u < 64 ? 1024 : 0) + (j & 1) * 256 + ((u & 1) * 4 + t) * 32), v, pol);
            }
#pragma unroll
            for (int j = 0; j < 5; j++) {
                const float* x = c1 + (OP ? 0 : j * 8);
                const int blk = qkv_blk(id, wg * 5 + j);
                if (blk < 512) stg128(dst + (((t >> 1) * 32 + ((blk >> 3) & 31)) * 1536 + (blk >> 8) * 512 + (t & 1) * 256 + (blk & 7) * 32),
                                      make_uint4(pack2(x[0], x[1]), pack2(x[2], x[3]), pack2(x[4], x[5]), pack2(x[6], x[7])), pol);
            }
        }
        __syncwarp();
        if (lane == 0) mbar_arrive(sb + G_BAR + (GB_DONE + (n & 1) * 2 + wg) * 8);
        PROF(threadIdx.x == 128, 1024 + n * 4 + 2);
    }
}

template <int NP, bool MMA>
__device__ __forceinline__ void sum_partials(float* x, const uint2* src, const uint32_t* r0, const uint32_t* r1, uint32_t idm) {
    uint2 v[4][NP];
#pragma unroll
    for (int s = 0; s < 4; s++)
#pragma unroll
        for (int i = 0; i < NP; i++) asm volatile("ld.global.cg.L2::cache_hint.v2.u32 {%0,%1},[%2],%3;" : "=r"(v[s][i].x), "=r"(v[s][i].y) : "l"(src + s * 8192 + i * 32), "l"(POL_LAST) : "memory");
#pragma unroll
    for (int i = 0; i < NP; i++) {
        uint32_t a, b;
        if (MMA) {
            float t[4] = {0, 0, 0, 0};
            mma16(t, v[0][i].x, v[0][i].y, v[1][i].x, v[1][i].y, idm, idm); mma16(t, v[2][i].x, v[2][i].y, v[3][i].x, v[3][i].y, idm, idm);
            a = pack2(t[0], t[2]); b = pack2(t[1], t[3]);
        } else {
            a = pack2((blo(v[0][i].x) + blo(v[1][i].x)) + (blo(v[2][i].x) + blo(v[3][i].x)), (blo(v[0][i].y) + blo(v[1][i].y)) + (blo(v[2][i].y) + blo(v[3][i].y)));
            b = pack2((bhi(v[0][i].x) + bhi(v[1][i].x)) + (bhi(v[2][i].x) + bhi(v[3][i].x)), (bhi(v[0][i].y) + bhi(v[1][i].y)) + (bhi(v[2][i].y) + bhi(v[3][i].y)));
        }
        const uint32_t s0 = hadd2(a, r0[i]), s1 = hadd2(b, r1[i]);
        x[4 * i] = blo(s0); x[4 * i + 2] = bhi(s0); x[4 * i + 1] = blo(s1); x[4 * i + 3] = bhi(s1);
    }
}
__device__ __forceinline__ const uint2* pp_src(int e, int tile, int lane) { return (const uint2*)g_pp + e * 32768 + tile * 128 + (lane >> 3) * 8 + (lane & 3) * 2 + ((lane >> 2) & 1); }

__device__ __forceinline__ void fin_warp(const Params& p, uint32_t sb, int id) {
    const int tile = (id & ~1) + (threadIdx.x & 1), lane = (id & 1) * 16 + ((threadIdx.x & 31) >> 1);
    wait_cnt_warp(g_gate, lds32(sb + S_GATE));
#pragma unroll 1
    for (int e = 32; e < 64; e++) {
        wait_cnt_warp(cnt_ptr(C_PP + e * 8 + (id >> 3)), 4);
        const uint4* rp = g_x + ((128 + tile * 2) * XP + (e - 32) * 32 + lane);
        uint32_t o0[4], o1[4];
#pragma unroll
        for (int h = 0; h < 2; h++) {
            const uint4 r = ldcg128(rp + h * XP);
            const uint32_t a[2] = {r.x, r.y}, b[2] = {r.z, r.w};
            float x[8];
            sum_partials<2, false>(x, pp_src(e, tile, lane) + h * 64, a, b, 0);
#pragma unroll
            for (int i = 0; i < 2; i++) {
                o0[h * 2 + i] = __byte_perm(__float_as_uint(x[4 * i]), __float_as_uint(x[4 * i + 2]), 0x7632);
                o1[h * 2 + i] = __byte_perm(__float_as_uint(x[4 * i + 1]), __float_as_uint(x[4 * i + 3]), 0x7632);
            }
        }
        uint4* dst = (uint4*)p.out + ((e - 32) * 64 + lane * 2) * 64 + tile;
        dst[0] = make_uint4(o0[0], o0[1], o0[2], o0[3]); dst[64] = make_uint4(o1[0], o1[1], o1[2], o1[3]);
        PROF((threadIdx.x & 31) == 0, 1536 + e);
    }
}

constexpr int PROW = 272, UROW = 2304, UPRE = 256;
constexpr int C_UR = 0  , C_TB = 65536  , C_BG = C_TB + 51200,
              CB_M = 8960, CB_U = CB_M + 1792, CB_BIG = CB_U + 2560, C_ST = C_BG + 8 * CB_BIG  ;
static_assert(C_ST + 4736 <= B_BAR, "smem map");
enum { CB_TB = 0, CB_UF = 1  , CB_CF = 5  , CB_LD = 9   };
__device__ __forceinline__ void conv_init(uint32_t sb, bool spare) {
    const int i = threadIdx.x & 31;
    mbar_init(sb + B_BAR + i * 8, (i >= CB_UF && i < CB_CF && !spare) ? 2 : 1);
    if (i == CB_TB && !spare) mbar_expect(sb + B_BAR + i * 8, 51200);
    asm volatile("fence.mbarrier_init.release.cluster;" ::: "memory");
}
__device__ __forceinline__ void mma_q(float* c, const uint32_t* a, const uint4& q) {
    mma16(c, a[0], a[1], a[2], a[3], q.x, q.y); mma16(c, a[4], a[5], a[6], a[7], q.z, q.w);
}
__device__ __forceinline__ uint2 ld_acc(const uint2* p, bool on) {
    uint2 v = make_uint2(0, 0);
    asm volatile("{.reg .pred p; setp.ne.u32 p,%3,0; @p ld.global.cg.v2.u32 {%0,%1},[%2];}" : "+r"(v.x), "+r"(v.y) : "l"(p), "r"((uint32_t)on) : "memory");
    return v;
}
__device__ __forceinline__ void add_acc(float* c, uint2 v) { c[0] += blo(v.x); c[1] += bhi(v.x); c[2] += blo(v.y); c[3] += bhi(v.y); }
__device__ __forceinline__ void st_acc(uint2* p, const float* c) { *p = make_uint2(pack2(c[0], c[1]), pack2(c[2], c[3])); }
__device__ __forceinline__ float sum8(const uint4* v, int k) {
#define VK(i) __uint_as_float(k == 0 ? v[i].x : k == 1 ? v[i].y : k == 2 ? v[i].z : v[i].w)
    return ((VK(0) + VK(1)) + (VK(2) + VK(3))) + ((VK(4) + VK(5)) + (VK(6) + VK(7)));
}
template <int XW>
__device__ __forceinline__ void stats_send(uint32_t l16, const float* x, uint4* gs, int q, int w) {
    float s0 = 0, s1 = 0, m0 = 0, m1 = 0;
#pragma unroll
    for (int i = 0; i < 8; i++) { s0 += x[2 * i]; s1 += x[2 * i + 1]; m0 = fmaf(x[2 * i], x[2 * i], m0); m1 = fmaf(x[2 * i + 1], x[2 * i + 1], m1); }
    sts128(l16 + C_ST + w * 512, __float_as_uint(s0), __float_as_uint(m0), __float_as_uint(s1), __float_as_uint(m1));
    if (w == XW) {
        bar_sync(2, 256);
        uint4 v[8];
#pragma unroll
        for (int i = 0; i < 8; i++) v[i] = lds128(l16 + C_ST + i * 512);
        st_rlx128(gs + q * 32, __float_as_uint(sum8(v, 0)), __float_as_uint(sum8(v, 1)) & 0x7fffffffu, __float_as_uint(sum8(v, 2)), __float_as_uint(sum8(v, 3)));
    } else bar_arrive(2, 256);
}
template <int XW>
__device__ __forceinline__ float4 stats_recv(uint32_t l16, const uint4* gs, int w) {
    if (w == XW) {
        uint4 v[8];
        int n = 0;
        while (true) {
            uint32_t bad = 0;
#pragma unroll
            for (int i = 0; i < 8; i++) v[i] = ld_rlx128(gs + i * 32);
#pragma unroll
            for (int i = 0; i < 8; i++) bad |= v[i].y;
            if (!__any_sync(0xffffffffu, bad >> 31)) break;
            if (++n > 2000000) __trap();
        }
        const float s0 = sum8(v, 0) * (1.f / 512.f), s1 = sum8(v, 2) * (1.f / 512.f);
        const float2 l0 = ln_finish(s0, fmaxf(fmaf(sum8(v, 1), 1.f / 512.f, -s0 * s0), 0.f)), l1 = ln_finish(s1, fmaxf(fmaf(sum8(v, 3), 1.f / 512.f, -s1 * s1), 0.f));
        sts128(l16 + C_ST + 4096, __float_as_uint(l0.x), __float_as_uint(rcp(l0.y)), __float_as_uint(l1.x), __float_as_uint(rcp(l1.y)));
    }
    bar_sync(3, 256);
    const uint4 r = lds128(l16 + C_ST + 4096);
    return make_float4(__uint_as_float(r.x), __uint_as_float(r.y), __uint_as_float(r.z), __uint_as_float(r.w));
}

#define HOIST_STOP(k) asm volatile("{.reg .pred p; setp.eq.u32 p,%0,%1; @p nanosleep.u32 1;}" ::"r"(zero), "r"((k) + 1) : "memory")
__device__ __forceinline__ void conv_near(float (*acc)[4], uint32_t ta, uint32_t qa, uint32_t zero) {
#pragma unroll
    for (int k = 0; k < 8; k++) {
        uint32_t a[8];
#pragma unroll
        for (int j = 0; j < 8; j++) a[j] = lds32(ta + k * 800 + j * 32);
        mma_q(acc[k], a, ldsm4(qa + k * 1024));
        if (k % NFE == NFE - 1 && k < 7) HOIST_STOP(k);
    }
}
template <int K0>
__device__ __forceinline__ void conv_pair(float (*acc)[4], float (*pend)[4], uint32_t ta, uint32_t q0, uint32_t q1, uint32_t q2, uint32_t zero) {
#pragma unroll
    for (int i = 0; i < 4; i++) {
        const int k = K0 + i;
#pragma unroll
        for (int e = 0; e < 4; e++) { acc[4 - K0 + i][e] += pend[i][e]; pend[i][e] = 0; }
        uint32_t a[16];
#pragma unroll
        for (int j = 0; j < 16; j++) a[j] = lds32(ta + 256 + k * 800 + j * 32);
        const uint4 x1 = ldsm4(q1 + k * 1024);
        mma_q(acc[k], a, x1); mma_q(pend[i], a, ldsm4(q2 + k * 1024));
        mma_q(pend[i], a + 8, x1); mma_q(acc[k], a + 8, ldsm4(q0 + k * 1024));
        if (i % NFP == NFP - 1 && i < 3) HOIST_STOP(k);
    }
}

__device__ __forceinline__ void conv_tile(const Params& p, uint32_t sb, int q, int w) {
    const int lane = __shfl_sync(0xffffffffu, threadIdx.x & 31, threadIdx.x & 31), g = lane >> 2, c = lane & 3, tile = q * 8 + w;
    const uint32_t l16 = sb + lane * 16;
#pragma unroll
    for (int i = 0; i < 16; i++) sts128(l16 + C_UR + w * 8192 + i * 512, 0, 0, 0, 0);
    wait_cnt_warp(g_gate, lds32(sb + S_GATE));
    if (lane < 8) bulk_g2s(sb + C_TB + (w * 8 + lane) * 800, g_P + (tile * 8 + lane) * PROW + 72, 800, sb + B_BAR + CB_TB * 8, POL_N);
    uint32_t A[8][8];
#pragma unroll
    for (int k = 0; k < 8; k++)
#pragma unroll
        for (int j = 0; j < 8; j++) A[k][j] = __ldcg(g_P + (tile * 8 + k) * PROW + 16 + 8 * j + g - 2 * c);
    if (lane == 0) { const uint4 d = __ldg((const uint4*)p.Dskip + tile); sts128(sb + C_ST + 4608 + w * 16, d.x, d.y, d.z, d.w); }
    float acc[8][4], pend[4][4];
#pragma unroll
    for (int k = 0; k < 8; k++) acc[k][0] = acc[k][1] = acc[k][2] = acc[k][3] = pend[k & 3][k >> 2] = pend[k & 3][2 + (k >> 2)] = 0;
    const uint32_t row = sb + C_UR + w * 8192, ta = sb + C_TB + w * 6400 + (8 + g - 2 * c) * 4, zero = p.zero, qo = (lane & 7) * 16 - (lane >> 3) * 32;
    bar_sync(4, 384);
    mbar_wait(sb + B_BAR + CB_TB * 8, 0);
#pragma unroll 1
    for (int b = 0; b < 32; b++) {
        const int lz = lane + (b & p.zero);
        const uint4 r0 = ldcg128(g_x + (tile * 2 * XP + b * 32 + lz)), r1 = ldcg128(g_x + (tile * 2 * XP + b * 32 + lz) + XP);
        const uint32_t q1 = row + ((qo + (b - 1) * 128) & 1023);
        if (w == 0) conv_near(acc, ta, q1, zero);
        PROF(threadIdx.x == 0, 2048 + b * 8);
        const uint2* pps = pp_src(b, tile, lz);
        asm volatile("" : "+l"(pps));
        wait_flag_warp(cnt_ptr(C_PP + b * 8 + q), 4);
        PROF(threadIdx.x == 0, 2048 + b * 8 + 1);
        float x[16];
        {
            const uint32_t a[4] = {r0.x, r0.y, r1.x, r1.y}, bb[4] = {r0.z, r0.w, r1.z, r1.w};
            sum_partials<4, true>(x, pps, a, bb, (2 * (lz & 3) == lz >> 2) ? 0x00003f80u : (2 * (lz & 3) + 1 == lz >> 2) ? 0x3f800000u : 0u);
        }
        stats_send<0>(l16, x, g_st + b * 256 + lz, q, w);
        {
            PROF(threadIdx.x == 0, 2048 + b * 8 + 2);
            if (b) mbar_wait(sb + B_BAR + (CB_CF + (w >> 1)) * 8, (b - 1) & 1);
            const uint2* cb = g_carry + ((tile * 320 + b) * 32 + lz);
            uint2 cr[8];
#pragma unroll
            for (int k = 0; k < 8; k++) cr[k] = ld_acc(cb + k * 1280, b >= 4);
            if (w) conv_near(acc, ta, q1, zero);
#pragma unroll
            for (int k = 0; k < 8; k++) add_acc(acc[k], cr[k]);
        }
        float4 ln = stats_recv<0>(l16, g_st + b * 256 + lz, w);
        PROF(threadIdx.x == 0, 2048 + b * 8 + 3);
        uint32_t u[8];
#pragma unroll
        for (int k = 0; k < 8; k++) {
            u[k] = pack2(rbf(x[2 * k] - ln.x) * ln.y, rbf(x[2 * k + 1] - ln.z) * ln.w);
            sts32(row + k * 1024 + (b & 7) * 128 + lane * 4, u[k]);
        }
        __syncwarp();
        if (UFE && lane == 0) mbar_arrive(sb + B_BAR + (CB_UF + (w >> 1)) * 8);
        const uint32_t qa = row + ((qo + b * 128) & 1023);
#pragma unroll
        for (int k = 0; k < 8; k++) mma_q(acc[k], A[k], ldsm4(qa + k * 1024));
        const uint4 dk = lds128(sb + C_ST + 4608 + w * 16);
#pragma unroll
        for (int k = 0; k < 8; k++) {
            const float t = __shfl_sync(0xffffffffu, acc[k][3], (lz & ~3) | ((lz - 1) & 3));
            const uint32_t y = movm(pack2(acc[k][0] + (c ? t : 0.f), acc[k][1] + acc[k][2]));
            acc[k][0] = c ? 0.f : t; acc[k][1] = acc[k][2] = acc[k][3] = 0;
            const uint32_t dw = k >> 1 == 0 ? dk.x : k >> 1 == 1 ? dk.y : k >> 1 == 2 ? dk.z : dk.w;
            const uint32_t s = hadd2(hadd2(y, hmul2(u[k], __byte_perm(dw, 0, (k & 1) ? 0x3232 : 0x1010))), __byte_perm(__float_as_uint(x[2 * k]), __float_as_uint(x[2 * k + 1]), 0x7632));
            x[2 * k] = blo(s); x[2 * k + 1] = bhi(s);
        }
        if (!UFE && lane == 0) mbar_arrive(sb + B_BAR + (CB_UF + (w >> 1)) * 8);
        stats_send<1>(l16, x, g_st + (32 + b) * 256 + lz, q, w);
        {
            PROF(threadIdx.x == 0, 2048 + b * 8 + 4);
            uint4* dst = g_x + ((128 + tile * 2) * XP + b * 32 + lz);
#pragma unroll
            for (int e = 0; e < 2; e++) {
                const float* y = x + e * 8;
                dst[e * XP] = make_uint4(__byte_perm(__float_as_uint(y[0]), __float_as_uint(y[2]), 0x7632), __byte_perm(__float_as_uint(y[4]), __float_as_uint(y[6]), 0x7632),
                                           __byte_perm(__float_as_uint(y[1]), __float_as_uint(y[3]), 0x7632), __byte_perm(__float_as_uint(y[5]), __float_as_uint(y[7]), 0x7632));
            }
            uint32_t* du = g_u + (tile * 8 * (UROW / 2) + UPRE / 2 + b * 32 + lz);
#pragma unroll
            for (int k = 0; k < 8; k++) du[k * (UROW / 2)] = u[k];
        }
#pragma unroll 1
        for (int pass = 0; pass < 2; pass++) {
            if (pass == (w == 1)) {
                const uint32_t q0 = row + ((qo + (b - 2) * 128) & 1023);
                if (b & 1) conv_pair<4>(acc, pend, ta, q0, q1, qa, zero); else conv_pair<0>(acc, pend, ta, q0, q1, qa, zero);
            }
            if (pass) break;
            ln = stats_recv<1>(l16, g_st + (32 + b) * 256 + lz, w);
            PROF(threadIdx.x == 0, 2048 + b * 8 + 5);
            uint32_t o[2][4];
#pragma unroll
            for (int e = 0; e < 2; e++) {
                const float mu = e ? ln.z : ln.x, rs = e ? ln.w : ln.y;
#pragma unroll
                for (int i = 0; i < 4; i++) o[e][i] = pack2(rbf(x[4 * i + e] - mu) * rs, rbf(x[4 * i + 2 + e] - mu) * rs);
            }
#pragma unroll
            for (int i = 0; i < 4; i++) {
                const uint32_t t = __shfl_xor_sync(0xffffffffu, (lz & 1) ? o[0][i] : o[1][i], 1);
                if (lz & 1) o[0][i] = t; else o[1][i] = t;
            }
            uint4* dst = g_xn + ((32 + b) * 4096 + q * 512 + (lz >> 2) * 64 + w * 8 + (lz & 2) * 2 + (lz & 1));
            dst[0] = make_uint4(o[0][0], o[0][1], o[0][2], o[0][3]); dst[2] = make_uint4(o[1][0], o[1][1], o[1][2], o[1][3]);
            if (w == 7) {
                bar_sync(5, 256);
                if (elect()) red_release(cnt_ptr(C_XN + 32 + b), 2);
                PROF(lane == 0, 2048 + b * 8 + 6);
                __syncwarp();
            } else bar_arrive(5, 256);
        }
    }
}

template <int P0, bool TRI = false>
__device__ __forceinline__ void bg_half(float (*acc)[4], uint4* win, uint32_t ta, uint32_t qa, uint32_t mask, uint32_t row) {
#pragma unroll
    for (int i = 0; i < 4; i++) {
        win[P0 + i] = ldsm4(((qa + i * 128) & mask) + row);
        const uint4 a = lds128(ta + (3 - i) * 448), e = lds128(ta + (3 - i) * 448 + 224);
#pragma unroll
        for (int r = TRI ? 7 - P0 - i : 0; r < 8; r++) mma16(acc[r], a.x, a.y, a.z, a.w, win[(P0 + i + 1 + r) & 7].x, win[(P0 + i + 1 + r) & 7].y);
#pragma unroll
        for (int r = TRI ? 7 - P0 - i : 0; r < 8; r++) mma16(acc[r], e.x, e.y, e.z, e.w, win[(P0 + i + 1 + r) & 7].z, win[(P0 + i + 1 + r) & 7].w);
    }
}
__device__ __forceinline__ void bg_fetch(uint32_t sb, int q, int j, int n, int lane) {
    const int b0 = n >> 1, ch = q * 64 + j * 16 + (n & 1) * 8 + (b0 & 7), lo = max(b0 - 24, -4), nu = b0 > 4 ? (b0 - 4 - lo) * 128 : 0;
    const uint32_t bar = sb + B_BAR + (CB_LD + j * 2 + (n & 1)) * 8, buf = sb + C_BG + (j * 2 + (n & 1)) * CB_BIG;
    const int nt = min((b0 + 7) >> 2, 5) * 1792;
    if (elect()) {
        mbar_expect(bar, nt + nu + 1792);
        bulk_g2s(buf, g_W + ch * 784, nt, bar, POL_N);
        bulk_g2s(buf + CB_M, g_W + (ch ^ 4) * 784, 1792, bar, POL_N);
        if (nu) bulk_g2s(buf + CB_U + (lo - b0 + 24) * 128, g_u + ch * (UROW / 2) + UPRE / 2 + lo * 32, nu, bar, POL_N);
    }
    __syncwarp();
}
__device__ __forceinline__ void conv_back(uint32_t sb, int q, int j) {
    const int lane = __shfl_sync(0xffffffffu, threadIdx.x & 31, threadIdx.x & 31), g = lane >> 2, c = lane & 3;
    wait_cnt_warp(g_gate, lds32(sb + S_GATE));
    bg_fetch(sb, q, j, 2, lane);
    bar_sync(4, 384);
    const uint32_t to = (6 + g - 2 * c) * 16, qo = (lane & 7) * 16 - (lane >> 3) * 32;
#pragma unroll 1
    for (int n = 2; n < 64; n++) {
        const int b0 = n >> 1, i = n & 1, chl = j * 16 + i * 8 + (b0 & 7), hm = (b0 + 7) >> 2;
        const uint32_t buf = sb + C_BG + (j * 2 + i) * CB_BIG, ta = buf + to;
        float acc[8][4];
        uint4 win[8];
        if (n < 63) bg_fetch(sb, q, j, n + 1, lane);
        if (n == 34 || n == 42) wait_flag_warp(cnt_ptr(C_FAR + (n == 42)), 12);
        mbar_wait(sb + B_BAR + (CB_LD + j * 2 + i) * 8, (b0 - 1) & 1);
#pragma unroll
        for (int r = 0; r < 8; r++) {
            acc[r][0] = acc[r][1] = acc[r][2] = acc[r][3] = 0;
            win[r] = make_uint4(0, 0, 0, 0);
            if (r) asm volatile("{.reg .pred p; setp.ge.s32 p,%5,24; @p ldmatrix.sync.aligned.m8n8.x4.shared.b16 {%0,%1,%2,%3},[%4];}"
                                : "+r"(win[r].x), "+r"(win[r].y), "+r"(win[r].z), "+r"(win[r].w) : "r"(buf + CB_U + qo + r * 128), "r"(b0 + r) : "memory");
        }
        const uint2* fr = g_far + (((q * 64 + chl) * 8 + b0 - 24) * 32 + lane);
        uint2* cr = g_carry + (((q * 64 + chl) * 40 + b0) * 32 + lane);
        uint2* cm = g_carry + (((q * 64 + (chl ^ 4)) * 40 + b0) * 32 + lane);
        const uint32_t fm = 0xff000000u >> b0;
        uint2 pf[8], pm[4];
#pragma unroll
        for (int r = 0; r < 8; r++) pf[r] = ld_acc(fr + r * 32, (fm >> r) & 1);
#pragma unroll
        for (int r = 0; r < 4; r++) pm[r] = ld_acc(cm + r * 32, b0 > 4);
#pragma unroll 1
        for (int h = hm > 3 ? 5 : 3; h >= 3; h -= 2) {
            if (h <= hm) bg_half<0>(acc, win, ta + (h - 1) * 1792, qo + (28 - 4 * h) * 128, ~0u, buf + CB_U);
            if (h == 3 && i == 0) mbar_wait(sb + B_BAR + (CB_UF + j) * 8, (b0 - 1) & 1);
            bg_half<4>(acc, win, ta + (h - 2) * 1792, qo + (h == 3 ? b0 - 4 : 12) * 128, h == 3 ? 1023u : ~0u, h == 3 ? sb + C_UR + chl * 1024 : buf + CB_U);
        }
        uint4 wm[8];
#pragma unroll
        for (int r = 1; r < 8; r++) wm[r] = ldsm4(sb + C_UR + (chl ^ 4) * 1024 + ((qo + (b0 + r) * 128) & 1023));
#pragma unroll
        for (int r = 0; r < 8; r++) add_acc(acc[r], pf[r]);
#pragma unroll
        for (int r = 4; r < 8; r++) { st_acc(cr + r * 32, acc[r]); acc[r][0] = blo(pm[r - 4].x); acc[r][1] = bhi(pm[r - 4].x); acc[r][2] = blo(pm[r - 4].y); acc[r][3] = bhi(pm[r - 4].y); }
#pragma unroll
        for (int t = 7; t >= 0; t--) {
            const uint4 a = lds128(ta + t * 224), e = lds128(ta + CB_M + t * 224);
#pragma unroll
            for (int r = 0; r < 4; r++) { const uint4& x = win[4 + r - (t >> 1)]; mma16(acc[r], a.x, a.y, a.z, a.w, (t & 1) ? x.z : x.x, (t & 1) ? x.w : x.y); }
#pragma unroll
            for (int r = 0; r < 4; r++) { const uint4& x = wm[4 + r - (t >> 1)]; mma16(acc[4 + r], e.x, e.y, e.z, e.w, (t & 1) ? x.z : x.x, (t & 1) ? x.w : x.y); }
        }
#pragma unroll
        for (int r = 0; r < 4; r++) { st_acc(cr + r * 32, acc[r]); st_acc(cm + r * 32, acc[4 + r]); }
        __syncwarp();
        if (lane == 0 && i) mbar_arrive(sb + B_BAR + (CB_CF + j) * 8);
        PROF(j == 0 && lane == 0 && i, 2048 + b0 * 8 + 7);
    }
}
__device__ __forceinline__ void conv_far(uint32_t sb, int w) {
    const int lane = __shfl_sync(0xffffffffu, threadIdx.x & 31, threadIdx.x & 31), g = lane >> 2, c = lane & 3;
    wait_cnt_warp(g_gate, lds32(sb + S_GATE));
    wait_cnt_warp(cnt_ptr(C_XN + 39), 16);
    const uint32_t to = (6 + g - 2 * c) * 16, qo = (lane & 7) * 16 - (lane >> 3) * 32;
#pragma unroll 1
    for (int n = -1; n * 12 + w < 512; n++) {
        const int t = n * 12 + w, ch = (t & 63) * 8 + (((t >> 6) + 1) & 7), cn = ((t + 12) & 63) * 8 + ((((t + 12) >> 6) + 1) & 7);
        const uint32_t bar = sb + B_BAR + (w * 2 + (n & 1)) * 8, buf = sb + (w * 2 + (n & 1)) * 5120;
        if (t + 12 < 512 && elect()) {
            const uint32_t nb = sb + (w * 2 + (~n & 1)) * 5120;
            mbar_expect(bar ^ 8, 3584 + 1152);
            bulk_g2s(nb, g_W + cn * 784 + 560, 3584, bar ^ 8, POL_N);
            bulk_g2s(nb + 3584, g_u + cn * (UROW / 2) + UPRE / 2 - 32, 1152, bar ^ 8, POL_N);
        }
        __syncwarp();
        if (n < 0) continue;
        float acc[8][4];
        uint4 win[8];
#pragma unroll
        for (int r = 0; r < 8; r++) { acc[r][0] = acc[r][1] = acc[r][2] = acc[r][3] = 0; win[r] = make_uint4(0, 0, 0, 0); }
        mbar_wait(bar, (n >> 1) & 1);
        bg_half<0, true>(acc, win, buf + to + 1792, qo + 128, ~0u, buf + 3584);
        bg_half<4, true>(acc, win, buf + to, qo + 640, ~0u, buf + 3584);
#pragma unroll
        for (int r = 0; r < 8; r++) st_acc(g_far + (ch * 256 + lane) + r * 32, acc[r]);
        __syncwarp();
        if (((t + 12) ^ t) >= 256 && elect()) red_release(cnt_ptr(C_FAR + (t >> 8)), 1);
        __syncwarp();
    }
    PROF(threadIdx.x == 0, 2048);
}

constexpr int P_X = 131072  , P_K6 = P_X + 32768  , P_P = P_K6 + 10496  , P_U = P_P + 33280  ,
              P_END = P_U + 17408, P_PRM = P_P + 8192  , P_Y = P_P  ;
static_assert(P_END <= B_BAR && P_END <= R_SEL, "prologue scratch");
#define KGUN 2
constexpr int KGU = KGUN;
__device__ __forceinline__ void csq(float& r, float& i) { const float t = r * i; r = fmaf(r, r, -(i * i)); i = t + t; }
__device__ __forceinline__ void cpow(float ar, float ph, float p, float& r, float& i) {
    const float e = ex2(ar * p);
    const float u = ph * p, n = fabsf(u) < 4194304.f ? (u + 12582912.f) - 12582912.f : u;
    const float t = (u - n) * 6.283185307179586f;
    r = e * __cosf(t); i = e * __sinf(t);
}
__device__ __forceinline__ void mma_tf32(float* c, float a0, float a1, float a2, float a3, float b0, float b1) {
    asm volatile("mma.sync.aligned.m16n8k8.row.col.f32.tf32.tf32.f32 {%0,%1,%2,%3},{%4,%5,%6,%7},{%8,%9},{%0,%1,%2,%3};"
                 : "+f"(c[0]), "+f"(c[1]), "+f"(c[2]), "+f"(c[3])
                 : "r"(__float_as_uint(a0)), "r"(__float_as_uint(a1)), "r"(__float_as_uint(a2)), "r"(__float_as_uint(a3)), "r"(__float_as_uint(b0)), "r"(__float_as_uint(b1)));
}

__device__ __forceinline__ void early_fetch(const Params& p, uint32_t sb) {
    const int v = blockIdx.x;
    if (elect()) {
        if (v >= V_QKV) { if (v < V_QKV + NQ && (p.roles & 8)) qkv_fetch(p, sb, v - V_QKV, 0, Q_PRE); }
        else if (v >= V_OP) { if (p.roles & 4) op_fetch(p, sb, v - V_OP, 0); }
        else if (v >= V_REC && (p.roles & 2)) { rec_fetch(p, sb, (v - V_REC) >> 1, v & 1, 0, R_STQ); rec_fetch(p, sb, (v - V_REC) >> 1, v & 1, 2, R_STV); }
    }
    __syncwarp();
}
struct ProRegs { uint32_t v[2][4], ldt[2]; };
__device__ __forceinline__ void prologue_load(const ProArgs& a, int b, ProRegs& pr) {
    const int w = threadIdx.x >> 5;
#pragma unroll
    for (int i = 0; i < 2; i++) {
        const int gi = b * 512 + (w & 3) * 128 + ((w >> 2) & 1) * 64 + i * 32 + (threadIdx.x & 31);
        pr.ldt[i] = __ldg((const uint16_t*)a.ldt + b * 4 + (w & 3));
        pr.v[i][0] = __ldg((const uint16_t*)a.lAr + gi); pr.v[i][1] = __ldg((const uint16_t*)a.Ai + gi);
        pr.v[i][2] = __ldg((const uint16_t*)a.Cr + gi); pr.v[i][3] = __ldg((const uint16_t*)a.Ci + gi);
    }
}
__device__ __forceinline__ void prologue(const Params& p, uint32_t sb, int b, int w, const ProRegs& pr) {
    const ProArgs& a = p.pa;
    const int tid = threadIdx.x, lane = tid & 31, g = lane >> 2, c = lane & 3;
    const int d0 = b * 4;
    if (w >= 8) {
        const int t2 = tid - 256;
        if (w < 10) {
            const int row = b * 16 + (w - 8) * 8 + g;
            uint4 v[16];
            const float2 r = row_stats512(v, (const uint4*)(a.x + (size_t)row * 512) + c, 8, 4);
            const float2 l = ln_finish(r.x * (1.f / 512.f), r.y * (1.f / 512.f));
            if (c == (g >> 1)) asm volatile("st.relaxed.gpu.global.u32 [%0],%1;" ::"l"(g_ln0 + row), "r"(pack2(l.x, l.y)) : "memory");
        }
        else if (b + 4 >= V_REC && b + 4 < V_OP) rec_slots(b + 4 - V_REC, w - 10);
        PROF(t2 == 0, 3516);
        const int gi = b * 128 + t2;
        g_st[gi] = make_uint4(~0u, ~0u, ~0u, ~0u);
        if (gi < 900 * 8) g_cnt[gi] = 0;
        bar_sync(6, 384);
        if (lane < 4 && ((PFM >> (w - 8)) & 1)) asm volatile("cp.async.bulk.prefetch.L2.global [%0],%1;" ::"l"(a.W[w - 8] + (b * 4 + lane) * 4096), "r"(8192) : "memory");
        bar_sync(9, 384);
        if (w == 10) early_fetch(p, sb);
#pragma unroll 2
        for (int i = t2; i < 4 * 784; i += 128) {
            const int ch = i / 784, k = i - ch * 784;
            const uint32_t o = sb + P_P + (ch * 2080 + 266 + (k / 14) * 18 + k) * 4;
            g_W[d0 * 784 + i] = make_uint4(lds32(o), lds32(o + 32), lds32(o + 64), lds32(o + 96));
        }
        bar_arrive(10, 384);
        PROF(t2 == 0, 3517);
        return;
    }
#pragma unroll
    for (int i = 0; i < 2; i++) {
        const float dt = rbf(expf(blo(pr.ldt[i])));
        const float ar = -rbf(expf(blo(pr.v[i][0]))) * dt, ai = blo(pr.v[i][1]) * dt;
        sts128(sb + P_PRM + (w * 64 + i * 32 + lane) * 16, __float_as_uint(ar * 1.4426950408889634f), __float_as_uint(ai * 0.15915494309189535f),
               __float_as_uint(2.f * (blo(pr.v[i][2]) * dt)), __float_as_uint(2.f * (blo(pr.v[i][3]) * dt)));
    }
    if (tid < 64) sts128(sb + P_U + (tid >> 3) * 2176 + (tid & 7) * 16, 0, 0, 0, 0);
    bar_arrive(6, 384);
    __syncwarp();
    PROF(tid == 0, 3510);
    const int ch = w & 3, hf = w >> 2;
    {
        float k0[4] = {0, 0, 0, 0}, k1[4] = {0, 0, 0, 0}, k2[4] = {0, 0, 0, 0}, k3[4] = {0, 0, 0, 0}, k4[4] = {0, 0, 0, 0}, kl = 0;
#pragma unroll KGU
        for (int j = 0; j < 16; j++) {
            const uint4 q = lds128(sb + P_PRM + (w * 64 + j * 4 + c) * 16);
            const float cr = __uint_as_float(q.z), ci = __uint_as_float(q.w);
            float wr[4], wi[4], vr[4], vi[4];
            cpow(__uint_as_float(q.x), __uint_as_float(q.y), (float)g, wr[0], wi[0]);
            cpow(__uint_as_float(q.x), __uint_as_float(q.y), (float)(g + 8), vr[0], vi[0]);
#pragma unroll
            for (int i = 1; i < 4; i++) { wr[i] = wr[i - 1]; wi[i] = wi[i - 1]; csq(wr[i], wi[i]); vr[i] = vr[i - 1]; vi[i] = vi[i - 1]; csq(vr[i], vi[i]); }
            float hr = wr[3], hi = wi[3];
            csq(hr, hi);
            mma_tf32(k0, wr[0], vr[0], wi[0], vi[0], cr * hr - ci * hi, -(cr * hi + ci * hr));
            hr = vr[3]; hi = vi[3]; csq(hr, hi);
            mma_tf32(k1, wr[0], vr[0], wi[0], vi[0], cr * hr - ci * hi, -(cr * hi + ci * hr));
            csq(hr, hi);
            mma_tf32(k2, wr[1], vr[1], wi[1], vi[1], cr * hr - ci * hi, -(cr * hi + ci * hr));
            csq(hr, hi);
            mma_tf32(k3, wr[2], vr[2], wi[2], vi[2], cr * hr - ci * hi, -(cr * hi + ci * hr));
            csq(hr, hi);
            mma_tf32(k4, wr[3], vr[3], wi[3], vi[3], cr * hr - ci * hi, -(cr * hi + ci * hr));
            csq(hr, hi);
            kl += cr * hr - ci * hi;
        }
        kl += __shfl_xor_sync(0xffffffffu, kl, 1); kl += __shfl_xor_sync(0xffffffffu, kl, 2);
        const uint32_t o = sb + P_K6 + (ch * 656 + c * 32 + g) * 4, ol = sb + P_K6 + (ch * 656 + 640) * 4;
#define KST(k, base) sts32(o + (base) * 4, __float_as_uint(k[0])); sts32(o + (base) * 4 + 64, __float_as_uint(k[1])); \
                     sts32(o + (base) * 4 + 32, __float_as_uint(k[2])); sts32(o + (base) * 4 + 96, __float_as_uint(k[3]))
#define KAD(k, base) k[0] += __uint_as_float(lds32(o + (base) * 4)); k[1] += __uint_as_float(lds32(o + (base) * 4 + 64)); \
                     k[2] += __uint_as_float(lds32(o + (base) * 4 + 32)); k[3] += __uint_as_float(lds32(o + (base) * 4 + 96))
        if (hf == 0) {
            bar_sync(2 + ch, 64);
            KAD(k0, 0); KAD(k1, 128); KAD(k2, 256); KAD(k3, 384); KAD(k4, 512);
            kl += __uint_as_float(lds32(ol));
            __syncwarp();
        }
        KST(k0, 0); KST(k1, 128); KST(k2, 256); KST(k3, 384); KST(k4, 512);
        if (lane == 0) sts32(ol, __float_as_uint(kl));
        if (hf == 1) { __syncwarp(); bar_arrive(2 + ch, 64); }
    }
    PROF(tid == 0, 3511);
    {
        uint4 l0, l1;
        int n = 0;
        while (true) {
            l0 = ld_rlx128((const uint4*)g_ln0 + tid * 2); l1 = ld_rlx128((const uint4*)g_ln0 + tid * 2 + 1);
            if (__all_sync(0xffffffffu, l0.x && l0.y && l0.z && l0.w && l1.x && l1.y && l1.z && l1.w)) break;
            if (++n > 2000000) __trap();
        }
        sts128(sb + P_P + tid * 32, l0.x, l0.y, l0.z, l0.w); sts128(sb + P_P + tid * 32 + 16, l1.x, l1.y, l1.z, l1.w);
        bar_sync(8, 384);
        mbar_wait(sb + S_XBAR, 0);
        __syncwarp();
#pragma unroll 2
        for (int i = 0; i < 8; i++) {
            const int t = w * 256 + i * 32 + lane;
            const uint32_t ln = lds32(sb + P_P + t * 4);
            const uint2 x = lds64(sb + P_X + t * 16 + (b & 1) * 8);
            const float m = blo(ln), rs = rcp(bhi(ln));
            const uint32_t u0 = pack2(rbf(blo(x.x) - m) * rs, rbf(bhi(x.x) - m) * rs), u1 = pack2(rbf(blo(x.y) - m) * rs, rbf(bhi(x.y) - m) * rs);
            sts128(sb + P_X + t * 16, x.x, x.y, u0, u1);
            const uint32_t o = sb + P_U + ((t >> 3) & 1) * 2176 + ((t >> 4) + 8) * 16 + (t & 7) * 2;
            asm volatile("st.shared.u16 [%0],%1;" ::"r"(o), "h"((uint16_t)u0) : "memory");
            asm volatile("st.shared.u16 [%0],%1;" ::"r"(o + 4352), "h"((uint16_t)(u0 >> 16)) : "memory");
            asm volatile("st.shared.u16 [%0],%1;" ::"r"(o + 8704), "h"((uint16_t)u1) : "memory");
            asm volatile("st.shared.u16 [%0],%1;" ::"r"(o + 13056), "h"((uint16_t)(u1 >> 16)) : "memory");
        }
    }
    bar_sync(1, 256);
    PROF(tid == 0, 3512);
    if (tid < 64) sts32(sb + P_P + ((tid >> 4) * 2080 + (tid & 15)) * 4, 0);
#pragma unroll 1
    for (int x = tid; x < 2048; x += 512) {
        uint32_t pw[2][4];
#pragma unroll
        for (int h = 0; h < 2; h++) {
            const int y = x + h * 256;
            const int i0 = y <= 256 ? y : 256 + (int)((pack2((float)y, 0.f) & 0xffff) - 0x4380);
            const int i1 = y <= 256 ? max(y - 1, 0) : 256 + (int)((pack2((float)(y - 1), 0.f) & 0xffff) - 0x4380);
#pragma unroll
            for (int k = 0; k < 4; k++) {
                const float lo = __uint_as_float(lds32(sb + P_K6 + k * 2624 + i0 * 4)), hi = __uint_as_float(lds32(sb + P_K6 + k * 2624 + i1 * 4));
                pw[h][k] = pack2(lo, y ? hi : 0.f);
            }
        }
#pragma unroll
        for (int h = 0; h < 2; h++)
#pragma unroll
            for (int k = 0; k < 4; k++) sts32(sb + P_P + (k * 2080 + x + h * 256 + 16) * 4, pw[h][k]);
    }
    fence_async_smem();
    bar_arrive(9, 384);
    bar_sync(1, 256);
    if (tid < 4) {
        asm volatile("cp.async.bulk.global.shared::cta.bulk_group [%0],[%1],%2;" ::"l"(g_P + (d0 + tid) * PROW), "r"(sb + P_P + tid * 8320), "r"(PROW * 4) : "memory");
        asm volatile("cp.async.bulk.commit_group;" ::: "memory");
    }
    __syncwarp();
    PROF(tid == 0, 3513);
    {
        float acc[16][4];
#pragma unroll
        for (int j = 0; j < 16; j++) acc[j][0] = acc[j][1] = acc[j][2] = acc[j][3] = 0;
#pragma unroll 1
        for (int e = hf * 4; e < hf * 4 + 4; e++) {
            uint32_t B[16][2];
            const uint32_t ua = sb + P_U + ch * 4352 + ((lane >> 3) & 1) * 2176 + (8 + (lane >> 4) * 8 + (lane & 7) - e) * 16;
#pragma unroll
            for (int j = 0; j < 8; j++) { const uint4 v = ldsm4(ua + j * 256); B[2 * j][0] = v.x; B[2 * j][1] = v.y; B[2 * j + 1][0] = v.z; B[2 * j + 1][1] = v.w; }
            const uint32_t pa = sb + P_P + (ch * 2080 + 16 + e * 16 + g - 2 * c) * 4;
#pragma unroll
            for (int d = 0; d < 16; d++) {
                const uint32_t a0 = lds32(pa + d * 512), a1 = lds32(pa + d * 512 + 32), a2 = lds32(pa + d * 512 - 32);
#pragma unroll
                for (int j = d; j < 16; j++) mma16(acc[j], a0, a1, a2, a0, B[j - d][0], B[j - d][1]);
            }
        }
        PROF(tid == 0, 3514);
        const uint32_t o = sb + P_Y + (ch * 2560 + c * 40 + g) * 4;
        if (tid < 4) asm volatile("cp.async.bulk.wait_group 0;" ::: "memory");
        __syncwarp();
        bar_sync(10, 384);
        if (hf == 0) {
            bar_sync(2 + ch, 64);
#pragma unroll
            for (int j = 0; j < 16; j++) {
                acc[j][0] += __uint_as_float(lds32(o + j * 640)); acc[j][1] += __uint_as_float(lds32(o + j * 640 + 80));
                acc[j][2] += __uint_as_float(lds32(o + j * 640 + 32)); acc[j][3] += __uint_as_float(lds32(o + j * 640 + 112));
            }
        }
#pragma unroll
        for (int j = 0; j < 16; j++) {
            sts32(o + j * 640, __float_as_uint(acc[j][0])); sts32(o + j * 640 + 80, __float_as_uint(acc[j][1]));
            sts32(o + j * 640 + 32, __float_as_uint(acc[j][2])); sts32(o + j * 640 + 112, __float_as_uint(acc[j][3]));
        }
        if (hf == 1) bar_arrive(2 + ch, 64);
    }
    const uint2 dk = __ldg((const uint2*)(a.Dk + d0));
    bar_sync(1, 256);
#pragma unroll 2
    for (int i = 0; i < 8; i++) {
        const int t = i * 256 + tid;
        const uint32_t o = sb + P_Y + (t + 4 * (t >> 4)) * 4;
        const uint4 xu = lds128(sb + P_X + t * 16);
        float y[4];
#pragma unroll
        for (int k = 0; k < 4; k++) y[k] = rbf(__uint_as_float(lds32(o + k * 10240)));
        uint2 r;
        r.x = pack2(blo(xu.x) + rbf(y[0] + rbf(blo(xu.z) * blo(dk.x))), bhi(xu.x) + rbf(y[1] + rbf(bhi(xu.z) * bhi(dk.x))));
        r.y = pack2(blo(xu.y) + rbf(y[2] + rbf(blo(xu.w) * blo(dk.y))), bhi(xu.y) + rbf(y[3] + rbf(bhi(xu.w) * bhi(dk.y))));
        ((uint2*)g_x)[b * 2 * XP + t] = r;
    }
    PROF(tid == 0, 3515);
}

__global__ void __cluster_dims__(2, 1, 1) __launch_bounds__(384, 1) main_kernel(const __grid_constant__ Params p) {
    extern __shared__ __align__(1024) uint8_t smem[];
    const uint32_t sb = smem_u32(smem);
    uint32_t rank; asm("mov.u32 %0,%%cluster_ctarank;" : "=r"(rank));
    const int wi = __shfl_sync(0xffffffffu, threadIdx.x >> 5, 0);
    const int v = blockIdx.x, cl = v >> 1, wg = wi >> 2;
    PROF(threadIdx.x == 0, 3500);
    ProRegs pr;
    prologue_load(p.pa, max((int)blockIdx.x - 4, 0), pr);
    if (wi == 11 && p.dopro && cl >= 2 && elect()) {
        mbar_init(sb + S_XBAR, 1);
        asm volatile("fence.mbarrier_init.release.cluster;" ::: "memory");
        mbar_expect(sb + S_XBAR, 32768);
        for (int j = 0; j < 8; j++) tma2d(sb + P_X + j * 4096, &p.tm[3], ((blockIdx.x - 4) >> 1) * 8, j * 256, sb + S_XBAR);
    }
    if (threadIdx.x == 320) {
        unsigned v = 0;
        if (p.dopro) {
            asm volatile("ld.relaxed.gpu.global.u32 %0,[%1];" : "=r"(v) : "l"(g_gate) : "memory");
            v = (v / (4 * NCL) + 1) * (4 * NCL);
        }
        sts32(sb + S_GATE, v);
    }
    __syncwarp();
    if (wi == 10) {
        if (v < V_REC || v == 131) conv_init(sb, v == 131); else if (v < V_OP) rec_init(sb); else gemm_init(sb, v < V_QKV);
        __syncwarp();
    }
    if (wg == 2) bar_arrive(8, 384);
    asm volatile("barrier.cluster.arrive.relaxed.aligned;" ::: "memory");
    if (p.dopro && cl >= 2) prologue(p, sb, blockIdx.x - 4, wi, pr); else if (wg < 2) bar_sync(8, 384); else if (wi == 10) early_fetch(p, sb);
    asm volatile("barrier.cluster.wait.aligned;" ::: "memory");
    const int role = (v < V_REC ? 1 : v < V_OP ? 2 : v < V_QKV ? 4 : v < V_QKV + NQ ? 24 : 1) & p.roles;
    fence_async_smem();
    bar_sync(wg == 2 ? 7 : 1, wg == 2 ? 128 : 256);
    if (p.dopro && (threadIdx.x == 32 || threadIdx.x == 352)) red_release(g_gate, 1);
    PROF(threadIdx.x == 32, 3509);
    if (wi == 0 && (role & 8) && elect()) qkv_stage(p, sb + 131072, sb + G_BAR + GB_RS * 8, v - V_QKV, 0, 6);
    PROF(threadIdx.x == 0, 3506);
    __syncwarp();
    if (p.dopro && v >= V_REC && v < V_QKV && (v < V_OP ? wi == 8 : wi < 8)) {
        bool on = v >= V_OP;
#pragma unroll 1
        for (int r = on ? 64 + (v - V_OP) * 8 + wi : v - V_REC; r < 512;) {
            if (on) wait_flag_warp(g_gate, lds32(sb + S_GATE));
            PROF(threadIdx.x == 256 && on, 3507);
            x1_norm(on ? (const uint2*)g_x : (const uint2*)p.pa.W[0], r, on);
            __syncwarp();
            if (on && elect()) red_release(cnt_ptr(C_XN + (r >> 4)), 1);
            __syncwarp();
            PROF(threadIdx.x == 256, on ? 3508 : 3499);
            if (on) r += v < V_OP ? 512 : 128;
            on = true;
        }
    }
    if (role == 2) {
        const int head = (v - V_REC) >> 1;
        if (wi == 0 && elect()) rec_fetch(p, sb, head, rank, 1, R_STK);
        __syncwarp();
        if (wg == 2) {
            reg_dec<RH>();
            const int w = wi & 3;
            wait_cnt_warp(g_gate, lds32(sb + S_GATE));
            if (w < 2) { const uint32_t x = __ldcg(g_sel + (threadIdx.x & 63)); sts32(sb + R_SEL + (threadIdx.x & 63) * 4, (x | x >> 16) & 15); }
            __syncthreads();
            cluster_sync();
            if ((p.chains >> (w & 1)) & 1) { if (w < 2) rec_comm(p, sb, w, head, rank); else rec_attn(p, sb, w & 1, head, rank); }
        } else {
            reg_inc<RW0>();
            rec_weights(p, sb, head, rank, wi);
        }
    } else if (role == 1) {
        if (v == 131) conv_far(sb, wi); else if (wg == 2) { reg_dec<RCB>(); conv_back(sb, v, wi & 3); } else { reg_inc<RCU>(); conv_tile(p, sb, v, wi); }
    } else if (role == 4) {
        if (wg == 2) {
            reg_dec<40>();
            if (wi == 8) gemm_producer<true>(p, sb, v - V_OP); else if (wi == 9) gemm_release<true>(p, sb, v - V_OP);
        } else { reg_inc<232>(); gemm_consumer<true>(p, sb, v - V_OP, wi); }
    } else if (role) {
        if (wg == 2) {
            reg_dec<40>();
            if (wi < 10) {
                if (role & 8) { if (wi == 8) gemm_producer<false>(p, sb, v - V_QKV); else gemm_release<false>(p, sb, v - V_QKV); }
            } else if (v < V_QKV + 32 && (role & 16)) fin_warp(p, sb, (v - V_QKV) * 2 + wi - 10);
        } else { reg_inc<232>(); if (role & 8) gemm_consumer<false>(p, sb, v - V_QKV, wi); }
    }
    __syncwarp();
    cluster_sync();
}

typedef CUresult (*EncFn)(CUtensorMap*, CUtensorMapDataType, cuuint32_t, void*, const cuuint64_t*, const cuuint64_t*, const cuuint32_t*, const cuuint32_t*,
                          CUtensorMapInterleave, CUtensorMapSwizzle, CUtensorMapL2promotion, CUtensorMapFloatOOBfill);
constexpr int SMEM_BYTES = 232448;
#define LAG 8
#define QLEAD 6
#define OLEAD (LAG / 2 + 2)
void plan(Params& P) {
    P.roles = 31; P.chains = 3; P.lag = LAG; P.dopro = 1;
    for (int r = 0; r < 2; r++) {
        const int lead = r ? OLEAD : QLEAD;
        int n = 0;
        for (int i = 0; i < 32 + lead; i++) {
            if (i >= lead) P.list[r][n++] = 32 + i - lead;
            if (i < 32) P.list[r][n++] = i;
        }
        P.nl[r] = n;
    }
}

#define TK() do {} while (0)
}

extern "C" void kernel_launch(void* const* d_in, const int* in_sizes, int n_in, void* d_out, int out_size) {
    typedef const __nv_bfloat16* BP;
    static EncFn enc = nullptr;
    if (!enc) {
        void* fn = nullptr; cudaDriverEntryPointQueryResult qr;
        cudaGetDriverEntryPoint("cuTensorMapEncodeTiled", &fn, cudaEnableDefault, &qr);
        enc = (EncFn)fn;
        cudaFuncSetAttribute(main_kernel, cudaFuncAttributeMaxDynamicSharedMemorySize, SMEM_BYTES);
    }
    static Params P;
    for (int i = 0; i < 4; i++) {
        const cuuint64_t cols = i < 3 ? 4096 : 512, rows = i < 3 ? 512 : 4096;
        cuuint64_t d2[2] = {cols, rows}, str[1] = {cols * 2};
        cuuint32_t box[2] = {64, 64}, bn[2] = {16, 256}, es[2] = {1, 1};
        enc(&P.tm[i < 3 ? i : 4], CU_TENSOR_MAP_DATA_TYPE_BFLOAT16, 2, d_in[9 + i], d2, str, box, es, CU_TENSOR_MAP_INTERLEAVE_NONE, CU_TENSOR_MAP_SWIZZLE_128B,
            CU_TENSOR_MAP_L2_PROMOTION_L2_128B, CU_TENSOR_MAP_FLOAT_OOB_FILL_NONE);
        if (i < 2) enc(&P.tn[i], CU_TENSOR_MAP_DATA_TYPE_BFLOAT16, 2, d_in[9 + i], d2, str, bn, es, CU_TENSOR_MAP_INTERLEAVE_NONE, CU_TENSOR_MAP_SWIZZLE_32B,
                       CU_TENSOR_MAP_L2_PROMOTION_L2_128B, CU_TENSOR_MAP_FLOAT_OOB_FILL_NONE);
    }
    {
        cuuint64_t dims[2] = {512, 2048}, str[1] = {1024};
        cuuint32_t box[2] = {8, 256}, es[2] = {1, 1};
        enc(&P.tm[3], CU_TENSOR_MAP_DATA_TYPE_BFLOAT16, 2, d_in[0], dims, str, box, es, CU_TENSOR_MAP_INTERLEAVE_NONE, CU_TENSOR_MAP_SWIZZLE_NONE,
            CU_TENSOR_MAP_L2_PROMOTION_NONE, CU_TENSOR_MAP_FLOAT_OOB_FILL_NONE);
    }
    P.mem0 = (BP)d_in[8]; P.Wo = (BP)d_in[12]; P.Dskip = (BP)d_in[6]; P.out = (__nv_bfloat16*)d_out;
    cudaStream_t s = cudaStreamPerThread;
    P.pa = {(BP)d_in[0], (BP)d_in[1], (BP)d_in[2], (BP)d_in[3], (BP)d_in[4], (BP)d_in[5], (BP)d_in[6], {(BP)d_in[9], (BP)d_in[10], (BP)d_in[11], (BP)d_in[12]}};
    plan(P);
    TK(); main_kernel<<<2 * NCL, 384, SMEM_BYTES, s>>>(P); TK();
}
```

```cpp
#include <cuda_runtime.h>
#include <cuda_bf16.h>
#include <cuda.h>
#include <stdint.h>
#include <string.h>
#include <math.h>

namespace {

constexpr int NCL = 66;
constexpr int NQ = 43;
constexpr int V_REC = 8, V_OP = 72, V_QKV = 88;

#define XP 1024
__device__ uint4 g_x[2 * 128 * XP];
__device__ uint4 g_xn[64 * 4096];
__device__ uint4 g_st[64 * 256];
__device__ uint4 g_qkv[128 * 32 * 1536];
__device__ uint4 g_o[64 * 64 * 512];
__device__ uint4 g_pp[64 * 4 * 4096];
__device__ uint4 g_xch[133 * 512];
__device__ unsigned g_sel[64];
__device__ unsigned g_gate[32];
__device__ __align__(16) uint32_t g_P[512 * 272];
__device__ uint4 g_W[512 * 784];
__device__ __align__(16) uint32_t g_u[512 * 1152];
__device__ uint2 g_carry[512 * 40 * 32];
__device__ uint2 g_far[512 * 8 * 32];
__device__ unsigned g_cnt[900 * 8];
__device__ uint32_t g_ln0[2048];

enum { C_XN = 0  , C_QKV = 64  , C_O = 128  , C_PP = 384  , C_FAR = 896 };
__device__ __forceinline__ unsigned* cnt_ptr(int i) { return g_cnt + i * 8; }

struct ProArgs { const __nv_bfloat16 *x, *lAr, *Ai, *Cr, *Ci, *ldt, *Dk, *W[4]; };
struct Params {
    CUtensorMap tm[5];
    CUtensorMap tn[2];
    ProArgs pa;
    int dopro;
    const __nv_bfloat16* mem0;
    const __nv_bfloat16* Wo;
    const __nv_bfloat16* Dskip;
    __nv_bfloat16* out;
    int roles;
    int chains;
    int lag;
    int zero;
    int nl[2];
    uint8_t list[2][64];
};

__device__ __forceinline__ uint32_t smem_u32(const void* p) { return (uint32_t)__cvta_generic_to_shared(p); }
__device__ __forceinline__ uint32_t mapa(uint32_t a, uint32_t r) {
    uint32_t o; asm("mapa.shared::cluster.u32 %0,%1,%2;" : "=r"(o) : "r"(a), "r"(r)); return o;
}
__device__ __forceinline__ void mbar_init(uint32_t b, int c) { asm volatile("mbarrier.init.shared::cta.b64 [%0],%1;" ::"r"(b), "r"(c) : "memory"); }
__device__ __forceinline__ void mbar_expect(uint32_t b, int bytes) { asm volatile("mbarrier.arrive.expect_tx.shared::cta.b64 _,[%0],%1;" ::"r"(b), "r"(bytes) : "memory"); }
__device__ __forceinline__ void mbar_arrive(uint32_t b) { asm volatile("mbarrier.arrive.shared::cta.b64 _,[%0];" ::"r"(b) : "memory"); }
__device__ __forceinline__ void mbar_arrive_cluster(uint32_t b) { asm volatile("mbarrier.arrive.shared::cluster.b64 _,[%0];" ::"r"(b) : "memory"); }
__device__ __forceinline__ void mbar_wait(uint32_t b, uint32_t ph) {
    asm volatile(
        "{.reg .pred p; .reg .u32 n; mov.u32 n,0;\n"
        "W%=: mbarrier.try_wait.parity.shared::cta.b64 p,[%0],%1;\n"
        "@p bra D%=;\n"
        "add.u32 n,n,1; setp.lt.u32 p,n,2000000; @p bra W%=;\n"
        "trap;\n"
        "D%=: }" ::"r"(b), "r"(ph) : "memory");
}
__device__ __forceinline__ bool wait_lds128(uint32_t b, uint32_t ph, uint32_t a, uint4& v) {
    uint32_t ok;
    asm volatile("{.reg .pred p; mbarrier.try_wait.parity.shared::cta.b64 p,[%5],%6,20000; ld.shared.v4.u32 {%0,%1,%2,%3},[%7]; selp.u32 %4,1,0,p;}"
                 : "=r"(v.x), "=r"(v.y), "=r"(v.z), "=r"(v.w), "=r"(ok) : "r"(b), "r"(ph), "r"(a) : "memory");
    return ok;
}
__device__ __forceinline__ bool wait_lds64(uint32_t b, uint32_t ph, uint32_t a, uint2& v) {
    uint32_t ok;
    asm volatile("{.reg .pred p; mbarrier.try_wait.parity.shared::cta.b64 p,[%3],%4,20000; ld.shared.v2.u32 {%0,%1},[%5]; selp.u32 %2,1,0,p;}"
                 : "=r"(v.x), "=r"(v.y), "=r"(ok) : "r"(b), "r"(ph), "r"(a) : "memory");
    return ok;
}
template <int PH> __device__ __forceinline__ void mbar_wait_c(uint32_t b) {
    asm volatile(
        "{.reg .pred p; .reg .u32 n; mov.u32 n,%2;\n"
        "W%=: mbarrier.try_wait.parity.shared::cta.b64 p,[%0],%1;\n"
        "@p bra D%=;\n"
        "add.u32 n,n,1; setp.lt.u32 p,n,2000000; @p bra W%=;\n"
        "trap;\n"
        "D%=: }" ::"r"(b), "n"(PH), "n"(PH) : "memory");
}
__device__ __forceinline__ bool elect() {
    uint32_t r; asm volatile("{.reg .pred p; elect.sync _|p,0xffffffff; selp.u32 %0,1,0,p;}" : "=r"(r)); return r;
}
__device__ __forceinline__ void bar_sync(int id, int n) { asm volatile("bar.sync %0,%1;" ::"r"(id), "r"(n) : "memory"); }
__device__ __forceinline__ void bar_arrive(int id, int n) { asm volatile("bar.arrive %0,%1;" ::"r"(id), "r"(n) : "memory"); }
__device__ __forceinline__ void cluster_sync() { asm volatile("barrier.cluster.arrive.relaxed.aligned; barrier.cluster.wait.aligned;" ::: "memory"); }
__device__ __forceinline__ void fence_async() { asm volatile("fence.proxy.async;" ::: "memory"); }
__device__ __forceinline__ void fence_async_smem() { asm volatile("fence.proxy.async.shared::cta;" ::: "memory"); }
#define EFR 1
#define EFW 2
constexpr uint64_t POL_N = 0x1000000000000000ull, POL_F = 0x12F0000000000000ull;
constexpr uint64_t POL_LAST = EFR ? POL_F : POL_N  , POL_LATE = EFW ? POL_F : POL_N  , POL_SOON = EFW > 1 ? POL_F : POL_N;
__device__ __forceinline__ void bulk_g2s(uint32_t dst, const void* src, int bytes, uint32_t bar, uint64_t pol) {
    asm volatile("cp.async.bulk.shared::cluster.global.mbarrier::complete_tx::bytes.L2::cache_hint [%0],[%1],%2,[%3],%4;" ::"r"(dst), "l"(src), "r"(bytes), "r"(bar), "l"(pol) : "memory");
}
__device__ __forceinline__ void bulk_g2s_mc(uint32_t dst, const void* src, int bytes, uint32_t bar, uint64_t pol) {
    asm volatile("cp.async.bulk.shared::cluster.global.mbarrier::complete_tx::bytes.multicast::cluster.L2::cache_hint [%0],[%1],%2,[%3],%4,%5;" ::"r"(dst), "l"(src), "r"(bytes), "r"(bar), "h"((uint16_t)3), "l"(pol) : "memory");
}
__device__ __forceinline__ void stg128(uint4* p, uint4 v, uint64_t pol) {
    asm volatile("st.global.L2::cache_hint.v4.u32 [%0],{%1,%2,%3,%4},%5;" ::"l"(p), "r"(v.x), "r"(v.y), "r"(v.z), "r"(v.w), "l"(pol));
}
__device__ __forceinline__ void stg32(uint32_t* p, uint32_t v, uint64_t pol) { asm volatile("st.global.L2::cache_hint.u32 [%0],%1,%2;" ::"l"(p), "r"(v), "l"(pol)); }
__device__ __forceinline__ uint4 ldcg128_last(const uint4* p) {
    uint4 v; asm volatile("ld.global.cg.L2::cache_hint.v4.u32 {%0,%1,%2,%3},[%4],%5;" : "=r"(v.x), "=r"(v.y), "=r"(v.z), "=r"(v.w) : "l"(p), "l"(POL_LAST) : "memory"); return v;
}
__device__ __forceinline__ void tma2d(uint32_t dst, const CUtensorMap* tm, int x, int y, uint32_t bar) {
    asm volatile("cp.async.bulk.tensor.2d.shared::cluster.global.mbarrier::complete_tx::bytes [%0],[%1,{%2,%3}],[%4];" ::"r"(dst), "l"(tm), "r"(x), "r"(y), "r"(bar) : "memory");
}
__device__ __forceinline__ void tma3d(uint32_t dst, const CUtensorMap* tm, int y, int z, uint32_t bar) {
    asm volatile("cp.async.bulk.tensor.3d.shared::cluster.global.mbarrier::complete_tx::bytes [%0],[%1,{0,%2,%3}],[%4];" ::"r"(dst), "l"(tm), "r"(y), "r"(z), "r"(bar) : "memory");
}
__device__ __forceinline__ void st_async4(uint32_t a, uint32_t x, uint32_t y, uint32_t z, uint32_t w, uint32_t mb) {
    asm volatile("st.async.shared::cluster.mbarrier::complete_tx::bytes.v4.b32 [%0],{%1,%2,%3,%4},[%5];" ::"r"(a), "r"(x), "r"(y), "r"(z), "r"(w), "r"(mb) : "memory");
}
__device__ __forceinline__ void st_async2(uint32_t a, uint32_t x, uint32_t y, uint32_t mb) {
    asm volatile("st.async.shared::cluster.mbarrier::complete_tx::bytes.v2.b32 [%0],{%1,%2},[%3];" ::"r"(a), "r"(x), "r"(y), "r"(mb) : "memory");
}
#define LDSQ "ld.shared"
__device__ __forceinline__ uint4 lds128(uint32_t a) { uint4 v; asm volatile(LDSQ ".v4.u32 {%0,%1,%2,%3},[%4];" : "=r"(v.x), "=r"(v.y), "=r"(v.z), "=r"(v.w) : "r"(a) : "memory"); return v; }
__device__ __forceinline__ uint4 lds128v(uint32_t a) { uint4 v; asm volatile("ld.volatile.shared.v4.u32 {%0,%1,%2,%3},[%4];" : "=r"(v.x), "=r"(v.y), "=r"(v.z), "=r"(v.w) : "r"(a) : "memory"); return v; }
__device__ __forceinline__ uint2 lds64(uint32_t a) { uint2 v; asm volatile(LDSQ ".v2.u32 {%0,%1},[%2];" : "=r"(v.x), "=r"(v.y) : "r"(a) : "memory"); return v; }
__device__ __forceinline__ uint32_t lds32(uint32_t a) { uint32_t v; asm volatile(LDSQ ".u32 %0,[%1];" : "=r"(v) : "r"(a) : "memory"); return v; }
__device__ __forceinline__ void sts128(uint32_t a, uint32_t x, uint32_t y, uint32_t z, uint32_t w) { asm volatile("st.shared.v4.u32 [%0],{%1,%2,%3,%4};" ::"r"(a), "r"(x), "r"(y), "r"(z), "r"(w) : "memory"); }
__device__ __forceinline__ void sts64(uint32_t a, uint32_t x, uint32_t y) { asm volatile("st.shared.v2.u32 [%0],{%1,%2};" ::"r"(a), "r"(x), "r"(y) : "memory"); }
__device__ __forceinline__ void sts32(uint32_t a, uint32_t x) { asm volatile("st.shared.u32 [%0],%1;" ::"r"(a), "r"(x) : "memory"); }
__device__ __forceinline__ uint4 ldsm4(uint32_t a) { uint4 v; asm volatile("ldmatrix.sync.aligned.m8n8.x4.shared.b16 {%0,%1,%2,%3},[%4];" : "=r"(v.x), "=r"(v.y), "=r"(v.z), "=r"(v.w) : "r"(a) : "memory"); return v; }
__device__ __forceinline__ uint4 ldsm4t(uint32_t a) { uint4 v; asm volatile("ldmatrix.sync.aligned.m8n8.x4.trans.shared.b16 {%0,%1,%2,%3},[%4];" : "=r"(v.x), "=r"(v.y), "=r"(v.z), "=r"(v.w) : "r"(a) : "memory"); return v; }
__device__ __forceinline__ uint32_t movm(uint32_t a) { uint32_t d; asm volatile("movmatrix.sync.aligned.m8n8.trans.b16 %0,%1;" : "=r"(d) : "r"(a)); return d; }
__device__ __forceinline__ uint32_t pack2(float lo, float hi) { uint32_t d; asm("cvt.rn.bf16x2.f32 %0,%1,%2;" : "=r"(d) : "f"(hi), "f"(lo)); return d; }
__device__ __forceinline__ uint32_t hadd2(uint32_t a, uint32_t b) { uint32_t d; asm("add.rn.bf16x2 %0,%1,%2;" : "=r"(d) : "r"(a), "r"(b)); return d; }
__device__ __forceinline__ uint32_t hmul2(uint32_t a, uint32_t b) { uint32_t d; asm("mul.rn.bf16x2 %0,%1,%2;" : "=r"(d) : "r"(a), "r"(b)); return d; }
__device__ __forceinline__ float blo(uint32_t v) { return __uint_as_float(v << 16); }
__device__ __forceinline__ float bhi(uint32_t v) { return __uint_as_float(v & 0xffff0000u); }
__device__ __forceinline__ float rbf(float x) { return __uint_as_float(pack2(0.f, x)); }
__device__ __forceinline__ float ex2(float x) { float y; asm("ex2.approx.ftz.f32 %0,%1;" : "=f"(y) : "f"(x)); return y; }
__device__ __forceinline__ float rcp(float x) { float y; asm("rcp.approx.ftz.f32 %0,%1;" : "=f"(y) : "f"(x)); return y; }
__device__ __forceinline__ void mma16(float* c, uint32_t a0, uint32_t a1, uint32_t a2, uint32_t a3, uint32_t b0, uint32_t b1) {
    asm volatile("mma.sync.aligned.m16n8k16.row.col.f32.bf16.bf16.f32 {%0,%1,%2,%3},{%4,%5,%6,%7},{%8,%9},{%0,%1,%2,%3};"
                 : "+f"(c[0]), "+f"(c[1]), "+f"(c[2]), "+f"(c[3]) : "r"(a0), "r"(a1), "r"(a2), "r"(a3), "r"(b0), "r"(b1));
}
__device__ __forceinline__ void mma16_top(float& d0, float& d1, uint32_t a0, uint32_t a2, uint32_t b0, uint32_t b1) {
    asm volatile("{.reg .b32 j; .reg .f32 e,f; mma.sync.aligned.m16n8k16.row.col.f32.bf16.bf16.f32 {%0,%1,e,f},{%2,j,%3,j},{%4,%5},{0f00000000,0f00000000,0f00000000,0f00000000};}"
                 : "=f"(d0), "=f"(d1) : "r"(a0), "r"(a2), "r"(b0), "r"(b1));
}
__device__ __forceinline__ void mma8(float* c, uint32_t a0, uint32_t a1, uint32_t b0) {
    asm volatile("mma.sync.aligned.m16n8k8.row.col.f32.bf16.bf16.f32 {%0,%1,%2,%3},{%4,%5},{%6},{%0,%1,%2,%3};"
                 : "+f"(c[0]), "+f"(c[1]), "+f"(c[2]), "+f"(c[3]) : "r"(a0), "r"(a1), "r"(b0));
}
__device__ __forceinline__ uint4 ld_rlx128(const uint4* p) {
    uint4 v;
    asm volatile("{.reg .b128 t; ld.relaxed.gpu.global.b128 t,[%4]; mov.b128 {%0,%1,%2,%3},t;}" : "=r"(v.x), "=r"(v.y), "=r"(v.z), "=r"(v.w) : "l"(p) : "memory");
    return v;
}
__device__ __forceinline__ void st_rlx128(uint4* p, uint32_t x, uint32_t y, uint32_t z, uint32_t w) {
    asm volatile("{.reg .b128 t; mov.b128 t,{%1,%2,%3,%4}; st.relaxed.gpu.global.b128 [%0],t;}" ::"l"(p), "r"(x), "r"(y), "r"(z), "r"(w) : "memory");
}
__device__ __forceinline__ uint4 ldcg128(const uint4* p) { uint4 v; asm volatile("ld.global.cg.v4.u32 {%0,%1,%2,%3},[%4];" : "=r"(v.x), "=r"(v.y), "=r"(v.z), "=r"(v.w) : "l"(p) : "memory"); return v; }
__device__ __forceinline__ void red_release(unsigned* p, unsigned v) {
    asm volatile("fence.proxy.async; red.relaxed.gpu.global.add.u32 [%0],%1;" ::"l"(p), "r"(v) : "memory");
}
__device__ __forceinline__ void red_relaxed(unsigned* p, unsigned v) { asm volatile("red.relaxed.gpu.global.add.u32 [%0],%1;" ::"l"(p), "r"(v) : "memory"); }
__device__ __forceinline__ void wait_cnt(const unsigned* p, unsigned target) {
    asm volatile(
        "{.reg .pred p; .reg .u32 n,v; mov.u32 n,0;\n"
        "W%=: ld.acquire.gpu.global.u32 v,[%0]; setp.ge.u32 p,v,%1; @p bra D%=;\n"
        "nanosleep.u32 20; add.u32 n,n,1; setp.lt.u32 p,n,4000000; @p bra W%=;\n"
        "trap;\n"
        "D%=: }" ::"l"(p), "r"(target) : "memory");
}
__device__ __forceinline__ void wait_cnt_warp(const unsigned* p, unsigned target) {
    asm volatile(
        "{.reg .pred p; .reg .u32 n,v; mov.u32 n,0;\n"
        "W%=: ld.acquire.gpu.global.u32 v,[%0]; setp.ge.u32 p,v,%1; vote.sync.all.pred p,p,0xffffffff; @p bra.uni D%=;\n"
        "nanosleep.u32 20; add.u32 n,n,1; setp.lt.u32 p,n,4000000; @p bra.uni W%=;\n"
        "trap;\n"
        "D%=: }" ::"l"(p), "r"(target) : "memory");
}
__device__ __forceinline__ void wait_flag_warp(const unsigned* p, unsigned target) {
    asm volatile(
        "{.reg .pred p; .reg .u32 n,v; mov.u32 n,0;\n"
        "W%=: ld.relaxed.gpu.global.u32 v,[%0]; setp.ge.u32 p,v,%1; vote.sync.all.pred p,p,0xffffffff; @p bra.uni D%=;\n"
        "add.u32 n,n,1; setp.lt.u32 p,n,10000000; @p bra.uni W%=;\n"
        "trap;\n"
        "D%=: }" ::"l"(p), "r"(target) : "memory");
}
__device__ __forceinline__ uint64_t mkdesc(uint32_t addr, uint32_t lbo, uint32_t sbo, uint32_t sw) {
    return (uint64_t)((addr & 0x3FFFF) >> 4) | ((uint64_t)(lbo >> 4) << 16) | ((uint64_t)(sbo >> 4) << 32) | ((uint64_t)sw << 62);
}
__device__ __forceinline__ void wg_fence() { asm volatile("wgmma.fence.sync.aligned;" ::: "memory"); }
__device__ __forceinline__ void wg_commit() { asm volatile("wgmma.commit_group.sync.aligned;" ::: "memory"); }
template <int N> __device__ __forceinline__ void wg_wait() { asm volatile("wgmma.wait_group.sync.aligned %0;" ::"n"(N) : "memory"); }
#define R8(c, o) "+f"(c[o]), "+f"(c[o + 1]), "+f"(c[o + 2]), "+f"(c[o + 3]), "+f"(c[o + 4]), "+f"(c[o + 5]), "+f"(c[o + 6]), "+f"(c[o + 7])
#define R32(c, o) R8(c, o), R8(c, o + 8), R8(c, o + 16), R8(c, o + 24)
#define S32A "%0,%1,%2,%3,%4,%5,%6,%7,%8,%9,%10,%11,%12,%13,%14,%15,%16,%17,%18,%19,%20,%21,%22,%23,%24,%25,%26,%27,%28,%29,%30,%31"
template <int ACC> __device__ __forceinline__ void wgmma64_rs(float* c, const uint32_t* a, uint64_t db) {
    asm volatile("wgmma.mma_async.sync.aligned.m64n64k16.f32.bf16.bf16 {" S32A "},{%32,%33,%34,%35},%36,%37,1,1,0;"
                 : R32(c, 0) : "r"(a[0]), "r"(a[1]), "r"(a[2]), "r"(a[3]), "l"(db), "n"(ACC));
}
template <int ACC> __device__ __forceinline__ void wgmma64_ta(float* c, uint64_t da, uint64_t db) {
    asm volatile("wgmma.mma_async.sync.aligned.m64n64k16.f32.bf16.bf16 {" S32A "},%32,%33,%34,1,1,1,0;" : R32(c, 0) : "l"(da), "l"(db), "n"(ACC));
}
template <int ACC> __device__ __forceinline__ void wgmma80_tb(float* c, uint64_t da, uint64_t db) {
    asm volatile("wgmma.mma_async.sync.aligned.m64n80k16.f32.bf16.bf16 {" S32A ",%32,%33,%34,%35,%36,%37,%38,%39},%40,%41,%42,1,1,0,1;"
                 : R32(c, 0), R8(c, 32) : "l"(da), "l"(db), "n"(ACC));
}
template <int N> __device__ __forceinline__ void reg_inc() { asm volatile("setmaxnreg.inc.sync.aligned.u32 %0;" ::"n"(N)); }
template <int N> __device__ __forceinline__ void reg_dec() { asm volatile("setmaxnreg.dec.sync.aligned.u32 %0;" ::"n"(N)); }

#define PROF(cond, idx) do {} while (0)
#define CPROF(k) do {} while (0)

constexpr int S_GATE = 232440, S_XBAR = 232432, B_BAR = 231936;
#define RCB 136
#define RCU 184
#define NFP 2
#define UFE 0
#define PFM 8
#define NFE 2
#define QLAG 3
constexpr float SC_LOG2E = 0.08838834764831845f * 1.4426950408889634f;

__device__ __forceinline__ float2 ln_finish(float mean, float var) {
    float sd; asm("sqrt.approx.f32 %0,%1;" : "=f"(sd) : "f"(rbf(rbf(var) + 1e-5f)));
    sd = rbf(sd);
    return make_float2(rbf(mean), sd);
}

__device__ __forceinline__ float2 row_stats512(uint4* v, const uint4* src, int s1, int s2) {
    const int g = (threadIdx.x & 31) >> 2;
#pragma unroll
    for (int i = 0; i < 16; i++) v[i] = ldcg128(src + (i >> 1) * s1 + (i & 1) * s2);
    float a[4] = {0, 0, 0, 0}, q0[4] = {0, 0, 0, 0}, q1[4] = {0, 0, 0, 0};
#pragma unroll
    for (int i = 0; i < 16; i++) {
        mma16(a, v[i].x, v[i].y, v[i].z, v[i].w, 0x3f803f80u, 0x3f803f80u);
        mma8(q0, v[i].x, v[i].y, v[i].x); mma8(q1, v[i].x, v[i].y, v[i].y);
        mma8(q0, v[i].z, v[i].w, v[i].z); mma8(q1, v[i].z, v[i].w, v[i].w);
    }
    const float sum = a[0] + a[2], sq = (g & 1) ? q0[1] + q1[3] : q0[0] + q1[2];
    return make_float2(sum, fmaxf(sq - sum * sum * (1.f / 512.f), 0.f));
}
__device__ __forceinline__ void x1_norm(const uint2* src, int r, bool on) {
    const int lane = threadIdx.x & 31, g = lane >> 2, t = r * 4 + (lane & 3);
    constexpr int xp = XP;
    uint2 v[16];
#pragma unroll
    for (int i = 0; i < 16; i++) asm volatile("ld.global.cg.v2.u32 {%0,%1},[%2];" : "=r"(v[i].x), "=r"(v[i].y) : "l"(src + (g * 4 * xp + t) + ((i >> 1) * 16 + (i & 1)) * 2 * xp) : "memory");
    float s = 0, q = 0;
#pragma unroll
    for (int i = 0; i < 32; i++) {
        const uint32_t w = (i & 1) ? v[i >> 1].y : v[i >> 1].x;
        s += blo(w) + bhi(w); q = fmaf(blo(w), blo(w), fmaf(bhi(w), bhi(w), q));
    }
#pragma unroll
    for (int d = 4; d < 32; d *= 2) { s += __shfl_xor_sync(0xffffffffu, s, d); q += __shfl_xor_sync(0xffffffffu, q, d); }
    if (g == 0 && on) g_ln0[t] = 0;
    s *= 1.f / 512.f;
    const float2 l = ln_finish(s, fmaxf(fmaf(q, 1.f / 512.f, -s * s), 0.f));
    const float rs = rcp(l.y);
    const uint32_t mm = pack2(-l.x, -l.x);
    uint4* dst = g_xn + ((t >> 6) * 4096 + ((t >> 3) & 7) * 64 + g * 8 + (t & 7));
#define NRM(w) pack2(blo(hadd2(w, mm)) * rs, bhi(hadd2(w, mm)) * rs)
#pragma unroll
    for (int i = 0; i < 8; i++)
        asm volatile("{.reg .pred p; setp.ne.u32 p,%5,0; @p st.global.v4.u32 [%0],{%1,%2,%3,%4};}" ::"l"(dst + i * 512), "r"(NRM(v[2 * i].x)), "r"(NRM(v[2 * i].y)),
                     "r"(NRM(v[2 * i + 1].x)), "r"(NRM(v[2 * i + 1].y)), "r"((uint32_t)on) : "memory");
}

#define NWO 10
#define VMASK 0x4444
#define VPRE 2
#define VFIRST 1
#define OA 0
#define OL 0x16
#define PINS 0xae1
#define NPX 2
#define NPF 2
constexpr int SLOT = 24576, SL_V = 8192, SL_Q = 16384, SL_KM = 20480, SL_VM = 22528;
constexpr int R_SL = 0, R_WV = 4 * SLOT  , R_WO = R_WV + 65536, R_M = 196608  , R_U = R_M + 8192  ,
              R_OS = R_U + 8192  , R_SB = R_OS + 8192  , R_OB = R_SB + 5248  , R_PB = R_OB + 2048  ,
              R_IL = R_PB + 1024  , R_SEL = 231680, R_BAR = R_SEL + 256, R_STV = 0, R_STQ = 65536, R_STK = 131072;
static_assert(R_WO + (16 - NWO) * 4096 <= R_M && R_IL + 64 <= R_SEL && R_BAR + 512 <= 232448, "smem map");
enum { RB_XFULL = 0  , RB_GO = 4  , RB_QK = 8  , RB_INIT = 24, RB_SV = 25   };

enum { NB_MFULL = 1  , NB_PART = 3  , NB_S = 5, NB_P = 6, NB_O = 7, NB_W = 10 };
#define HL 2
#define XU 8
#define XFW 1
#define RACC 2
#define WDEP 1
#define RH 56
#define RW0 224
#define D1 400
#define D2 400
#define DX 0
__device__ __forceinline__ uint32_t clk32() { uint32_t c; asm volatile("mov.u32 %0,%%clock;" : "=r"(c)::"memory"); return c; }
__device__ __forceinline__ void spin(int cycles) {
    if (cycles <= 0) return;
    asm volatile("{.reg .pred p; .reg .u32 a,b; mov.u32 a,%%clock; add.u32 a,a,%0;\nS%=: mov.u32 b,%%clock; sub.u32 b,b,a; setp.lt.s32 p,b,0; @p bra.uni S%=;}" ::"r"(cycles) : "memory");
}
__device__ __forceinline__ uint4* xregion(int X, int r) { return (uint4*)(((size_t)g_xch + 8191) & ~(size_t)8191) + (X * 66 + r) * 512; }

__device__ __forceinline__ void arrive_if(uint32_t bar, uint32_t a, uint32_t b) {
    asm volatile("{.reg .pred p; setp.eq.u32 p,%1,%2; @p mbarrier.arrive.shared::cta.b64 _,[%0];}" ::"r"(bar), "r"(a), "r"(b) : "memory");
}
struct RecW { uint32_t po, dp, lw, sp  , w; };
#define PIN(n) if ((PINS >> (n)) & 1) asm volatile("griddepcontrol.launch_dependents;" ::: "memory")
constexpr int v_stream(int n) {
    int ks = 0;
    for (; ks < 16; ks++) if (!((VMASK >> ks) & 1) && n-- == 0) break;
    return ks;
}
constexpr uint64_t v_next() {
    uint64_t r = 0;
    for (int n = 0; v_stream(n + VPRE) < 16; n++) r |= (uint64_t)v_stream(n + VPRE) << (4 * v_stream(n));
    return r;
}
constexpr uint64_t V_NEXT = v_next();
constexpr int V_PRE = v_stream(VPRE);

template <int X>
__device__ __forceinline__ void rec_step(const RecW& k, uint32_t sb, int s, uint32_t zero, int lo, int hi, int d, const uint32_t (*wq)[4], const uint32_t (*wk)[4], uint4* wv, uint4* wo) {
    constexpr int SL = R_SL + X * 2 * SLOT;
    uint4 mk[8];
    bar_sync(NB_MFULL + X, 288);
    mk[0] = ldsm4(k.lw + X * 4096 + R_M);
    PIN(0);
    mk[1] = ldsm4(k.lw + X * 4096 + R_M + 512);
    PIN(0);
    asm volatile("" : "+r"(s));
    const uint32_t z = s & zero, wz = k.w + z, w5 = wz * 512, so = (s & 1) * SLOT + w5;
    const uint32_t qb = sb + R_BAR + (RB_QK + X * 8) * 8 + wz * 8;
    uint32_t x[4], vv[2], l8;
    {
        float aq[4] = {0, 0, 0, 0}, ak[4] = {0, 0, 0, 0}, av[4] = {0, 0, 0, 0};
#pragma unroll
        for (int t = 0; t < 16; t++) {
            const uint32_t b0 = (t & 1) ? mk[t >> 1].z : mk[t >> 1].x, b1 = (t & 1) ? mk[t >> 1].w : mk[t >> 1].y;
            mma16(aq, wq[t][0], wq[t][1], wq[t][2], wq[t][3], b0, b1);
            PIN(8);
            mma16(ak, wk[t][0], wk[t][1], wk[t][2], wk[t][3], b0, b1);
            PIN(9);
            mma16(av, wv[t].x, wv[t].y, wv[t].z, wv[t].w, b0, b1);
            PIN(10);
            if ((t & 1) && t < 13) mk[(t >> 1) + 2] = ldsm4(k.lw + X * 4096 + R_M + (t >> 1) * 512 + 1024);
            const int nx = (V_NEXT >> (4 * t)) & 15;
            if (nx) wv[nx] = lds128(k.lw + w5 + R_WV + nx * 4096);
            if (t == 14) l8 = ((k.lw + z) >> 1) + (sb - (sb >> 1) + SL + (s & 1) * SLOT + wz * 256);
            if (t < 15) PIN(1);
        }
        x[0] = movm(pack2(aq[0], aq[1])); x[1] = movm(pack2(aq[2], aq[3]));
        x[2] = movm(pack2(ak[0], ak[1])); x[3] = movm(pack2(ak[2], ak[3]));
        vv[0] = pack2(av[0], av[1]); vv[1] = pack2(av[2], av[3]);
        if (VFIRST) st_async2(l8 + (SL_VM + k.dp), vv[0], vv[1], qb + k.dp);
        st_async4(k.lw + (R_U + X * 4096 + w5 + k.dp), x[0], x[1], x[2], x[3], qb + k.dp);
        if (!VFIRST) st_async2(l8 + (SL_VM + k.dp), vv[0], vv[1], qb + k.dp);
    }
    {
        arrive_if(sb + R_BAR + (RB_GO + 2 - 2 * X + ((s + d) & 1)) * 8, k.sp, X ? s >= hi : s <= lo);
        const uint32_t swr = ((k.sp + z) & 0xffff) + (sb + R_SB);
        if (XFW) mbar_wait(sb + R_BAR + (RB_XFULL + X * 2) * 8 + (s & 1) * 8, (s >> 1) & 1);
        const uint4 k0 = lds128(k.lw + so + SL), k1 = lds128(k.lw + so + SL + 4096);
#pragma unroll
        for (int i = 0; i < NPX; i++) wo[i] = lds128(k.lw + w5 + R_WO + i * 4096);
        mbar_wait(qb, s & 1);
        const uint4 u = lds128(k.lw + w5 + R_U + X * 4096);
        const uint32_t q0 = hadd2(x[0], u.x), q1 = hadd2(x[1], u.y);
        x[2] = hadd2(x[2], u.z); x[3] = hadd2(x[3], u.w);
        float sa[4] = {0, 0, 0, 0}, sc[4] = {0, 0, 0, 0}, sm0, sm1;
        mma16(sa, k0.x, k0.y, k0.z, k0.w, q0, q1);
        mma16(sc, k1.x, k1.y, k1.z, k1.w, q0, q1);
        mma16_top(sm0, sm1, x[2], x[3], q0, q1);
        asm volatile("stmatrix.sync.aligned.m8n8.x4.trans.shared.b16 [%0],{%1,%2,%3,%4};" ::"r"(swr), "r"(pack2(sa[0], sa[1])), "r"(pack2(sa[2], sa[3])),
                     "r"(pack2(sc[0], sc[1])), "r"(pack2(sc[2], sc[3])) : "memory");
        asm volatile("stmatrix.sync.aligned.m8n8.x1.trans.shared.b16 [%0],{%1};" ::"r"(swr + 512), "r"(pack2(sm0, sm1)) : "memory");
    }
    bar_sync(NB_S, 256);
    uint4 v0, v1;
    uint32_t ls;
    {
        const uint4 y = ldsm4t(k.lw + wz * 656 + R_SB);
        PIN(2);
        uint32_t y4; asm volatile("ldmatrix.sync.aligned.m8n8.x1.trans.shared.b16 {%0},[%1];" : "=r"(y4) : "r"(k.lw + wz * 656 + R_SB + 512) : "memory");
        PIN(2);
        const uint2 vp = lds64(l8 + SL_VM);
        sts64(l8 + SL_KM, x[2], x[3]);
        const uint32_t ONE = 0x3f803f80u + z;
        float a[4] = {0, 0, 0, 0}, b[4] = {0, 0, 0, 0}, e[4] = {0, 0, 0, 0};
        mma16(a, ONE, z, z, ONE, y.x, y.y); mma16(b, ONE, z, z, ONE, y.z, y.w); mma8(e, ONE, z, y4);
        vv[0] = hadd2(vv[0], vp.x); vv[1] = hadd2(vv[1], vp.y);
        sts64(l8 + SL_VM, vv[0], vv[1]);
        float s0, s1;
        asm("{.reg .pred p1,p2,p4; .reg .f32 t0,t1,u0,u1; .reg .b32 m; and.b32 m,%12,64; setp.ne.u32 p1,m,0; and.b32 m,%12,128; setp.ne.u32 p2,m,0; and.b32 m,%12,256; setp.ne.u32 p4,m,0;"
            "selp.f32 t0,%4,%2,p1; selp.f32 t1,%5,%3,p1; selp.f32 u0,%8,%6,p1; selp.f32 u1,%9,%7,p1; selp.f32 t0,u0,t0,p2; selp.f32 t1,u1,t1,p2; selp.f32 %0,%10,t0,p4; selp.f32 %1,%11,t1,p4;}"
            : "=f"(s0), "=f"(s1) : "f"(a[0]), "f"(a[1]), "f"(a[2]), "f"(a[3]), "f"(b[0]), "f"(b[1]), "f"(b[2]), "f"(b[3]), "f"(e[0]), "f"(e[1]), "r"(k.lw));
        const int mi = __float_as_int(fmaxf(s0, s1));
        const int mp = __reduce_max_sync(0xffffffffu, mi), mn = (int)__reduce_min_sync(0xffffffffu, (unsigned)mi);
        PIN(3);
        v0 = lds128(k.lw + so + SL + SL_V); v1 = lds128(k.lw + so + SL + SL_V + 4096);
#pragma unroll
        for (int i = NPX; i < NPF; i++) wo[i] = lds128(k.lw + w5 + R_WO + i * 4096);
        PIN(4);
        const float mo = -__int_as_float(mp >= 0 ? mp : mn) * SC_LOG2E;
        s0 = ex2(fmaf(s0, SC_LOG2E, mo)); s1 = ex2(fmaf(s1, SC_LOG2E, mo));
        sts32(((k.sp + z) >> 16) + (sb + R_PB), pack2(s0, s1));
        ls = k.lw < sb + 320 ? __float_as_uint((s0 + s1) + 4.f) : 0;
    }
    bar_sync(NB_P, 256);
    {
        const uint4 pp = lds128(k.lw + R_PB);
        PIN(5);
        const uint32_t pm = lds32(((k.lw + z) >> 2) + (sb - (sb >> 2) + R_PB + 512));
        PIN(5);
        sts32(sb + R_IL + (wz >> 1) * 16 + (wz & 1) * 4, __reduce_add_sync(0xffffffffu, ls) - 20u * 0x40800000u);
        float o0[4] = {0, 0, 0, 0}, o1[4] = {0, 0, 0, 0}, o2[4] = {0, 0, 0, 0};
        mma16(o0, v0.x, v0.y, v0.z, v0.w, pp.x, pp.y);
        mma16(o1, v1.x, v1.y, v1.z, v1.w, pp.z, pp.w);
        mma8(o2, vv[0], vv[1], pm);
        asm volatile("stmatrix.sync.aligned.m8n8.x2.trans.shared.b16 [%0],{%1,%2};" ::"r"(k.lw + wz * 256 + R_OB),
                     "r"(pack2(o0[0] + o1[0] + o2[0], o0[1] + o1[1] + o2[1])), "r"(pack2(o0[2] + o1[2] + o2[2], o0[3] + o1[3] + o2[3])) : "memory");
    }
    bar_sync(NB_O, 256);
    {
        float r0[2][4] = {{0, 0, 0, 0}, {0, 0, 0, 0}}, r1[2][4] = {{0, 0, 0, 0}, {0, 0, 0, 0}};
        uint4 b[4];
        b[0] = ldsm4(k.lw + R_OB);
        PIN(6);
        b[1] = ldsm4(k.lw + R_OB + 512);
        PIN(6);
#pragma unroll
        for (int m = NWO + NPF; m < 16; m++) if (((OL >> (2 * (15 - m))) & 3) == 3) wo[m] = lds128(k.lw + w5 + R_WO + (m - NWO) * 4096);
        const uint2 il = lds64(sb + R_IL + ((k.lw + z) & 48));
        PIN(6);
        float i0, i1;
        uint4* dst;
#pragma unroll
        for (int i = 0; i < 4; i++) {
            mma16(r0[0], wo[4 * i].x, wo[4 * i].y, wo[4 * i].z, wo[4 * i].w, b[i].x, b[i].y);
            mma16(r1[0], wo[4 * i + 1].x, wo[4 * i + 1].y, wo[4 * i + 1].z, wo[4 * i + 1].w, b[i].x, b[i].y);
            mma16(r0[OA], wo[4 * i + 2].x, wo[4 * i + 2].y, wo[4 * i + 2].z, wo[4 * i + 2].w, b[i].z, b[i].w);
            mma16(r1[OA], wo[4 * i + 3].x, wo[4 * i + 3].y, wo[4 * i + 3].z, wo[4 * i + 3].w, b[i].z, b[i].w);
            if (i < 2) b[i + 2] = ldsm4(k.lw + R_OB + (i + 2) * 512);
#pragma unroll
            for (int m = NWO + NPF; m < 16; m++) if (i < 3 && i == ((OL >> (2 * (15 - m))) & 3)) wo[m] = lds128(k.lw + w5 + R_WO + (m - NWO) * 4096);
            if (i == 1) { i0 = rcp(__uint2float_rn(il.x)) * 2097152.f; i1 = rcp(__uint2float_rn(il.y)) * 2097152.f; }
            if (i == 2) {
                const uint32_t po = k.po + z;
                dst = (uint4*)((char*)xregion(X, 0) + ((po & ~1u) ^ ((po & X) << 12)));
                asm volatile("" : "+l"(dst));
            }
            PIN(7);
        }
        const uint32_t tag = (s + 1) & 1;
#pragma unroll
        for (int i = 0; i < 4; i++) { r0[0][i] = (OA ? r0[0][i] + r0[1][i] : r0[0][i]) * ((i & 1) ? i1 : i0); r1[0][i] = (OA ? r1[0][i] + r1[1][i] : r1[0][i]) * ((i & 1) ? i1 : i0); }
        st_rlx128(dst, (pack2(r0[0][0], r0[0][2]) & ~1u) | tag,
                  pack2(r1[0][0], r1[0][2]), pack2(r0[0][1], r0[0][3]), pack2(r1[0][1], r1[0][3]));
        bar_arrive(NB_PART + X, 288);
#pragma unroll
        for (int t = 0; t < V_PRE; t++) if (!((VMASK >> t) & 1)) wv[t] = lds128(k.lw + w5 + R_WV + t * 4096);
        arrive_if(sb + R_BAR + (RB_GO + 2 * X + (s & 1)) * 8, k.sp, X ? s + 1 < hi : s >= lo);
    }
}

__device__ __forceinline__ void rec_fetch(const Params& p, uint32_t sb, int head, uint32_t rank, int which, int dst) {
#pragma unroll 1
    for (int j = 0; j < 8; j++) tma2d(sb + dst + j * 8192, &p.tm[which], head * 128 + (j >> 2) * 64, rank * 256 + (j & 3) * 64, sb + R_BAR + RB_INIT * 8);
}

__device__ __forceinline__ void rec_weights(const Params& p, uint32_t sb, int head, uint32_t rank, int w) {
    const int lane = threadIdx.x & 31, g = lane >> 2, c = lane & 3;
    const int t = w & 3, WG = w >> 2;
    uint32_t wq[16][4], wk[16][4];
    uint4 wo[16], wv[16];
    const uint32_t woff = sb + WG * 32768 + (((lane >> 4) << 3) + (lane & 7)) * 128 + (((2 * t + ((lane >> 3) & 1)) ^ (lane & 7)) << 4);
    const uint32_t lw = sb + lane * 16;
    PROF(threadIdx.x == 0, 3501);
    {
        const __nv_bfloat16* wp = p.Wo + (size_t)(head * 128 + 2 * c) * 512 + rank * 256 + w * 32 + g * 4;
#pragma unroll
        for (int ks = 0; ks < 8; ks++) {
            const uint2 r0 = *(const uint2*)(wp + (ks * 16) * 512), r1 = *(const uint2*)(wp + (ks * 16 + 1) * 512);
            const uint2 r2 = *(const uint2*)(wp + (ks * 16 + 8) * 512), r3 = *(const uint2*)(wp + (ks * 16 + 9) * 512);
            const uint4 f[2] = {make_uint4(__byte_perm(r0.x, r1.x, 0x5410), __byte_perm(r0.x, r1.x, 0x7632), __byte_perm(r2.x, r3.x, 0x5410), __byte_perm(r2.x, r3.x, 0x7632)),
                                make_uint4(__byte_perm(r0.y, r1.y, 0x5410), __byte_perm(r0.y, r1.y, 0x7632), __byte_perm(r2.y, r3.y, 0x5410), __byte_perm(r2.y, r3.y, 0x7632))};
#pragma unroll
            for (int h = 0; h < 2; h++) {
                const int m = 2 * ks + h;
                wo[m] = f[h];
            }
        }
    }
    PROF(threadIdx.x == 0, 3502);
    mbar_wait(sb + R_BAR + RB_INIT * 8, 0);
    PROF(threadIdx.x == 0, 3503);
#pragma unroll
    for (int ks = 0; ks < 16; ks++) {
        uint4 a = ldsm4t(woff + R_STQ + ks * 2048), b = ldsm4t(woff + R_STK + ks * 2048);
        wq[ks][0] = a.x; wq[ks][1] = a.y; wq[ks][2] = a.z; wq[ks][3] = a.w;
        wk[ks][0] = b.x; wk[ks][1] = b.y; wk[ks][2] = b.z; wk[ks][3] = b.w;
    }
    bar_sync(NB_W, 256);
#pragma unroll
    for (int m = 0; m < 16; m++)
        if (m < NPF || m >= NPF + NWO) sts128(lw + w * 512 + R_WO + (m < NPF ? m : m - NWO) * 4096, wo[m].x, wo[m].y, wo[m].z, wo[m].w);
#pragma unroll
    for (int i = 0; i < 16; i++) {
        wv[i] = ldsm4t(woff + R_STV + i * 2048);
        if (!((VMASK >> i) & 1)) sts128(lw + w * 512 + R_WV + i * 4096, wv[i].x, wv[i].y, wv[i].z, wv[i].w);
    }
    fence_async_smem();
    PROF(threadIdx.x == 0, 3504);
    __syncthreads();
    cluster_sync();
    PROF(threadIdx.x == 0, 3505);
    RecW k;
    {
        const int r = (w * 4 + (lane >> 3)) * 2 + rank;
        const uint32_t sl = lds32(sb + R_SEL + r * 4);
        const int slot = HL == 0 ? head * 8 + (lane & 7) : HL == 1 ? (head >> 2) * 32 + ((lane & 7) >> 1) * 8 + (head & 3) * 2 + (lane & 1) : (head >> 1) * 16 + ((lane & 7) >> 2) * 8 + (head & 1) * 4 + (lane & 3);
        k.po = (r * 512 + slot + (sl & 1) * 256) * 16 + (((sl >> 1) ^ sl) & 1);
    }
    k.dp = mapa(sb, rank ^ 1) - sb;
    k.lw = __shfl_sync(0xffffffffu, lw, lane);
    k.sp = __shfl_sync(0xffffffffu, (lane & 7) * 656 + (lane >> 3) * 128 + w * 16 + ((g < 4 ? (w * 4 + c) * 16 + g * 4 : 512 + (w * 4 + c) * 4) << 16), lane);
    k.w = w;
    const int e0 = (p.chains & 1) ? 64 : 0, o1 = (p.chains & 2) ? p.lag : 1000, nit = (p.chains & 2) ? p.lag + 64 : e0;
    const uint32_t zero = p.zero;
#pragma unroll 1
    for (int it = 0; it < nit; it++) {
        if (it < e0) rec_step<0>(k, sb, it, zero, o1, 0, o1 + 1, wq, wk, wv, wo);
        if (it >= o1) rec_step<1>(k, sb, it - o1, zero, 0, e0 - o1, o1, wq, wk, wv, wo);
    }
}

__device__ __forceinline__ uint32_t mism(uint32_t a, uint32_t b, uint32_t t) {
    uint32_t d; asm("lop3.b32 %0,%1,%2,%3,0x7e;" : "=r"(d) : "r"(a), "r"(b), "r"(t)); return d;
}
__device__ __forceinline__ uint32_t or3(uint32_t a, uint32_t b, uint32_t c) {
    uint32_t d; asm("lop3.b32 %0,%1,%2,%3,0xfe;" : "=r"(d) : "r"(a), "r"(b), "r"(c)); return d;
}
template <bool TWO, class F>
__device__ __forceinline__ void poll8(uint4* x, const uint4* src, uint32_t tag, F&& use) {
#pragma unroll
    for (int j = 0; j < 8; j++) x[j] = ld_rlx128(src + j * 32);
    int n = 0;
    while (true) {
        use();
        uint32_t bad = or3(mism(x[0].x, x[1].x, tag), mism(x[2].x, x[3].x, tag), mism(x[4].x, x[5].x, tag));
        if (TWO) bad = or3(bad, or3(mism(x[0].z, x[1].z, tag), mism(x[2].z, x[3].z, tag), mism(x[4].z, x[5].z, tag)), mism(x[6].z, x[7].z, tag));
        if (!__any_sync(0xffffffffu, (bad | mism(x[6].x, x[7].x, tag)) & 1)) break;
#pragma unroll
        for (int j = 0; j < 8; j++)
            asm volatile("{.reg .pred p; .reg .b128 t; .reg .b32 m; lop3.b32 m,%0,%6,%5,0x7e; and.b32 m,m,1; setp.ne.u32 p,m,0; mov.b128 t,{%0,%1,%2,%3};"
                         "@p ld.relaxed.gpu.global.b128 t,[%4]; mov.b128 {%0,%1,%2,%3},t;}"
                         : "+r"(x[j].x), "+r"(x[j].y), "+r"(x[j].z), "+r"(x[j].w) : "l"(src + j * 32), "r"(tag), "r"(TWO ? x[j].z : tag) : "memory");
        if (++n > 2000000) __trap();
    }
}

__device__ __forceinline__ void rec_comm(const Params& p, uint32_t sb, int X, int head, uint32_t rank) {
    const int lane = threadIdx.x & 31, g = lane >> 2, c = lane & 3;
    const int me = head * 2 + rank;
    const uint32_t mb = sb + R_M + X * 4096 + lane * 16;
    uint4 x[8];
#pragma unroll
    for (int j = 0; j < 8; j++) x[j] = *(const uint4*)(p.mem0 + (lane & 7) * 512 + rank * 256 + (j * 4 + (lane >> 3)) * 8);
    const uint32_t sl = lds32(sb + R_SEL + me * 4);
    const uint4* src1 = xregion(X, me) + ((sl >> X) & 1) * 256 + (HL == 0 ? c * 8 + g : HL == 1 ? (g >> 1) * 8 + c * 2 + (g & 1) : (c >> 1) * 16 + (g >> 2) * 8 + (c & 1) * 4 + (g & 3));
    const uint4* src2 = xregion(X, 64 + rank) + ((sl >> (2 + X)) & 1) * 256 + lane;
    uint2* mdst = (uint2*)(xregion(X, 64 + rank) + (c >> 1) * 256 + head * 8 + (g & 3) * 2 + (c & 1)) + (g >> 2);
    const uint32_t one = (g & 1) ? 0x3f800000u : 0x00003f80u, selA = (g & 2) ? 0u : one, selB = (g & 2) ? one : 0u;
    const uint32_t qb = sb + R_BAR + (RB_QK + X * 8 + lane) * 8;
    if (lane < 8) mbar_expect(qb, 768);
    if (!XFW) mbar_wait(sb + R_BAR + (RB_XFULL + X * 2) * 8, 0);
#pragma unroll
    for (int j = 0; j < 8; j++) sts128(mb + j * 512, x[j].x, x[j].y, x[j].z, x[j].w);
#pragma unroll 1
    for (int s = 0;; s++) {
        bar_arrive(NB_MFULL + X, 288);
        PROF(lane == 0, X * 64 + s);
        bar_sync(NB_PART + X, 288);
        if (s == 63) break;
        const uint32_t tag = (s + 1) & 1;
        if (lane < 8) mbar_expect(qb, 768);
        spin(D1);
        uint32_t m0, m1;
        poll8<false>(x, src1, tag, [&]() {
            float a[RACC][4];
#pragma unroll
            for (int j = 0; j < 8; j++) {
                if (j < RACC) a[j][0] = a[j][1] = a[j][2] = a[j][3] = 0;
                mma16(a[j % RACC], x[j].x, x[j].y, x[j].z, x[j].w, selA, selB);
            }
#pragma unroll
            for (int i = 0; i < 4; i++) a[0][i] = RACC == 3 ? a[0][i] + a[1][i] + a[2 % RACC][i] : a[0][i] + a[1][i];
            m0 = (pack2(a[0][0], a[0][1]) & ~1u) | tag; m1 = pack2(a[0][2], a[0][3]);
        });
        asm volatile("st.relaxed.gpu.global.b64 [%0],%1;" ::"l"(mdst), "l"(((uint64_t)m1 << 32) | m0) : "memory");
        const uint32_t t2 = clk32();
        if (!XFW) mbar_wait(sb + R_BAR + (RB_XFULL + X * 2 + tag) * 8, ((s + 1) >> 1) & 1);
        while (clk32() - t2 < D2) {}
        poll8<true>(x, src2, tag, [&]() {
#pragma unroll
            for (int j = 0; j < 8; j++) sts128(mb + j * 512, x[j].x, x[j].y, x[j].z, x[j].w);
        });
    }
}

template <int MT>
__device__ __forceinline__ void xattn(uint32_t l16, uint32_t l8, uint32_t os, int g, int c) {
    constexpr int NT = 3 + 2 * MT, XUN = XU;
    float S[NT][4];
#pragma unroll
    for (int i = 0; i < NT; i++) S[i][0] = S[i][1] = S[i][2] = S[i][3] = 0;
#pragma unroll XUN
    for (int ks = 0; ks < 8; ks++) {
        const uint4 q = lds128(l16 + SL_Q + ks * 512);
        const uint2 u = lds64(l8 + SL_KM + ks * 256);
        mma16(S[0], q.x, q.y, q.z, q.w, u.x, u.y);
#pragma unroll
        for (int m = 0; m <= MT; m++) {
            const uint4 kk = lds128(l16 + m * 4096 + ks * 512);
            mma16(S[1 + 2 * m], q.x, q.y, q.z, q.w, kk.x, kk.z); mma16(S[2 + 2 * m], q.x, q.y, q.z, q.w, kk.y, kk.w);
        }
    }
    const float NEG = -__int_as_float(0x7f800000);
    if (2 * c > g) { S[NT - 2][0] = NEG; S[NT - 1][2] = NEG; }
    if (2 * c + 1 > g) { S[NT - 2][1] = NEG; S[NT - 1][3] = NEG; }
    S[NT - 1][0] = S[NT - 1][1] = NEG;
    float m0 = fmaxf(S[0][0], S[0][1]), m1 = fmaxf(S[0][2], S[0][3]);
#pragma unroll
    for (int i = 1; i < NT; i++) { if (i < NT - 1) m0 = fmaxf(m0, fmaxf(S[i][0], S[i][1])); m1 = fmaxf(m1, fmaxf(S[i][2], S[i][3])); }
    m0 = fmaxf(m0, __shfl_xor_sync(0xffffffffu, m0, 1)); m1 = fmaxf(m1, __shfl_xor_sync(0xffffffffu, m1, 1));
    m0 = fmaxf(m0, __shfl_xor_sync(0xffffffffu, m0, 2)); m1 = fmaxf(m1, __shfl_xor_sync(0xffffffffu, m1, 2));
    m0 *= -SC_LOG2E; m1 *= -SC_LOG2E;
    float l0 = 0, l1 = 0;
#pragma unroll
    for (int i = 0; i < NT; i++) {
        if (i < NT - 1) { S[i][0] = ex2(fmaf(S[i][0], SC_LOG2E, m0)); S[i][1] = ex2(fmaf(S[i][1], SC_LOG2E, m0)); l0 += S[i][0] + S[i][1]; }
        S[i][2] = ex2(fmaf(S[i][2], SC_LOG2E, m1)); S[i][3] = ex2(fmaf(S[i][3], SC_LOG2E, m1)); l1 += S[i][2] + S[i][3];
    }
    l0 += __shfl_xor_sync(0xffffffffu, l0, 1); l1 += __shfl_xor_sync(0xffffffffu, l1, 1);
    l0 += __shfl_xor_sync(0xffffffffu, l0, 2); l1 += __shfl_xor_sync(0xffffffffu, l1, 2);
    uint2 vm = lds64(l8 + SL_VM);
    uint4 v[2];
#pragma unroll
    for (int m = 0; m <= MT; m++) v[m] = lds128(l16 + SL_V + m * 4096);
    l0 = rcp(l0); l1 = rcp(l1);
    uint32_t P[NT][2];
#pragma unroll
    for (int i = 0; i < NT; i++) { P[i][0] = i < NT - 1 ? pack2(S[i][0] * l0, S[i][1] * l0) : 0u; P[i][1] = pack2(S[i][2] * l1, S[i][3] * l1); }
#pragma unroll
    for (int et = 0; et < 8; et++) {
        float a[4] = {0, 0, 0, 0}, b[4] = {0, 0, 0, 0};
        const uint2 um = vm;
        const uint4 u[2] = {v[0], v[MT]};
        if (et < 7) {
            vm = lds64(l8 + SL_VM + et * 256 + 256);
#pragma unroll
            for (int m = 0; m <= MT; m++) v[m] = lds128(l16 + SL_V + m * 4096 + et * 512 + 512);
            PIN(11);
        }
        mma8(a, um.x, um.y, P[0][0]); mma8(b, um.x, um.y, P[0][1]);
#pragma unroll
        for (int m = 0; m <= MT; m++) {
            mma16(a, u[m].x, u[m].y, u[m].z, u[m].w, P[1 + 2 * m][0], P[2 + 2 * m][0]); mma16(b, u[m].x, u[m].y, u[m].z, u[m].w, P[1 + 2 * m][1], P[2 + 2 * m][1]);
        }
        asm volatile("stmatrix.sync.aligned.m8n8.x4.trans.shared.b16 [%0],{%1,%2,%3,%4};" ::"r"(os + (et >> 2) * 2048 + (et & 3) * 256),
                     "r"(pack2(a[0], a[1])), "r"(pack2(a[2], a[3])), "r"(pack2(b[0], b[1])), "r"(pack2(b[2], b[3])) : "memory");
    }
}

__device__ __forceinline__ void rec_tiles(uint32_t sb, int X, int head, uint32_t rank, int& nxt, int lim, int need) {
#pragma unroll 1
    while (nxt <= lim) {
        if ((nxt & 1) == 0) {
            unsigned v; int n = 0;
            while (true) {
                asm volatile("ld.relaxed.gpu.global.u32 %0,[%1];" : "=r"(v) : "l"(cnt_ptr(C_QKV + X * 32 + (nxt >> 1))) : "memory");
                if (__all_sync(0xffffffffu, v >= 2 * NQ)) break;
                if (nxt > need) return;
                if (++n > 3000000) __trap();
            }
        }
        if (elect()) {
            const uint32_t bar = sb + R_BAR + (RB_XFULL + X * 2 + (nxt & 1)) * 8, dst = sb + R_SL + (X * 2 + (nxt & 1)) * SLOT;
            const uint4* src = g_qkv + (size_t)((X * 64 + nxt) * 32 + head) * 1536;
            mbar_expect(bar, 20480);
            bulk_g2s_mc(dst + rank * 8192, src + 512 + rank * 512, 8192, bar, POL_LAST);
            bulk_g2s(dst + SL_Q, src + (rank ^ X) * 256, 4096, bar, POL_LAST);
        }
        __syncwarp();
        nxt++;
    }
}

__device__ __forceinline__ void rec_attn(const Params& p, uint32_t sb, int X, int head, uint32_t rank) {
    const int lane = __shfl_sync(0xffffffffu, threadIdx.x & 31, threadIdx.x & 31), g = lane >> 2, c = lane & 3;
    const int mt = rank ^ X;
    const uint32_t dp = mapa(sb, rank ^ 1) - sb;
    int nxt = 0;
    rec_tiles(sb, X, head, rank, nxt, 1, 0);
#pragma unroll 1
    for (int s = 0; s < 64; s++) {
        const uint32_t so = sb + R_SL + (X * 2 + (s & 1)) * SLOT;
        while (nxt <= min(s + 1, 63)) {
            uint32_t ok;
            asm volatile("{.reg .pred p; mbarrier.test_wait.parity.shared::cta.b64 p,[%1],%2; selp.u32 %0,1,0,p;}" : "=r"(ok) : "r"(sb + R_BAR + (RB_GO + X * 2 + (s & 1)) * 8), "r"((s >> 1) & 1) : "memory");
            if (__any_sync(0xffffffffu, ok)) break;
            rec_tiles(sb, X, head, rank, nxt, s + 1, -1);
        }
        mbar_wait(sb + R_BAR + (RB_GO + X * 2 + (s & 1)) * 8, (s >> 1) & 1);
        spin(DX);
        mbar_wait(sb + R_BAR + (RB_XFULL + X * 2 + (s & 1)) * 8, (s >> 1) & 1);
        if (elect()) asm volatile("cp.async.bulk.wait_group.read 0;" ::: "memory");
        __syncwarp();
        const uint32_t os = sb + R_OS + X * 4096 + (lane >> 4) * 1024 + (lane & 15) * 16;
        if (mt) xattn<1>(so + lane * 16, so + lane * 8, os, g, c); else xattn<0>(so + lane * 16, so + lane * 8, os, g, c);
        fence_async_smem();
        __syncwarp();
        const uint32_t svb = sb + R_BAR + (RB_SV + X * 2 + (s & 1)) * 8;
        if (elect()) {
            mbar_arrive(svb); mbar_arrive_cluster(svb + dp);
            const uint64_t pol = POL_SOON;
#pragma unroll
            for (int kb = 0; kb < 2; kb++)
                asm volatile("cp.async.bulk.global.shared::cta.bulk_group.L2::cache_hint [%0],[%1],%2,%3;" ::"l"(g_o + ((X * 32 + (s >> 1)) * 64 + head * 2 + kb) * 512 + ((s & 1) * 4 + mt * 2) * 64),
                             "r"(sb + R_OS + X * 4096 + kb * 2048), "r"(2048), "l"(pol) : "memory");
            asm volatile("cp.async.bulk.commit_group;" ::: "memory");
        }
        __syncwarp();
        if (s & 1) {
            if (elect()) { asm volatile("cp.async.bulk.wait_group 0;" ::: "memory"); red_relaxed(cnt_ptr(C_O + (X * 32 + (s >> 1)) * 4 + (head >> 3)), 1); }
            __syncwarp();
        }
        rec_tiles(sb, X, head, rank, nxt, min(s + 1, 63), s + 1);
        mbar_wait(svb, (s >> 1) & 1);
        rec_tiles(sb, X, head, rank, nxt, min(s + 2, 63), -1);
    }
}

__device__ __forceinline__ uint32_t timed_clear(unsigned* r, int lane) {
    uint32_t v = 0;
    const uint32_t t0 = clk32();
    asm volatile("{.reg .pred p; setp.eq.u32 p,%2,0; @p atom.relaxed.gpu.global.exch.b32 %0,[%1],0;}" : "+r"(v) : "l"(r), "r"(lane) : "memory");
    v = __shfl_sync(0xffffffffu, v, 0);
    asm volatile("{.reg .pred p; setp.eq.u32 p,%0,0x5a5a5a5b; @p nanosleep.u32 1;}" ::"r"(v) : "memory");
    return clk32() - t0;
}
__device__ __forceinline__ void rec_slots(int me, int X) {
    const int lane = threadIdx.x & 31;
#pragma unroll 1
    for (int i = lane; i < 512; i += 32) xregion(X, me)[i] = make_uint4(0, 0, 0, 0);
    if (lane < 16) xregion(X, 64 + (me & 1))[(lane >> 3) * 256 + (me >> 1) * 8 + (lane & 7)] = make_uint4(0, 0, 0, 0);
    __syncwarp();
    uint32_t sel = 0;
#pragma unroll 1
    for (int k = 0; k < 2; k++) {
        unsigned* r = (unsigned*)xregion(X, k ? 64 + (me & 1) : me) + k * (me >> 1) * 32;
        uint32_t b0 = ~0u, b1 = ~0u;
#pragma unroll 1
        for (int i = 0; i < 4; i++) { b0 = min(b0, timed_clear(r, lane)); b1 = min(b1, timed_clear(r + 1024, lane)); }
        sel |= (b1 < b0) << (2 * k + X);
    }
    if (lane == 0) ((uint16_t*)g_sel)[me * 2 + X] = sel;
}

__device__ __forceinline__ void rec_init(uint32_t sb) {
    const uint32_t b = sb + R_BAR;
    const int i = threadIdx.x & 31;
    mbar_init(b + i * 8, i >= RB_SV ? 2 : 1);
    if (i == RB_INIT) mbar_expect(b + RB_INIT * 8, 196608);
    asm volatile("fence.mbarrier_init.release.cluster;" ::: "memory");
}
constexpr int G_BAR = B_BAR;
enum { GB_FULL = 0  , GB_EMPTY = 8  , GB_RS = 16, GB_SS = 17, GB_LAG = 18, GB_FREE = 19, GB_DONE = 20  , GB_N = 24 };
constexpr int Q_PRE = 8;
constexpr int NQRS = 2 * NQ - 64;
__device__ __forceinline__ void gemm_init(uint32_t sb, bool op) {
    const int i = threadIdx.x & 31;
    if (i < GB_N) mbar_init(sb + G_BAR + i * 8, i >= GB_DONE ? 4 : i == GB_FREE ? 8 : (i >= GB_EMPTY && i < GB_RS) ? 2 : 1);
    if (i == GB_RS) mbar_expect(sb + G_BAR + i * 8, op ? 131072 : 98304);
    if (i == GB_SS) mbar_expect(sb + G_BAR + i * 8, op ? 131072 : 163840);
    asm volatile("fence.mbarrier_init.release.cluster;" ::: "memory");
}
__device__ __forceinline__ int qkv_blk(int id, int j) { return NQRS * 4 + id * 10 + j; }
__device__ __forceinline__ void qkv_fetch(const Params& p, uint32_t sb, int id, int j0, int j1) {
#pragma unroll 1
    for (int j = j0 * 2; j < j1 * 2; j++) {
        const int blk = min(qkv_blk(id, j >> 1), 511);
        tma2d(sb + j * 8192, &p.tn[blk >> 8], (blk & 255) * 16, (j & 1) * 256, sb + G_BAR + GB_SS * 8);
    }
}
__device__ __forceinline__ void qkv_stage(const Params& p, uint32_t dst, uint32_t bar, int id, int k0, int nk) {
#pragma unroll 1
    for (int j = 0; j < 2 * nk; j++) {
        const int u = id * 2 + (j >= nk);
        tma2d(dst + j * 8192, &p.tm[u < 64 ? 2 : 0], (u & 63) * 64, (k0 + (j >= nk ? j - nk : j)) * 64, bar);
    }
}
__device__ __forceinline__ void op_fetch(const Params& p, uint32_t sb, int id, int half) {
#pragma unroll 1
    for (int j = 0; j < 16; j++) tma2d(sb + j * 8192, &p.tm[4], ((id * 2 + (j >> 3)) & 7) * 64, (id >> 2) * 1024 + (j & 7) * 128 + half * 64, sb + G_BAR + (GB_RS + half) * 8);
}
template <bool OP>
__device__ __forceinline__ void gemm_producer(const Params& p, uint32_t sb, int id) {
    constexpr int NS = OP ? 6 : 8, SB = OP ? 16384 : 8192, RING = OP ? 131072 : 163840;
    if (!elect()) return;
    mbar_wait(sb + G_BAR + GB_FREE * 8, 0);
    if (OP) op_fetch(p, sb, id, 1);
    else {
        mbar_expect(sb + G_BAR + GB_RS * 8, 32768);
        qkv_stage(p, sb + 196608, sb + G_BAR + GB_RS * 8, id, 6, 2);
        qkv_fetch(p, sb, id, Q_PRE, 10);
        mbar_wait(sb + G_BAR + GB_FREE * 8, 1);
    }
    wait_cnt(g_gate, lds32(sb + S_GATE));
    int st = 0; uint32_t ph = 1;
#pragma unroll 1
    for (int n = 0; n < p.nl[OP]; n++) {
        const int e = p.list[OP][n];
        wait_cnt(OP ? cnt_ptr(C_O + e * 4 + (id >> 2)) : cnt_ptr(C_XN + e), 16);
        PROF(true, 1024 + n * 4);
        const uint4* src = OP ? g_o + (e * 64 + (id >> 2) * 16) * 512 : g_xn + e * 4096;
#pragma unroll 1
        for (int s = 0; s < 8; s++) {
            mbar_wait(sb + G_BAR + (GB_EMPTY + st) * 8, ph);
            mbar_expect(sb + G_BAR + (GB_FULL + st) * 8, SB);
            bulk_g2s(sb + RING + st * SB, src + s * (SB / 16), SB, sb + G_BAR + (GB_FULL + st) * 8, POL_N);
            if (++st == NS) { st = 0; ph ^= 1; }
        }
    }
}
template <bool OP>
__device__ __forceinline__ void gemm_release(const Params& p, uint32_t sb, int id, int n0) {
    if (!elect()) return;
#pragma unroll 1
    for (int n = n0; n < 2 * p.nl[OP]; n += OP ? 2 : 1) {
        const int e = p.list[OP][n >> 1];
        mbar_wait(sb + G_BAR + (GB_DONE + (n & 3)) * 8, (n >> 2) & 1);
        red_release(OP ? cnt_ptr(C_PP + e * 8 + (id & 3) * 2 + (n & 1)) : cnt_ptr(C_QKV + e), 1);
        PROF(n & 1, 1024 + (n >> 1) * 4 + 3);
    }
}
__device__ __forceinline__ void op_permute(uint32_t sb) {
#pragma unroll 2
    for (int i = threadIdx.x; i < 4096; i += 256) {
        const uint32_t a = sb + i * 32 + ((i >> 2) & 1) * 16, b = a ^ 16;
        const uint4 x = lds128(a), y = lds128(b);
        sts128(a, __byte_perm(x.x, x.y, 0x5410), __byte_perm(x.z, x.w, 0x5410), __byte_perm(y.x, y.y, 0x5410), __byte_perm(y.z, y.w, 0x5410));
        sts128(b, __byte_perm(x.x, x.y, 0x7632), __byte_perm(x.z, x.w, 0x7632), __byte_perm(y.x, y.y, 0x7632), __byte_perm(y.z, y.w, 0x7632));
    }
    fence_async_smem();
    bar_sync(1, 256);
}
template <bool OP>
__device__ __forceinline__ void gemm_consumer(const Params& p, uint32_t sb, int id, int w) {
    constexpr int NS = OP ? 6 : 8, SB = OP ? 16384 : 8192, RING = OP ? 131072 : 163840;
    const int lane = threadIdx.x & 31, wg = w >> 2, t = w & 3, u = id * 2 + wg;
    uint32_t a[128];
    mbar_wait(sb + G_BAR + GB_RS * 8, 0);
    PROF(threadIdx.x == 0, 3501);
    if (OP) op_permute(sb);
    const uint32_t wo = sb + (((lane >> 4) << 3) + (lane & 7)) * 128 + (((2 * t + ((lane >> 3) & 1)) ^ (lane & 7)) << 4);
#pragma unroll
    for (int ks = 0; ks < 32; ks++) {
        const uint4 v = ldsm4t(wo + ks * 2048 + (OP ? wg * 65536 : ks < 24 ? 131072 + wg * 49152 : 196608 - 49152 + wg * 16384));
        a[ks * 4] = v.x; a[ks * 4 + 1] = v.y; a[ks * 4 + 2] = v.z; a[ks * 4 + 3] = v.w;
        if (ks == 31 || (!OP && ks == 23)) {
            fence_async_smem();
            __syncwarp();
            if (lane == 0) mbar_arrive(sb + G_BAR + GB_FREE * 8);
            if (ks == 23) mbar_wait(sb + G_BAR + GB_RS * 8, 1);
        }
    }
    PROF(threadIdx.x == 0, 3502);
    mbar_wait(sb + G_BAR + GB_SS * 8, 0);
    if (OP) op_permute(sb);
    PROF(threadIdx.x == 0, 3503);
    float c0[32], c1[OP ? 32 : 40];
    int st = 0; uint32_t ph = 0;
    const bool el = (threadIdx.x & 127) == 0;
#pragma unroll 1
    for (int n = 0; n < p.nl[OP]; n++) {
        int prev = 0;
        const uint32_t wb = sb + wg * (OP ? 65536 : 81920) + (n & p.zero);
        const uint64_t dw = OP ? mkdesc(wb, 0, 1024, 1) : mkdesc(wb, 16384, 256, 3);
        if (!OP && wg) mbar_wait(sb + G_BAR + GB_LAG * 8, n & 1);
#pragma unroll
        for (int s = 0; s < 8; s++) {
            mbar_wait(sb + G_BAR + (GB_FULL + st) * 8, ph);
            const uint64_t dx = mkdesc(sb + RING + st * SB, 128, 1024, 0);
            wg_fence();
#pragma unroll
            for (int kk = 0; kk < 4; kk++) {
                const int ks = s * 4 + kk;
                if (ks == 0) { wgmma64_rs<0>(c0, a, dx); if (OP) wgmma64_ta<0>(c1, dw, dx + 512); else wgmma80_tb<0>(c1, dx, dw); }
                else { wgmma64_rs<1>(c0, a + ks * 4, dx + kk * 16); if (OP) wgmma64_ta<1>(c1, dw + ks * 128, dx + 512 + kk * 16); else wgmma80_tb<1>(c1, dx + kk * 16, dw + ks * 32); }
            }
            wg_commit();
            if (s) {
                wg_wait<1>();
                if (el) { mbar_arrive(sb + G_BAR + (GB_EMPTY + prev) * 8); if (!OP && s == QLAG && !wg) mbar_arrive(sb + G_BAR + GB_LAG * 8); }
            }
            prev = st;
            if (++st == NS) { st = 0; ph ^= 1; }
        }
        const int e = p.list[OP][n];
        wg_wait<0>();
        if (el) mbar_arrive(sb + G_BAR + (GB_EMPTY + prev) * 8);
        PROF(threadIdx.x == 128, 1024 + n * 4 + 1);
        if (OP) {
            uint4* dst = g_pp + (e * 4 + (id >> 2)) * 4096 + ((u & 7) * 32 + t * 8) * 16 + (lane >> 2) * 16 + (lane & 3);
#pragma unroll
            for (int j = 0; j < 4; j++) {
                const float* x = c0 + j * 8; const float* y = c1 + j * 8;
                stg128(dst + j * 4, make_uint4(pack2(x[0] + y[0], x[1] + y[1]), pack2(x[2] + y[2], x[3] + y[3]), pack2(x[4] + y[4], x[5] + y[5]), pack2(x[6] + y[6], x[7] + y[7])), POL_SOON);
            }
        } else {
            uint4* dst = g_qkv + (size_t)e * 2 * 32 * 1536 + lane;
            const uint64_t pol = POL_SOON;
#pragma unroll
            for (int j = 0; j < 4; j++) {
                const float* x = c0 + j * 8;
                uint4 v = make_uint4(pack2(x[0], x[1]), pack2(x[2], x[3]), pack2(x[4], x[5]), pack2(x[6], x[7]));
                if (u >= 64) v = make_uint4(movm(v.x), movm(v.z), movm(v.y), movm(v.w));
                stg128(dst + (((j >> 1) * 32 + ((u & 63) >> 1)) * 1536 + (u < 64 ? 1024 : 0) + (j & 1) * 256 + ((u & 1) * 4 + t) * 32), v, pol);
            }
#pragma unroll
            for (int j = 0; j < 5; j++) {
                const float* x = c1 + (OP ? 0 : j * 8);
                const int blk = qkv_blk(id, wg * 5 + j);
                if (blk < 512) stg128(dst + (((t >> 1) * 32 + ((blk >> 3) & 31)) * 1536 + (blk >> 8) * 512 + (t & 1) * 256 + (blk & 7) * 32),
                                      make_uint4(pack2(x[0], x[1]), pack2(x[2], x[3]), pack2(x[4], x[5]), pack2(x[6], x[7])), pol);
            }
        }
        __syncwarp();
        if (lane == 0) mbar_arrive(sb + G_BAR + (GB_DONE + (n & 1) * 2 + wg) * 8);
        PROF(threadIdx.x == 128, 1024 + n * 4 + 2);
    }
}

template <int NP, bool MMA>
__device__ __forceinline__ void sum_partials(float* x, const uint2* src, const uint32_t* r0, const uint32_t* r1, uint32_t idm) {
    uint2 v[4][NP];
#pragma unroll
    for (int s = 0; s < 4; s++)
#pragma unroll
        for (int i = 0; i < NP; i++) asm volatile("ld.global.cg.L2::cache_hint.v2.u32 {%0,%1},[%2],%3;" : "=r"(v[s][i].x), "=r"(v[s][i].y) : "l"(src + s * 8192 + i * 32), "l"(POL_LAST) : "memory");
#pragma unroll
    for (int i = 0; i < NP; i++) {
        uint32_t a, b;
        if (MMA) {
            float t[4] = {0, 0, 0, 0};
            mma16(t, v[0][i].x, v[0][i].y, v[1][i].x, v[1][i].y, idm, idm); mma16(t, v[2][i].x, v[2][i].y, v[3][i].x, v[3][i].y, idm, idm);
            a = pack2(t[0], t[2]); b = pack2(t[1], t[3]);
        } else {
            a = pack2((blo(v[0][i].x) + blo(v[1][i].x)) + (blo(v[2][i].x) + blo(v[3][i].x)), (blo(v[0][i].y) + blo(v[1][i].y)) + (blo(v[2][i].y) + blo(v[3][i].y)));
            b = pack2((bhi(v[0][i].x) + bhi(v[1][i].x)) + (bhi(v[2][i].x) + bhi(v[3][i].x)), (bhi(v[0][i].y) + bhi(v[1][i].y)) + (bhi(v[2][i].y) + bhi(v[3][i].y)));
        }
        const uint32_t s0 = hadd2(a, r0[i]), s1 = hadd2(b, r1[i]);
        x[4 * i] = blo(s0); x[4 * i + 2] = bhi(s0); x[4 * i + 1] = blo(s1); x[4 * i + 3] = bhi(s1);
    }
}
__device__ __forceinline__ const uint2* pp_src(int e, int tile, int lane) { return (const uint2*)g_pp + e * 32768 + tile * 128 + (lane >> 3) * 8 + (lane & 3) * 2 + ((lane >> 2) & 1); }

__device__ __forceinline__ void fin_warp(const Params& p, uint32_t sb, int id) {
    const int tile = (id & ~1) + (threadIdx.x & 1), lane = (id & 1) * 16 + ((threadIdx.x & 31) >> 1);
    wait_cnt_warp(g_gate, lds32(sb + S_GATE));
#pragma unroll 1
    for (int e = 32; e < 64; e++) {
        wait_cnt_warp(cnt_ptr(C_PP + e * 8 + (id >> 3)), 4);
        const uint4* rp = g_x + ((128 + tile * 2) * XP + (e - 32) * 32 + lane);
        uint32_t o0[4], o1[4];
#pragma unroll
        for (int h = 0; h < 2; h++) {
            const uint4 r = ldcg128(rp + h * XP);
            const uint32_t a[2] = {r.x, r.y}, b[2] = {r.z, r.w};
            float x[8];
            sum_partials<2, false>(x, pp_src(e, tile, lane) + h * 64, a, b, 0);
#pragma unroll
            for (int i = 0; i < 2; i++) {
                o0[h * 2 + i] = __byte_perm(__float_as_uint(x[4 * i]), __float_as_uint(x[4 * i + 2]), 0x7632);
                o1[h * 2 + i] = __byte_perm(__float_as_uint(x[4 * i + 1]), __float_as_uint(x[4 * i + 3]), 0x7632);
            }
        }
        uint4* dst = (uint4*)p.out + ((e - 32) * 64 + lane * 2) * 64 + tile;
        dst[0] = make_uint4(o0[0], o0[1], o0[2], o0[3]); dst[64] = make_uint4(o1[0], o1[1], o1[2], o1[3]);
        PROF((threadIdx.x & 31) == 0, 1536 + e);
    }
}

constexpr int PROW = 272, UROW = 2304, UPRE = 256;
constexpr int C_UR = 0  , C_TB = 65536  , C_BG = C_TB + 51200,
              CB_M = 8960, CB_U = CB_M + 1792, CB_BIG = CB_U + 2560, C_ST = C_BG + 8 * CB_BIG  ;
static_assert(C_ST + 4736 <= B_BAR, "smem map");
enum { CB_TB = 0, CB_UF = 1  , CB_CF = 5  , CB_LD = 9   };
__device__ __forceinline__ void conv_init(uint32_t sb, bool spare) {
    const int i = threadIdx.x & 31;
    mbar_init(sb + B_BAR + i * 8, (i >= CB_UF && i < CB_CF && !spare) ? 2 : 1);
    if (i == CB_TB && !spare) mbar_expect(sb + B_BAR + i * 8, 51200);
    asm volatile("fence.mbarrier_init.release.cluster;" ::: "memory");
}
__device__ __forceinline__ void mma_q(float* c, const uint32_t* a, const uint4& q) {
    mma16(c, a[0], a[1], a[2], a[3], q.x, q.y); mma16(c, a[4], a[5], a[6], a[7], q.z, q.w);
}
__device__ __forceinline__ uint2 ld_acc(const uint2* p, bool on) {
    uint2 v = make_uint2(0, 0);
    asm volatile("{.reg .pred p; setp.ne.u32 p,%3,0; @p ld.global.cg.v2.u32 {%0,%1},[%2];}" : "+r"(v.x), "+r"(v.y) : "l"(p), "r"((uint32_t)on) : "memory");
    return v;
}
__device__ __forceinline__ void add_acc(float* c, uint2 v) { c[0] += blo(v.x); c[1] += bhi(v.x); c[2] += blo(v.y); c[3] += bhi(v.y); }
__device__ __forceinline__ void st_acc(uint2* p, const float* c) { *p = make_uint2(pack2(c[0], c[1]), pack2(c[2], c[3])); }
__device__ __forceinline__ float sum8(const uint4* v, int k) {
#define VK(i) __uint_as_float(k == 0 ? v[i].x : k == 1 ? v[i].y : k == 2 ? v[i].z : v[i].w)
    return ((VK(0) + VK(1)) + (VK(2) + VK(3))) + ((VK(4) + VK(5)) + (VK(6) + VK(7)));
}
template <int XW>
__device__ __forceinline__ void stats_send(uint32_t l16, const float* x, uint4* gs, int q, int w) {
    float s0 = 0, s1 = 0, m0 = 0, m1 = 0;
#pragma unroll
    for (int i = 0; i < 8; i++) { s0 += x[2 * i]; s1 += x[2 * i + 1]; m0 = fmaf(x[2 * i], x[2 * i], m0); m1 = fmaf(x[2 * i + 1], x[2 * i + 1], m1); }
    sts128(l16 + C_ST + w * 512, __float_as_uint(s0), __float_as_uint(m0), __float_as_uint(s1), __float_as_uint(m1));
    if (w == XW) {
        bar_sync(2, 256);
        uint4 v[8];
#pragma unroll
        for (int i = 0; i < 8; i++) v[i] = lds128(l16 + C_ST + i * 512);
        st_rlx128(gs + q * 32, __float_as_uint(sum8(v, 0)), __float_as_uint(sum8(v, 1)) & 0x7fffffffu, __float_as_uint(sum8(v, 2)), __float_as_uint(sum8(v, 3)));
    } else bar_arrive(2, 256);
}
template <int XW>
__device__ __forceinline__ float4 stats_recv(uint32_t l16, const uint4* gs, int w) {
    if (w == XW) {
        uint4 v[8];
        int n = 0;
        while (true) {
            uint32_t bad = 0;
#pragma unroll
            for (int i = 0; i < 8; i++) v[i] = ld_rlx128(gs + i * 32);
#pragma unroll
            for (int i = 0; i < 8; i++) bad |= v[i].y;
            if (!__any_sync(0xffffffffu, bad >> 31)) break;
            if (++n > 2000000) __trap();
        }
        const float s0 = sum8(v, 0) * (1.f / 512.f), s1 = sum8(v, 2) * (1.f / 512.f);
        const float2 l0 = ln_finish(s0, fmaxf(fmaf(sum8(v, 1), 1.f / 512.f, -s0 * s0), 0.f)), l1 = ln_finish(s1, fmaxf(fmaf(sum8(v, 3), 1.f / 512.f, -s1 * s1), 0.f));
        sts128(l16 + C_ST + 4096, __float_as_uint(l0.x), __float_as_uint(rcp(l0.y)), __float_as_uint(l1.x), __float_as_uint(rcp(l1.y)));
    }
    bar_sync(3, 256);
    const uint4 r = lds128(l16 + C_ST + 4096);
    return make_float4(__uint_as_float(r.x), __uint_as_float(r.y), __uint_as_float(r.z), __uint_as_float(r.w));
}

#define HOIST_STOP(k) asm volatile("{.reg .pred p; setp.eq.u32 p,%0,%1; @p nanosleep.u32 1;}" ::"r"(zero), "r"((k) + 1) : "memory")
__device__ __forceinline__ void conv_near(float (*acc)[4], uint32_t ta, uint32_t qa, uint32_t zero) {
#pragma unroll
    for (int k = 0; k < 8; k++) {
        uint32_t a[8];
#pragma unroll
        for (int j = 0; j < 8; j++) a[j] = lds32(ta + k * 800 + j * 32);
        mma_q(acc[k], a, ldsm4(qa + k * 1024));
        if (k % NFE == NFE - 1 && k < 7) HOIST_STOP(k);
    }
}
template <int K0>
__device__ __forceinline__ void conv_pair(float (*acc)[4], float (*pend)[4], uint32_t ta, uint32_t q0, uint32_t q1, uint32_t q2, uint32_t zero) {
#pragma unroll
    for (int i = 0; i < 4; i++) {
        const int k = K0 + i;
#pragma unroll
        for (int e = 0; e < 4; e++) { acc[4 - K0 + i][e] += pend[i][e]; pend[i][e] = 0; }
        uint32_t a[16];
#pragma unroll
        for (int j = 0; j < 16; j++) a[j] = lds32(ta + 256 + k * 800 + j * 32);
        const uint4 x1 = ldsm4(q1 + k * 1024);
        mma_q(acc[k], a, x1); mma_q(pend[i], a, ldsm4(q2 + k * 1024));
        mma_q(pend[i], a + 8, x1); mma_q(acc[k], a + 8, ldsm4(q0 + k * 1024));
        if (i % NFP == NFP - 1 && i < 3) HOIST_STOP(k);
    }
}

__device__ __forceinline__ void conv_tile(const Params& p, uint32_t sb, int q, int w) {
    const int lane = __shfl_sync(0xffffffffu, threadIdx.x & 31, threadIdx.x & 31), g = lane >> 2, c = lane & 3, tile = q * 8 + w;
    const uint32_t l16 = sb + lane * 16;
#pragma unroll
    for (int i = 0; i < 16; i++) sts128(l16 + C_UR + w * 8192 + i * 512, 0, 0, 0, 0);
    wait_cnt_warp(g_gate, lds32(sb + S_GATE));
    if (lane < 8) bulk_g2s(sb + C_TB + (w * 8 + lane) * 800, g_P + (tile * 8 + lane) * PROW + 72, 800, sb + B_BAR + CB_TB * 8, POL_N);
    uint32_t A[8][8];
#pragma unroll
    for (int k = 0; k < 8; k++)
#pragma unroll
        for (int j = 0; j < 8; j++) A[k][j] = __ldcg(g_P + (tile * 8 + k) * PROW + 16 + 8 * j + g - 2 * c);
    if (lane == 0) { const uint4 d = __ldg((const uint4*)p.Dskip + tile); sts128(sb + C_ST + 4608 + w * 16, d.x, d.y, d.z, d.w); }
    float acc[8][4], pend[4][4];
#pragma unroll
    for (int k = 0; k < 8; k++) acc[k][0] = acc[k][1] = acc[k][2] = acc[k][3] = pend[k & 3][k >> 2] = pend[k & 3][2 + (k >> 2)] = 0;
    const uint32_t row = sb + C_UR + w * 8192, ta = sb + C_TB + w * 6400 + (8 + g - 2 * c) * 4, zero = p.zero, qo = (lane & 7) * 16 - (lane >> 3) * 32;
    bar_sync(4, 384);
    mbar_wait(sb + B_BAR + CB_TB * 8, 0);
#pragma unroll 1
    for (int b = 0; b < 32; b++) {
        const int lz = lane + (b & p.zero);
        const uint4 r0 = ldcg128(g_x + (tile * 2 * XP + b * 32 + lz)), r1 = ldcg128(g_x + (tile * 2 * XP + b * 32 + lz) + XP);
        const uint32_t q1 = row + ((qo + (b - 1) * 128) & 1023);
        if (w == 0) conv_near(acc, ta, q1, zero);
        PROF(threadIdx.x == 0, 2048 + b * 8);
        const uint2* pps = pp_src(b, tile, lz);
        asm volatile("" : "+l"(pps));
        wait_flag_warp(cnt_ptr(C_PP + b * 8 + q), 4);
        PROF(threadIdx.x == 0, 2048 + b * 8 + 1);
        float x[16];
        {
            const uint32_t a[4] = {r0.x, r0.y, r1.x, r1.y}, bb[4] = {r0.z, r0.w, r1.z, r1.w};
            sum_partials<4, true>(x, pps, a, bb, (2 * (lz & 3) == lz >> 2) ? 0x00003f80u : (2 * (lz & 3) + 1 == lz >> 2) ? 0x3f800000u : 0u);
        }
        stats_send<0>(l16, x, g_st + b * 256 + lz, q, w);
        {
            PROF(threadIdx.x == 0, 2048 + b * 8 + 2);
            if (b) mbar_wait(sb + B_BAR + (CB_CF + (w >> 1)) * 8, (b - 1) & 1);
            const uint2* cb = g_carry + ((tile * 320 + b) * 32 + lz);
            uint2 cr[8];
#pragma unroll
            for (int k = 0; k < 8; k++) cr[k] = ld_acc(cb + k * 1280, b >= 4);
            if (w) conv_near(acc, ta, q1, zero);
#pragma unroll
            for (int k = 0; k < 8; k++) add_acc(acc[k], cr[k]);
        }
        float4 ln = stats_recv<0>(l16, g_st + b * 256 + lz, w);
        PROF(threadIdx.x == 0, 2048 + b * 8 + 3);
        uint32_t u[8];
#pragma unroll
        for (int k = 0; k < 8; k++) {
            u[k] = pack2(rbf(x[2 * k] - ln.x) * ln.y, rbf(x[2 * k + 1] - ln.z) * ln.w);
            sts32(row + k * 1024 + (b & 7) * 128 + lane * 4, u[k]);
        }
        __syncwarp();
        if (UFE && lane == 0) mbar_arrive(sb + B_BAR + (CB_UF + (w >> 1)) * 8);
        const uint32_t qa = row + ((qo + b * 128) & 1023);
#pragma unroll
        for (int k = 0; k < 8; k++) mma_q(acc[k], A[k], ldsm4(qa + k * 1024));
        const uint4 dk = lds128(sb + C_ST + 4608 + w * 16);
#pragma unroll
        for (int k = 0; k < 8; k++) {
            const float t = __shfl_sync(0xffffffffu, acc[k][3], (lz & ~3) | ((lz - 1) & 3));
            const uint32_t y = movm(pack2(acc[k][0] + (c ? t : 0.f), acc[k][1] + acc[k][2]));
            acc[k][0] = c ? 0.f : t; acc[k][1] = acc[k][2] = acc[k][3] = 0;
            const uint32_t dw = k >> 1 == 0 ? dk.x : k >> 1 == 1 ? dk.y : k >> 1 == 2 ? dk.z : dk.w;
            const uint32_t s = hadd2(hadd2(y, hmul2(u[k], __byte_perm(dw, 0, (k & 1) ? 0x3232 : 0x1010))), __byte_perm(__float_as_uint(x[2 * k]), __float_as_uint(x[2 * k + 1]), 0x7632));
            x[2 * k] = blo(s); x[2 * k + 1] = bhi(s);
        }
        if (!UFE && lane == 0) mbar_arrive(sb + B_BAR + (CB_UF + (w >> 1)) * 8);
        stats_send<1>(l16, x, g_st + (32 + b) * 256 + lz, q, w);
        {
            PROF(threadIdx.x == 0, 2048 + b * 8 + 4);
            uint4* dst = g_x + ((128 + tile * 2) * XP + b * 32 + lz);
#pragma unroll
            for (int e = 0; e < 2; e++) {
                const float* y = x + e * 8;
                dst[e * XP] = make_uint4(__byte_perm(__float_as_uint(y[0]), __float_as_uint(y[2]), 0x7632), __byte_perm(__float_as_uint(y[4]), __float_as_uint(y[6]), 0x7632),
                                           __byte_perm(__float_as_uint(y[1]), __float_as_uint(y[3]), 0x7632), __byte_perm(__float_as_uint(y[5]), __float_as_uint(y[7]), 0x7632));
            }
            uint32_t* du = g_u + (tile * 8 * (UROW / 2) + UPRE / 2 + b * 32 + lz);
#pragma unroll
            for (int k = 0; k < 8; k++) du[k * (UROW / 2)] = u[k];
        }
#pragma unroll 1
        for (int pass = 0; pass < 2; pass++) {
            if (pass == (w == 1)) {
                const uint32_t q0 = row + ((qo + (b - 2) * 128) & 1023);
                if (b & 1) conv_pair<4>(acc, pend, ta, q0, q1, qa, zero); else conv_pair<0>(acc, pend, ta, q0, q1, qa, zero);
            }
            if (pass) break;
            ln = stats_recv<1>(l16, g_st + (32 + b) * 256 + lz, w);
            PROF(threadIdx.x == 0, 2048 + b * 8 + 5);
            uint32_t o[2][4];
#pragma unroll
            for (int e = 0; e < 2; e++) {
                const float mu = e ? ln.z : ln.x, rs = e ? ln.w : ln.y;
#pragma unroll
                for (int i = 0; i < 4; i++) o[e][i] = pack2(rbf(x[4 * i + e] - mu) * rs, rbf(x[4 * i + 2 + e] - mu) * rs);
            }
#pragma unroll
            for (int i = 0; i < 4; i++) {
                const uint32_t t = __shfl_xor_sync(0xffffffffu, (lz & 1) ? o[0][i] : o[1][i], 1);
                if (lz & 1) o[0][i] = t; else o[1][i] = t;
            }
            uint4* dst = g_xn + ((32 + b) * 4096 + q * 512 + (lz >> 2) * 64 + w * 8 + (lz & 2) * 2 + (lz & 1));
            dst[0] = make_uint4(o[0][0], o[0][1], o[0][2], o[0][3]); dst[2] = make_uint4(o[1][0], o[1][1], o[1][2], o[1][3]);
            if (w == 7) {
                bar_sync(5, 256);
                if (elect()) red_release(cnt_ptr(C_XN + 32 + b), 2);
                PROF(lane == 0, 2048 + b * 8 + 6);
                __syncwarp();
            } else bar_arrive(5, 256);
        }
    }
}

template <int P0, bool TRI = false>
__device__ __forceinline__ void bg_half(float (*acc)[4], uint4* win, uint32_t ta, uint32_t qa, uint32_t mask, uint32_t row) {
#pragma unroll
    for (int i = 0; i < 4; i++) {
        win[P0 + i] = ldsm4(((qa + i * 128) & mask) + row);
        const uint4 a = lds128(ta + (3 - i) * 448), e = lds128(ta + (3 - i) * 448 + 224);
#pragma unroll
        for (int r = TRI ? 7 - P0 - i : 0; r < 8; r++) mma16(acc[r], a.x, a.y, a.z, a.w, win[(P0 + i + 1 + r) & 7].x, win[(P0 + i + 1 + r) & 7].y);
#pragma unroll
        for (int r = TRI ? 7 - P0 - i : 0; r < 8; r++) mma16(acc[r], e.x, e.y, e.z, e.w, win[(P0 + i + 1 + r) & 7].z, win[(P0 + i + 1 + r) & 7].w);
    }
}
__device__ __forceinline__ void bg_fetch(uint32_t sb, int q, int j, int n, int lane) {
    const int b0 = n >> 1, ch = q * 64 + j * 16 + (n & 1) * 8 + (b0 & 7), lo = max(b0 - 24, -4), nu = b0 > 4 ? (b0 - 4 - lo) * 128 : 0;
    const uint32_t bar = sb + B_BAR + (CB_LD + j * 2 + (n & 1)) * 8, buf = sb + C_BG + (j * 2 + (n & 1)) * CB_BIG;
    const int nt = min((b0 + 7) >> 2, 5) * 1792;
    if (elect()) {
        mbar_expect(bar, nt + nu + 1792);
        bulk_g2s(buf, g_W + ch * 784, nt, bar, POL_N);
        bulk_g2s(buf + CB_M, g_W + (ch ^ 4) * 784, 1792, bar, POL_N);
        if (nu) bulk_g2s(buf + CB_U + (lo - b0 + 24) * 128, g_u + ch * (UROW / 2) + UPRE / 2 + lo * 32, nu, bar, POL_N);
    }
    __syncwarp();
}
__device__ __forceinline__ void conv_back(uint32_t sb, int q, int j) {
    const int lane = __shfl_sync(0xffffffffu, threadIdx.x & 31, threadIdx.x & 31), g = lane >> 2, c = lane & 3;
    wait_cnt_warp(g_gate, lds32(sb + S_GATE));
    bg_fetch(sb, q, j, 2, lane);
    bar_sync(4, 384);
    const uint32_t to = (6 + g - 2 * c) * 16, qo = (lane & 7) * 16 - (lane >> 3) * 32;
#pragma unroll 1
    for (int n = 2; n < 64; n++) {
        const int b0 = n >> 1, i = n & 1, chl = j * 16 + i * 8 + (b0 & 7), hm = (b0 + 7) >> 2;
        const uint32_t buf = sb + C_BG + (j * 2 + i) * CB_BIG, ta = buf + to;
        float acc[8][4];
        uint4 win[8];
        if (n < 63) bg_fetch(sb, q, j, n + 1, lane);
        if (n == 34 || n == 42) wait_flag_warp(cnt_ptr(C_FAR + (n == 42)), 12);
        mbar_wait(sb + B_BAR + (CB_LD + j * 2 + i) * 8, (b0 - 1) & 1);
#pragma unroll
        for (int r = 0; r < 8; r++) {
            acc[r][0] = acc[r][1] = acc[r][2] = acc[r][3] = 0;
            win[r] = make_uint4(0, 0, 0, 0);
            if (r) asm volatile("{.reg .pred p; setp.ge.s32 p,%5,24; @p ldmatrix.sync.aligned.m8n8.x4.shared.b16 {%0,%1,%2,%3},[%4];}"
                                : "+r"(win[r].x), "+r"(win[r].y), "+r"(win[r].z), "+r"(win[r].w) : "r"(buf + CB_U + qo + r * 128), "r"(b0 + r) : "memory");
        }
        const uint2* fr = g_far + (((q * 64 + chl) * 8 + b0 - 24) * 32 + lane);
        uint2* cr = g_carry + (((q * 64 + chl) * 40 + b0) * 32 + lane);
        uint2* cm = g_carry + (((q * 64 + (chl ^ 4)) * 40 + b0) * 32 + lane);
        const uint32_t fm = 0xff000000u >> b0;
        uint2 pf[8], pm[4];
#pragma unroll
        for (int r = 0; r < 8; r++) pf[r] = ld_acc(fr + r * 32, (fm >> r) & 1);
#pragma unroll
        for (int r = 0; r < 4; r++) pm[r] = ld_acc(cm + r * 32, b0 > 4);
#pragma unroll 1
        for (int h = hm > 3 ? 5 : 3; h >= 3; h -= 2) {
            if (h <= hm) bg_half<0>(acc, win, ta + (h - 1) * 1792, qo + (28 - 4 * h) * 128, ~0u, buf + CB_U);
            if (h == 3 && i == 0) mbar_wait(sb + B_BAR + (CB_UF + j) * 8, (b0 - 1) & 1);
            bg_half<4>(acc, win, ta + (h - 2) * 1792, qo + (h == 3 ? b0 - 4 : 12) * 128, h == 3 ? 1023u : ~0u, h == 3 ? sb + C_UR + chl * 1024 : buf + CB_U);
        }
        uint4 wm[8];
#pragma unroll
        for (int r = 1; r < 8; r++) wm[r] = ldsm4(sb + C_UR + (chl ^ 4) * 1024 + ((qo + (b0 + r) * 128) & 1023));
#pragma unroll
        for (int r = 0; r < 8; r++) add_acc(acc[r], pf[r]);
#pragma unroll
        for (int r = 4; r < 8; r++) { st_acc(cr + r * 32, acc[r]); acc[r][0] = blo(pm[r - 4].x); acc[r][1] = bhi(pm[r - 4].x); acc[r][2] = blo(pm[r - 4].y); acc[r][3] = bhi(pm[r - 4].y); }
#pragma unroll
        for (int t = 7; t >= 0; t--) {
            const uint4 a = lds128(ta + t * 224), e = lds128(ta + CB_M + t * 224);
#pragma unroll
            for (int r = 0; r < 4; r++) { const uint4& x = win[4 + r - (t >> 1)]; mma16(acc[r], a.x, a.y, a.z, a.w, (t & 1) ? x.z : x.x, (t & 1) ? x.w : x.y); }
#pragma unroll
            for (int r = 0; r < 4; r++) { const uint4& x = wm[4 + r - (t >> 1)]; mma16(acc[4 + r], e.x, e.y, e.z, e.w, (t & 1) ? x.z : x.x, (t & 1) ? x.w : x.y); }
        }
#pragma unroll
        for (int r = 0; r < 4; r++) { st_acc(cr + r * 32, acc[r]); st_acc(cm + r * 32, acc[4 + r]); }
        __syncwarp();
        if (lane == 0 && i) mbar_arrive(sb + B_BAR + (CB_CF + j) * 8);
        PROF(j == 0 && lane == 0 && i, 2048 + b0 * 8 + 7);
    }
}
__device__ __forceinline__ void conv_far(uint32_t sb, int w) {
    const int lane = __shfl_sync(0xffffffffu, threadIdx.x & 31, threadIdx.x & 31), g = lane >> 2, c = lane & 3;
    wait_cnt_warp(g_gate, lds32(sb + S_GATE));
    wait_cnt_warp(cnt_ptr(C_XN + 39), 16);
    const uint32_t to = (6 + g - 2 * c) * 16, qo = (lane & 7) * 16 - (lane >> 3) * 32;
#pragma unroll 1
    for (int n = -1; n * 12 + w < 512; n++) {
        const int t = n * 12 + w, ch = (t & 63) * 8 + (((t >> 6) + 1) & 7), cn = ((t + 12) & 63) * 8 + ((((t + 12) >> 6) + 1) & 7);
        const uint32_t bar = sb + B_BAR + (w * 2 + (n & 1)) * 8, buf = sb + (w * 2 + (n & 1)) * 5120;
        if (t + 12 < 512 && elect()) {
            const uint32_t nb = sb + (w * 2 + (~n & 1)) * 5120;
            mbar_expect(bar ^ 8, 3584 + 1152);
            bulk_g2s(nb, g_W + cn * 784 + 560, 3584, bar ^ 8, POL_N);
            bulk_g2s(nb + 3584, g_u + cn * (UROW / 2) + UPRE / 2 - 32, 1152, bar ^ 8, POL_N);
        }
        __syncwarp();
        if (n < 0) continue;
        float acc[8][4];
        uint4 win[8];
#pragma unroll
        for (int r = 0; r < 8; r++) { acc[r][0] = acc[r][1] = acc[r][2] = acc[r][3] = 0; win[r] = make_uint4(0, 0, 0, 0); }
        mbar_wait(bar, (n >> 1) & 1);
        bg_half<0, true>(acc, win, buf + to + 1792, qo + 128, ~0u, buf + 3584);
        bg_half<4, true>(acc, win, buf + to, qo + 640, ~0u, buf + 3584);
#pragma unroll
        for (int r = 0; r < 8; r++) st_acc(g_far + (ch * 256 + lane) + r * 32, acc[r]);
        __syncwarp();
        if (((t + 12) ^ t) >= 256 && elect()) red_release(cnt_ptr(C_FAR + (t >> 8)), 1);
        __syncwarp();
    }
    PROF(threadIdx.x == 0, 2048);
}

constexpr int P_X = 131072  , P_K6 = P_X + 32768  , P_P = P_K6 + 10496  , P_U = P_P + 33280  ,
              P_END = P_U + 17408, P_PRM = P_P + 8192  , P_Y = P_P  ;
static_assert(P_END <= B_BAR && P_END <= R_SEL, "prologue scratch");
#define KGUN 2
constexpr int KGU = KGUN;
__device__ __forceinline__ void csq(float& r, float& i) { const float t = r * i; r = fmaf(r, r, -(i * i)); i = t + t; }
__device__ __forceinline__ void cpow(float ar, float ph, float p, float& r, float& i) {
    const float e = ex2(ar * p);
    const float u = ph * p, n = fabsf(u) < 4194304.f ? (u + 12582912.f) - 12582912.f : u;
    const float t = (u - n) * 6.283185307179586f;
    r = e * __cosf(t); i = e * __sinf(t);
}
__device__ __forceinline__ void mma_tf32(float* c, float a0, float a1, float a2, float a3, float b0, float b1) {
    asm volatile("mma.sync.aligned.m16n8k8.row.col.f32.tf32.tf32.f32 {%0,%1,%2,%3},{%4,%5,%6,%7},{%8,%9},{%0,%1,%2,%3};"
                 : "+f"(c[0]), "+f"(c[1]), "+f"(c[2]), "+f"(c[3])
                 : "r"(__float_as_uint(a0)), "r"(__float_as_uint(a1)), "r"(__float_as_uint(a2)), "r"(__float_as_uint(a3)), "r"(__float_as_uint(b0)), "r"(__float_as_uint(b1)));
}

__device__ __forceinline__ void early_fetch(const Params& p, uint32_t sb) {
    const int v = blockIdx.x;
    if (elect()) {
        if (v >= V_QKV) { if (v < V_QKV + NQ && (p.roles & 8)) qkv_fetch(p, sb, v - V_QKV, 0, Q_PRE); }
        else if (v >= V_OP) { if (p.roles & 4) op_fetch(p, sb, v - V_OP, 0); }
        else if (v >= V_REC && (p.roles & 2)) { rec_fetch(p, sb, (v - V_REC) >> 1, v & 1, 0, R_STQ); rec_fetch(p, sb, (v - V_REC) >> 1, v & 1, 2, R_STV); }
    }
    __syncwarp();
}
struct ProRegs { uint32_t v[2][4], ldt[2]; };
__device__ __forceinline__ void prologue_load(const ProArgs& a, int b, ProRegs& pr) {
    const int w = threadIdx.x >> 5;
#pragma unroll
    for (int i = 0; i < 2; i++) {
        const int gi = b * 512 + (w & 3) * 128 + ((w >> 2) & 1) * 64 + i * 32 + (threadIdx.x & 31);
        pr.ldt[i] = __ldg((const uint16_t*)a.ldt + b * 4 + (w & 3));
        pr.v[i][0] = __ldg((const uint16_t*)a.lAr + gi); pr.v[i][1] = __ldg((const uint16_t*)a.Ai + gi);
        pr.v[i][2] = __ldg((const uint16_t*)a.Cr + gi); pr.v[i][3] = __ldg((const uint16_t*)a.Ci + gi);
    }
}
__device__ __forceinline__ void prologue(const Params& p, uint32_t sb, int b, int w, const ProRegs& pr) {
    const ProArgs& a = p.pa;
    const int tid = threadIdx.x, lane = tid & 31, g = lane >> 2, c = lane & 3;
    const int d0 = b * 4;
    if (w >= 8) {
        const int t2 = tid - 256;
        if (w < 10) {
            const int row = b * 16 + (w - 8) * 8 + g;
            uint4 v[16];
            const float2 r = row_stats512(v, (const uint4*)(a.x + (size_t)row * 512) + c, 8, 4);
            const float2 l = ln_finish(r.x * (1.f / 512.f), r.y * (1.f / 512.f));
            if (c == (g >> 1)) asm volatile("st.relaxed.gpu.global.u32 [%0],%1;" ::"l"(g_ln0 + row), "r"(pack2(l.x, l.y)) : "memory");
        }
        else if (b + 4 >= V_REC && b + 4 < V_OP) rec_slots(b + 4 - V_REC, w - 10);
        PROF(t2 == 0, 3516);
        const int gi = b * 128 + t2;
        g_st[gi] = make_uint4(~0u, ~0u, ~0u, ~0u);
        if (gi < 900 * 8) g_cnt[gi] = 0;
        bar_sync(6, 384);
        if (lane < 4 && ((PFM >> (w - 8)) & 1)) asm volatile("cp.async.bulk.prefetch.L2.global [%0],%1;" ::"l"(a.W[w - 8] + (b * 4 + lane) * 4096), "r"(8192) : "memory");
        bar_sync(9, 384);
        if (w == 10) early_fetch(p, sb);
#pragma unroll 2
        for (int i = t2; i < 4 * 784; i += 128) {
            const int ch = i / 784, k = i - ch * 784;
            const uint32_t o = sb + P_P + (ch * 2080 + 266 + (k / 14) * 18 + k) * 4;
            g_W[d0 * 784 + i] = make_uint4(lds32(o), lds32(o + 32), lds32(o + 64), lds32(o + 96));
        }
        bar_arrive(10, 384);
        PROF(t2 == 0, 3517);
        return;
    }
#pragma unroll
    for (int i = 0; i < 2; i++) {
        const float dt = rbf(expf(blo(pr.ldt[i])));
        const float ar = -rbf(expf(blo(pr.v[i][0]))) * dt, ai = blo(pr.v[i][1]) * dt;
        sts128(sb + P_PRM + (w * 64 + i * 32 + lane) * 16, __float_as_uint(ar * 1.4426950408889634f), __float_as_uint(ai * 0.15915494309189535f),
               __float_as_uint(2.f * (blo(pr.v[i][2]) * dt)), __float_as_uint(2.f * (blo(pr.v[i][3]) * dt)));
    }
    if (tid < 64) sts128(sb + P_U + (tid >> 3) * 2176 + (tid & 7) * 16, 0, 0, 0, 0);
    bar_arrive(6, 384);
    __syncwarp();
    PROF(tid == 0, 3510);
    const int ch = w & 3, hf = w >> 2;
    {
        float k0[4] = {0, 0, 0, 0}, k1[4] = {0, 0, 0, 0}, k2[4] = {0, 0, 0, 0}, k3[4] = {0, 0, 0, 0}, k4[4] = {0, 0, 0, 0}, kl = 0;
#pragma unroll KGU
        for (int j = 0; j < 16; j++) {
            const uint4 q = lds128(sb + P_PRM + (w * 64 + j * 4 + c) * 16);
            const float cr = __uint_as_float(q.z), ci = __uint_as_float(q.w);
            float wr[4], wi[4], vr[4], vi[4];
            cpow(__uint_as_float(q.x), __uint_as_float(q.y), (float)g, wr[0], wi[0]);
            cpow(__uint_as_float(q.x), __uint_as_float(q.y), (float)(g + 8), vr[0], vi[0]);
#pragma unroll
            for (int i = 1; i < 4; i++) { wr[i] = wr[i - 1]; wi[i] = wi[i - 1]; csq(wr[i], wi[i]); vr[i] = vr[i - 1]; vi[i] = vi[i - 1]; csq(vr[i], vi[i]); }
            float hr = wr[3], hi = wi[3];
            csq(hr, hi);
            mma_tf32(k0, wr[0], vr[0], wi[0], vi[0], cr * hr - ci * hi, -(cr * hi + ci * hr));
            hr = vr[3]; hi = vi[3]; csq(hr, hi);
            mma_tf32(k1, wr[0], vr[0], wi[0], vi[0], cr * hr - ci * hi, -(cr * hi + ci * hr));
            csq(hr, hi);
            mma_tf32(k2, wr[1], vr[1], wi[1], vi[1], cr * hr - ci * hi, -(cr * hi + ci * hr));
            csq(hr, hi);
            mma_tf32(k3, wr[2], vr[2], wi[2], vi[2], cr * hr - ci * hi, -(cr * hi + ci * hr));
            csq(hr, hi);
            mma_tf32(k4, wr[3], vr[3], wi[3], vi[3], cr * hr - ci * hi, -(cr * hi + ci * hr));
            csq(hr, hi);
            kl += cr * hr - ci * hi;
        }
        kl += __shfl_xor_sync(0xffffffffu, kl, 1); kl += __shfl_xor_sync(0xffffffffu, kl, 2);
        const uint32_t o = sb + P_K6 + (ch * 656 + c * 32 + g) * 4, ol = sb + P_K6 + (ch * 656 + 640) * 4;
#define KST(k, base) sts32(o + (base) * 4, __float_as_uint(k[0])); sts32(o + (base) * 4 + 64, __float_as_uint(k[1])); \
                     sts32(o + (base) * 4 + 32, __float_as_uint(k[2])); sts32(o + (base) * 4 + 96, __float_as_uint(k[3]))
#define KAD(k, base) k[0] += __uint_as_float(lds32(o + (base) * 4)); k[1] += __uint_as_float(lds32(o + (base) * 4 + 64)); \
                     k[2] += __uint_as_float(lds32(o + (base) * 4 + 32)); k[3] += __uint_as_float(lds32(o + (base) * 4 + 96))
        if (hf == 0) {
            bar_sync(2 + ch, 64);
            KAD(k0, 0); KAD(k1, 128); KAD(k2, 256); KAD(k3, 384); KAD(k4, 512);
            kl += __uint_as_float(lds32(ol));
            __syncwarp();
        }
        KST(k0, 0); KST(k1, 128); KST(k2, 256); KST(k3, 384); KST(k4, 512);
        if (lane == 0) sts32(ol, __float_as_uint(kl));
        if (hf == 1) { __syncwarp(); bar_arrive(2 + ch, 64); }
    }
    PROF(tid == 0, 3511);
    {
        uint4 l0, l1;
        int n = 0;
        while (true) {
            l0 = ld_rlx128((const uint4*)g_ln0 + tid * 2); l1 = ld_rlx128((const uint4*)g_ln0 + tid * 2 + 1);
            if (__all_sync(0xffffffffu, l0.x && l0.y && l0.z && l0.w && l1.x && l1.y && l1.z && l1.w)) break;
            if (++n > 2000000) __trap();
        }
        sts128(sb + P_P + tid * 32, l0.x, l0.y, l0.z, l0.w); sts128(sb + P_P + tid * 32 + 16, l1.x, l1.y, l1.z, l1.w);
        bar_sync(8, 384);
        mbar_wait(sb + S_XBAR, 0);
        __syncwarp();
#pragma unroll 2
        for (int i = 0; i < 8; i++) {
            const int t = w * 256 + i * 32 + lane;
            const uint32_t ln = lds32(sb + P_P + t * 4);
            const uint2 x = lds64(sb + P_X + t * 16 + (b & 1) * 8);
            const float m = blo(ln), rs = rcp(bhi(ln));
            const uint32_t u0 = pack2(rbf(blo(x.x) - m) * rs, rbf(bhi(x.x) - m) * rs), u1 = pack2(rbf(blo(x.y) - m) * rs, rbf(bhi(x.y) - m) * rs);
            sts128(sb + P_X + t * 16, x.x, x.y, u0, u1);
            const uint32_t o = sb + P_U + ((t >> 3) & 1) * 2176 + ((t >> 4) + 8) * 16 + (t & 7) * 2;
            asm volatile("st.shared.u16 [%0],%1;" ::"r"(o), "h"((uint16_t)u0) : "memory");
            asm volatile("st.shared.u16 [%0],%1;" ::"r"(o + 4352), "h"((uint16_t)(u0 >> 16)) : "memory");
            asm volatile("st.shared.u16 [%0],%1;" ::"r"(o + 8704), "h"((uint16_t)u1) : "memory");
            asm volatile("st.shared.u16 [%0],%1;" ::"r"(o + 13056), "h"((uint16_t)(u1 >> 16)) : "memory");
        }
    }
    bar_sync(1, 256);
    PROF(tid == 0, 3512);
    if (tid < 64) sts32(sb + P_P + ((tid >> 4) * 2080 + (tid & 15)) * 4, 0);
#pragma unroll 1
    for (int x = tid; x < 2048; x += 512) {
        uint32_t pw[2][4];
#pragma unroll
        for (int h = 0; h < 2; h++) {
            const int y = x + h * 256;
            const int i0 = y <= 256 ? y : 256 + (int)((pack2((float)y, 0.f) & 0xffff) - 0x4380);
            const int i1 = y <= 256 ? max(y - 1, 0) : 256 + (int)((pack2((float)(y - 1), 0.f) & 0xffff) - 0x4380);
#pragma unroll
            for (int k = 0; k < 4; k++) {
                const float lo = __uint_as_float(lds32(sb + P_K6 + k * 2624 + i0 * 4)), hi = __uint_as_float(lds32(sb + P_K6 + k * 2624 + i1 * 4));
                pw[h][k] = pack2(lo, y ? hi : 0.f);
            }
        }
#pragma unroll
        for (int h = 0; h < 2; h++)
#pragma unroll
            for (int k = 0; k < 4; k++) sts32(sb + P_P + (k * 2080 + x + h * 256 + 16) * 4, pw[h][k]);
    }
    fence_async_smem();
    bar_arrive(9, 384);
    bar_sync(1, 256);
    if (tid < 4) {
        asm volatile("cp.async.bulk.global.shared::cta.bulk_group [%0],[%1],%2;" ::"l"(g_P + (d0 + tid) * PROW), "r"(sb + P_P + tid * 8320), "r"(PROW * 4) : "memory");
        asm volatile("cp.async.bulk.commit_group;" ::: "memory");
    }
    __syncwarp();
    PROF(tid == 0, 3513);
    {
        float acc[16][4];
#pragma unroll
        for (int j = 0; j < 16; j++) acc[j][0] = acc[j][1] = acc[j][2] = acc[j][3] = 0;
#pragma unroll 1
        for (int e = hf * 4; e < hf * 4 + 4; e++) {
            uint32_t B[16][2];
            const uint32_t ua = sb + P_U + ch * 4352 + ((lane >> 3) & 1) * 2176 + (8 + (lane >> 4) * 8 + (lane & 7) - e) * 16;
#pragma unroll
            for (int j = 0; j < 8; j++) { const uint4 v = ldsm4(ua + j * 256); B[2 * j][0] = v.x; B[2 * j][1] = v.y; B[2 * j + 1][0] = v.z; B[2 * j + 1][1] = v.w; }
            const uint32_t pa = sb + P_P + (ch * 2080 + 16 + e * 16 + g - 2 * c) * 4;
#pragma unroll
            for (int d = 0; d < 16; d++) {
                const uint32_t a0 = lds32(pa + d * 512), a1 = lds32(pa + d * 512 + 32), a2 = lds32(pa + d * 512 - 32);
#pragma unroll
                for (int j = d; j < 16; j++) mma16(acc[j], a0, a1, a2, a0, B[j - d][0], B[j - d][1]);
            }
        }
        PROF(tid == 0, 3514);
        const uint32_t o = sb + P_Y + (ch * 2560 + c * 40 + g) * 4;
        if (tid < 4) asm volatile("cp.async.bulk.wait_group 0;" ::: "memory");
        __syncwarp();
        bar_sync(10, 384);
        if (hf == 0) {
            bar_sync(2 + ch, 64);
#pragma unroll
            for (int j = 0; j < 16; j++) {
                acc[j][0] += __uint_as_float(lds32(o + j * 640)); acc[j][1] += __uint_as_float(lds32(o + j * 640 + 80));
                acc[j][2] += __uint_as_float(lds32(o + j * 640 + 32)); acc[j][3] += __uint_as_float(lds32(o + j * 640 + 112));
            }
        }
#pragma unroll
        for (int j = 0; j < 16; j++) {
            sts32(o + j * 640, __float_as_uint(acc[j][0])); sts32(o + j * 640 + 80, __float_as_uint(acc[j][1]));
            sts32(o + j * 640 + 32, __float_as_uint(acc[j][2])); sts32(o + j * 640 + 112, __float_as_uint(acc[j][3]));
        }
        if (hf == 1) bar_arrive(2 + ch, 64);
    }
    const uint2 dk = __ldg((const uint2*)(a.Dk + d0));
    bar_sync(1, 256);
#pragma unroll 2
    for (int i = 0; i < 8; i++) {
        const int t = i * 256 + tid;
        const uint32_t o = sb + P_Y + (t + 4 * (t >> 4)) * 4;
        const uint4 xu = lds128(sb + P_X + t * 16);
        float y[4];
#pragma unroll
        for (int k = 0; k < 4; k++) y[k] = rbf(__uint_as_float(lds32(o + k * 10240)));
        uint2 r;
        r.x = pack2(blo(xu.x) + rbf(y[0] + rbf(blo(xu.z) * blo(dk.x))), bhi(xu.x) + rbf(y[1] + rbf(bhi(xu.z) * bhi(dk.x))));
        r.y = pack2(blo(xu.y) + rbf(y[2] + rbf(blo(xu.w) * blo(dk.y))), bhi(xu.y) + rbf(y[3] + rbf(bhi(xu.w) * bhi(dk.y))));
        ((uint2*)g_x)[b * 2 * XP + t] = r;
    }
    PROF(tid == 0, 3515);
}

__global__ void __cluster_dims__(2, 1, 1) __launch_bounds__(384, 1) main_kernel(const __grid_constant__ Params p) {
    extern __shared__ __align__(1024) uint8_t smem[];
    const uint32_t sb = smem_u32(smem);
    uint32_t rank; asm("mov.u32 %0,%%cluster_ctarank;" : "=r"(rank));
    const int wi = __shfl_sync(0xffffffffu, threadIdx.x >> 5, 0);
    const int v = blockIdx.x, cl = v >> 1, wg = wi >> 2;
    PROF(threadIdx.x == 0, 3500);
    ProRegs pr;
    prologue_load(p.pa, max((int)blockIdx.x - 4, 0), pr);
    if (wi == 11 && p.dopro && cl >= 2 && elect()) {
        mbar_init(sb + S_XBAR, 1);
        asm volatile("fence.mbarrier_init.release.cluster;" ::: "memory");
        mbar_expect(sb + S_XBAR, 32768);
        for (int j = 0; j < 8; j++) tma2d(sb + P_X + j * 4096, &p.tm[3], ((blockIdx.x - 4) >> 1) * 8, j * 256, sb + S_XBAR);
    }
    if (threadIdx.x == 320) {
        unsigned v = 0;
        if (p.dopro) {
            asm volatile("ld.relaxed.gpu.global.u32 %0,[%1];" : "=r"(v) : "l"(g_gate) : "memory");
            v = (v / (4 * NCL) + 1) * (4 * NCL);
        }
        sts32(sb + S_GATE, v);
    }
    __syncwarp();
    if (wi == 10) {
        if (v < V_REC || v == 131) conv_init(sb, v == 131); else if (v < V_OP) rec_init(sb); else gemm_init(sb, v < V_QKV);
        __syncwarp();
    }
    if (wg == 2) bar_arrive(8, 384);
    asm volatile("barrier.cluster.arrive.relaxed.aligned;" ::: "memory");
    if (p.dopro && cl >= 2) prologue(p, sb, blockIdx.x - 4, wi, pr); else if (wg < 2) bar_sync(8, 384); else if (wi == 10) early_fetch(p, sb);
    asm volatile("barrier.cluster.wait.aligned;" ::: "memory");
    const int role = (v < V_REC ? 1 : v < V_OP ? 2 : v < V_QKV ? 4 : v < V_QKV + NQ ? 24 : 1) & p.roles;
    fence_async_smem();
    bar_sync(wg == 2 ? 7 : 1, wg == 2 ? 128 : 256);
    if (p.dopro && (threadIdx.x == 32 || threadIdx.x == 352)) red_release(g_gate, 1);
    PROF(threadIdx.x == 32, 3509);
    if (wi == 0 && (role & 8) && elect()) qkv_stage(p, sb + 131072, sb + G_BAR + GB_RS * 8, v - V_QKV, 0, 6);
    PROF(threadIdx.x == 0, 3506);
    __syncwarp();
    if (p.dopro && v >= V_REC && v < V_QKV && (v < V_OP ? wi == 8 : wi < 8)) {
        bool on = v >= V_OP;
#pragma unroll 1
        for (int r = on ? 64 + (v - V_OP) * 8 + wi : v - V_REC; r < 512;) {
            if (on) wait_flag_warp(g_gate, lds32(sb + S_GATE));
            PROF(threadIdx.x == 256 && on, 3507);
            x1_norm(on ? (const uint2*)g_x : (const uint2*)p.pa.W[0], r, on);
            __syncwarp();
            if (on && elect()) red_release(cnt_ptr(C_XN + (r >> 4)), 1);
            __syncwarp();
            PROF(threadIdx.x == 256, on ? 3508 : 3499);
            if (on) r += v < V_OP ? 512 : 128;
            on = true;
        }
    }
    if (role == 2) {
        const int head = (v - V_REC) >> 1;
        if (wi == 0 && elect()) rec_fetch(p, sb, head, rank, 1, R_STK);
        __syncwarp();
        if (wg == 2) {
            reg_dec<RH>();
            const int w = wi & 3;
            wait_cnt_warp(g_gate, lds32(sb + S_GATE));
            if (w < 2) { const uint32_t x = __ldcg(g_sel + (threadIdx.x & 63)); sts32(sb + R_SEL + (threadIdx.x & 63) * 4, (x | x >> 16) & 15); }
            __syncthreads();
            cluster_sync();
            if ((p.chains >> (w & 1)) & 1) { if (w < 2) rec_comm(p, sb, w, head, rank); else rec_attn(p, sb, w & 1, head, rank); }
        } else {
            reg_inc<RW0>();
            rec_weights(p, sb, head, rank, wi);
        }
    } else if (role == 1) {
        if (v == 131) conv_far(sb, wi); else if (wg == 2) { reg_dec<RCB>(); conv_back(sb, v, wi & 3); } else { reg_inc<RCU>(); conv_tile(p, sb, v, wi); }
    } else if (role == 4) {
        if (wg == 2) {
            reg_dec<40>();
            if (wi == 8) gemm_producer<true>(p, sb, v - V_OP); else if (wi < 11) gemm_release<true>(p, sb, v - V_OP, wi - 9);
        } else { reg_inc<232>(); gemm_consumer<true>(p, sb, v - V_OP, wi); }
    } else if (role) {
        if (wg == 2) {
            reg_dec<40>();
            if (wi < 10) {
                if (role & 8) { if (wi == 8) gemm_producer<false>(p, sb, v - V_QKV); else gemm_release<false>(p, sb, v - V_QKV, 0); }
            } else if (v < V_QKV + 32 && (role & 16)) fin_warp(p, sb, (v - V_QKV) * 2 + wi - 10);
        } else { reg_inc<232>(); if (role & 8) gemm_consumer<false>(p, sb, v - V_QKV, wi); }
    }
    __syncwarp();
    cluster_sync();
}

typedef CUresult (*EncFn)(CUtensorMap*, CUtensorMapDataType, cuuint32_t, void*, const cuuint64_t*, const cuuint64_t*, const cuuint32_t*, const cuuint32_t*,
                          CUtensorMapInterleave, CUtensorMapSwizzle, CUtensorMapL2promotion, CUtensorMapFloatOOBfill);
constexpr int SMEM_BYTES = 232448;
#define LAG 9
#define QLEAD 6
#define OLEAD (LAG / 2 + 2)
void plan(Params& P) {
    P.roles = 31; P.chains = 3; P.lag = LAG; P.dopro = 1;
    for (int r = 0; r < 2; r++) {
        const int lead = r ? OLEAD : QLEAD;
        int n = 0;
        for (int i = 0; i < 32 + lead; i++) {
            if (i >= lead) P.list[r][n++] = 32 + i - lead;
            if (i < 32) P.list[r][n++] = i;
        }
        P.nl[r] = n;
    }
}

#define TK() do {} while (0)
}

extern "C" void kernel_launch(void* const* d_in, const int* in_sizes, int n_in, void* d_out, int out_size) {
    typedef const __nv_bfloat16* BP;
    static EncFn enc = nullptr;
    if (!enc) {
        void* fn = nullptr; cudaDriverEntryPointQueryResult qr;
        cudaGetDriverEntryPoint("cuTensorMapEncodeTiled", &fn, cudaEnableDefault, &qr);
        enc = (EncFn)fn;
        cudaFuncSetAttribute(main_kernel, cudaFuncAttributeMaxDynamicSharedMemorySize, SMEM_BYTES);
    }
    static Params P;
    for (int i = 0; i < 4; i++) {
        const cuuint64_t cols = i < 3 ? 4096 : 512, rows = i < 3 ? 512 : 4096;
        cuuint64_t d2[2] = {cols, rows}, str[1] = {cols * 2};
        cuuint32_t box[2] = {64, 64}, bn[2] = {16, 256}, es[2] = {1, 1};
        enc(&P.tm[i < 3 ? i : 4], CU_TENSOR_MAP_DATA_TYPE_BFLOAT16, 2, d_in[9 + i], d2, str, box, es, CU_TENSOR_MAP_INTERLEAVE_NONE, CU_TENSOR_MAP_SWIZZLE_128B,
            CU_TENSOR_MAP_L2_PROMOTION_L2_128B, CU_TENSOR_MAP_FLOAT_OOB_FILL_NONE);
        if (i < 2) enc(&P.tn[i], CU_TENSOR_MAP_DATA_TYPE_BFLOAT16, 2, d_in[9 + i], d2, str, bn, es, CU_TENSOR_MAP_INTERLEAVE_NONE, CU_TENSOR_MAP_SWIZZLE_32B,
                       CU_TENSOR_MAP_L2_PROMOTION_L2_128B, CU_TENSOR_MAP_FLOAT_OOB_FILL_NONE);
    }
    {
        cuuint64_t dims[2] = {512, 2048}, str[1] = {1024};
        cuuint32_t box[2] = {8, 256}, es[2] = {1, 1};
        enc(&P.tm[3], CU_TENSOR_MAP_DATA_TYPE_BFLOAT16, 2, d_in[0], dims, str, box, es, CU_TENSOR_MAP_INTERLEAVE_NONE, CU_TENSOR_MAP_SWIZZLE_NONE,
            CU_TENSOR_MAP_L2_PROMOTION_NONE, CU_TENSOR_MAP_FLOAT_OOB_FILL_NONE);
    }
    P.mem0 = (BP)d_in[8]; P.Wo = (BP)d_in[12]; P.Dskip = (BP)d_in[6]; P.out = (__nv_bfloat16*)d_out;
    cudaStream_t s = cudaStreamPerThread;
    P.pa = {(BP)d_in[0], (BP)d_in[1], (BP)d_in[2], (BP)d_in[3], (BP)d_in[4], (BP)d_in[5], (BP)d_in[6], {(BP)d_in[9], (BP)d_in[10], (BP)d_in[11], (BP)d_in[12]}};
    plan(P);
    TK(); main_kernel<<<2 * NCL, 384, SMEM_BYTES, s>>>(P); TK();
}
```

```cpp
#include <cuda_runtime.h>
#include <cuda_bf16.h>
#include <cuda.h>
#include <stdint.h>
#include <string.h>
#include <math.h>

namespace {

constexpr int NCL = 66;
constexpr int NQ = 43;
constexpr int V_REC = 8, V_OP = 72, V_QKV = 88;

#define XP 1024
__device__ uint4 g_x[2 * 128 * XP];
__device__ uint4 g_xn[64 * 4096];
__device__ uint4 g_st[68 * 256];
__device__ uint4 g_qkv[128 * 32 * 1536];
__device__ uint4 g_o[64 * 64 * 512];
__device__ uint4 g_pp[64 * 4 * 4096];
__device__ uint4 g_xch[133 * 512];
__device__ unsigned g_sel[64];
__device__ unsigned g_gate[32];
__device__ __align__(16) uint32_t g_P[512 * 272];
__device__ uint4 g_W[512 * 784];
__device__ __align__(16) uint32_t g_u[512 * 1152];
__device__ uint2 g_carry[512 * 40 * 32];
__device__ uint2 g_far[512 * 8 * 32];
__device__ unsigned g_cnt[900 * 8];
__device__ uint32_t g_ln0[2048];

enum { C_XN = 0  , C_QKV = 64  , C_O = 128  , C_PP = 384  , C_FAR = 896 };
__device__ __forceinline__ unsigned* cnt_ptr(int i) { return g_cnt + i * 8; }

struct ProArgs { const __nv_bfloat16 *x, *lAr, *Ai, *Cr, *Ci, *ldt, *Dk, *W[4]; };
struct Params {
    CUtensorMap tm[5];
    CUtensorMap tn[2];
    ProArgs pa;
    int dopro;
    const __nv_bfloat16* mem0;
    const __nv_bfloat16* Wo;
    const __nv_bfloat16* Dskip;
    __nv_bfloat16* out;
    int roles;
    int chains;
    int lag;
    int zero;
    int nl[2];
    uint8_t list[2][64];
};

__device__ __forceinline__ uint32_t smem_u32(const void* p) { return (uint32_t)__cvta_generic_to_shared(p); }
__device__ __forceinline__ uint32_t mapa(uint32_t a, uint32_t r) {
    uint32_t o; asm("mapa.shared::cluster.u32 %0,%1,%2;" : "=r"(o) : "r"(a), "r"(r)); return o;
}
__device__ __forceinline__ void mbar_init(uint32_t b, int c) { asm volatile("mbarrier.init.shared::cta.b64 [%0],%1;" ::"r"(b), "r"(c) : "memory"); }
__device__ __forceinline__ void mbar_expect(uint32_t b, int bytes) { asm volatile("mbarrier.arrive.expect_tx.shared::cta.b64 _,[%0],%1;" ::"r"(b), "r"(bytes) : "memory"); }
__device__ __forceinline__ void mbar_arrive(uint32_t b) { asm volatile("mbarrier.arrive.shared::cta.b64 _,[%0];" ::"r"(b) : "memory"); }
__device__ __forceinline__ void mbar_arrive_cluster(uint32_t b) { asm volatile("mbarrier.arrive.shared::cluster.b64 _,[%0];" ::"r"(b) : "memory"); }
__device__ __forceinline__ void mbar_wait(uint32_t b, uint32_t ph) {
    asm volatile(
        "{.reg .pred p; .reg .u32 n; mov.u32 n,0;\n"
        "W%=: mbarrier.try_wait.parity.shared::cta.b64 p,[%0],%1;\n"
        "@p bra D%=;\n"
        "add.u32 n,n,1; setp.lt.u32 p,n,2000000; @p bra W%=;\n"
        "trap;\n"
        "D%=: }" ::"r"(b), "r"(ph) : "memory");
}
__device__ __forceinline__ bool wait_lds128(uint32_t b, uint32_t ph, uint32_t a, uint4& v) {
    uint32_t ok;
    asm volatile("{.reg .pred p; mbarrier.try_wait.parity.shared::cta.b64 p,[%5],%6,20000; ld.shared.v4.u32 {%0,%1,%2,%3},[%7]; selp.u32 %4,1,0,p;}"
                 : "=r"(v.x), "=r"(v.y), "=r"(v.z), "=r"(v.w), "=r"(ok) : "r"(b), "r"(ph), "r"(a) : "memory");
    return ok;
}
__device__ __forceinline__ bool wait_lds64(uint32_t b, uint32_t ph, uint32_t a, uint2& v) {
    uint32_t ok;
    asm volatile("{.reg .pred p; mbarrier.try_wait.parity.shared::cta.b64 p,[%3],%4,20000; ld.shared.v2.u32 {%0,%1},[%5]; selp.u32 %2,1,0,p;}"
                 : "=r"(v.x), "=r"(v.y), "=r"(ok) : "r"(b), "r"(ph), "r"(a) : "memory");
    return ok;
}
template <int PH> __device__ __forceinline__ void mbar_wait_c(uint32_t b) {
    asm volatile(
        "{.reg .pred p; .reg .u32 n; mov.u32 n,%2;\n"
        "W%=: mbarrier.try_wait.parity.shared::cta.b64 p,[%0],%1;\n"
        "@p bra D%=;\n"
        "add.u32 n,n,1; setp.lt.u32 p,n,2000000; @p bra W%=;\n"
        "trap;\n"
        "D%=: }" ::"r"(b), "n"(PH), "n"(PH) : "memory");
}
__device__ __forceinline__ bool elect() {
    uint32_t r; asm volatile("{.reg .pred p; elect.sync _|p,0xffffffff; selp.u32 %0,1,0,p;}" : "=r"(r)); return r;
}
__device__ __forceinline__ void bar_sync(int id, int n) { asm volatile("bar.sync %0,%1;" ::"r"(id), "r"(n) : "memory"); }
__device__ __forceinline__ void bar_arrive(int id, int n) { asm volatile("bar.arrive %0,%1;" ::"r"(id), "r"(n) : "memory"); }
__device__ __forceinline__ void cluster_sync() { asm volatile("barrier.cluster.arrive.relaxed.aligned; barrier.cluster.wait.aligned;" ::: "memory"); }
__device__ __forceinline__ void fence_async() { asm volatile("fence.proxy.async;" ::: "memory"); }
__device__ __forceinline__ void fence_async_smem() { asm volatile("fence.proxy.async.shared::cta;" ::: "memory"); }
#define EFR 1
#define EFW 2
constexpr uint64_t POL_N = 0x1000000000000000ull, POL_F = 0x12F0000000000000ull;
constexpr uint64_t POL_LAST = EFR ? POL_F : POL_N  , POL_LATE = EFW ? POL_F : POL_N  , POL_SOON = EFW > 1 ? POL_F : POL_N;
__device__ __forceinline__ void bulk_g2s(uint32_t dst, const void* src, int bytes, uint32_t bar, uint64_t pol) {
    asm volatile("cp.async.bulk.shared::cluster.global.mbarrier::complete_tx::bytes.L2::cache_hint [%0],[%1],%2,[%3],%4;" ::"r"(dst), "l"(src), "r"(bytes), "r"(bar), "l"(pol) : "memory");
}
__device__ __forceinline__ void bulk_g2s_mc(uint32_t dst, const void* src, int bytes, uint32_t bar, uint64_t pol) {
    asm volatile("cp.async.bulk.shared::cluster.global.mbarrier::complete_tx::bytes.multicast::cluster.L2::cache_hint [%0],[%1],%2,[%3],%4,%5;" ::"r"(dst), "l"(src), "r"(bytes), "r"(bar), "h"((uint16_t)3), "l"(pol) : "memory");
}
__device__ __forceinline__ void stg128(uint4* p, uint4 v, uint64_t pol) {
    asm volatile("st.global.L2::cache_hint.v4.u32 [%0],{%1,%2,%3,%4},%5;" ::"l"(p), "r"(v.x), "r"(v.y), "r"(v.z), "r"(v.w), "l"(pol));
}
__device__ __forceinline__ void stg32(uint32_t* p, uint32_t v, uint64_t pol) { asm volatile("st.global.L2::cache_hint.u32 [%0],%1,%2;" ::"l"(p), "r"(v), "l"(pol)); }
__device__ __forceinline__ uint4 ldcg128_last(const uint4* p) {
    uint4 v; asm volatile("ld.global.cg.L2::cache_hint.v4.u32 {%0,%1,%2,%3},[%4],%5;" : "=r"(v.x), "=r"(v.y), "=r"(v.z), "=r"(v.w) : "l"(p), "l"(POL_LAST) : "memory"); return v;
}
__device__ __forceinline__ void tma2d(uint32_t dst, const CUtensorMap* tm, int x, int y, uint32_t bar) {
    asm volatile("cp.async.bulk.tensor.2d.shared::cluster.global.mbarrier::complete_tx::bytes [%0],[%1,{%2,%3}],[%4];" ::"r"(dst), "l"(tm), "r"(x), "r"(y), "r"(bar) : "memory");
}
__device__ __forceinline__ void tma3d(uint32_t dst, const CUtensorMap* tm, int y, int z, uint32_t bar) {
    asm volatile("cp.async.bulk.tensor.3d.shared::cluster.global.mbarrier::complete_tx::bytes [%0],[%1,{0,%2,%3}],[%4];" ::"r"(dst), "l"(tm), "r"(y), "r"(z), "r"(bar) : "memory");
}
__device__ __forceinline__ void st_async4(uint32_t a, uint32_t x, uint32_t y, uint32_t z, uint32_t w, uint32_t mb) {
    asm volatile("st.async.shared::cluster.mbarrier::complete_tx::bytes.v4.b32 [%0],{%1,%2,%3,%4},[%5];" ::"r"(a), "r"(x), "r"(y), "r"(z), "r"(w), "r"(mb) : "memory");
}
__device__ __forceinline__ void st_async2(uint32_t a, uint32_t x, uint32_t y, uint32_t mb) {
    asm volatile("st.async.shared::cluster.mbarrier::complete_tx::bytes.v2.b32 [%0],{%1,%2},[%3];" ::"r"(a), "r"(x), "r"(y), "r"(mb) : "memory");
}
#define LDSQ "ld.shared"
__device__ __forceinline__ uint4 lds128(uint32_t a) { uint4 v; asm volatile(LDSQ ".v4.u32 {%0,%1,%2,%3},[%4];" : "=r"(v.x), "=r"(v.y), "=r"(v.z), "=r"(v.w) : "r"(a) : "memory"); return v; }
__device__ __forceinline__ uint4 lds128v(uint32_t a) { uint4 v; asm volatile("ld.volatile.shared.v4.u32 {%0,%1,%2,%3},[%4];" : "=r"(v.x), "=r"(v.y), "=r"(v.z), "=r"(v.w) : "r"(a) : "memory"); return v; }
__device__ __forceinline__ uint2 lds64(uint32_t a) { uint2 v; asm volatile(LDSQ ".v2.u32 {%0,%1},[%2];" : "=r"(v.x), "=r"(v.y) : "r"(a) : "memory"); return v; }
__device__ __forceinline__ uint32_t lds32(uint32_t a) { uint32_t v; asm volatile(LDSQ ".u32 %0,[%1];" : "=r"(v) : "r"(a) : "memory"); return v; }
__device__ __forceinline__ void sts128(uint32_t a, uint32_t x, uint32_t y, uint32_t z, uint32_t w) { asm volatile("st.shared.v4.u32 [%0],{%1,%2,%3,%4};" ::"r"(a), "r"(x), "r"(y), "r"(z), "r"(w) : "memory"); }
__device__ __forceinline__ void sts64(uint32_t a, uint32_t x, uint32_t y) { asm volatile("st.shared.v2.u32 [%0],{%1,%2};" ::"r"(a), "r"(x), "r"(y) : "memory"); }
__device__ __forceinline__ void sts32(uint32_t a, uint32_t x) { asm volatile("st.shared.u32 [%0],%1;" ::"r"(a), "r"(x) : "memory"); }
__device__ __forceinline__ uint4 ldsm4(uint32_t a) { uint4 v; asm volatile("ldmatrix.sync.aligned.m8n8.x4.shared.b16 {%0,%1,%2,%3},[%4];" : "=r"(v.x), "=r"(v.y), "=r"(v.z), "=r"(v.w) : "r"(a) : "memory"); return v; }
__device__ __forceinline__ uint4 ldsm4t(uint32_t a) { uint4 v; asm volatile("ldmatrix.sync.aligned.m8n8.x4.trans.shared.b16 {%0,%1,%2,%3},[%4];" : "=r"(v.x), "=r"(v.y), "=r"(v.z), "=r"(v.w) : "r"(a) : "memory"); return v; }
__device__ __forceinline__ uint32_t movm(uint32_t a) { uint32_t d; asm volatile("movmatrix.sync.aligned.m8n8.trans.b16 %0,%1;" : "=r"(d) : "r"(a)); return d; }
__device__ __forceinline__ uint32_t pack2(float lo, float hi) { uint32_t d; asm("cvt.rn.bf16x2.f32 %0,%1,%2;" : "=r"(d) : "f"(hi), "f"(lo)); return d; }
__device__ __forceinline__ uint32_t hadd2(uint32_t a, uint32_t b) { uint32_t d; asm("add.rn.bf16x2 %0,%1,%2;" : "=r"(d) : "r"(a), "r"(b)); return d; }
__device__ __forceinline__ uint32_t hmul2(uint32_t a, uint32_t b) { uint32_t d; asm("mul.rn.bf16x2 %0,%1,%2;" : "=r"(d) : "r"(a), "r"(b)); return d; }
__device__ __forceinline__ float blo(uint32_t v) { return __uint_as_float(v << 16); }
__device__ __forceinline__ float bhi(uint32_t v) { return __uint_as_float(v & 0xffff0000u); }
__device__ __forceinline__ float rbf(float x) { return __uint_as_float(pack2(0.f, x)); }
__device__ __forceinline__ float ex2(float x) { float y; asm("ex2.approx.ftz.f32 %0,%1;" : "=f"(y) : "f"(x)); return y; }
__device__ __forceinline__ float rcp(float x) { float y; asm("rcp.approx.ftz.f32 %0,%1;" : "=f"(y) : "f"(x)); return y; }
__device__ __forceinline__ void mma16(float* c, uint32_t a0, uint32_t a1, uint32_t a2, uint32_t a3, uint32_t b0, uint32_t b1) {
    asm volatile("mma.sync.aligned.m16n8k16.row.col.f32.bf16.bf16.f32 {%0,%1,%2,%3},{%4,%5,%6,%7},{%8,%9},{%0,%1,%2,%3};"
                 : "+f"(c[0]), "+f"(c[1]), "+f"(c[2]), "+f"(c[3]) : "r"(a0), "r"(a1), "r"(a2), "r"(a3), "r"(b0), "r"(b1));
}
__device__ __forceinline__ void mma16_top(float& d0, float& d1, uint32_t a0, uint32_t a2, uint32_t b0, uint32_t b1) {
    asm volatile("{.reg .b32 j; .reg .f32 e,f; mma.sync.aligned.m16n8k16.row.col.f32.bf16.bf16.f32 {%0,%1,e,f},{%2,j,%3,j},{%4,%5},{0f00000000,0f00000000,0f00000000,0f00000000};}"
                 : "=f"(d0), "=f"(d1) : "r"(a0), "r"(a2), "r"(b0), "r"(b1));
}
__device__ __forceinline__ void mma8(float* c, uint32_t a0, uint32_t a1, uint32_t b0) {
    asm volatile("mma.sync.aligned.m16n8k8.row.col.f32.bf16.bf16.f32 {%0,%1,%2,%3},{%4,%5},{%6},{%0,%1,%2,%3};"
                 : "+f"(c[0]), "+f"(c[1]), "+f"(c[2]), "+f"(c[3]) : "r"(a0), "r"(a1), "r"(b0));
}
__device__ __forceinline__ uint4 ld_rlx128(const uint4* p) {
    uint4 v;
    asm volatile("{.reg .b128 t; ld.relaxed.gpu.global.b128 t,[%4]; mov.b128 {%0,%1,%2,%3},t;}" : "=r"(v.x), "=r"(v.y), "=r"(v.z), "=r"(v.w) : "l"(p) : "memory");
    return v;
}
__device__ __forceinline__ void st_rlx128(uint4* p, uint32_t x, uint32_t y, uint32_t z, uint32_t w) {
    asm volatile("{.reg .b128 t; mov.b128 t,{%1,%2,%3,%4}; st.relaxed.gpu.global.b128 [%0],t;}" ::"l"(p), "r"(x), "r"(y), "r"(z), "r"(w) : "memory");
}
__device__ __forceinline__ uint4 ldcg128(const uint4* p) { uint4 v; asm volatile("ld.global.cg.v4.u32 {%0,%1,%2,%3},[%4];" : "=r"(v.x), "=r"(v.y), "=r"(v.z), "=r"(v.w) : "l"(p) : "memory"); return v; }
__device__ __forceinline__ void red_release(unsigned* p, unsigned v) {
    asm volatile("fence.proxy.async; red.relaxed.gpu.global.add.u32 [%0],%1;" ::"l"(p), "r"(v) : "memory");
}
__device__ __forceinline__ void red_relaxed(unsigned* p, unsigned v) { asm volatile("red.relaxed.gpu.global.add.u32 [%0],%1;" ::"l"(p), "r"(v) : "memory"); }
__device__ __forceinline__ void wait_cnt(const unsigned* p, unsigned target) {
    asm volatile(
        "{.reg .pred p; .reg .u32 n,v; mov.u32 n,0;\n"
        "W%=: ld.acquire.gpu.global.u32 v,[%0]; setp.ge.u32 p,v,%1; @p bra D%=;\n"
        "nanosleep.u32 20; add.u32 n,n,1; setp.lt.u32 p,n,4000000; @p bra W%=;\n"
        "trap;\n"
        "D%=: }" ::"l"(p), "r"(target) : "memory");
}
__device__ __forceinline__ void wait_cnt_warp(const unsigned* p, unsigned target) {
    asm volatile(
        "{.reg .pred p; .reg .u32 n,v; mov.u32 n,0;\n"
        "W%=: ld.acquire.gpu.global.u32 v,[%0]; setp.ge.u32 p,v,%1; vote.sync.all.pred p,p,0xffffffff; @p bra.uni D%=;\n"
        "nanosleep.u32 20; add.u32 n,n,1; setp.lt.u32 p,n,4000000; @p bra.uni W%=;\n"
        "trap;\n"
        "D%=: }" ::"l"(p), "r"(target) : "memory");
}
__device__ __forceinline__ void wait_flag_warp(const unsigned* p, unsigned target) {
    asm volatile(
        "{.reg .pred p; .reg .u32 n,v; mov.u32 n,0;\n"
        "W%=: ld.relaxed.gpu.global.u32 v,[%0]; setp.ge.u32 p,v,%1; vote.sync.all.pred p,p,0xffffffff; @p bra.uni D%=;\n"
        "add.u32 n,n,1; setp.lt.u32 p,n,10000000; @p bra.uni W%=;\n"
        "trap;\n"
        "D%=: }" ::"l"(p), "r"(target) : "memory");
}
__device__ __forceinline__ uint64_t mkdesc(uint32_t addr, uint32_t lbo, uint32_t sbo, uint32_t sw) {
    return (uint64_t)((addr & 0x3FFFF) >> 4) | ((uint64_t)(lbo >> 4) << 16) | ((uint64_t)(sbo >> 4) << 32) | ((uint64_t)sw << 62);
}
__device__ __forceinline__ void wg_fence() { asm volatile("wgmma.fence.sync.aligned;" ::: "memory"); }
__device__ __forceinline__ void wg_commit() { asm volatile("wgmma.commit_group.sync.aligned;" ::: "memory"); }
template <int N> __device__ __forceinline__ void wg_wait() { asm volatile("wgmma.wait_group.sync.aligned %0;" ::"n"(N) : "memory"); }
#define R8(c, o) "+f"(c[o]), "+f"(c[o + 1]), "+f"(c[o + 2]), "+f"(c[o + 3]), "+f"(c[o + 4]), "+f"(c[o + 5]), "+f"(c[o + 6]), "+f"(c[o + 7])
#define R32(c, o) R8(c, o), R8(c, o + 8), R8(c, o + 16), R8(c, o + 24)
#define S32A "%0,%1,%2,%3,%4,%5,%6,%7,%8,%9,%10,%11,%12,%13,%14,%15,%16,%17,%18,%19,%20,%21,%22,%23,%24,%25,%26,%27,%28,%29,%30,%31"
template <int ACC> __device__ __forceinline__ void wgmma64_rs(float* c, const uint32_t* a, uint64_t db) {
    asm volatile("wgmma.mma_async.sync.aligned.m64n64k16.f32.bf16.bf16 {" S32A "},{%32,%33,%34,%35},%36,%37,1,1,0;"
                 : R32(c, 0) : "r"(a[0]), "r"(a[1]), "r"(a[2]), "r"(a[3]), "l"(db), "n"(ACC));
}
template <int ACC> __device__ __forceinline__ void wgmma64_ta(float* c, uint64_t da, uint64_t db) {
    asm volatile("wgmma.mma_async.sync.aligned.m64n64k16.f32.bf16.bf16 {" S32A "},%32,%33,%34,1,1,1,0;" : R32(c, 0) : "l"(da), "l"(db), "n"(ACC));
}
template <int ACC> __device__ __forceinline__ void wgmma80_tb(float* c, uint64_t da, uint64_t db) {
    asm volatile("wgmma.mma_async.sync.aligned.m64n80k16.f32.bf16.bf16 {" S32A ",%32,%33,%34,%35,%36,%37,%38,%39},%40,%41,%42,1,1,0,1;"
                 : R32(c, 0), R8(c, 32) : "l"(da), "l"(db), "n"(ACC));
}
template <int N> __device__ __forceinline__ void reg_inc() { asm volatile("setmaxnreg.inc.sync.aligned.u32 %0;" ::"n"(N)); }
template <int N> __device__ __forceinline__ void reg_dec() { asm volatile("setmaxnreg.dec.sync.aligned.u32 %0;" ::"n"(N)); }

#define PROF(cond, idx) do {} while (0)
#define CPROF(k) do {} while (0)

constexpr int S_GATE = 232440, S_XBAR = 232432, B_BAR = 231936;
#define RCB 136
#define RCU 184
#define NFP 2
#define NLATE 1
#define PFM 8
#define NFE 2
#define QLAG 3
constexpr float SC_LOG2E = 0.08838834764831845f * 1.4426950408889634f;

__device__ __forceinline__ float2 ln_finish(float mean, float var) {
    float sd; asm("sqrt.approx.f32 %0,%1;" : "=f"(sd) : "f"(rbf(rbf(var) + 1e-5f)));
    sd = rbf(sd);
    return make_float2(rbf(mean), sd);
}

__device__ __forceinline__ float2 row_stats512(uint4* v, const uint4* src, int s1, int s2) {
    const int g = (threadIdx.x & 31) >> 2;
#pragma unroll
    for (int i = 0; i < 16; i++) v[i] = ldcg128(src + (i >> 1) * s1 + (i & 1) * s2);
    float a[4] = {0, 0, 0, 0}, q0[4] = {0, 0, 0, 0}, q1[4] = {0, 0, 0, 0};
#pragma unroll
    for (int i = 0; i < 16; i++) {
        mma16(a, v[i].x, v[i].y, v[i].z, v[i].w, 0x3f803f80u, 0x3f803f80u);
        mma8(q0, v[i].x, v[i].y, v[i].x); mma8(q1, v[i].x, v[i].y, v[i].y);
        mma8(q0, v[i].z, v[i].w, v[i].z); mma8(q1, v[i].z, v[i].w, v[i].w);
    }
    const float sum = a[0] + a[2], sq = (g & 1) ? q0[1] + q1[3] : q0[0] + q1[2];
    return make_float2(sum, fmaxf(sq - sum * sum * (1.f / 512.f), 0.f));
}
__device__ __forceinline__ void x1_norm(const uint2* src, int r, bool on) {
    const int lane = threadIdx.x & 31, g = lane >> 2, t = r * 4 + (lane & 3);
    constexpr int xp = XP;
    uint2 v[16];
#pragma unroll
    for (int i = 0; i < 16; i++) asm volatile("ld.global.cg.v2.u32 {%0,%1},[%2];" : "=r"(v[i].x), "=r"(v[i].y) : "l"(src + (g * 4 * xp + t) + ((i >> 1) * 16 + (i & 1)) * 2 * xp) : "memory");
    float s = 0, q = 0;
#pragma unroll
    for (int i = 0; i < 32; i++) {
        const uint32_t w = (i & 1) ? v[i >> 1].y : v[i >> 1].x;
        s += blo(w) + bhi(w); q = fmaf(blo(w), blo(w), fmaf(bhi(w), bhi(w), q));
    }
#pragma unroll
    for (int d = 4; d < 32; d *= 2) { s += __shfl_xor_sync(0xffffffffu, s, d); q += __shfl_xor_sync(0xffffffffu, q, d); }
    if (g == 0 && on) g_ln0[t] = 0;
    s *= 1.f / 512.f;
    const float2 l = ln_finish(s, fmaxf(fmaf(q, 1.f / 512.f, -s * s), 0.f));
    const float rs = rcp(l.y);
    const uint32_t mm = pack2(-l.x, -l.x);
    uint4* dst = g_xn + ((t >> 6) * 4096 + ((t >> 3) & 7) * 64 + g * 8 + (t & 7));
#define NRM(w) pack2(blo(hadd2(w, mm)) * rs, bhi(hadd2(w, mm)) * rs)
#pragma unroll
    for (int i = 0; i < 8; i++)
        asm volatile("{.reg .pred p; setp.ne.u32 p,%5,0; @p st.global.v4.u32 [%0],{%1,%2,%3,%4};}" ::"l"(dst + i * 512), "r"(NRM(v[2 * i].x)), "r"(NRM(v[2 * i].y)),
                     "r"(NRM(v[2 * i + 1].x)), "r"(NRM(v[2 * i + 1].y)), "r"((uint32_t)on) : "memory");
}

#define NWO 10
#define VMASK 0x4444
#define VPRE 2
#define VFIRST 1
#define OA 0
#define OL 0x16
#define PINS 0xae1
#define NPX 2
#define NPF 2
constexpr int SLOT = 24576, SL_V = 8192, SL_Q = 16384, SL_KM = 20480, SL_VM = 22528;
constexpr int R_SL = 0, R_WV = 4 * SLOT  , R_WO = R_WV + 65536, R_M = 196608  , R_U = R_M + 8192  ,
              R_OS = R_U + 8192  , R_SB = R_OS + 8192  , R_OB = R_SB + 5248  , R_PB = R_OB + 2048  ,
              R_IL = R_PB + 1024  , R_SEL = 231680, R_BAR = R_SEL + 256, R_STV = 0, R_STQ = 65536, R_STK = 131072;
static_assert(R_WO + (16 - NWO) * 4096 <= R_M && R_IL + 64 <= R_SEL && R_BAR + 512 <= 232448, "smem map");
enum { RB_XFULL = 0  , RB_GO = 4  , RB_QK = 8  , RB_INIT = 24, RB_SV = 25   };

enum { NB_MFULL = 1  , NB_PART = 3  , NB_S = 5, NB_P = 6, NB_O = 7, NB_W = 10 };
#define HL 2
#define XU 8
#define XFW 1
#define RACC 2
#define WDEP 1
#define RH 56
#define RW0 224
#define D1 400
#define D2 400
#define DX 0
__device__ __forceinline__ uint32_t clk32() { uint32_t c; asm volatile("mov.u32 %0,%%clock;" : "=r"(c)::"memory"); return c; }
__device__ __forceinline__ void spin(int cycles) {
    if (cycles <= 0) return;
    asm volatile("{.reg .pred p; .reg .u32 a,b; mov.u32 a,%%clock; add.u32 a,a,%0;\nS%=: mov.u32 b,%%clock; sub.u32 b,b,a; setp.lt.s32 p,b,0; @p bra.uni S%=;}" ::"r"(cycles) : "memory");
}
__device__ __forceinline__ uint4* xregion(int X, int r) { return (uint4*)(((size_t)g_xch + 8191) & ~(size_t)8191) + (X * 66 + r) * 512; }

__device__ __forceinline__ void arrive_if(uint32_t bar, uint32_t a, uint32_t b) {
    asm volatile("{.reg .pred p; setp.eq.u32 p,%1,%2; @p mbarrier.arrive.shared::cta.b64 _,[%0];}" ::"r"(bar), "r"(a), "r"(b) : "memory");
}
struct RecW { uint32_t po, dp, lw, sp  , w; };
#define PIN(n) if ((PINS >> (n)) & 1) asm volatile("griddepcontrol.launch_dependents;" ::: "memory")
constexpr int v_stream(int n) {
    int ks = 0;
    for (; ks < 16; ks++) if (!((VMASK >> ks) & 1) && n-- == 0) break;
    return ks;
}
constexpr uint64_t v_next() {
    uint64_t r = 0;
    for (int n = 0; v_stream(n + VPRE) < 16; n++) r |= (uint64_t)v_stream(n + VPRE) << (4 * v_stream(n));
    return r;
}
constexpr uint64_t V_NEXT = v_next();
constexpr int V_PRE = v_stream(VPRE);

template <int X>
__device__ __forceinline__ void rec_step(const RecW& k, uint32_t sb, int s, uint32_t zero, int lo, int hi, int d, const uint32_t (*wq)[4], const uint32_t (*wk)[4], uint4* wv, uint4* wo) {
    constexpr int SL = R_SL + X * 2 * SLOT;
    uint4 mk[8];
    bar_sync(NB_MFULL + X, 288);
    mk[0] = ldsm4(k.lw + X * 4096 + R_M);
    PIN(0);
    mk[1] = ldsm4(k.lw + X * 4096 + R_M + 512);
    PIN(0);
    asm volatile("" : "+r"(s));
    const uint32_t z = s & zero, wz = k.w + z, w5 = wz * 512, so = (s & 1) * SLOT + w5;
    const uint32_t qb = sb + R_BAR + (RB_QK + X * 8) * 8 + wz * 8;
    uint32_t x[4], vv[2], l8;
    {
        float aq[4] = {0, 0, 0, 0}, ak[4] = {0, 0, 0, 0}, av[4] = {0, 0, 0, 0};
#pragma unroll
        for (int t = 0; t < 16; t++) {
            const uint32_t b0 = (t & 1) ? mk[t >> 1].z : mk[t >> 1].x, b1 = (t & 1) ? mk[t >> 1].w : mk[t >> 1].y;
            mma16(aq, wq[t][0], wq[t][1], wq[t][2], wq[t][3], b0, b1);
            PIN(8);
            mma16(ak, wk[t][0], wk[t][1], wk[t][2], wk[t][3], b0, b1);
            PIN(9);
            mma16(av, wv[t].x, wv[t].y, wv[t].z, wv[t].w, b0, b1);
            PIN(10);
            if ((t & 1) && t < 13) mk[(t >> 1) + 2] = ldsm4(k.lw + X * 4096 + R_M + (t >> 1) * 512 + 1024);
            const int nx = (V_NEXT >> (4 * t)) & 15;
            if (nx) wv[nx] = lds128(k.lw + w5 + R_WV + nx * 4096);
            if (t == 14) l8 = ((k.lw + z) >> 1) + (sb - (sb >> 1) + SL + (s & 1) * SLOT + wz * 256);
            if (t < 15) PIN(1);
        }
        x[0] = movm(pack2(aq[0], aq[1])); x[1] = movm(pack2(aq[2], aq[3]));
        x[2] = movm(pack2(ak[0], ak[1])); x[3] = movm(pack2(ak[2], ak[3]));
        vv[0] = pack2(av[0], av[1]); vv[1] = pack2(av[2], av[3]);
        if (VFIRST) st_async2(l8 + (SL_VM + k.dp), vv[0], vv[1], qb + k.dp);
        st_async4(k.lw + (R_U + X * 4096 + w5 + k.dp), x[0], x[1], x[2], x[3], qb + k.dp);
        if (!VFIRST) st_async2(l8 + (SL_VM + k.dp), vv[0], vv[1], qb + k.dp);
    }
    {
        arrive_if(sb + R_BAR + (RB_GO + 2 - 2 * X + ((s + d) & 1)) * 8, k.sp, X ? s >= hi : s <= lo);
        const uint32_t swr = ((k.sp + z) & 0xffff) + (sb + R_SB);
        if (XFW) mbar_wait(sb + R_BAR + (RB_XFULL + X * 2) * 8 + (s & 1) * 8, (s >> 1) & 1);
        const uint4 k0 = lds128(k.lw + so + SL), k1 = lds128(k.lw + so + SL + 4096);
#pragma unroll
        for (int i = 0; i < NPX; i++) wo[i] = lds128(k.lw + w5 + R_WO + i * 4096);
        mbar_wait(qb, s & 1);
        const uint4 u = lds128(k.lw + w5 + R_U + X * 4096);
        const uint32_t q0 = hadd2(x[0], u.x), q1 = hadd2(x[1], u.y);
        x[2] = hadd2(x[2], u.z); x[3] = hadd2(x[3], u.w);
        float sa[4] = {0, 0, 0, 0}, sc[4] = {0, 0, 0, 0}, sm0, sm1;
        mma16(sa, k0.x, k0.y, k0.z, k0.w, q0, q1);
        mma16(sc, k1.x, k1.y, k1.z, k1.w, q0, q1);
        mma16_top(sm0, sm1, x[2], x[3], q0, q1);
        asm volatile("stmatrix.sync.aligned.m8n8.x4.trans.shared.b16 [%0],{%1,%2,%3,%4};" ::"r"(swr), "r"(pack2(sa[0], sa[1])), "r"(pack2(sa[2], sa[3])),
                     "r"(pack2(sc[0], sc[1])), "r"(pack2(sc[2], sc[3])) : "memory");
        asm volatile("stmatrix.sync.aligned.m8n8.x1.trans.shared.b16 [%0],{%1};" ::"r"(swr + 512), "r"(pack2(sm0, sm1)) : "memory");
    }
    bar_sync(NB_S, 256);
    uint4 v0, v1;
    uint32_t ls;
    {
        const uint4 y = ldsm4t(k.lw + wz * 656 + R_SB);
        PIN(2);
        uint32_t y4; asm volatile("ldmatrix.sync.aligned.m8n8.x1.trans.shared.b16 {%0},[%1];" : "=r"(y4) : "r"(k.lw + wz * 656 + R_SB + 512) : "memory");
        PIN(2);
        const uint2 vp = lds64(l8 + SL_VM);
        sts64(l8 + SL_KM, x[2], x[3]);
        const uint32_t ONE = 0x3f803f80u + z;
        float a[4] = {0, 0, 0, 0}, b[4] = {0, 0, 0, 0}, e[4] = {0, 0, 0, 0};
        mma16(a, ONE, z, z, ONE, y.x, y.y); mma16(b, ONE, z, z, ONE, y.z, y.w); mma8(e, ONE, z, y4);
        vv[0] = hadd2(vv[0], vp.x); vv[1] = hadd2(vv[1], vp.y);
        sts64(l8 + SL_VM, vv[0], vv[1]);
        float s0, s1;
        asm("{.reg .pred p1,p2,p4; .reg .f32 t0,t1,u0,u1; .reg .b32 m; and.b32 m,%12,64; setp.ne.u32 p1,m,0; and.b32 m,%12,128; setp.ne.u32 p2,m,0; and.b32 m,%12,256; setp.ne.u32 p4,m,0;"
            "selp.f32 t0,%4,%2,p1; selp.f32 t1,%5,%3,p1; selp.f32 u0,%8,%6,p1; selp.f32 u1,%9,%7,p1; selp.f32 t0,u0,t0,p2; selp.f32 t1,u1,t1,p2; selp.f32 %0,%10,t0,p4; selp.f32 %1,%11,t1,p4;}"
            : "=f"(s0), "=f"(s1) : "f"(a[0]), "f"(a[1]), "f"(a[2]), "f"(a[3]), "f"(b[0]), "f"(b[1]), "f"(b[2]), "f"(b[3]), "f"(e[0]), "f"(e[1]), "r"(k.lw));
        const int mi = __float_as_int(fmaxf(s0, s1));
        const int mp = __reduce_max_sync(0xffffffffu, mi), mn = (int)__reduce_min_sync(0xffffffffu, (unsigned)mi);
        PIN(3);
        v0 = lds128(k.lw + so + SL + SL_V); v1 = lds128(k.lw + so + SL + SL_V + 4096);
#pragma unroll
        for (int i = NPX; i < NPF; i++) wo[i] = lds128(k.lw + w5 + R_WO + i * 4096);
        PIN(4);
        const float mo = -__int_as_float(mp >= 0 ? mp : mn) * SC_LOG2E;
        s0 = ex2(fmaf(s0, SC_LOG2E, mo)); s1 = ex2(fmaf(s1, SC_LOG2E, mo));
        sts32(((k.sp + z) >> 16) + (sb + R_PB), pack2(s0, s1));
        ls = k.lw < sb + 320 ? __float_as_uint((s0 + s1) + 4.f) : 0;
    }
    bar_sync(NB_P, 256);
    {
        const uint4 pp = lds128(k.lw + R_PB);
        PIN(5);
        const uint32_t pm = lds32(((k.lw + z) >> 2) + (sb - (sb >> 2) + R_PB + 512));
        PIN(5);
        sts32(sb + R_IL + (wz >> 1) * 16 + (wz & 1) * 4, __reduce_add_sync(0xffffffffu, ls) - 20u * 0x40800000u);
        float o0[4] = {0, 0, 0, 0}, o1[4] = {0, 0, 0, 0}, o2[4] = {0, 0, 0, 0};
        mma16(o0, v0.x, v0.y, v0.z, v0.w, pp.x, pp.y);
        mma16(o1, v1.x, v1.y, v1.z, v1.w, pp.z, pp.w);
        mma8(o2, vv[0], vv[1], pm);
        asm volatile("stmatrix.sync.aligned.m8n8.x2.trans.shared.b16 [%0],{%1,%2};" ::"r"(k.lw + wz * 256 + R_OB),
                     "r"(pack2(o0[0] + o1[0] + o2[0], o0[1] + o1[1] + o2[1])), "r"(pack2(o0[2] + o1[2] + o2[2], o0[3] + o1[3] + o2[3])) : "memory");
    }
    bar_sync(NB_O, 256);
    {
        float r0[2][4] = {{0, 0, 0, 0}, {0, 0, 0, 0}}, r1[2][4] = {{0, 0, 0, 0}, {0, 0, 0, 0}};
        uint4 b[4];
        b[0] = ldsm4(k.lw + R_OB);
        PIN(6);
        b[1] = ldsm4(k.lw + R_OB + 512);
        PIN(6);
#pragma unroll
        for (int m = NWO + NPF; m < 16; m++) if (((OL >> (2 * (15 - m))) & 3) == 3) wo[m] = lds128(k.lw + w5 + R_WO + (m - NWO) * 4096);
        const uint2 il = lds64(sb + R_IL + ((k.lw + z) & 48));
        PIN(6);
        float i0, i1;
        uint4* dst;
#pragma unroll
        for (int i = 0; i < 4; i++) {
            mma16(r0[0], wo[4 * i].x, wo[4 * i].y, wo[4 * i].z, wo[4 * i].w, b[i].x, b[i].y);
            mma16(r1[0], wo[4 * i + 1].x, wo[4 * i + 1].y, wo[4 * i + 1].z, wo[4 * i + 1].w, b[i].x, b[i].y);
            mma16(r0[OA], wo[4 * i + 2].x, wo[4 * i + 2].y, wo[4 * i + 2].z, wo[4 * i + 2].w, b[i].z, b[i].w);
            mma16(r1[OA], wo[4 * i + 3].x, wo[4 * i + 3].y, wo[4 * i + 3].z, wo[4 * i + 3].w, b[i].z, b[i].w);
            if (i < 2) b[i + 2] = ldsm4(k.lw + R_OB + (i + 2) * 512);
#pragma unroll
            for (int m = NWO + NPF; m < 16; m++) if (i < 3 && i == ((OL >> (2 * (15 - m))) & 3)) wo[m] = lds128(k.lw + w5 + R_WO + (m - NWO) * 4096);
            if (i == 1) { i0 = rcp(__uint2float_rn(il.x)) * 2097152.f; i1 = rcp(__uint2float_rn(il.y)) * 2097152.f; }
            if (i == 2) {
                const uint32_t po = k.po + z;
                dst = (uint4*)((char*)xregion(X, 0) + ((po & ~1u) ^ ((po & X) << 12)));
                asm volatile("" : "+l"(dst));
            }
            PIN(7);
        }
        const uint32_t tag = (s + 1) & 1;
#pragma unroll
        for (int i = 0; i < 4; i++) { r0[0][i] = (OA ? r0[0][i] + r0[1][i] : r0[0][i]) * ((i & 1) ? i1 : i0); r1[0][i] = (OA ? r1[0][i] + r1[1][i] : r1[0][i]) * ((i & 1) ? i1 : i0); }
        st_rlx128(dst, (pack2(r0[0][0], r0[0][2]) & ~1u) | tag,
                  pack2(r1[0][0], r1[0][2]), pack2(r0[0][1], r0[0][3]), pack2(r1[0][1], r1[0][3]));
        bar_arrive(NB_PART + X, 288);
#pragma unroll
        for (int t = 0; t < V_PRE; t++) if (!((VMASK >> t) & 1)) wv[t] = lds128(k.lw + w5 + R_WV + t * 4096);
        arrive_if(sb + R_BAR + (RB_GO + 2 * X + (s & 1)) * 8, k.sp, X ? s + 1 < hi : s >= lo);
    }
}

__device__ __forceinline__ void rec_fetch(const Params& p, uint32_t sb, int head, uint32_t rank, int which, int dst) {
#pragma unroll 1
    for (int j = 0; j < 8; j++) tma2d(sb + dst + j * 8192, &p.tm[which], head * 128 + (j >> 2) * 64, rank * 256 + (j & 3) * 64, sb + R_BAR + RB_INIT * 8);
}

__device__ __forceinline__ void rec_weights(const Params& p, uint32_t sb, int head, uint32_t rank, int w) {
    const int lane = threadIdx.x & 31, g = lane >> 2, c = lane & 3;
    const int t = w & 3, WG = w >> 2;
    uint32_t wq[16][4], wk[16][4];
    uint4 wo[16], wv[16];
    const uint32_t woff = sb + WG * 32768 + (((lane >> 4) << 3) + (lane & 7)) * 128 + (((2 * t + ((lane >> 3) & 1)) ^ (lane & 7)) << 4);
    const uint32_t lw = sb + lane * 16;
    PROF(threadIdx.x == 0, 3501);
    {
        const __nv_bfloat16* wp = p.Wo + (size_t)(head * 128 + 2 * c) * 512 + rank * 256 + w * 32 + g * 4;
#pragma unroll
        for (int ks = 0; ks < 8; ks++) {
            const uint2 r0 = *(const uint2*)(wp + (ks * 16) * 512), r1 = *(const uint2*)(wp + (ks * 16 + 1) * 512);
            const uint2 r2 = *(const uint2*)(wp + (ks * 16 + 8) * 512), r3 = *(const uint2*)(wp + (ks * 16 + 9) * 512);
            const uint4 f[2] = {make_uint4(__byte_perm(r0.x, r1.x, 0x5410), __byte_perm(r0.x, r1.x, 0x7632), __byte_perm(r2.x, r3.x, 0x5410), __byte_perm(r2.x, r3.x, 0x7632)),
                                make_uint4(__byte_perm(r0.y, r1.y, 0x5410), __byte_perm(r0.y, r1.y, 0x7632), __byte_perm(r2.y, r3.y, 0x5410), __byte_perm(r2.y, r3.y, 0x7632))};
#pragma unroll
            for (int h = 0; h < 2; h++) {
                const int m = 2 * ks + h;
                wo[m] = f[h];
            }
        }
    }
    PROF(threadIdx.x == 0, 3502);
    mbar_wait(sb + R_BAR + RB_INIT * 8, 0);
    PROF(threadIdx.x == 0, 3503);
#pragma unroll
    for (int ks = 0; ks < 16; ks++) {
        uint4 a = ldsm4t(woff + R_STQ + ks * 2048), b = ldsm4t(woff + R_STK + ks * 2048);
        wq[ks][0] = a.x; wq[ks][1] = a.y; wq[ks][2] = a.z; wq[ks][3] = a.w;
        wk[ks][0] = b.x; wk[ks][1] = b.y; wk[ks][2] = b.z; wk[ks][3] = b.w;
    }
    bar_sync(NB_W, 256);
#pragma unroll
    for (int m = 0; m < 16; m++)
        if (m < NPF || m >= NPF + NWO) sts128(lw + w * 512 + R_WO + (m < NPF ? m : m - NWO) * 4096, wo[m].x, wo[m].y, wo[m].z, wo[m].w);
#pragma unroll
    for (int i = 0; i < 16; i++) {
        wv[i] = ldsm4t(woff + R_STV + i * 2048);
        if (!((VMASK >> i) & 1)) sts128(lw + w * 512 + R_WV + i * 4096, wv[i].x, wv[i].y, wv[i].z, wv[i].w);
    }
    fence_async_smem();
    PROF(threadIdx.x == 0, 3504);
    __syncthreads();
    cluster_sync();
    PROF(threadIdx.x == 0, 3505);
    RecW k;
    {
        const int r = (w * 4 + (lane >> 3)) * 2 + rank;
        const uint32_t sl = lds32(sb + R_SEL + r * 4);
        const int slot = HL == 0 ? head * 8 + (lane & 7) : HL == 1 ? (head >> 2) * 32 + ((lane & 7) >> 1) * 8 + (head & 3) * 2 + (lane & 1) : (head >> 1) * 16 + ((lane & 7) >> 2) * 8 + (head & 1) * 4 + (lane & 3);
        k.po = (r * 512 + slot + (sl & 1) * 256) * 16 + (((sl >> 1) ^ sl) & 1);
    }
    k.dp = mapa(sb, rank ^ 1) - sb;
    k.lw = __shfl_sync(0xffffffffu, lw, lane);
    k.sp = __shfl_sync(0xffffffffu, (lane & 7) * 656 + (lane >> 3) * 128 + w * 16 + ((g < 4 ? (w * 4 + c) * 16 + g * 4 : 512 + (w * 4 + c) * 4) << 16), lane);
    k.w = w;
    const int e0 = (p.chains & 1) ? 64 : 0, o1 = (p.chains & 2) ? p.lag : 1000, nit = (p.chains & 2) ? p.lag + 64 : e0;
    const uint32_t zero = p.zero;
#pragma unroll 1
    for (int it = 0; it < nit; it++) {
        if (it < e0) rec_step<0>(k, sb, it, zero, o1, 0, o1 + 1, wq, wk, wv, wo);
        if (it >= o1) rec_step<1>(k, sb, it - o1, zero, 0, e0 - o1, o1, wq, wk, wv, wo);
    }
}

__device__ __forceinline__ uint32_t mism(uint32_t a, uint32_t b, uint32_t t) {
    uint32_t d; asm("lop3.b32 %0,%1,%2,%3,0x7e;" : "=r"(d) : "r"(a), "r"(b), "r"(t)); return d;
}
__device__ __forceinline__ uint32_t or3(uint32_t a, uint32_t b, uint32_t c) {
    uint32_t d; asm("lop3.b32 %0,%1,%2,%3,0xfe;" : "=r"(d) : "r"(a), "r"(b), "r"(c)); return d;
}
template <bool TWO, class F>
__device__ __forceinline__ void poll8(uint4* x, const uint4* src, uint32_t tag, F&& use) {
#pragma unroll
    for (int j = 0; j < 8; j++) x[j] = ld_rlx128(src + j * 32);
    int n = 0;
    while (true) {
        use();
        uint32_t bad = or3(mism(x[0].x, x[1].x, tag), mism(x[2].x, x[3].x, tag), mism(x[4].x, x[5].x, tag));
        if (TWO) bad = or3(bad, or3(mism(x[0].z, x[1].z, tag), mism(x[2].z, x[3].z, tag), mism(x[4].z, x[5].z, tag)), mism(x[6].z, x[7].z, tag));
        if (!__any_sync(0xffffffffu, (bad | mism(x[6].x, x[7].x, tag)) & 1)) break;
#pragma unroll
        for (int j = 0; j < 8; j++)
            asm volatile("{.reg .pred p; .reg .b128 t; .reg .b32 m; lop3.b32 m,%0,%6,%5,0x7e; and.b32 m,m,1; setp.ne.u32 p,m,0; mov.b128 t,{%0,%1,%2,%3};"
                         "@p ld.relaxed.gpu.global.b128 t,[%4]; mov.b128 {%0,%1,%2,%3},t;}"
                         : "+r"(x[j].x), "+r"(x[j].y), "+r"(x[j].z), "+r"(x[j].w) : "l"(src + j * 32), "r"(tag), "r"(TWO ? x[j].z : tag) : "memory");
        if (++n > 2000000) __trap();
    }
}

__device__ __forceinline__ void rec_comm(const Params& p, uint32_t sb, int X, int head, uint32_t rank) {
    const int lane = threadIdx.x & 31, g = lane >> 2, c = lane & 3;
    const int me = head * 2 + rank;
    const uint32_t mb = sb + R_M + X * 4096 + lane * 16;
    uint4 x[8];
#pragma unroll
    for (int j = 0; j < 8; j++) x[j] = *(const uint4*)(p.mem0 + (lane & 7) * 512 + rank * 256 + (j * 4 + (lane >> 3)) * 8);
    const uint32_t sl = lds32(sb + R_SEL + me * 4);
    const uint4* src1 = xregion(X, me) + ((sl >> X) & 1) * 256 + (HL == 0 ? c * 8 + g : HL == 1 ? (g >> 1) * 8 + c * 2 + (g & 1) : (c >> 1) * 16 + (g >> 2) * 8 + (c & 1) * 4 + (g & 3));
    const uint4* src2 = xregion(X, 64 + rank) + ((sl >> (2 + X)) & 1) * 256 + lane;
    uint2* mdst = (uint2*)(xregion(X, 64 + rank) + (c >> 1) * 256 + head * 8 + (g & 3) * 2 + (c & 1)) + (g >> 2);
    const uint32_t one = (g & 1) ? 0x3f800000u : 0x00003f80u, selA = (g & 2) ? 0u : one, selB = (g & 2) ? one : 0u;
    const uint32_t qb = sb + R_BAR + (RB_QK + X * 8 + lane) * 8;
    if (lane < 8) mbar_expect(qb, 768);
    if (!XFW) mbar_wait(sb + R_BAR + (RB_XFULL + X * 2) * 8, 0);
#pragma unroll
    for (int j = 0; j < 8; j++) sts128(mb + j * 512, x[j].x, x[j].y, x[j].z, x[j].w);
#pragma unroll 1
    for (int s = 0;; s++) {
        bar_arrive(NB_MFULL + X, 288);
        PROF(lane == 0, X * 64 + s);
        bar_sync(NB_PART + X, 288);
        if (s == 63) break;
        const uint32_t tag = (s + 1) & 1;
        if (lane < 8) mbar_expect(qb, 768);
        spin(D1);
        uint32_t m0, m1;
        poll8<false>(x, src1, tag, [&]() {
            float a[RACC][4];
#pragma unroll
            for (int j = 0; j < 8; j++) {
                if (j < RACC) a[j][0] = a[j][1] = a[j][2] = a[j][3] = 0;
                mma16(a[j % RACC], x[j].x, x[j].y, x[j].z, x[j].w, selA, selB);
            }
#pragma unroll
            for (int i = 0; i < 4; i++) a[0][i] = RACC == 3 ? a[0][i] + a[1][i] + a[2 % RACC][i] : a[0][i] + a[1][i];
            m0 = (pack2(a[0][0], a[0][1]) & ~1u) | tag; m1 = pack2(a[0][2], a[0][3]);
        });
        asm volatile("st.relaxed.gpu.global.b64 [%0],%1;" ::"l"(mdst), "l"(((uint64_t)m1 << 32) | m0) : "memory");
        const uint32_t t2 = clk32();
        if (!XFW) mbar_wait(sb + R_BAR + (RB_XFULL + X * 2 + tag) * 8, ((s + 1) >> 1) & 1);
        while (clk32() - t2 < D2) {}
        poll8<true>(x, src2, tag, [&]() {
#pragma unroll
            for (int j = 0; j < 8; j++) sts128(mb + j * 512, x[j].x, x[j].y, x[j].z, x[j].w);
        });
    }
}

template <int MT>
__device__ __forceinline__ void xattn(uint32_t l16, uint32_t l8, uint32_t os, int g, int c) {
    constexpr int NT = 3 + 2 * MT, XUN = XU;
    float S[NT][4];
#pragma unroll
    for (int i = 0; i < NT; i++) S[i][0] = S[i][1] = S[i][2] = S[i][3] = 0;
#pragma unroll XUN
    for (int ks = 0; ks < 8; ks++) {
        const uint4 q = lds128(l16 + SL_Q + ks * 512);
        const uint2 u = lds64(l8 + SL_KM + ks * 256);
        mma16(S[0], q.x, q.y, q.z, q.w, u.x, u.y);
#pragma unroll
        for (int m = 0; m <= MT; m++) {
            const uint4 kk = lds128(l16 + m * 4096 + ks * 512);
            mma16(S[1 + 2 * m], q.x, q.y, q.z, q.w, kk.x, kk.z); mma16(S[2 + 2 * m], q.x, q.y, q.z, q.w, kk.y, kk.w);
        }
    }
    const float NEG = -__int_as_float(0x7f800000);
    if (2 * c > g) { S[NT - 2][0] = NEG; S[NT - 1][2] = NEG; }
    if (2 * c + 1 > g) { S[NT - 2][1] = NEG; S[NT - 1][3] = NEG; }
    S[NT - 1][0] = S[NT - 1][1] = NEG;
    float m0 = fmaxf(S[0][0], S[0][1]), m1 = fmaxf(S[0][2], S[0][3]);
#pragma unroll
    for (int i = 1; i < NT; i++) { if (i < NT - 1) m0 = fmaxf(m0, fmaxf(S[i][0], S[i][1])); m1 = fmaxf(m1, fmaxf(S[i][2], S[i][3])); }
    m0 = fmaxf(m0, __shfl_xor_sync(0xffffffffu, m0, 1)); m1 = fmaxf(m1, __shfl_xor_sync(0xffffffffu, m1, 1));
    m0 = fmaxf(m0, __shfl_xor_sync(0xffffffffu, m0, 2)); m1 = fmaxf(m1, __shfl_xor_sync(0xffffffffu, m1, 2));
    m0 *= -SC_LOG2E; m1 *= -SC_LOG2E;
    float l0 = 0, l1 = 0;
#pragma unroll
    for (int i = 0; i < NT; i++) {
        if (i < NT - 1) { S[i][0] = ex2(fmaf(S[i][0], SC_LOG2E, m0)); S[i][1] = ex2(fmaf(S[i][1], SC_LOG2E, m0)); l0 += S[i][0] + S[i][1]; }
        S[i][2] = ex2(fmaf(S[i][2], SC_LOG2E, m1)); S[i][3] = ex2(fmaf(S[i][3], SC_LOG2E, m1)); l1 += S[i][2] + S[i][3];
    }
    l0 += __shfl_xor_sync(0xffffffffu, l0, 1); l1 += __shfl_xor_sync(0xffffffffu, l1, 1);
    l0 += __shfl_xor_sync(0xffffffffu, l0, 2); l1 += __shfl_xor_sync(0xffffffffu, l1, 2);
    uint2 vm = lds64(l8 + SL_VM);
    uint4 v[2];
#pragma unroll
    for (int m = 0; m <= MT; m++) v[m] = lds128(l16 + SL_V + m * 4096);
    l0 = rcp(l0); l1 = rcp(l1);
    uint32_t P[NT][2];
#pragma unroll
    for (int i = 0; i < NT; i++) { P[i][0] = i < NT - 1 ? pack2(S[i][0] * l0, S[i][1] * l0) : 0u; P[i][1] = pack2(S[i][2] * l1, S[i][3] * l1); }
#pragma unroll
    for (int et = 0; et < 8; et++) {
        float a[4] = {0, 0, 0, 0}, b[4] = {0, 0, 0, 0};
        const uint2 um = vm;
        const uint4 u[2] = {v[0], v[MT]};
        if (et < 7) {
            vm = lds64(l8 + SL_VM + et * 256 + 256);
#pragma unroll
            for (int m = 0; m <= MT; m++) v[m] = lds128(l16 + SL_V + m * 4096 + et * 512 + 512);
            PIN(11);
        }
        mma8(a, um.x, um.y, P[0][0]); mma8(b, um.x, um.y, P[0][1]);
#pragma unroll
        for (int m = 0; m <= MT; m++) {
            mma16(a, u[m].x, u[m].y, u[m].z, u[m].w, P[1 + 2 * m][0], P[2 + 2 * m][0]); mma16(b, u[m].x, u[m].y, u[m].z, u[m].w, P[1 + 2 * m][1], P[2 + 2 * m][1]);
        }
        asm volatile("stmatrix.sync.aligned.m8n8.x4.trans.shared.b16 [%0],{%1,%2,%3,%4};" ::"r"(os + (et >> 2) * 2048 + (et & 3) * 256),
                     "r"(pack2(a[0], a[1])), "r"(pack2(a[2], a[3])), "r"(pack2(b[0], b[1])), "r"(pack2(b[2], b[3])) : "memory");
    }
}

__device__ __forceinline__ void rec_tiles(uint32_t sb, int X, int head, uint32_t rank, int& nxt, int lim, int need) {
#pragma unroll 1
    while (nxt <= lim) {
        if ((nxt & 1) == 0) {
            unsigned v; int n = 0;
            while (true) {
                asm volatile("ld.relaxed.gpu.global.u32 %0,[%1];" : "=r"(v) : "l"(cnt_ptr(C_QKV + X * 32 + (nxt >> 1))) : "memory");
                if (__all_sync(0xffffffffu, v >= 2 * NQ)) break;
                if (nxt > need) return;
                if (++n > 3000000) __trap();
            }
        }
        if (elect()) {
            const uint32_t bar = sb + R_BAR + (RB_XFULL + X * 2 + (nxt & 1)) * 8, dst = sb + R_SL + (X * 2 + (nxt & 1)) * SLOT;
            const uint4* src = g_qkv + (size_t)((X * 64 + nxt) * 32 + head) * 1536;
            mbar_expect(bar, 20480);
            bulk_g2s_mc(dst + rank * 8192, src + 512 + rank * 512, 8192, bar, POL_LAST);
            bulk_g2s(dst + SL_Q, src + (rank ^ X) * 256, 4096, bar, POL_LAST);
        }
        __syncwarp();
        nxt++;
    }
}

__device__ __forceinline__ void rec_attn(const Params& p, uint32_t sb, int X, int head, uint32_t rank) {
    const int lane = __shfl_sync(0xffffffffu, threadIdx.x & 31, threadIdx.x & 31), g = lane >> 2, c = lane & 3;
    const int mt = rank ^ X;
    const uint32_t dp = mapa(sb, rank ^ 1) - sb;
    int nxt = 0;
    rec_tiles(sb, X, head, rank, nxt, 1, 0);
#pragma unroll 1
    for (int s = 0; s < 64; s++) {
        const uint32_t so = sb + R_SL + (X * 2 + (s & 1)) * SLOT;
        while (nxt <= min(s + 1, 63)) {
            uint32_t ok;
            asm volatile("{.reg .pred p; mbarrier.test_wait.parity.shared::cta.b64 p,[%1],%2; selp.u32 %0,1,0,p;}" : "=r"(ok) : "r"(sb + R_BAR + (RB_GO + X * 2 + (s & 1)) * 8), "r"((s >> 1) & 1) : "memory");
            if (__any_sync(0xffffffffu, ok)) break;
            rec_tiles(sb, X, head, rank, nxt, s + 1, -1);
        }
        mbar_wait(sb + R_BAR + (RB_GO + X * 2 + (s & 1)) * 8, (s >> 1) & 1);
        spin(DX);
        mbar_wait(sb + R_BAR + (RB_XFULL + X * 2 + (s & 1)) * 8, (s >> 1) & 1);
        if (elect()) asm volatile("cp.async.bulk.wait_group.read 0;" ::: "memory");
        __syncwarp();
        const uint32_t os = sb + R_OS + X * 4096 + (lane >> 4) * 1024 + (lane & 15) * 16;
        if (mt) xattn<1>(so + lane * 16, so + lane * 8, os, g, c); else xattn<0>(so + lane * 16, so + lane * 8, os, g, c);
        fence_async_smem();
        __syncwarp();
        const uint32_t svb = sb + R_BAR + (RB_SV + X * 2 + (s & 1)) * 8;
        if (elect()) {
            mbar_arrive(svb); mbar_arrive_cluster(svb + dp);
            const uint64_t pol = POL_SOON;
#pragma unroll
            for (int kb = 0; kb < 2; kb++)
                asm volatile("cp.async.bulk.global.shared::cta.bulk_group.L2::cache_hint [%0],[%1],%2,%3;" ::"l"(g_o + ((X * 32 + (s >> 1)) * 64 + head * 2 + kb) * 512 + ((s & 1) * 4 + mt * 2) * 64),
                             "r"(sb + R_OS + X * 4096 + kb * 2048), "r"(2048), "l"(pol) : "memory");
            asm volatile("cp.async.bulk.commit_group;" ::: "memory");
        }
        __syncwarp();
        if (s & 1) {
            if (elect()) { asm volatile("cp.async.bulk.wait_group 0;" ::: "memory"); red_relaxed(cnt_ptr(C_O + (X * 32 + (s >> 1)) * 4 + (head >> 3)), 1); }
            __syncwarp();
        }
        rec_tiles(sb, X, head, rank, nxt, min(s + 1, 63), s + 1);
        mbar_wait(svb, (s >> 1) & 1);
        rec_tiles(sb, X, head, rank, nxt, min(s + 2, 63), -1);
    }
}

__device__ __forceinline__ uint32_t timed_clear(unsigned* r, int lane) {
    uint32_t v = 0;
    const uint32_t t0 = clk32();
    asm volatile("{.reg .pred p; setp.eq.u32 p,%2,0; @p atom.relaxed.gpu.global.exch.b32 %0,[%1],0;}" : "+r"(v) : "l"(r), "r"(lane) : "memory");
    v = __shfl_sync(0xffffffffu, v, 0);
    asm volatile("{.reg .pred p; setp.eq.u32 p,%0,0x5a5a5a5b; @p nanosleep.u32 1;}" ::"r"(v) : "memory");
    return clk32() - t0;
}
__device__ __forceinline__ void rec_slots(int me, int X) {
    const int lane = threadIdx.x & 31;
#pragma unroll 1
    for (int i = lane; i < 512; i += 32) xregion(X, me)[i] = make_uint4(0, 0, 0, 0);
    if (lane < 16) xregion(X, 64 + (me & 1))[(lane >> 3) * 256 + (me >> 1) * 8 + (lane & 7)] = make_uint4(0, 0, 0, 0);
    __syncwarp();
    uint32_t sel = 0;
#pragma unroll 1
    for (int k = 0; k < 2; k++) {
        unsigned* r = (unsigned*)xregion(X, k ? 64 + (me & 1) : me) + k * (me >> 1) * 32;
        uint32_t b0 = ~0u, b1 = ~0u;
#pragma unroll 1
        for (int i = 0; i < 4; i++) { b0 = min(b0, timed_clear(r, lane)); b1 = min(b1, timed_clear(r + 1024, lane)); }
        sel |= (b1 < b0) << (2 * k + X);
    }
    if (lane == 0) ((uint16_t*)g_sel)[me * 2 + X] = sel;
}

__device__ __forceinline__ void rec_init(uint32_t sb) {
    const uint32_t b = sb + R_BAR;
    const int i = threadIdx.x & 31;
    mbar_init(b + i * 8, i >= RB_SV ? 2 : 1);
    if (i == RB_INIT) mbar_expect(b + RB_INIT * 8, 196608);
    asm volatile("fence.mbarrier_init.release.cluster;" ::: "memory");
}
constexpr int G_BAR = B_BAR;
enum { GB_FULL = 0  , GB_EMPTY = 8  , GB_RS = 16, GB_SS = 17, GB_LAG = 18, GB_FREE = 19, GB_DONE = 20  , GB_N = 24 };
constexpr int Q_PRE = 8;
constexpr int NQRS = 2 * NQ - 64;
__device__ __forceinline__ void gemm_init(uint32_t sb, bool op) {
    const int i = threadIdx.x & 31;
    if (i < GB_N) mbar_init(sb + G_BAR + i * 8, i >= GB_DONE ? 4 : i == GB_FREE ? 8 : (i >= GB_EMPTY && i < GB_RS) ? 2 : 1);
    if (i == GB_RS) mbar_expect(sb + G_BAR + i * 8, op ? 131072 : 98304);
    if (i == GB_SS) mbar_expect(sb + G_BAR + i * 8, op ? 131072 : 163840);
    asm volatile("fence.mbarrier_init.release.cluster;" ::: "memory");
}
__device__ __forceinline__ int qkv_blk(int id, int j) { return NQRS * 4 + id * 10 + j; }
__device__ __forceinline__ void qkv_fetch(const Params& p, uint32_t sb, int id, int j0, int j1) {
#pragma unroll 1
    for (int j = j0 * 2; j < j1 * 2; j++) {
        const int blk = min(qkv_blk(id, j >> 1), 511);
        tma2d(sb + j * 8192, &p.tn[blk >> 8], (blk & 255) * 16, (j & 1) * 256, sb + G_BAR + GB_SS * 8);
    }
}
__device__ __forceinline__ void qkv_stage(const Params& p, uint32_t dst, uint32_t bar, int id, int k0, int nk) {
#pragma unroll 1
    for (int j = 0; j < 2 * nk; j++) {
        const int u = id * 2 + (j >= nk);
        tma2d(dst + j * 8192, &p.tm[u < 64 ? 2 : 0], (u & 63) * 64, (k0 + (j >= nk ? j - nk : j)) * 64, bar);
    }
}
__device__ __forceinline__ void op_fetch(const Params& p, uint32_t sb, int id, int half) {
#pragma unroll 1
    for (int j = 0; j < 16; j++) tma2d(sb + j * 8192, &p.tm[4], ((id * 2 + (j >> 3)) & 7) * 64, (id >> 2) * 1024 + (j & 7) * 128 + half * 64, sb + G_BAR + (GB_RS + half) * 8);
}
template <bool OP>
__device__ __forceinline__ void gemm_producer(const Params& p, uint32_t sb, int id) {
    constexpr int NS = OP ? 6 : 8, SB = OP ? 16384 : 8192, RING = OP ? 131072 : 163840;
    if (!elect()) return;
    mbar_wait(sb + G_BAR + GB_FREE * 8, 0);
    if (OP) op_fetch(p, sb, id, 1);
    else {
        mbar_expect(sb + G_BAR + GB_RS * 8, 32768);
        qkv_stage(p, sb + 196608, sb + G_BAR + GB_RS * 8, id, 6, 2);
        qkv_fetch(p, sb, id, Q_PRE, 10);
        mbar_wait(sb + G_BAR + GB_FREE * 8, 1);
    }
    wait_cnt(g_gate, lds32(sb + S_GATE));
    int st = 0; uint32_t ph = 1;
#pragma unroll 1
    for (int n = 0; n < p.nl[OP]; n++) {
        const int e = p.list[OP][n];
        wait_cnt(OP ? cnt_ptr(C_O + e * 4 + (id >> 2)) : cnt_ptr(C_XN + e), 16);
        PROF(true, 1024 + n * 4);
        const uint4* src = OP ? g_o + (e * 64 + (id >> 2) * 16) * 512 : g_xn + e * 4096;
#pragma unroll 1
        for (int s = 0; s < 8; s++) {
            mbar_wait(sb + G_BAR + (GB_EMPTY + st) * 8, ph);
            mbar_expect(sb + G_BAR + (GB_FULL + st) * 8, SB);
            bulk_g2s(sb + RING + st * SB, src + s * (SB / 16), SB, sb + G_BAR + (GB_FULL + st) * 8, POL_N);
            if (++st == NS) { st = 0; ph ^= 1; }
        }
    }
}
template <bool OP>
__device__ __forceinline__ void gemm_release(const Params& p, uint32_t sb, int id, int n0) {
    if (!elect()) return;
#pragma unroll 1
    for (int n = n0; n < 2 * p.nl[OP]; n += OP ? 2 : 1) {
        const int e = p.list[OP][n >> 1];
        mbar_wait(sb + G_BAR + (GB_DONE + (n & 3)) * 8, (n >> 2) & 1);
        red_release(OP ? cnt_ptr(C_PP + e * 8 + (id & 3) * 2 + (n & 1)) : cnt_ptr(C_QKV + e), 1);
        PROF(n & 1, 1024 + (n >> 1) * 4 + 3);
    }
}
__device__ __forceinline__ void op_permute(uint32_t sb) {
#pragma unroll 2
    for (int i = threadIdx.x; i < 4096; i += 256) {
        const uint32_t a = sb + i * 32 + ((i >> 2) & 1) * 16, b = a ^ 16;
        const uint4 x = lds128(a), y = lds128(b);
        sts128(a, __byte_perm(x.x, x.y, 0x5410), __byte_perm(x.z, x.w, 0x5410), __byte_perm(y.x, y.y, 0x5410), __byte_perm(y.z, y.w, 0x5410));
        sts128(b, __byte_perm(x.x, x.y, 0x7632), __byte_perm(x.z, x.w, 0x7632), __byte_perm(y.x, y.y, 0x7632), __byte_perm(y.z, y.w, 0x7632));
    }
    fence_async_smem();
    bar_sync(1, 256);
}
template <bool OP>
__device__ __forceinline__ void gemm_consumer(const Params& p, uint32_t sb, int id, int w) {
    constexpr int NS = OP ? 6 : 8, SB = OP ? 16384 : 8192, RING = OP ? 131072 : 163840;
    const int lane = threadIdx.x & 31, wg = w >> 2, t = w & 3, u = id * 2 + wg;
    uint32_t a[128];
    mbar_wait(sb + G_BAR + GB_RS * 8, 0);
    PROF(threadIdx.x == 0, 3501);
    if (OP) op_permute(sb);
    const uint32_t wo = sb + (((lane >> 4) << 3) + (lane & 7)) * 128 + (((2 * t + ((lane >> 3) & 1)) ^ (lane & 7)) << 4);
#pragma unroll
    for (int ks = 0; ks < 32; ks++) {
        const uint4 v = ldsm4t(wo + ks * 2048 + (OP ? wg * 65536 : ks < 24 ? 131072 + wg * 49152 : 196608 - 49152 + wg * 16384));
        a[ks * 4] = v.x; a[ks * 4 + 1] = v.y; a[ks * 4 + 2] = v.z; a[ks * 4 + 3] = v.w;
        if (ks == 31 || (!OP && ks == 23)) {
            fence_async_smem();
            __syncwarp();
            if (lane == 0) mbar_arrive(sb + G_BAR + GB_FREE * 8);
            if (ks == 23) mbar_wait(sb + G_BAR + GB_RS * 8, 1);
        }
    }
    PROF(threadIdx.x == 0, 3502);
    mbar_wait(sb + G_BAR + GB_SS * 8, 0);
    if (OP) op_permute(sb);
    PROF(threadIdx.x == 0, 3503);
    float c0[32], c1[OP ? 32 : 40];
    int st = 0; uint32_t ph = 0;
    const bool el = (threadIdx.x & 127) == 0;
#pragma unroll 1
    for (int n = 0; n < p.nl[OP]; n++) {
        int prev = 0;
        const uint32_t wb = sb + wg * (OP ? 65536 : 81920) + (n & p.zero);
        const uint64_t dw = OP ? mkdesc(wb, 0, 1024, 1) : mkdesc(wb, 16384, 256, 3);
        if (!OP && wg) mbar_wait(sb + G_BAR + GB_LAG * 8, n & 1);
#pragma unroll
        for (int s = 0; s < 8; s++) {
            mbar_wait(sb + G_BAR + (GB_FULL + st) * 8, ph);
            const uint64_t dx = mkdesc(sb + RING + st * SB, 128, 1024, 0);
            wg_fence();
#pragma unroll
            for (int kk = 0; kk < 4; kk++) {
                const int ks = s * 4 + kk;
                if (ks == 0) { wgmma64_rs<0>(c0, a, dx); if (OP) wgmma64_ta<0>(c1, dw, dx + 512); else wgmma80_tb<0>(c1, dx, dw); }
                else { wgmma64_rs<1>(c0, a + ks * 4, dx + kk * 16); if (OP) wgmma64_ta<1>(c1, dw + ks * 128, dx + 512 + kk * 16); else wgmma80_tb<1>(c1, dx + kk * 16, dw + ks * 32); }
            }
            wg_commit();
            if (s) {
                wg_wait<1>();
                if (el) { mbar_arrive(sb + G_BAR + (GB_EMPTY + prev) * 8); if (!OP && s == QLAG && !wg) mbar_arrive(sb + G_BAR + GB_LAG * 8); }
            }
            prev = st;
            if (++st == NS) { st = 0; ph ^= 1; }
        }
        const int e = p.list[OP][n];
        wg_wait<0>();
        if (el) mbar_arrive(sb + G_BAR + (GB_EMPTY + prev) * 8);
        PROF(threadIdx.x == 128, 1024 + n * 4 + 1);
        if (OP) {
            uint4* dst = g_pp + (e * 4 + (id >> 2)) * 4096 + ((u & 7) * 32 + t * 8) * 16 + (lane >> 2) * 16 + (lane & 3);
#pragma unroll
            for (int j = 0; j < 4; j++) {
                const float* x = c0 + j * 8; const float* y = c1 + j * 8;
                stg128(dst + j * 4, make_uint4(pack2(x[0] + y[0], x[1] + y[1]), pack2(x[2] + y[2], x[3] + y[3]), pack2(x[4] + y[4], x[5] + y[5]), pack2(x[6] + y[6], x[7] + y[7])), POL_SOON);
            }
        } else {
            uint4* dst = g_qkv + (size_t)e * 2 * 32 * 1536 + lane;
            const uint64_t pol = POL_SOON;
#pragma unroll
            for (int j = 0; j < 4; j++) {
                const float* x = c0 + j * 8;
                uint4 v = make_uint4(pack2(x[0], x[1]), pack2(x[2], x[3]), pack2(x[4], x[5]), pack2(x[6], x[7]));
                if (u >= 64) v = make_uint4(movm(v.x), movm(v.z), movm(v.y), movm(v.w));
                stg128(dst + (((j >> 1) * 32 + ((u & 63) >> 1)) * 1536 + (u < 64 ? 1024 : 0) + (j & 1) * 256 + ((u & 1) * 4 + t) * 32), v, pol);
            }
#pragma unroll
            for (int j = 0; j < 5; j++) {
                const float* x = c1 + (OP ? 0 : j * 8);
                const int blk = qkv_blk(id, wg * 5 + j);
                if (blk < 512) stg128(dst + (((t >> 1) * 32 + ((blk >> 3) & 31)) * 1536 + (blk >> 8) * 512 + (t & 1) * 256 + (blk & 7) * 32),
                                      make_uint4(pack2(x[0], x[1]), pack2(x[2], x[3]), pack2(x[4], x[5]), pack2(x[6], x[7])), pol);
            }
        }
        __syncwarp();
        if (lane == 0) mbar_arrive(sb + G_BAR + (GB_DONE + (n & 1) * 2 + wg) * 8);
        PROF(threadIdx.x == 128, 1024 + n * 4 + 2);
    }
}

template <int NP, bool MMA>
__device__ __forceinline__ void sum_partials(float* x, const uint2* src, const uint32_t* r0, const uint32_t* r1, uint32_t idm, bool on) {
    uint2 v[4][NP];
#pragma unroll
    for (int s = 0; s < 4; s++)
#pragma unroll
        for (int i = 0; i < NP; i++) {
            if (MMA) {
                v[s][i] = make_uint2(0, 0);
                asm volatile("{.reg .pred p; setp.ne.u32 p,%4,0; @p ld.global.cg.L2::cache_hint.v2.u32 {%0,%1},[%2],%3;}" : "+r"(v[s][i].x), "+r"(v[s][i].y) : "l"(src + s * 8192 + i * 32), "l"(POL_LAST), "r"((uint32_t)on) : "memory");
            } else asm volatile("ld.global.cg.L2::cache_hint.v2.u32 {%0,%1},[%2],%3;" : "=r"(v[s][i].x), "=r"(v[s][i].y) : "l"(src + s * 8192 + i * 32), "l"(POL_LAST) : "memory");
        }
#pragma unroll
    for (int i = 0; i < NP; i++) {
        uint32_t a, b;
        if (MMA) {
            float t[4] = {0, 0, 0, 0};
            mma16(t, v[0][i].x, v[0][i].y, v[1][i].x, v[1][i].y, idm, idm); mma16(t, v[2][i].x, v[2][i].y, v[3][i].x, v[3][i].y, idm, idm);
            a = pack2(t[0], t[2]); b = pack2(t[1], t[3]);
        } else {
            a = pack2((blo(v[0][i].x) + blo(v[1][i].x)) + (blo(v[2][i].x) + blo(v[3][i].x)), (blo(v[0][i].y) + blo(v[1][i].y)) + (blo(v[2][i].y) + blo(v[3][i].y)));
            b = pack2((bhi(v[0][i].x) + bhi(v[1][i].x)) + (bhi(v[2][i].x) + bhi(v[3][i].x)), (bhi(v[0][i].y) + bhi(v[1][i].y)) + (bhi(v[2][i].y) + bhi(v[3][i].y)));
        }
        const uint32_t s0 = hadd2(a, r0[i]), s1 = hadd2(b, r1[i]);
        x[4 * i] = blo(s0); x[4 * i + 2] = bhi(s0); x[4 * i + 1] = blo(s1); x[4 * i + 3] = bhi(s1);
    }
}
__device__ __forceinline__ const uint2* pp_src(int e, int tile, int lane) { return (const uint2*)g_pp + e * 32768 + tile * 128 + (lane >> 3) * 8 + (lane & 3) * 2 + ((lane >> 2) & 1); }

__device__ __forceinline__ void fin_warp(const Params& p, uint32_t sb, int id) {
    const int tile = (id & ~1) + (threadIdx.x & 1), lane = (id & 1) * 16 + ((threadIdx.x & 31) >> 1);
    wait_cnt_warp(g_gate, lds32(sb + S_GATE));
#pragma unroll 1
    for (int e = 32; e < 64; e++) {
        wait_cnt_warp(cnt_ptr(C_PP + e * 8 + (id >> 3)), 4);
        const uint4* rp = g_x + ((128 + tile * 2) * XP + (e - 32) * 32 + lane);
        uint32_t o0[4], o1[4];
#pragma unroll
        for (int h = 0; h < 2; h++) {
            const uint4 r = ldcg128(rp + h * XP);
            const uint32_t a[2] = {r.x, r.y}, b[2] = {r.z, r.w};
            float x[8];
            sum_partials<2, false>(x, pp_src(e, tile, lane) + h * 64, a, b, 0, true);
#pragma unroll
            for (int i = 0; i < 2; i++) {
                o0[h * 2 + i] = __byte_perm(__float_as_uint(x[4 * i]), __float_as_uint(x[4 * i + 2]), 0x7632);
                o1[h * 2 + i] = __byte_perm(__float_as_uint(x[4 * i + 1]), __float_as_uint(x[4 * i + 3]), 0x7632);
            }
        }
        uint4* dst = (uint4*)p.out + ((e - 32) * 64 + lane * 2) * 64 + tile;
        dst[0] = make_uint4(o0[0], o0[1], o0[2], o0[3]); dst[64] = make_uint4(o1[0], o1[1], o1[2], o1[3]);
        PROF((threadIdx.x & 31) == 0, 1536 + e);
    }
}

constexpr int PROW = 272, UROW = 2304, UPRE = 256;
constexpr int C_UR = 0  , C_TB = 65536  , C_BG = C_TB + 51200,
              CB_M = 8960, CB_U = CB_M + 1792, CB_BIG = CB_U + 2560, C_ST = C_BG + 8 * CB_BIG  ;
static_assert(C_ST + 4736 <= B_BAR, "smem map");
enum { CB_TB = 0, CB_UF = 1  , CB_CF = 5  , CB_LD = 9   };
__device__ __forceinline__ void conv_init(uint32_t sb, bool spare) {
    const int i = threadIdx.x & 31;
    mbar_init(sb + B_BAR + i * 8, (i >= CB_UF && i < CB_CF && !spare) ? 2 : 1);
    if (i == CB_TB && !spare) mbar_expect(sb + B_BAR + i * 8, 51200);
    asm volatile("fence.mbarrier_init.release.cluster;" ::: "memory");
}
__device__ __forceinline__ void mma_q(float* c, const uint32_t* a, const uint4& q) {
    mma16(c, a[0], a[1], a[2], a[3], q.x, q.y); mma16(c, a[4], a[5], a[6], a[7], q.z, q.w);
}
__device__ __forceinline__ uint2 ld_acc(const uint2* p, bool on) {
    uint2 v = make_uint2(0, 0);
    asm volatile("{.reg .pred p; setp.ne.u32 p,%3,0; @p ld.global.cg.v2.u32 {%0,%1},[%2];}" : "+r"(v.x), "+r"(v.y) : "l"(p), "r"((uint32_t)on) : "memory");
    return v;
}
__device__ __forceinline__ void add_acc(float* c, uint2 v) { c[0] += blo(v.x); c[1] += bhi(v.x); c[2] += blo(v.y); c[3] += bhi(v.y); }
__device__ __forceinline__ void st_acc(uint2* p, const float* c) { *p = make_uint2(pack2(c[0], c[1]), pack2(c[2], c[3])); }
__device__ __forceinline__ float sum8(const uint4* v, int k) {
#define VK(i) __uint_as_float(k == 0 ? v[i].x : k == 1 ? v[i].y : k == 2 ? v[i].z : v[i].w)
    return ((VK(0) + VK(1)) + (VK(2) + VK(3))) + ((VK(4) + VK(5)) + (VK(6) + VK(7)));
}
template <int XW>
__device__ __forceinline__ void stats_send(uint32_t l16, const float* x, uint4* gs, int q, int w) {
    float s0 = 0, s1 = 0, m0 = 0, m1 = 0;
#pragma unroll
    for (int i = 0; i < 8; i++) { s0 += x[2 * i]; s1 += x[2 * i + 1]; m0 = fmaf(x[2 * i], x[2 * i], m0); m1 = fmaf(x[2 * i + 1], x[2 * i + 1], m1); }
    sts128(l16 + C_ST + w * 512, __float_as_uint(s0), __float_as_uint(m0), __float_as_uint(s1), __float_as_uint(m1));
    if (w == XW) {
        bar_sync(2, 256);
        uint4 v[8];
#pragma unroll
        for (int i = 0; i < 8; i++) v[i] = lds128(l16 + C_ST + i * 512);
        st_rlx128(gs + q * 32, __float_as_uint(sum8(v, 0)), __float_as_uint(sum8(v, 1)) & 0x7fffffffu, __float_as_uint(sum8(v, 2)), __float_as_uint(sum8(v, 3)));
    } else bar_arrive(2, 256);
}
template <int XW>
__device__ __forceinline__ float4 stats_recv(uint32_t l16, const uint4* gs, int w) {
    if (w == XW) {
        uint4 v[8];
        int n = 0;
        while (true) {
            uint32_t bad = 0;
#pragma unroll
            for (int i = 0; i < 8; i++) v[i] = ld_rlx128(gs + i * 32);
#pragma unroll
            for (int i = 0; i < 8; i++) bad |= v[i].y;
            if (!__any_sync(0xffffffffu, bad >> 31)) break;
            if (++n > 2000000) __trap();
        }
        const float s0 = sum8(v, 0) * (1.f / 512.f), s1 = sum8(v, 2) * (1.f / 512.f);
        const float2 l0 = ln_finish(s0, fmaxf(fmaf(sum8(v, 1), 1.f / 512.f, -s0 * s0), 0.f)), l1 = ln_finish(s1, fmaxf(fmaf(sum8(v, 3), 1.f / 512.f, -s1 * s1), 0.f));
        sts128(l16 + C_ST + 4096, __float_as_uint(l0.x), __float_as_uint(rcp(l0.y)), __float_as_uint(l1.x), __float_as_uint(rcp(l1.y)));
    }
    bar_sync(3, 256);
    const uint4 r = lds128(l16 + C_ST + 4096);
    return make_float4(__uint_as_float(r.x), __uint_as_float(r.y), __uint_as_float(r.z), __uint_as_float(r.w));
}

#define HOIST_STOP(k) asm volatile("{.reg .pred p; setp.eq.u32 p,%0,%1; @p nanosleep.u32 1;}" ::"r"(zero), "r"((k) + 1) : "memory")
__device__ __forceinline__ void conv_near(float (*acc)[4], uint32_t ta, uint32_t qa, uint32_t zero) {
#pragma unroll
    for (int k = 0; k < 8; k++) {
        uint32_t a[8];
#pragma unroll
        for (int j = 0; j < 8; j++) a[j] = lds32(ta + k * 800 + j * 32);
        mma_q(acc[k], a, ldsm4(qa + k * 1024));
        if (k % NFE == NFE - 1 && k < 7) HOIST_STOP(k);
    }
}
template <int K0>
__device__ __forceinline__ void conv_pair(float (*acc)[4], float (*pend)[4], uint32_t ta, uint32_t q0, uint32_t q1, uint32_t q2, uint32_t zero) {
#pragma unroll
    for (int i = 0; i < 4; i++) {
        const int k = K0 + i;
#pragma unroll
        for (int e = 0; e < 4; e++) { acc[4 - K0 + i][e] += pend[i][e]; pend[i][e] = 0; }
        uint32_t a[16];
#pragma unroll
        for (int j = 0; j < 16; j++) a[j] = lds32(ta + 256 + k * 800 + j * 32);
        const uint4 x1 = ldsm4(q1 + k * 1024);
        mma_q(acc[k], a, x1); mma_q(pend[i], a, ldsm4(q2 + k * 1024));
        mma_q(pend[i], a + 8, x1); mma_q(acc[k], a + 8, ldsm4(q0 + k * 1024));
        if (i % NFP == NFP - 1 && i < 3) HOIST_STOP(k);
    }
}

__device__ __forceinline__ void conv_tile(const Params& p, uint32_t sb, int q, int w) {
    const int lane = __shfl_sync(0xffffffffu, threadIdx.x & 31, threadIdx.x & 31), g = lane >> 2, c = lane & 3, tile = q * 8 + w;
    const uint32_t l16 = sb + lane * 16;
#pragma unroll
    for (int i = 0; i < 16; i++) sts128(l16 + C_UR + w * 8192 + i * 512, 0, 0, 0, 0);
    wait_cnt_warp(g_gate, lds32(sb + S_GATE));
    if (lane < 8) bulk_g2s(sb + C_TB + (w * 8 + lane) * 800, g_P + (tile * 8 + lane) * PROW + 72, 800, sb + B_BAR + CB_TB * 8, POL_N);
    uint32_t A[8][8];
#pragma unroll
    for (int k = 0; k < 8; k++)
#pragma unroll
        for (int j = 0; j < 8; j++) A[k][j] = __ldcg(g_P + (tile * 8 + k) * PROW + 16 + 8 * j + g - 2 * c);
    if (lane == 0) { const uint4 d = __ldg((const uint4*)p.Dskip + tile); sts128(sb + C_ST + 4608 + w * 16, d.x, d.y, d.z, d.w); }
    float acc[8][4], pend[4][4];
#pragma unroll
    for (int k = 0; k < 8; k++) acc[k][0] = acc[k][1] = acc[k][2] = acc[k][3] = pend[k & 3][k >> 2] = pend[k & 3][2 + (k >> 2)] = 0;
    const uint32_t row = sb + C_UR + w * 8192, ta = sb + C_TB + w * 6400 + (8 + g - 2 * c) * 4, zero = p.zero, qo = (lane & 7) * 16 - (lane >> 3) * 32;
    bar_sync(4, 384);
    mbar_wait(sb + B_BAR + CB_TB * 8, 0);
#pragma unroll 1
    for (int b = -2; b < 32; b++) {
        const int lz = lane + (b & p.zero);
        const bool on = b >= 0;
        uint4 r0 = make_uint4(0, 0, 0, 0), r1 = r0;
        asm volatile("{.reg .pred p; setp.ge.s32 p,%9,0; @p ld.global.cg.v4.u32 {%0,%1,%2,%3},[%8]; @p ld.global.cg.v4.u32 {%4,%5,%6,%7},[%8+%10];}"
                     : "+r"(r0.x), "+r"(r0.y), "+r"(r0.z), "+r"(r0.w), "+r"(r1.x), "+r"(r1.y), "+r"(r1.z), "+r"(r1.w) : "l"(g_x + (tile * 2 * XP + b * 32 + lz)), "r"(b), "n"(XP * 16) : "memory");
        const uint32_t q1 = row + ((qo + (b - 1) * 128) & 1023);
        if (w == 0) conv_near(acc, ta, q1, zero);
        PROF(threadIdx.x == 0 && on, 2048 + b * 8);
        const uint2* pps = pp_src(b, tile, lz);
        asm volatile("" : "+l"(pps));
        wait_flag_warp(cnt_ptr(C_PP + b * 8 + q), on ? 4 : 0);
        PROF(threadIdx.x == 0 && on, 2048 + b * 8 + 1);
        float x[16];
        {
            const uint32_t a[4] = {r0.x, r0.y, r1.x, r1.y}, bb[4] = {r0.z, r0.w, r1.z, r1.w};
            sum_partials<4, true>(x, pps, a, bb, (2 * (lz & 3) == lz >> 2) ? 0x00003f80u : (2 * (lz & 3) + 1 == lz >> 2) ? 0x3f800000u : 0u, on);
        }
        stats_send<0>(l16, x, g_st + (b + 2) * 256 + lz, q, w);
        {
            PROF(threadIdx.x == 0 && on, 2048 + b * 8 + 2);
            if (on) mbar_wait(sb + B_BAR + (CB_CF + (w >> 1)) * 8, b & 1);
            const uint2* cb = g_carry + ((tile * 320 + b) * 32 + lz);
            uint2 cr[8];
#pragma unroll
            for (int k = 0; k < 8; k++) cr[k] = ld_acc(cb + k * 1280, b >= 4);
            if (w && b) conv_near(acc, ta, q1, zero);
#pragma unroll
            for (int k = 0; k < 8; k++) add_acc(acc[k], cr[k]);
        }
        float4 ln = stats_recv<0>(l16, g_st + (b + 2) * 256 + lz, w);
        PROF(threadIdx.x == 0 && on, 2048 + b * 8 + 3);
        uint32_t u[8];
#pragma unroll
        for (int k = 0; k < 8; k++) {
            u[k] = pack2(rbf(x[2 * k] - ln.x) * ln.y, rbf(x[2 * k + 1] - ln.z) * ln.w);
            sts32(row + k * 1024 + (b & 7) * 128 + lane * 4, u[k]);
        }
        __syncwarp();
        const uint32_t qa = row + ((qo + b * 128) & 1023);
#pragma unroll
        for (int k = 0; k < 8; k++) mma_q(acc[k], A[k], ldsm4(qa + k * 1024));
        const uint4 dk = lds128(sb + C_ST + 4608 + w * 16);
#pragma unroll
        for (int k = 0; k < 8; k++) {
            const float t = __shfl_sync(0xffffffffu, acc[k][3], (lz & ~3) | ((lz - 1) & 3));
            const uint32_t y = movm(pack2(acc[k][0] + (c ? t : 0.f), acc[k][1] + acc[k][2]));
            acc[k][0] = c ? 0.f : t; acc[k][1] = acc[k][2] = acc[k][3] = 0;
            const uint32_t dw = k >> 1 == 0 ? dk.x : k >> 1 == 1 ? dk.y : k >> 1 == 2 ? dk.z : dk.w;
            const uint32_t s = hadd2(hadd2(y, hmul2(u[k], __byte_perm(dw, 0, (k & 1) ? 0x3232 : 0x1010))), __byte_perm(__float_as_uint(x[2 * k]), __float_as_uint(x[2 * k + 1]), 0x7632));
            x[2 * k] = blo(s); x[2 * k + 1] = bhi(s);
        }
        arrive_if(sb + B_BAR + (CB_UF + (w >> 1)) * 8, lz, b < -1 ? 32 : 0);
        stats_send<1>(l16, x, g_st + (36 + b) * 256 + lz, q, w);
        {
            PROF(threadIdx.x == 0 && on, 2048 + b * 8 + 4);
            uint4* dst = g_x + ((128 + tile * 2) * XP + b * 32 + lz);
#pragma unroll
            for (int e = 0; e < 2; e++) {
                const float* y = x + e * 8;
                if (on) dst[e * XP] = make_uint4(__byte_perm(__float_as_uint(y[0]), __float_as_uint(y[2]), 0x7632), __byte_perm(__float_as_uint(y[4]), __float_as_uint(y[6]), 0x7632),
                                           __byte_perm(__float_as_uint(y[1]), __float_as_uint(y[3]), 0x7632), __byte_perm(__float_as_uint(y[5]), __float_as_uint(y[7]), 0x7632));
            }
            uint32_t* du = g_u + (tile * 8 * (UROW / 2) + UPRE / 2 + b * 32 + lz);
#pragma unroll
            for (int k = 0; k < 8; k++) if (on) du[k * (UROW / 2)] = u[k];
        }
#pragma unroll 1
        for (int pass = 0; pass < 2; pass++) {
            if (pass == (w == 1 || b < NLATE)) {
                const uint32_t q0 = row + ((qo + (b - 2) * 128) & 1023);
                if (b & 1) conv_pair<4>(acc, pend, ta, q0, q1, qa, zero); else conv_pair<0>(acc, pend, ta, q0, q1, qa, zero);
            }
            if (pass) break;
            ln = stats_recv<1>(l16, g_st + (36 + b) * 256 + lz, w);
            PROF(threadIdx.x == 0 && on, 2048 + b * 8 + 5);
            uint32_t o[2][4];
#pragma unroll
            for (int e = 0; e < 2; e++) {
                const float mu = e ? ln.z : ln.x, rs = e ? ln.w : ln.y;
#pragma unroll
                for (int i = 0; i < 4; i++) o[e][i] = pack2(rbf(x[4 * i + e] - mu) * rs, rbf(x[4 * i + 2 + e] - mu) * rs);
            }
#pragma unroll
            for (int i = 0; i < 4; i++) {
                const uint32_t t = __shfl_xor_sync(0xffffffffu, (lz & 1) ? o[0][i] : o[1][i], 1);
                if (lz & 1) o[0][i] = t; else o[1][i] = t;
            }
            uint4* dst = g_xn + ((32 + b) * 4096 + q * 512 + (lz >> 2) * 64 + w * 8 + (lz & 2) * 2 + (lz & 1));
            if (on) { dst[0] = make_uint4(o[0][0], o[0][1], o[0][2], o[0][3]); dst[2] = make_uint4(o[1][0], o[1][1], o[1][2], o[1][3]); }
            if (w == 7) {
                bar_sync(5, 256);
                if (elect()) red_release(cnt_ptr(on ? C_XN + 32 + b : C_FAR + 2), 2);
                PROF(lane == 0 && on, 2048 + b * 8 + 6);
                __syncwarp();
            } else bar_arrive(5, 256);
        }
    }
}

template <int P0, bool TRI = false>
__device__ __forceinline__ void bg_half(float (*acc)[4], uint4* win, uint32_t ta, uint32_t qa, uint32_t mask, uint32_t row) {
#pragma unroll
    for (int i = 0; i < 4; i++) {
        win[P0 + i] = ldsm4(((qa + i * 128) & mask) + row);
        const uint4 a = lds128(ta + (3 - i) * 448), e = lds128(ta + (3 - i) * 448 + 224);
#pragma unroll
        for (int r = TRI ? 7 - P0 - i : 0; r < 8; r++) mma16(acc[r], a.x, a.y, a.z, a.w, win[(P0 + i + 1 + r) & 7].x, win[(P0 + i + 1 + r) & 7].y);
#pragma unroll
        for (int r = TRI ? 7 - P0 - i : 0; r < 8; r++) mma16(acc[r], e.x, e.y, e.z, e.w, win[(P0 + i + 1 + r) & 7].z, win[(P0 + i + 1 + r) & 7].w);
    }
}
__device__ __forceinline__ void bg_fetch(uint32_t sb, int q, int j, int n, int lane) {
    const int b0 = n >> 1, ch = q * 64 + j * 16 + (n & 1) * 8 + (b0 & 7), lo = max(b0 - 24, -4), nu = b0 > 4 ? (b0 - 4 - lo) * 128 : 0;
    const uint32_t bar = sb + B_BAR + (CB_LD + j * 2 + (n & 1)) * 8, buf = sb + C_BG + (j * 2 + (n & 1)) * CB_BIG;
    const int nt = min(max((b0 + 7) >> 2, 2), 5) * 1792;
    if (elect()) {
        mbar_expect(bar, nt + nu + 1792);
        bulk_g2s(buf, g_W + ch * 784, nt, bar, POL_N);
        bulk_g2s(buf + CB_M, g_W + (ch ^ 4) * 784, 1792, bar, POL_N);
        if (nu) bulk_g2s(buf + CB_U + (lo - b0 + 24) * 128, g_u + ch * (UROW / 2) + UPRE / 2 + lo * 32, nu, bar, POL_N);
    }
    __syncwarp();
}
__device__ __forceinline__ void conv_back(uint32_t sb, int q, int j) {
    const int lane = __shfl_sync(0xffffffffu, threadIdx.x & 31, threadIdx.x & 31), g = lane >> 2, c = lane & 3;
    wait_cnt_warp(g_gate, lds32(sb + S_GATE));
    bg_fetch(sb, q, j, 0, lane);
    bar_sync(4, 384);
    const uint32_t to = (6 + g - 2 * c) * 16, qo = (lane & 7) * 16 - (lane >> 3) * 32;
#pragma unroll 1
    for (int n = 0; n < 64; n++) {
        const int b0 = n >> 1, i = n & 1, chl = j * 16 + i * 8 + (b0 & 7), hm = (b0 + 7) >> 2;
        const uint32_t buf = sb + C_BG + (j * 2 + i) * CB_BIG, ta = buf + to;
        float acc[8][4];
        uint4 win[8];
        if (n < 63) bg_fetch(sb, q, j, n + 1, lane);
        if (n == 34 || n == 42) wait_flag_warp(cnt_ptr(C_FAR + (n == 42)), 12);
        mbar_wait(sb + B_BAR + (CB_LD + j * 2 + i) * 8, b0 & 1);
#pragma unroll
        for (int r = 0; r < 8; r++) {
            acc[r][0] = acc[r][1] = acc[r][2] = acc[r][3] = 0;
            win[r] = make_uint4(0, 0, 0, 0);
            if (r) asm volatile("{.reg .pred p; setp.ge.s32 p,%5,24; @p ldmatrix.sync.aligned.m8n8.x4.shared.b16 {%0,%1,%2,%3},[%4];}"
                                : "+r"(win[r].x), "+r"(win[r].y), "+r"(win[r].z), "+r"(win[r].w) : "r"(buf + CB_U + qo + r * 128), "r"(b0 + r) : "memory");
        }
        const uint2* fr = g_far + (((q * 64 + chl) * 8 + b0 - 24) * 32 + lane);
        uint2* cr = g_carry + (((q * 64 + chl) * 40 + b0) * 32 + lane);
        uint2* cm = g_carry + (((q * 64 + (chl ^ 4)) * 40 + b0) * 32 + lane);
        const uint32_t fm = 0xff000000u >> b0;
        uint2 pf[8], pm[4];
#pragma unroll
        for (int r = 0; r < 8; r++) pf[r] = ld_acc(fr + r * 32, (fm >> r) & 1);
#pragma unroll
        for (int r = 0; r < 4; r++) pm[r] = ld_acc(cm + r * 32, b0 > 4);
#pragma unroll 1
        for (int h = hm > 3 ? 5 : 3; h >= 3; h -= 2) {
            if (h <= hm) bg_half<0>(acc, win, ta + (h - 1) * 1792, qo + (28 - 4 * h) * 128, ~0u, buf + CB_U);
            if (h == 3 && i == 0) mbar_wait(sb + B_BAR + (CB_UF + j) * 8, b0 & 1);
            bg_half<4>(acc, win, ta + (h - 2) * 1792, qo + (h == 3 ? b0 - 4 : 12) * 128, h == 3 ? 1023u : ~0u, h == 3 ? sb + C_UR + chl * 1024 : buf + CB_U);
        }
        uint4 wm[8];
#pragma unroll
        for (int r = 1; r < 8; r++) wm[r] = ldsm4(sb + C_UR + (chl ^ 4) * 1024 + ((qo + (b0 + r) * 128) & 1023));
#pragma unroll
        for (int r = 0; r < 8; r++) add_acc(acc[r], pf[r]);
#pragma unroll
        for (int r = 4; r < 8; r++) { st_acc(cr + r * 32, acc[r]); acc[r][0] = blo(pm[r - 4].x); acc[r][1] = bhi(pm[r - 4].x); acc[r][2] = blo(pm[r - 4].y); acc[r][3] = bhi(pm[r - 4].y); }
#pragma unroll
        for (int t = 7; t >= 0; t--) {
            const uint4 a = lds128(ta + t * 224), e = lds128(ta + CB_M + t * 224);
#pragma unroll
            for (int r = 0; r < 4; r++) { const uint4& x = win[4 + r - (t >> 1)]; mma16(acc[r], a.x, a.y, a.z, a.w, (t & 1) ? x.z : x.x, (t & 1) ? x.w : x.y); }
#pragma unroll
            for (int r = 0; r < 4; r++) { const uint4& x = wm[4 + r - (t >> 1)]; mma16(acc[4 + r], e.x, e.y, e.z, e.w, (t & 1) ? x.z : x.x, (t & 1) ? x.w : x.y); }
        }
#pragma unroll
        for (int r = 0; r < 4; r++) { st_acc(cr + r * 32, acc[r]); st_acc(cm + r * 32, acc[4 + r]); }
        __syncwarp();
        if (lane == 0 && i) mbar_arrive(sb + B_BAR + (CB_CF + j) * 8);
        PROF(j == 0 && lane == 0 && i, 2048 + b0 * 8 + 7);
    }
}
__device__ __forceinline__ void conv_far(uint32_t sb, int w) {
    const int lane = __shfl_sync(0xffffffffu, threadIdx.x & 31, threadIdx.x & 31), g = lane >> 2, c = lane & 3;
    wait_cnt_warp(g_gate, lds32(sb + S_GATE));
    wait_cnt_warp(cnt_ptr(C_XN + 39), 16);
    const uint32_t to = (6 + g - 2 * c) * 16, qo = (lane & 7) * 16 - (lane >> 3) * 32;
#pragma unroll 1
    for (int n = -1; n * 12 + w < 512; n++) {
        const int t = n * 12 + w, ch = (t & 63) * 8 + (((t >> 6) + 1) & 7), cn = ((t + 12) & 63) * 8 + ((((t + 12) >> 6) + 1) & 7);
        const uint32_t bar = sb + B_BAR + (w * 2 + (n & 1)) * 8, buf = sb + (w * 2 + (n & 1)) * 5120;
        if (t + 12 < 512 && elect()) {
            const uint32_t nb = sb + (w * 2 + (~n & 1)) * 5120;
            mbar_expect(bar ^ 8, 3584 + 1152);
            bulk_g2s(nb, g_W + cn * 784 + 560, 3584, bar ^ 8, POL_N);
            bulk_g2s(nb + 3584, g_u + cn * (UROW / 2) + UPRE / 2 - 32, 1152, bar ^ 8, POL_N);
        }
        __syncwarp();
        if (n < 0) continue;
        float acc[8][4];
        uint4 win[8];
#pragma unroll
        for (int r = 0; r < 8; r++) { acc[r][0] = acc[r][1] = acc[r][2] = acc[r][3] = 0; win[r] = make_uint4(0, 0, 0, 0); }
        mbar_wait(bar, (n >> 1) & 1);
        bg_half<0, true>(acc, win, buf + to + 1792, qo + 128, ~0u, buf + 3584);
        bg_half<4, true>(acc, win, buf + to, qo + 640, ~0u, buf + 3584);
#pragma unroll
        for (int r = 0; r < 8; r++) st_acc(g_far + (ch * 256 + lane) + r * 32, acc[r]);
        __syncwarp();
        if (((t + 12) ^ t) >= 256 && elect()) red_release(cnt_ptr(C_FAR + (t >> 8)), 1);
        __syncwarp();
    }
    PROF(threadIdx.x == 0, 2048);
}

constexpr int P_X = 131072  , P_K6 = P_X + 32768  , P_P = P_K6 + 10496  , P_U = P_P + 33280  ,
              P_END = P_U + 17408, P_PRM = P_P + 8192  , P_Y = P_P  ;
static_assert(P_END <= B_BAR && P_END <= R_SEL, "prologue scratch");
#define KGUN 2
constexpr int KGU = KGUN;
__device__ __forceinline__ void csq(float& r, float& i) { const float t = r * i; r = fmaf(r, r, -(i * i)); i = t + t; }
__device__ __forceinline__ void cpow(float ar, float ph, float p, float& r, float& i) {
    const float e = ex2(ar * p);
    const float u = ph * p, n = fabsf(u) < 4194304.f ? (u + 12582912.f) - 12582912.f : u;
    const float t = (u - n) * 6.283185307179586f;
    r = e * __cosf(t); i = e * __sinf(t);
}
__device__ __forceinline__ void mma_tf32(float* c, float a0, float a1, float a2, float a3, float b0, float b1) {
    asm volatile("mma.sync.aligned.m16n8k8.row.col.f32.tf32.tf32.f32 {%0,%1,%2,%3},{%4,%5,%6,%7},{%8,%9},{%0,%1,%2,%3};"
                 : "+f"(c[0]), "+f"(c[1]), "+f"(c[2]), "+f"(c[3])
                 : "r"(__float_as_uint(a0)), "r"(__float_as_uint(a1)), "r"(__float_as_uint(a2)), "r"(__float_as_uint(a3)), "r"(__float_as_uint(b0)), "r"(__float_as_uint(b1)));
}

__device__ __forceinline__ void early_fetch(const Params& p, uint32_t sb) {
    const int v = blockIdx.x;
    if (elect()) {
        if (v >= V_QKV) { if (v < V_QKV + NQ && (p.roles & 8)) qkv_fetch(p, sb, v - V_QKV, 0, Q_PRE); }
        else if (v >= V_OP) { if (p.roles & 4) op_fetch(p, sb, v - V_OP, 0); }
        else if (v >= V_REC && (p.roles & 2)) { rec_fetch(p, sb, (v - V_REC) >> 1, v & 1, 0, R_STQ); rec_fetch(p, sb, (v - V_REC) >> 1, v & 1, 2, R_STV); }
    }
    __syncwarp();
}
struct ProRegs { uint32_t v[2][4], ldt[2]; };
__device__ __forceinline__ void prologue_load(const ProArgs& a, int b, ProRegs& pr) {
    const int w = threadIdx.x >> 5;
#pragma unroll
    for (int i = 0; i < 2; i++) {
        const int gi = b * 512 + (w & 3) * 128 + ((w >> 2) & 1) * 64 + i * 32 + (threadIdx.x & 31);
        pr.ldt[i] = __ldg((const uint16_t*)a.ldt + b * 4 + (w & 3));
        pr.v[i][0] = __ldg((const uint16_t*)a.lAr + gi); pr.v[i][1] = __ldg((const uint16_t*)a.Ai + gi);
        pr.v[i][2] = __ldg((const uint16_t*)a.Cr + gi); pr.v[i][3] = __ldg((const uint16_t*)a.Ci + gi);
    }
}
__device__ __forceinline__ void prologue(const Params& p, uint32_t sb, int b, int w, const ProRegs& pr) {
    const ProArgs& a = p.pa;
    const int tid = threadIdx.x, lane = tid & 31, g = lane >> 2, c = lane & 3;
    const int d0 = b * 4;
    if (w >= 8) {
        const int t2 = tid - 256;
        if (w < 10) {
            const int row = b * 16 + (w - 8) * 8 + g;
            uint4 v[16];
            const float2 r = row_stats512(v, (const uint4*)(a.x + (size_t)row * 512) + c, 8, 4);
            const float2 l = ln_finish(r.x * (1.f / 512.f), r.y * (1.f / 512.f));
            if (c == (g >> 1)) asm volatile("st.relaxed.gpu.global.u32 [%0],%1;" ::"l"(g_ln0 + row), "r"(pack2(l.x, l.y)) : "memory");
        }
        else if (b + 4 >= V_REC && b + 4 < V_OP) rec_slots(b + 4 - V_REC, w - 10);
        PROF(t2 == 0, 3516);
        const int gi = b * 128 + t2;
        g_st[gi] = make_uint4(~0u, ~0u, ~0u, ~0u);
        if (gi < 1024) g_st[16384 + gi] = make_uint4(~0u, ~0u, ~0u, ~0u);
        if (gi < 900 * 8) g_cnt[gi] = 0;
        bar_sync(6, 384);
        if (lane < 4 && ((PFM >> (w - 8)) & 1)) asm volatile("cp.async.bulk.prefetch.L2.global [%0],%1;" ::"l"(a.W[w - 8] + (b * 4 + lane) * 4096), "r"(8192) : "memory");
        bar_sync(9, 384);
        if (w == 10) early_fetch(p, sb);
#pragma unroll 2
        for (int i = t2; i < 4 * 784; i += 128) {
            const int ch = i / 784, k = i - ch * 784;
            const uint32_t o = sb + P_P + (ch * 2080 + 266 + (k / 14) * 18 + k) * 4;
            g_W[d0 * 784 + i] = make_uint4(lds32(o), lds32(o + 32), lds32(o + 64), lds32(o + 96));
        }
        bar_arrive(10, 384);
        PROF(t2 == 0, 3517);
        return;
    }
#pragma unroll
    for (int i = 0; i < 2; i++) {
        const float dt = rbf(expf(blo(pr.ldt[i])));
        const float ar = -rbf(expf(blo(pr.v[i][0]))) * dt, ai = blo(pr.v[i][1]) * dt;
        sts128(sb + P_PRM + (w * 64 + i * 32 + lane) * 16, __float_as_uint(ar * 1.4426950408889634f), __float_as_uint(ai * 0.15915494309189535f),
               __float_as_uint(2.f * (blo(pr.v[i][2]) * dt)), __float_as_uint(2.f * (blo(pr.v[i][3]) * dt)));
    }
    if (tid < 64) sts128(sb + P_U + (tid >> 3) * 2176 + (tid & 7) * 16, 0, 0, 0, 0);
    bar_arrive(6, 384);
    __syncwarp();
    PROF(tid == 0, 3510);
    const int ch = w & 3, hf = w >> 2;
    {
        float k0[4] = {0, 0, 0, 0}, k1[4] = {0, 0, 0, 0}, k2[4] = {0, 0, 0, 0}, k3[4] = {0, 0, 0, 0}, k4[4] = {0, 0, 0, 0}, kl = 0;
#pragma unroll KGU
        for (int j = 0; j < 16; j++) {
            const uint4 q = lds128(sb + P_PRM + (w * 64 + j * 4 + c) * 16);
            const float cr = __uint_as_float(q.z), ci = __uint_as_float(q.w);
            float wr[4], wi[4], vr[4], vi[4];
            cpow(__uint_as_float(q.x), __uint_as_float(q.y), (float)g, wr[0], wi[0]);
            cpow(__uint_as_float(q.x), __uint_as_float(q.y), (float)(g + 8), vr[0], vi[0]);
#pragma unroll
            for (int i = 1; i < 4; i++) { wr[i] = wr[i - 1]; wi[i] = wi[i - 1]; csq(wr[i], wi[i]); vr[i] = vr[i - 1]; vi[i] = vi[i - 1]; csq(vr[i], vi[i]); }
            float hr = wr[3], hi = wi[3];
            csq(hr, hi);
            mma_tf32(k0, wr[0], vr[0], wi[0], vi[0], cr * hr - ci * hi, -(cr * hi + ci * hr));
            hr = vr[3]; hi = vi[3]; csq(hr, hi);
            mma_tf32(k1, wr[0], vr[0], wi[0], vi[0], cr * hr - ci * hi, -(cr * hi + ci * hr));
            csq(hr, hi);
            mma_tf32(k2, wr[1], vr[1], wi[1], vi[1], cr * hr - ci * hi, -(cr * hi + ci * hr));
            csq(hr, hi);
            mma_tf32(k3, wr[2], vr[2], wi[2], vi[2], cr * hr - ci * hi, -(cr * hi + ci * hr));
            csq(hr, hi);
            mma_tf32(k4, wr[3], vr[3], wi[3], vi[3], cr * hr - ci * hi, -(cr * hi + ci * hr));
            csq(hr, hi);
            kl += cr * hr - ci * hi;
        }
        kl += __shfl_xor_sync(0xffffffffu, kl, 1); kl += __shfl_xor_sync(0xffffffffu, kl, 2);
        const uint32_t o = sb + P_K6 + (ch * 656 + c * 32 + g) * 4, ol = sb + P_K6 + (ch * 656 + 640) * 4;
#define KST(k, base) sts32(o + (base) * 4, __float_as_uint(k[0])); sts32(o + (base) * 4 + 64, __float_as_uint(k[1])); \
                     sts32(o + (base) * 4 + 32, __float_as_uint(k[2])); sts32(o + (base) * 4 + 96, __float_as_uint(k[3]))
#define KAD(k, base) k[0] += __uint_as_float(lds32(o + (base) * 4)); k[1] += __uint_as_float(lds32(o + (base) * 4 + 64)); \
                     k[2] += __uint_as_float(lds32(o + (base) * 4 + 32)); k[3] += __uint_as_float(lds32(o + (base) * 4 + 96))
        if (hf == 0) {
            bar_sync(2 + ch, 64);
            KAD(k0, 0); KAD(k1, 128); KAD(k2, 256); KAD(k3, 384); KAD(k4, 512);
            kl += __uint_as_float(lds32(ol));
            __syncwarp();
        }
        KST(k0, 0); KST(k1, 128); KST(k2, 256); KST(k3, 384); KST(k4, 512);
        if (lane == 0) sts32(ol, __float_as_uint(kl));
        if (hf == 1) { __syncwarp(); bar_arrive(2 + ch, 64); }
    }
    PROF(tid == 0, 3511);
    {
        uint4 l0, l1;
        int n = 0;
        while (true) {
            l0 = ld_rlx128((const uint4*)g_ln0 + tid * 2); l1 = ld_rlx128((const uint4*)g_ln0 + tid * 2 + 1);
            if (__all_sync(0xffffffffu, l0.x && l0.y && l0.z && l0.w && l1.x && l1.y && l1.z && l1.w)) break;
            if (++n > 2000000) __trap();
        }
        sts128(sb + P_P + tid * 32, l0.x, l0.y, l0.z, l0.w); sts128(sb + P_P + tid * 32 + 16, l1.x, l1.y, l1.z, l1.w);
        bar_sync(8, 384);
        mbar_wait(sb + S_XBAR, 0);
        __syncwarp();
#pragma unroll 2
        for (int i = 0; i < 8; i++) {
            const int t = w * 256 + i * 32 + lane;
            const uint32_t ln = lds32(sb + P_P + t * 4);
            const uint2 x = lds64(sb + P_X + t * 16 + (b & 1) * 8);
            const float m = blo(ln), rs = rcp(bhi(ln));
            const uint32_t u0 = pack2(rbf(blo(x.x) - m) * rs, rbf(bhi(x.x) - m) * rs), u1 = pack2(rbf(blo(x.y) - m) * rs, rbf(bhi(x.y) - m) * rs);
            sts128(sb + P_X + t * 16, x.x, x.y, u0, u1);
            const uint32_t o = sb + P_U + ((t >> 3) & 1) * 2176 + ((t >> 4) + 8) * 16 + (t & 7) * 2;
            asm volatile("st.shared.u16 [%0],%1;" ::"r"(o), "h"((uint16_t)u0) : "memory");
            asm volatile("st.shared.u16 [%0],%1;" ::"r"(o + 4352), "h"((uint16_t)(u0 >> 16)) : "memory");
            asm volatile("st.shared.u16 [%0],%1;" ::"r"(o + 8704), "h"((uint16_t)u1) : "memory");
            asm volatile("st.shared.u16 [%0],%1;" ::"r"(o + 13056), "h"((uint16_t)(u1 >> 16)) : "memory");
        }
    }
    bar_sync(1, 256);
    PROF(tid == 0, 3512);
    if (tid < 64) sts32(sb + P_P + ((tid >> 4) * 2080 + (tid & 15)) * 4, 0);
#pragma unroll 1
    for (int x = tid; x < 2048; x += 512) {
        uint32_t pw[2][4];
#pragma unroll
        for (int h = 0; h < 2; h++) {
            const int y = x + h * 256;
            const int i0 = y <= 256 ? y : 256 + (int)((pack2((float)y, 0.f) & 0xffff) - 0x4380);
            const int i1 = y <= 256 ? max(y - 1, 0) : 256 + (int)((pack2((float)(y - 1), 0.f) & 0xffff) - 0x4380);
#pragma unroll
            for (int k = 0; k < 4; k++) {
                const float lo = __uint_as_float(lds32(sb + P_K6 + k * 2624 + i0 * 4)), hi = __uint_as_float(lds32(sb + P_K6 + k * 2624 + i1 * 4));
                pw[h][k] = pack2(lo, y ? hi : 0.f);
            }
        }
#pragma unroll
        for (int h = 0; h < 2; h++)
#pragma unroll
            for (int k = 0; k < 4; k++) sts32(sb + P_P + (k * 2080 + x + h * 256 + 16) * 4, pw[h][k]);
    }
    fence_async_smem();
    bar_arrive(9, 384);
    bar_sync(1, 256);
    if (tid < 4) {
        asm volatile("cp.async.bulk.global.shared::cta.bulk_group [%0],[%1],%2;" ::"l"(g_P + (d0 + tid) * PROW), "r"(sb + P_P + tid * 8320), "r"(PROW * 4) : "memory");
        asm volatile("cp.async.bulk.commit_group;" ::: "memory");
    }
    __syncwarp();
    PROF(tid == 0, 3513);
    {
        float acc[16][4];
#pragma unroll
        for (int j = 0; j < 16; j++) acc[j][0] = acc[j][1] = acc[j][2] = acc[j][3] = 0;
#pragma unroll 1
        for (int e = hf * 4; e < hf * 4 + 4; e++) {
            uint32_t B[16][2];
            const uint32_t ua = sb + P_U + ch * 4352 + ((lane >> 3) & 1) * 2176 + (8 + (lane >> 4) * 8 + (lane & 7) - e) * 16;
#pragma unroll
            for (int j = 0; j < 8; j++) { const uint4 v = ldsm4(ua + j * 256); B[2 * j][0] = v.x; B[2 * j][1] = v.y; B[2 * j + 1][0] = v.z; B[2 * j + 1][1] = v.w; }
            const uint32_t pa = sb + P_P + (ch * 2080 + 16 + e * 16 + g - 2 * c) * 4;
#pragma unroll
            for (int d = 0; d < 16; d++) {
                const uint32_t a0 = lds32(pa + d * 512), a1 = lds32(pa + d * 512 + 32), a2 = lds32(pa + d * 512 - 32);
#pragma unroll
                for (int j = d; j < 16; j++) mma16(acc[j], a0, a1, a2, a0, B[j - d][0], B[j - d][1]);
            }
        }
        PROF(tid == 0, 3514);
        const uint32_t o = sb + P_Y + (ch * 2560 + c * 40 + g) * 4;
        if (tid < 4) asm volatile("cp.async.bulk.wait_group 0;" ::: "memory");
        __syncwarp();
        bar_sync(10, 384);
        if (hf == 0) {
            bar_sync(2 + ch, 64);
#pragma unroll
            for (int j = 0; j < 16; j++) {
                acc[j][0] += __uint_as_float(lds32(o + j * 640)); acc[j][1] += __uint_as_float(lds32(o + j * 640 + 80));
                acc[j][2] += __uint_as_float(lds32(o + j * 640 + 32)); acc[j][3] += __uint_as_float(lds32(o + j * 640 + 112));
            }
        }
#pragma unroll
        for (int j = 0; j < 16; j++) {
            sts32(o + j * 640, __float_as_uint(acc[j][0])); sts32(o + j * 640 + 80, __float_as_uint(acc[j][1]));
            sts32(o + j * 640 + 32, __float_as_uint(acc[j][2])); sts32(o + j * 640 + 112, __float_as_uint(acc[j][3]));
        }
        if (hf == 1) bar_arrive(2 + ch, 64);
    }
    const uint2 dk = __ldg((const uint2*)(a.Dk + d0));
    bar_sync(1, 256);
#pragma unroll 2
    for (int i = 0; i < 8; i++) {
        const int t = i * 256 + tid;
        const uint32_t o = sb + P_Y + (t + 4 * (t >> 4)) * 4;
        const uint4 xu = lds128(sb + P_X + t * 16);
        float y[4];
#pragma unroll
        for (int k = 0; k < 4; k++) y[k] = rbf(__uint_as_float(lds32(o + k * 10240)));
        uint2 r;
        r.x = pack2(blo(xu.x) + rbf(y[0] + rbf(blo(xu.z) * blo(dk.x))), bhi(xu.x) + rbf(y[1] + rbf(bhi(xu.z) * bhi(dk.x))));
        r.y = pack2(blo(xu.y) + rbf(y[2] + rbf(blo(xu.w) * blo(dk.y))), bhi(xu.y) + rbf(y[3] + rbf(bhi(xu.w) * bhi(dk.y))));
        ((uint2*)g_x)[b * 2 * XP + t] = r;
    }
    PROF(tid == 0, 3515);
}

__global__ void __cluster_dims__(2, 1, 1) __launch_bounds__(384, 1) main_kernel(const __grid_constant__ Params p) {
    extern __shared__ __align__(1024) uint8_t smem[];
    const uint32_t sb = smem_u32(smem);
    uint32_t rank; asm("mov.u32 %0,%%cluster_ctarank;" : "=r"(rank));
    const int wi = __shfl_sync(0xffffffffu, threadIdx.x >> 5, 0);
    const int v = blockIdx.x, cl = v >> 1, wg = wi >> 2;
    PROF(threadIdx.x == 0, 3500);
    ProRegs pr;
    prologue_load(p.pa, max((int)blockIdx.x - 4, 0), pr);
    if (wi == 11 && p.dopro && cl >= 2 && elect()) {
        mbar_init(sb + S_XBAR, 1);
        asm volatile("fence.mbarrier_init.release.cluster;" ::: "memory");
        mbar_expect(sb + S_XBAR, 32768);
        for (int j = 0; j < 8; j++) tma2d(sb + P_X + j * 4096, &p.tm[3], ((blockIdx.x - 4) >> 1) * 8, j * 256, sb + S_XBAR);
    }
    if (threadIdx.x == 320) {
        unsigned v = 0;
        if (p.dopro) {
            asm volatile("ld.relaxed.gpu.global.u32 %0,[%1];" : "=r"(v) : "l"(g_gate) : "memory");
            v = (v / (4 * NCL) + 1) * (4 * NCL);
        }
        sts32(sb + S_GATE, v);
    }
    __syncwarp();
    if (wi == 10) {
        if (v < V_REC || v == 131) conv_init(sb, v == 131); else if (v < V_OP) rec_init(sb); else gemm_init(sb, v < V_QKV);
        __syncwarp();
    }
    if (wg == 2) bar_arrive(8, 384);
    asm volatile("barrier.cluster.arrive.relaxed.aligned;" ::: "memory");
    if (p.dopro && cl >= 2) prologue(p, sb, blockIdx.x - 4, wi, pr); else if (wg < 2) bar_sync(8, 384); else if (wi == 10) early_fetch(p, sb);
    asm volatile("barrier.cluster.wait.aligned;" ::: "memory");
    const int role = (v < V_REC ? 1 : v < V_OP ? 2 : v < V_QKV ? 4 : v < V_QKV + NQ ? 24 : 1) & p.roles;
    fence_async_smem();
    bar_sync(wg == 2 ? 7 : 1, wg == 2 ? 128 : 256);
    if (p.dopro && (threadIdx.x == 32 || threadIdx.x == 352)) red_release(g_gate, 1);
    PROF(threadIdx.x == 32, 3509);
    if (wi == 0 && (role & 8) && elect()) qkv_stage(p, sb + 131072, sb + G_BAR + GB_RS * 8, v - V_QKV, 0, 6);
    PROF(threadIdx.x == 0, 3506);
    __syncwarp();
    if (p.dopro && v >= V_REC && v < V_QKV && (v < V_OP ? wi == 8 : wi < 8)) {
        bool on = v >= V_OP;
#pragma unroll 1
        for (int r = on ? 64 + (v - V_OP) * 8 + wi : v - V_REC; r < 512;) {
            if (on) wait_flag_warp(g_gate, lds32(sb + S_GATE));
            PROF(threadIdx.x == 256 && on, 3507);
            x1_norm(on ? (const uint2*)g_x : (const uint2*)p.pa.W[0], r, on);
            __syncwarp();
            if (on && elect()) red_release(cnt_ptr(C_XN + (r >> 4)), 1);
            __syncwarp();
            PROF(threadIdx.x == 256, on ? 3508 : 3499);
            if (on) r += v < V_OP ? 512 : 128;
            on = true;
        }
    }
    if (role == 2) {
        const int head = (v - V_REC) >> 1;
        if (wi == 0 && elect()) rec_fetch(p, sb, head, rank, 1, R_STK);
        __syncwarp();
        if (wg == 2) {
            reg_dec<RH>();
            const int w = wi & 3;
            wait_cnt_warp(g_gate, lds32(sb + S_GATE));
            if (w < 2) { const uint32_t x = __ldcg(g_sel + (threadIdx.x & 63)); sts32(sb + R_SEL + (threadIdx.x & 63) * 4, (x | x >> 16) & 15); }
            __syncthreads();
            cluster_sync();
            if ((p.chains >> (w & 1)) & 1) { if (w < 2) rec_comm(p, sb, w, head, rank); else rec_attn(p, sb, w & 1, head, rank); }
        } else {
            reg_inc<RW0>();
            rec_weights(p, sb, head, rank, wi);
        }
    } else if (role == 1) {
        if (v == 131) conv_far(sb, wi); else if (wg == 2) { reg_dec<RCB>(); conv_back(sb, v, wi & 3); } else { reg_inc<RCU>(); conv_tile(p, sb, v, wi); }
    } else if (role == 4) {
        if (wg == 2) {
            reg_dec<40>();
            if (wi == 8) gemm_producer<true>(p, sb, v - V_OP); else if (wi < 11) gemm_release<true>(p, sb, v - V_OP, wi - 9);
        } else { reg_inc<232>(); gemm_consumer<true>(p, sb, v - V_OP, wi); }
    } else if (role) {
        if (wg == 2) {
            reg_dec<40>();
            if (wi < 10) {
                if (role & 8) { if (wi == 8) gemm_producer<false>(p, sb, v - V_QKV); else gemm_release<false>(p, sb, v - V_QKV, 0); }
            } else if (v < V_QKV + 32 && (role & 16)) fin_warp(p, sb, (v - V_QKV) * 2 + wi - 10);
        } else { reg_inc<232>(); if (role & 8) gemm_consumer<false>(p, sb, v - V_QKV, wi); }
    }
    __syncwarp();
    cluster_sync();
}

typedef CUresult (*EncFn)(CUtensorMap*, CUtensorMapDataType, cuuint32_t, void*, const cuuint64_t*, const cuuint64_t*, const cuuint32_t*, const cuuint32_t*,
                          CUtensorMapInterleave, CUtensorMapSwizzle, CUtensorMapL2promotion, CUtensorMapFloatOOBfill);
constexpr int SMEM_BYTES = 232448;
#define LAG 9
#define QLEAD 6
#define OLEAD (LAG / 2 + 2)
void plan(Params& P) {
    P.roles = 31; P.chains = 3; P.lag = LAG; P.dopro = 1;
    for (int r = 0; r < 2; r++) {
        const int lead = r ? OLEAD : QLEAD;
        int n = 0;
        for (int i = 0; i < 32 + lead; i++) {
            if (i >= lead) P.list[r][n++] = 32 + i - lead;
            if (i < 32) P.list[r][n++] = i;
        }
        P.nl[r] = n;
    }
}

#define TK() do {} while (0)
}

extern "C" void kernel_launch(void* const* d_in, const int* in_sizes, int n_in, void* d_out, int out_size) {
    typedef const __nv_bfloat16* BP;
    static EncFn enc = nullptr;
    if (!enc) {
        void* fn = nullptr; cudaDriverEntryPointQueryResult qr;
        cudaGetDriverEntryPoint("cuTensorMapEncodeTiled", &fn, cudaEnableDefault, &qr);
        enc = (EncFn)fn;
        cudaFuncSetAttribute(main_kernel, cudaFuncAttributeMaxDynamicSharedMemorySize, SMEM_BYTES);
    }
    static Params P;
    for (int i = 0; i < 4; i++) {
        const cuuint64_t cols = i < 3 ? 4096 : 512, rows = i < 3 ? 512 : 4096;
        cuuint64_t d2[2] = {cols, rows}, str[1] = {cols * 2};
        cuuint32_t box[2] = {64, 64}, bn[2] = {16, 256}, es[2] = {1, 1};
        enc(&P.tm[i < 3 ? i : 4], CU_TENSOR_MAP_DATA_TYPE_BFLOAT16, 2, d_in[9 + i], d2, str, box, es, CU_TENSOR_MAP_INTERLEAVE_NONE, CU_TENSOR_MAP_SWIZZLE_128B,
            CU_TENSOR_MAP_L2_PROMOTION_L2_128B, CU_TENSOR_MAP_FLOAT_OOB_FILL_NONE);
        if (i < 2) enc(&P.tn[i], CU_TENSOR_MAP_DATA_TYPE_BFLOAT16, 2, d_in[9 + i], d2, str, bn, es, CU_TENSOR_MAP_INTERLEAVE_NONE, CU_TENSOR_MAP_SWIZZLE_32B,
                       CU_TENSOR_MAP_L2_PROMOTION_L2_128B, CU_TENSOR_MAP_FLOAT_OOB_FILL_NONE);
    }
    {
        cuuint64_t dims[2] = {512, 2048}, str[1] = {1024};
        cuuint32_t box[2] = {8, 256}, es[2] = {1, 1};
        enc(&P.tm[3], CU_TENSOR_MAP_DATA_TYPE_BFLOAT16, 2, d_in[0], dims, str, box, es, CU_TENSOR_MAP_INTERLEAVE_NONE, CU_TENSOR_MAP_SWIZZLE_NONE,
            CU_TENSOR_MAP_L2_PROMOTION_NONE, CU_TENSOR_MAP_FLOAT_OOB_FILL_NONE);
    }
    P.mem0 = (BP)d_in[8]; P.Wo = (BP)d_in[12]; P.Dskip = (BP)d_in[6]; P.out = (__nv_bfloat16*)d_out;
    cudaStream_t s = cudaStreamPerThread;
    P.pa = {(BP)d_in[0], (BP)d_in[1], (BP)d_in[2], (BP)d_in[3], (BP)d_in[4], (BP)d_in[5], (BP)d_in[6], {(BP)d_in[9], (BP)d_in[10], (BP)d_in[11], (BP)d_in[12]}};
    plan(P);
    TK(); main_kernel<<<2 * NCL, 384, SMEM_BYTES, s>>>(P); TK();
}
```

```cpp
#include <cuda_runtime.h>
#include <cuda_bf16.h>
#include <cuda.h>
#include <stdint.h>
#include <string.h>
#include <math.h>

namespace {

constexpr int NCL = 66;
constexpr int NQ = 43;
constexpr int V_REC = 8, V_OP = 72, V_QKV = 88;
static_assert(2 * NQ + 3 * 14 == 128, "warps of the final residual");

#define XP 1024
__device__ uint4 g_x[2 * 128 * XP];
__device__ uint4 g_xn[64 * 4096];
__device__ uint4 g_st[68 * 256];
__device__ uint4 g_qkv[128 * 32 * 1536];
__device__ uint4 g_o[64 * 64 * 512];
__device__ uint4 g_pp[64 * 4 * 4096];
__device__ uint4 g_xch[133 * 512];
__device__ unsigned g_sel[64];
__device__ unsigned g_gate[32];
__device__ __align__(16) uint32_t g_P[512 * 272];
__device__ uint4 g_W[512 * 784];
__device__ __align__(16) uint32_t g_u[512 * 1152];
__device__ uint2 g_carry[512 * 40 * 32];
__device__ uint2 g_far[512 * 8 * 32];
__device__ unsigned g_cnt[900 * 8];
__device__ uint32_t g_ln0[2048];

enum { C_XN = 0  , C_QKV = 64  , C_O = 128  , C_PP = 384  , C_FAR = 896 };
__device__ __forceinline__ unsigned* cnt_ptr(int i) { return g_cnt + i * 8; }

struct ProArgs { const __nv_bfloat16 *x, *lAr, *Ai, *Cr, *Ci, *ldt, *Dk, *W[4]; };
struct Params {
    CUtensorMap tm[5];
    CUtensorMap tn[2];
    ProArgs pa;
    int dopro;
    const __nv_bfloat16* mem0;
    const __nv_bfloat16* Wo;
    const __nv_bfloat16* Dskip;
    __nv_bfloat16* out;
    int roles;
    int chains;
    int lag;
    int zero;
    int nl[2];
    uint8_t list[2][64];
};

__device__ __forceinline__ uint32_t smem_u32(const void* p) { return (uint32_t)__cvta_generic_to_shared(p); }
__device__ __forceinline__ uint32_t mapa(uint32_t a, uint32_t r) {
    uint32_t o; asm("mapa.shared::cluster.u32 %0,%1,%2;" : "=r"(o) : "r"(a), "r"(r)); return o;
}
__device__ __forceinline__ void mbar_init(uint32_t b, int c) { asm volatile("mbarrier.init.shared::cta.b64 [%0],%1;" ::"r"(b), "r"(c) : "memory"); }
__device__ __forceinline__ void mbar_expect(uint32_t b, int bytes) { asm volatile("mbarrier.arrive.expect_tx.shared::cta.b64 _,[%0],%1;" ::"r"(b), "r"(bytes) : "memory"); }
__device__ __forceinline__ void mbar_arrive(uint32_t b) { asm volatile("mbarrier.arrive.shared::cta.b64 _,[%0];" ::"r"(b) : "memory"); }
__device__ __forceinline__ void mbar_arrive_cluster(uint32_t b) { asm volatile("mbarrier.arrive.shared::cluster.b64 _,[%0];" ::"r"(b) : "memory"); }
__device__ __forceinline__ void mbar_wait(uint32_t b, uint32_t ph) {
    asm volatile(
        "{.reg .pred p; .reg .u32 n; mov.u32 n,0;\n"
        "W%=: mbarrier.try_wait.parity.shared::cta.b64 p,[%0],%1;\n"
        "@p bra D%=;\n"
        "add.u32 n,n,1; setp.lt.u32 p,n,2000000; @p bra W%=;\n"
        "trap;\n"
        "D%=: }" ::"r"(b), "r"(ph) : "memory");
}
__device__ __forceinline__ bool wait_lds128(uint32_t b, uint32_t ph, uint32_t a, uint4& v) {
    uint32_t ok;
    asm volatile("{.reg .pred p; mbarrier.try_wait.parity.shared::cta.b64 p,[%5],%6,20000; ld.shared.v4.u32 {%0,%1,%2,%3},[%7]; selp.u32 %4,1,0,p;}"
                 : "=r"(v.x), "=r"(v.y), "=r"(v.z), "=r"(v.w), "=r"(ok) : "r"(b), "r"(ph), "r"(a) : "memory");
    return ok;
}
__device__ __forceinline__ bool wait_lds64(uint32_t b, uint32_t ph, uint32_t a, uint2& v) {
    uint32_t ok;
    asm volatile("{.reg .pred p; mbarrier.try_wait.parity.shared::cta.b64 p,[%3],%4,20000; ld.shared.v2.u32 {%0,%1},[%5]; selp.u32 %2,1,0,p;}"
                 : "=r"(v.x), "=r"(v.y), "=r"(ok) : "r"(b), "r"(ph), "r"(a) : "memory");
    return ok;
}
template <int PH> __device__ __forceinline__ void mbar_wait_c(uint32_t b) {
    asm volatile(
        "{.reg .pred p; .reg .u32 n; mov.u32 n,%2;\n"
        "W%=: mbarrier.try_wait.parity.shared::cta.b64 p,[%0],%1;\n"
        "@p bra D%=;\n"
        "add.u32 n,n,1; setp.lt.u32 p,n,2000000; @p bra W%=;\n"
        "trap;\n"
        "D%=: }" ::"r"(b), "n"(PH), "n"(PH) : "memory");
}
__device__ __forceinline__ bool elect() {
    uint32_t r; asm volatile("{.reg .pred p; elect.sync _|p,0xffffffff; selp.u32 %0,1,0,p;}" : "=r"(r)); return r;
}
__device__ __forceinline__ void bar_sync(int id, int n) { asm volatile("bar.sync %0,%1;" ::"r"(id), "r"(n) : "memory"); }
__device__ __forceinline__ void bar_arrive(int id, int n) { asm volatile("bar.arrive %0,%1;" ::"r"(id), "r"(n) : "memory"); }
__device__ __forceinline__ void cluster_sync() { asm volatile("barrier.cluster.arrive.relaxed.aligned; barrier.cluster.wait.aligned;" ::: "memory"); }
__device__ __forceinline__ void fence_async() { asm volatile("fence.proxy.async;" ::: "memory"); }
__device__ __forceinline__ void fence_async_smem() { asm volatile("fence.proxy.async.shared::cta;" ::: "memory"); }
#define EFR 1
#define EFW 2
constexpr uint64_t POL_N = 0x1000000000000000ull, POL_F = 0x12F0000000000000ull;
constexpr uint64_t POL_LAST = EFR ? POL_F : POL_N  , POL_LATE = EFW ? POL_F : POL_N  , POL_SOON = EFW > 1 ? POL_F : POL_N;
__device__ __forceinline__ void bulk_g2s(uint32_t dst, const void* src, int bytes, uint32_t bar, uint64_t pol) {
    asm volatile("cp.async.bulk.shared::cluster.global.mbarrier::complete_tx::bytes.L2::cache_hint [%0],[%1],%2,[%3],%4;" ::"r"(dst), "l"(src), "r"(bytes), "r"(bar), "l"(pol) : "memory");
}
__device__ __forceinline__ void bulk_g2s_mc(uint32_t dst, const void* src, int bytes, uint32_t bar, uint64_t pol) {
    asm volatile("cp.async.bulk.shared::cluster.global.mbarrier::complete_tx::bytes.multicast::cluster.L2::cache_hint [%0],[%1],%2,[%3],%4,%5;" ::"r"(dst), "l"(src), "r"(bytes), "r"(bar), "h"((uint16_t)3), "l"(pol) : "memory");
}
__device__ __forceinline__ void stg128(uint4* p, uint4 v, uint64_t pol) {
    asm volatile("st.global.L2::cache_hint.v4.u32 [%0],{%1,%2,%3,%4},%5;" ::"l"(p), "r"(v.x), "r"(v.y), "r"(v.z), "r"(v.w), "l"(pol));
}
__device__ __forceinline__ void stg32(uint32_t* p, uint32_t v, uint64_t pol) { asm volatile("st.global.L2::cache_hint.u32 [%0],%1,%2;" ::"l"(p), "r"(v), "l"(pol)); }
__device__ __forceinline__ uint4 ldcg128_last(const uint4* p) {
    uint4 v; asm volatile("ld.global.cg.L2::cache_hint.v4.u32 {%0,%1,%2,%3},[%4],%5;" : "=r"(v.x), "=r"(v.y), "=r"(v.z), "=r"(v.w) : "l"(p), "l"(POL_LAST) : "memory"); return v;
}
__device__ __forceinline__ void tma2d(uint32_t dst, const CUtensorMap* tm, int x, int y, uint32_t bar) {
    asm volatile("cp.async.bulk.tensor.2d.shared::cluster.global.mbarrier::complete_tx::bytes [%0],[%1,{%2,%3}],[%4];" ::"r"(dst), "l"(tm), "r"(x), "r"(y), "r"(bar) : "memory");
}
__device__ __forceinline__ void tma3d(uint32_t dst, const CUtensorMap* tm, int y, int z, uint32_t bar) {
    asm volatile("cp.async.bulk.tensor.3d.shared::cluster.global.mbarrier::complete_tx::bytes [%0],[%1,{0,%2,%3}],[%4];" ::"r"(dst), "l"(tm), "r"(y), "r"(z), "r"(bar) : "memory");
}
__device__ __forceinline__ void st_async4(uint32_t a, uint32_t x, uint32_t y, uint32_t z, uint32_t w, uint32_t mb) {
    asm volatile("st.async.shared::cluster.mbarrier::complete_tx::bytes.v4.b32 [%0],{%1,%2,%3,%4},[%5];" ::"r"(a), "r"(x), "r"(y), "r"(z), "r"(w), "r"(mb) : "memory");
}
__device__ __forceinline__ void st_async2(uint32_t a, uint32_t x, uint32_t y, uint32_t mb) {
    asm volatile("st.async.shared::cluster.mbarrier::complete_tx::bytes.v2.b32 [%0],{%1,%2},[%3];" ::"r"(a), "r"(x), "r"(y), "r"(mb) : "memory");
}
#define LDSQ "ld.shared"
__device__ __forceinline__ uint4 lds128(uint32_t a) { uint4 v; asm volatile(LDSQ ".v4.u32 {%0,%1,%2,%3},[%4];" : "=r"(v.x), "=r"(v.y), "=r"(v.z), "=r"(v.w) : "r"(a) : "memory"); return v; }
__device__ __forceinline__ uint4 lds128v(uint32_t a) { uint4 v; asm volatile("ld.volatile.shared.v4.u32 {%0,%1,%2,%3},[%4];" : "=r"(v.x), "=r"(v.y), "=r"(v.z), "=r"(v.w) : "r"(a) : "memory"); return v; }
__device__ __forceinline__ uint2 lds64(uint32_t a) { uint2 v; asm volatile(LDSQ ".v2.u32 {%0,%1},[%2];" : "=r"(v.x), "=r"(v.y) : "r"(a) : "memory"); return v; }
__device__ __forceinline__ uint32_t lds32(uint32_t a) { uint32_t v; asm volatile(LDSQ ".u32 %0,[%1];" : "=r"(v) : "r"(a) : "memory"); return v; }
__device__ __forceinline__ void sts128(uint32_t a, uint32_t x, uint32_t y, uint32_t z, uint32_t w) { asm volatile("st.shared.v4.u32 [%0],{%1,%2,%3,%4};" ::"r"(a), "r"(x), "r"(y), "r"(z), "r"(w) : "memory"); }
__device__ __forceinline__ void sts64(uint32_t a, uint32_t x, uint32_t y) { asm volatile("st.shared.v2.u32 [%0],{%1,%2};" ::"r"(a), "r"(x), "r"(y) : "memory"); }
__device__ __forceinline__ void sts32(uint32_t a, uint32_t x) { asm volatile("st.shared.u32 [%0],%1;" ::"r"(a), "r"(x) : "memory"); }
__device__ __forceinline__ uint4 ldsm4(uint32_t a) { uint4 v; asm volatile("ldmatrix.sync.aligned.m8n8.x4.shared.b16 {%0,%1,%2,%3},[%4];" : "=r"(v.x), "=r"(v.y), "=r"(v.z), "=r"(v.w) : "r"(a) : "memory"); return v; }
__device__ __forceinline__ uint4 ldsm4t(uint32_t a) { uint4 v; asm volatile("ldmatrix.sync.aligned.m8n8.x4.trans.shared.b16 {%0,%1,%2,%3},[%4];" : "=r"(v.x), "=r"(v.y), "=r"(v.z), "=r"(v.w) : "r"(a) : "memory"); return v; }
__device__ __forceinline__ uint32_t movm(uint32_t a) { uint32_t d; asm volatile("movmatrix.sync.aligned.m8n8.trans.b16 %0,%1;" : "=r"(d) : "r"(a)); return d; }
__device__ __forceinline__ uint32_t pack2(float lo, float hi) { uint32_t d; asm("cvt.rn.bf16x2.f32 %0,%1,%2;" : "=r"(d) : "f"(hi), "f"(lo)); return d; }
__device__ __forceinline__ uint32_t hadd2(uint32_t a, uint32_t b) { uint32_t d; asm("add.rn.bf16x2 %0,%1,%2;" : "=r"(d) : "r"(a), "r"(b)); return d; }
__device__ __forceinline__ uint32_t hmul2(uint32_t a, uint32_t b) { uint32_t d; asm("mul.rn.bf16x2 %0,%1,%2;" : "=r"(d) : "r"(a), "r"(b)); return d; }
__device__ __forceinline__ float blo(uint32_t v) { return __uint_as_float(v << 16); }
__device__ __forceinline__ float bhi(uint32_t v) { return __uint_as_float(v & 0xffff0000u); }
__device__ __forceinline__ float rbf(float x) { return __uint_as_float(pack2(0.f, x)); }
__device__ __forceinline__ float ex2(float x) { float y; asm("ex2.approx.ftz.f32 %0,%1;" : "=f"(y) : "f"(x)); return y; }
__device__ __forceinline__ float rcp(float x) { float y; asm("rcp.approx.ftz.f32 %0,%1;" : "=f"(y) : "f"(x)); return y; }
__device__ __forceinline__ void mma16(float* c, uint32_t a0, uint32_t a1, uint32_t a2, uint32_t a3, uint32_t b0, uint32_t b1) {
    asm volatile("mma.sync.aligned.m16n8k16.row.col.f32.bf16.bf16.f32 {%0,%1,%2,%3},{%4,%5,%6,%7},{%8,%9},{%0,%1,%2,%3};"
                 : "+f"(c[0]), "+f"(c[1]), "+f"(c[2]), "+f"(c[3]) : "r"(a0), "r"(a1), "r"(a2), "r"(a3), "r"(b0), "r"(b1));
}
__device__ __forceinline__ void mma16_top(float& d0, float& d1, uint32_t a0, uint32_t a2, uint32_t b0, uint32_t b1) {
    asm volatile("{.reg .b32 j; .reg .f32 e,f; mma.sync.aligned.m16n8k16.row.col.f32.bf16.bf16.f32 {%0,%1,e,f},{%2,j,%3,j},{%4,%5},{0f00000000,0f00000000,0f00000000,0f00000000};}"
                 : "=f"(d0), "=f"(d1) : "r"(a0), "r"(a2), "r"(b0), "r"(b1));
}
__device__ __forceinline__ void mma8(float* c, uint32_t a0, uint32_t a1, uint32_t b0) {
    asm volatile("mma.sync.aligned.m16n8k8.row.col.f32.bf16.bf16.f32 {%0,%1,%2,%3},{%4,%5},{%6},{%0,%1,%2,%3};"
                 : "+f"(c[0]), "+f"(c[1]), "+f"(c[2]), "+f"(c[3]) : "r"(a0), "r"(a1), "r"(b0));
}
__device__ __forceinline__ uint4 ld_rlx128(const uint4* p) {
    uint4 v;
    asm volatile("{.reg .b128 t; ld.relaxed.gpu.global.b128 t,[%4]; mov.b128 {%0,%1,%2,%3},t;}" : "=r"(v.x), "=r"(v.y), "=r"(v.z), "=r"(v.w) : "l"(p) : "memory");
    return v;
}
__device__ __forceinline__ void st_rlx128(uint4* p, uint32_t x, uint32_t y, uint32_t z, uint32_t w) {
    asm volatile("{.reg .b128 t; mov.b128 t,{%1,%2,%3,%4}; st.relaxed.gpu.global.b128 [%0],t;}" ::"l"(p), "r"(x), "r"(y), "r"(z), "r"(w) : "memory");
}
__device__ __forceinline__ uint4 ldcg128(const uint4* p) { uint4 v; asm volatile("ld.global.cg.v4.u32 {%0,%1,%2,%3},[%4];" : "=r"(v.x), "=r"(v.y), "=r"(v.z), "=r"(v.w) : "l"(p) : "memory"); return v; }
__device__ __forceinline__ void red_release(unsigned* p, unsigned v) {
    asm volatile("fence.proxy.async; red.relaxed.gpu.global.add.u32 [%0],%1;" ::"l"(p), "r"(v) : "memory");
}
__device__ __forceinline__ void red_relaxed(unsigned* p, unsigned v) { asm volatile("red.relaxed.gpu.global.add.u32 [%0],%1;" ::"l"(p), "r"(v) : "memory"); }
__device__ __forceinline__ void wait_cnt(const unsigned* p, unsigned target) {
    asm volatile(
        "{.reg .pred p; .reg .u32 n,v; mov.u32 n,0;\n"
        "W%=: ld.acquire.gpu.global.u32 v,[%0]; setp.ge.u32 p,v,%1; @p bra D%=;\n"
        "nanosleep.u32 20; add.u32 n,n,1; setp.lt.u32 p,n,4000000; @p bra W%=;\n"
        "trap;\n"
        "D%=: }" ::"l"(p), "r"(target) : "memory");
}
__device__ __forceinline__ void wait_cnt_warp(const unsigned* p, unsigned target) {
    asm volatile(
        "{.reg .pred p; .reg .u32 n,v; mov.u32 n,0;\n"
        "W%=: ld.acquire.gpu.global.u32 v,[%0]; setp.ge.u32 p,v,%1; vote.sync.all.pred p,p,0xffffffff; @p bra.uni D%=;\n"
        "nanosleep.u32 20; add.u32 n,n,1; setp.lt.u32 p,n,4000000; @p bra.uni W%=;\n"
        "trap;\n"
        "D%=: }" ::"l"(p), "r"(target) : "memory");
}
__device__ __forceinline__ void wait_flag_warp(const unsigned* p, unsigned target) {
    asm volatile(
        "{.reg .pred p; .reg .u32 n,v; mov.u32 n,0;\n"
        "W%=: ld.relaxed.gpu.global.u32 v,[%0]; setp.ge.u32 p,v,%1; vote.sync.all.pred p,p,0xffffffff; @p bra.uni D%=;\n"
        "add.u32 n,n,1; setp.lt.u32 p,n,10000000; @p bra.uni W%=;\n"
        "trap;\n"
        "D%=: }" ::"l"(p), "r"(target) : "memory");
}
__device__ __forceinline__ uint64_t mkdesc(uint32_t addr, uint32_t lbo, uint32_t sbo, uint32_t sw) {
    return (uint64_t)((addr & 0x3FFFF) >> 4) | ((uint64_t)(lbo >> 4) << 16) | ((uint64_t)(sbo >> 4) << 32) | ((uint64_t)sw << 62);
}
__device__ __forceinline__ void wg_fence() { asm volatile("wgmma.fence.sync.aligned;" ::: "memory"); }
__device__ __forceinline__ void wg_commit() { asm volatile("wgmma.commit_group.sync.aligned;" ::: "memory"); }
template <int N> __device__ __forceinline__ void wg_wait() { asm volatile("wgmma.wait_group.sync.aligned %0;" ::"n"(N) : "memory"); }
#define R8(c, o) "+f"(c[o]), "+f"(c[o + 1]), "+f"(c[o + 2]), "+f"(c[o + 3]), "+f"(c[o + 4]), "+f"(c[o + 5]), "+f"(c[o + 6]), "+f"(c[o + 7])
#define R32(c, o) R8(c, o), R8(c, o + 8), R8(c, o + 16), R8(c, o + 24)
#define S32A "%0,%1,%2,%3,%4,%5,%6,%7,%8,%9,%10,%11,%12,%13,%14,%15,%16,%17,%18,%19,%20,%21,%22,%23,%24,%25,%26,%27,%28,%29,%30,%31"
template <int ACC> __device__ __forceinline__ void wgmma64_rs(float* c, const uint32_t* a, uint64_t db) {
    asm volatile("wgmma.mma_async.sync.aligned.m64n64k16.f32.bf16.bf16 {" S32A "},{%32,%33,%34,%35},%36,%37,1,1,0;"
                 : R32(c, 0) : "r"(a[0]), "r"(a[1]), "r"(a[2]), "r"(a[3]), "l"(db), "n"(ACC));
}
template <int ACC> __device__ __forceinline__ void wgmma64_ta(float* c, uint64_t da, uint64_t db) {
    asm volatile("wgmma.mma_async.sync.aligned.m64n64k16.f32.bf16.bf16 {" S32A "},%32,%33,%34,1,1,1,0;" : R32(c, 0) : "l"(da), "l"(db), "n"(ACC));
}
template <int ACC> __device__ __forceinline__ void wgmma80_tb(float* c, uint64_t da, uint64_t db) {
    asm volatile("wgmma.mma_async.sync.aligned.m64n80k16.f32.bf16.bf16 {" S32A ",%32,%33,%34,%35,%36,%37,%38,%39},%40,%41,%42,1,1,0,1;"
                 : R32(c, 0), R8(c, 32) : "l"(da), "l"(db), "n"(ACC));
}
template <int N> __device__ __forceinline__ void reg_inc() { asm volatile("setmaxnreg.inc.sync.aligned.u32 %0;" ::"n"(N)); }
template <int N> __device__ __forceinline__ void reg_dec() { asm volatile("setmaxnreg.dec.sync.aligned.u32 %0;" ::"n"(N)); }

#define PROF(cond, idx) do {} while (0)
#define CPROF(k) do {} while (0)

constexpr int S_GATE = 232440, S_TAG = 232444, S_XBAR = 232432, B_BAR = 231936;
#define RCB 136
#define RCU 184
#define NFP 2
#define NLATE 1
#define PFM 8
#define NFE 2
#define QLAG 3
constexpr float SC_LOG2E = 0.08838834764831845f * 1.4426950408889634f;

__device__ __forceinline__ float2 ln_finish(float mean, float var) {
    float sd; asm("sqrt.approx.f32 %0,%1;" : "=f"(sd) : "f"(rbf(rbf(var) + 1e-5f)));
    sd = rbf(sd);
    return make_float2(rbf(mean), sd);
}

__device__ __forceinline__ float2 row_stats512(uint4* v, const uint4* src, int s1, int s2) {
    const int g = (threadIdx.x & 31) >> 2;
#pragma unroll
    for (int i = 0; i < 16; i++) v[i] = ldcg128(src + (i >> 1) * s1 + (i & 1) * s2);
    float a[4] = {0, 0, 0, 0}, q0[4] = {0, 0, 0, 0}, q1[4] = {0, 0, 0, 0};
#pragma unroll
    for (int i = 0; i < 16; i++) {
        mma16(a, v[i].x, v[i].y, v[i].z, v[i].w, 0x3f803f80u, 0x3f803f80u);
        mma8(q0, v[i].x, v[i].y, v[i].x); mma8(q1, v[i].x, v[i].y, v[i].y);
        mma8(q0, v[i].z, v[i].w, v[i].z); mma8(q1, v[i].z, v[i].w, v[i].w);
    }
    const float sum = a[0] + a[2], sq = (g & 1) ? q0[1] + q1[3] : q0[0] + q1[2];
    return make_float2(sum, fmaxf(sq - sum * sum * (1.f / 512.f), 0.f));
}
__device__ __forceinline__ void x1_norm(const uint2* src, int r, bool on) {
    const int lane = threadIdx.x & 31, g = lane >> 2, t = r * 4 + (lane & 3);
    constexpr int xp = XP;
    uint2 v[16];
#pragma unroll
    for (int i = 0; i < 16; i++) asm volatile("ld.global.cg.v2.u32 {%0,%1},[%2];" : "=r"(v[i].x), "=r"(v[i].y) : "l"(src + (g * 4 * xp + t) + ((i >> 1) * 16 + (i & 1)) * 2 * xp) : "memory");
    float s = 0, q = 0;
#pragma unroll
    for (int i = 0; i < 32; i++) {
        const uint32_t w = (i & 1) ? v[i >> 1].y : v[i >> 1].x;
        s += blo(w) + bhi(w); q = fmaf(blo(w), blo(w), fmaf(bhi(w), bhi(w), q));
    }
#pragma unroll
    for (int d = 4; d < 32; d *= 2) { s += __shfl_xor_sync(0xffffffffu, s, d); q += __shfl_xor_sync(0xffffffffu, q, d); }
    if (g == 0 && on) g_ln0[t] = 0;
    s *= 1.f / 512.f;
    const float2 l = ln_finish(s, fmaxf(fmaf(q, 1.f / 512.f, -s * s), 0.f));
    const float rs = rcp(l.y);
    const uint32_t mm = pack2(-l.x, -l.x);
    uint4* dst = g_xn + ((t >> 6) * 4096 + ((t >> 3) & 7) * 64 + g * 8 + (t & 7));
#define NRM(w) pack2(blo(hadd2(w, mm)) * rs, bhi(hadd2(w, mm)) * rs)
#pragma unroll
    for (int i = 0; i < 8; i++)
        asm volatile("{.reg .pred p; setp.ne.u32 p,%5,0; @p st.global.v4.u32 [%0],{%1,%2,%3,%4};}" ::"l"(dst + i * 512), "r"(NRM(v[2 * i].x)), "r"(NRM(v[2 * i].y)),
                     "r"(NRM(v[2 * i + 1].x)), "r"(NRM(v[2 * i + 1].y)), "r"((uint32_t)on) : "memory");
}

#define NWO 10
#define VMASK 0x4444
#define VPRE 2
#define VFIRST 1
#define OA 0
#define OL 0x16
#define PINS 0xae1
#define NPX 2
#define NPF 2
constexpr int SLOT = 24576, SL_V = 8192, SL_Q = 16384, SL_KM = 20480, SL_VM = 22528;
constexpr int R_SL = 0, R_WV = 4 * SLOT  , R_WO = R_WV + 65536, R_M = 196608  , R_U = R_M + 8192  ,
              R_OS = R_U + 8192  , R_SB = R_OS + 8192  , R_OB = R_SB + 5248  , R_PB = R_OB + 2048  ,
              R_IL = R_PB + 1024  , R_SEL = 231680, R_BAR = R_SEL + 256, R_STV = 0, R_STQ = 65536, R_STK = 131072;
static_assert(R_WO + (16 - NWO) * 4096 <= R_M && R_IL + 64 <= R_SEL && R_BAR + 512 <= 232448, "smem map");
enum { RB_XFULL = 0  , RB_GO = 4  , RB_QK = 8  , RB_INIT = 24, RB_SV = 25   };

enum { NB_MFULL = 1  , NB_PART = 3  , NB_S = 5, NB_P = 6, NB_O = 7, NB_W = 10 };
#define HL 2
#define XU 8
#define EGO 0
#define XFW 1
#define RACC 2
#define WDEP 1
#define RH 56
#define RW0 224
#define D1 350
#define D2 350
#define DX 0
__device__ __forceinline__ uint32_t clk32() { uint32_t c; asm volatile("mov.u32 %0,%%clock;" : "=r"(c)::"memory"); return c; }
__device__ __forceinline__ void spin(int cycles) {
    if (cycles <= 0) return;
    asm volatile("{.reg .pred p; .reg .u32 a,b; mov.u32 a,%%clock; add.u32 a,a,%0;\nS%=: mov.u32 b,%%clock; sub.u32 b,b,a; setp.lt.s32 p,b,0; @p bra.uni S%=;}" ::"r"(cycles) : "memory");
}
__device__ __forceinline__ uint4* xregion(int X, int r) { return (uint4*)(((size_t)g_xch + 8191) & ~(size_t)8191) + (X * 66 + r) * 512; }

__device__ __forceinline__ void arrive_if(uint32_t bar, uint32_t a, uint32_t b) {
    asm volatile("{.reg .pred p; setp.eq.u32 p,%1,%2; @p mbarrier.arrive.shared::cta.b64 _,[%0];}" ::"r"(bar), "r"(a), "r"(b) : "memory");
}
struct RecW { uint32_t po, dp, lw, sp  , w; };
#define PIN(n) if ((PINS >> (n)) & 1) asm volatile("griddepcontrol.launch_dependents;" ::: "memory")
constexpr int v_stream(int n) {
    int ks = 0;
    for (; ks < 16; ks++) if (!((VMASK >> ks) & 1) && n-- == 0) break;
    return ks;
}
constexpr uint64_t v_next() {
    uint64_t r = 0;
    for (int n = 0; v_stream(n + VPRE) < 16; n++) r |= (uint64_t)v_stream(n + VPRE) << (4 * v_stream(n));
    return r;
}
constexpr uint64_t V_NEXT = v_next();
constexpr int V_PRE = v_stream(VPRE);

__device__ __forceinline__ void rec_step(const RecW& k, uint32_t sb, const int X, int s, uint32_t zero, int lo, int hi, int d, const uint32_t (*wq)[4], const uint32_t (*wk)[4], uint4* wv, uint4* wo) {
    const int SL = R_SL + X * 2 * SLOT;
    uint4 mk[8];
    bar_sync(NB_MFULL + X, 288);
    mk[0] = ldsm4(k.lw + X * 4096 + R_M);
    PIN(0);
    mk[1] = ldsm4(k.lw + X * 4096 + R_M + 512);
    PIN(0);
    asm volatile("" : "+r"(s));
    const uint32_t z = s & zero, wz = k.w + z, w5 = wz * 512, so = (s & 1) * SLOT + w5;
    const uint32_t qb = sb + R_BAR + (RB_QK + X * 8) * 8 + wz * 8;
    uint32_t x[4], vv[2], l8;
    {
        float aq[4] = {0, 0, 0, 0}, ak[4] = {0, 0, 0, 0}, av[4] = {0, 0, 0, 0};
#pragma unroll
        for (int t = 0; t < 16; t++) {
            const uint32_t b0 = (t & 1) ? mk[t >> 1].z : mk[t >> 1].x, b1 = (t & 1) ? mk[t >> 1].w : mk[t >> 1].y;
            mma16(aq, wq[t][0], wq[t][1], wq[t][2], wq[t][3], b0, b1);
            PIN(8);
            mma16(ak, wk[t][0], wk[t][1], wk[t][2], wk[t][3], b0, b1);
            PIN(9);
            mma16(av, wv[t].x, wv[t].y, wv[t].z, wv[t].w, b0, b1);
            PIN(10);
            if ((t & 1) && t < 13) mk[(t >> 1) + 2] = ldsm4(k.lw + X * 4096 + R_M + (t >> 1) * 512 + 1024);
            const int nx = (V_NEXT >> (4 * t)) & 15;
            if (nx) wv[nx] = lds128(k.lw + w5 + R_WV + nx * 4096);
            if (t == 14) l8 = ((k.lw + z) >> 1) + (sb - (sb >> 1) + SL + (s & 1) * SLOT + wz * 256);
            if (t < 15) PIN(1);
        }
        x[0] = movm(pack2(aq[0], aq[1])); x[1] = movm(pack2(aq[2], aq[3]));
        x[2] = movm(pack2(ak[0], ak[1])); x[3] = movm(pack2(ak[2], ak[3]));
        vv[0] = pack2(av[0], av[1]); vv[1] = pack2(av[2], av[3]);
        if (VFIRST) st_async2(l8 + (SL_VM + k.dp), vv[0], vv[1], qb + k.dp);
        st_async4(k.lw + (R_U + X * 4096 + w5 + k.dp), x[0], x[1], x[2], x[3], qb + k.dp);
        if (!VFIRST) st_async2(l8 + (SL_VM + k.dp), vv[0], vv[1], qb + k.dp);
    }
    {
        arrive_if(sb + R_BAR + (RB_GO + 2 - 2 * X + ((s + d) & 1)) * 8, k.sp, X ? s >= hi : s <= lo);
        const uint32_t swr = ((k.sp + z) & 0xffff) + (sb + R_SB);
        if (XFW) mbar_wait(sb + R_BAR + (RB_XFULL + X * 2) * 8 + (s & 1) * 8, (s >> 1) & 1);
        const uint4 k0 = lds128(k.lw + so + SL), k1 = lds128(k.lw + so + SL + 4096);
#pragma unroll
        for (int i = 0; i < NPX; i++) wo[i] = lds128(k.lw + w5 + R_WO + i * 4096);
        mbar_wait(qb, s & 1);
        const uint4 u = lds128(k.lw + w5 + R_U + X * 4096);
        const uint32_t q0 = hadd2(x[0], u.x), q1 = hadd2(x[1], u.y);
        x[2] = hadd2(x[2], u.z); x[3] = hadd2(x[3], u.w);
        float sa[4] = {0, 0, 0, 0}, sc[4] = {0, 0, 0, 0}, sm0, sm1;
        mma16(sa, k0.x, k0.y, k0.z, k0.w, q0, q1);
        mma16(sc, k1.x, k1.y, k1.z, k1.w, q0, q1);
        mma16_top(sm0, sm1, x[2], x[3], q0, q1);
        asm volatile("stmatrix.sync.aligned.m8n8.x4.trans.shared.b16 [%0],{%1,%2,%3,%4};" ::"r"(swr), "r"(pack2(sa[0], sa[1])), "r"(pack2(sa[2], sa[3])),
                     "r"(pack2(sc[0], sc[1])), "r"(pack2(sc[2], sc[3])) : "memory");
        asm volatile("stmatrix.sync.aligned.m8n8.x1.trans.shared.b16 [%0],{%1};" ::"r"(swr + 512), "r"(pack2(sm0, sm1)) : "memory");
    }
    bar_sync(NB_S, 256);
    uint4 v0, v1;
    uint32_t ls;
    {
        const uint4 y = ldsm4t(k.lw + wz * 656 + R_SB);
        PIN(2);
        uint32_t y4; asm volatile("ldmatrix.sync.aligned.m8n8.x1.trans.shared.b16 {%0},[%1];" : "=r"(y4) : "r"(k.lw + wz * 656 + R_SB + 512) : "memory");
        PIN(2);
        const uint2 vp = lds64(l8 + SL_VM);
        sts64(l8 + SL_KM, x[2], x[3]);
        const uint32_t ONE = 0x3f803f80u + z;
        float a[4] = {0, 0, 0, 0}, b[4] = {0, 0, 0, 0}, e[4] = {0, 0, 0, 0};
        mma16(a, ONE, z, z, ONE, y.x, y.y); mma16(b, ONE, z, z, ONE, y.z, y.w); mma8(e, ONE, z, y4);
        vv[0] = hadd2(vv[0], vp.x); vv[1] = hadd2(vv[1], vp.y);
        sts64(l8 + SL_VM, vv[0], vv[1]);
        float s0, s1;
        asm("{.reg .pred p1,p2,p4; .reg .f32 t0,t1,u0,u1; .reg .b32 m; and.b32 m,%12,64; setp.ne.u32 p1,m,0; and.b32 m,%12,128; setp.ne.u32 p2,m,0; and.b32 m,%12,256; setp.ne.u32 p4,m,0;"
            "selp.f32 t0,%4,%2,p1; selp.f32 t1,%5,%3,p1; selp.f32 u0,%8,%6,p1; selp.f32 u1,%9,%7,p1; selp.f32 t0,u0,t0,p2; selp.f32 t1,u1,t1,p2; selp.f32 %0,%10,t0,p4; selp.f32 %1,%11,t1,p4;}"
            : "=f"(s0), "=f"(s1) : "f"(a[0]), "f"(a[1]), "f"(a[2]), "f"(a[3]), "f"(b[0]), "f"(b[1]), "f"(b[2]), "f"(b[3]), "f"(e[0]), "f"(e[1]), "r"(k.lw));
        const int mi = __float_as_int(fmaxf(s0, s1));
        const int mp = __reduce_max_sync(0xffffffffu, mi), mn = (int)__reduce_min_sync(0xffffffffu, (unsigned)mi);
        PIN(3);
        v0 = lds128(k.lw + so + SL + SL_V); v1 = lds128(k.lw + so + SL + SL_V + 4096);
#pragma unroll
        for (int i = NPX; i < NPF; i++) wo[i] = lds128(k.lw + w5 + R_WO + i * 4096);
        PIN(4);
        const float mo = -__int_as_float(mp >= 0 ? mp : mn) * SC_LOG2E;
        s0 = ex2(fmaf(s0, SC_LOG2E, mo)); s1 = ex2(fmaf(s1, SC_LOG2E, mo));
        sts32(((k.sp + z) >> 16) + (sb + R_PB), pack2(s0, s1));
        ls = k.lw < sb + 320 ? __float_as_uint((s0 + s1) + 4.f) : 0;
    }
    bar_sync(NB_P, 256);
    {
        const uint4 pp = lds128(k.lw + R_PB);
        PIN(5);
        const uint32_t pm = lds32(((k.lw + z) >> 2) + (sb - (sb >> 2) + R_PB + 512));
        PIN(5);
        if (EGO) arrive_if(sb + R_BAR + (RB_GO + 2 * X + (s & 1)) * 8, k.sp, X ? s + 1 < hi : s >= lo);
        sts32(sb + R_IL + (wz >> 1) * 16 + (wz & 1) * 4, __reduce_add_sync(0xffffffffu, ls) - 20u * 0x40800000u);
        float o0[4] = {0, 0, 0, 0}, o1[4] = {0, 0, 0, 0}, o2[4] = {0, 0, 0, 0};
        mma16(o0, v0.x, v0.y, v0.z, v0.w, pp.x, pp.y);
        mma16(o1, v1.x, v1.y, v1.z, v1.w, pp.z, pp.w);
        mma8(o2, vv[0], vv[1], pm);
        asm volatile("stmatrix.sync.aligned.m8n8.x2.trans.shared.b16 [%0],{%1,%2};" ::"r"(k.lw + wz * 256 + R_OB),
                     "r"(pack2(o0[0] + o1[0] + o2[0], o0[1] + o1[1] + o2[1])), "r"(pack2(o0[2] + o1[2] + o2[2], o0[3] + o1[3] + o2[3])) : "memory");
    }
    bar_sync(NB_O, 256);
    {
        float r0[2][4] = {{0, 0, 0, 0}, {0, 0, 0, 0}}, r1[2][4] = {{0, 0, 0, 0}, {0, 0, 0, 0}};
        uint4 b[4];
        b[0] = ldsm4(k.lw + R_OB);
        PIN(6);
        b[1] = ldsm4(k.lw + R_OB + 512);
        PIN(6);
#pragma unroll
        for (int m = NWO + NPF; m < 16; m++) if (((OL >> (2 * (15 - m))) & 3) == 3) wo[m] = lds128(k.lw + w5 + R_WO + (m - NWO) * 4096);
        const uint2 il = lds64(sb + R_IL + ((k.lw + z) & 48));
        PIN(6);
        float i0, i1;
        uint4* dst;
#pragma unroll
        for (int i = 0; i < 4; i++) {
            mma16(r0[0], wo[4 * i].x, wo[4 * i].y, wo[4 * i].z, wo[4 * i].w, b[i].x, b[i].y);
            mma16(r1[0], wo[4 * i + 1].x, wo[4 * i + 1].y, wo[4 * i + 1].z, wo[4 * i + 1].w, b[i].x, b[i].y);
            mma16(r0[OA], wo[4 * i + 2].x, wo[4 * i + 2].y, wo[4 * i + 2].z, wo[4 * i + 2].w, b[i].z, b[i].w);
            mma16(r1[OA], wo[4 * i + 3].x, wo[4 * i + 3].y, wo[4 * i + 3].z, wo[4 * i + 3].w, b[i].z, b[i].w);
            if (i < 2) b[i + 2] = ldsm4(k.lw + R_OB + (i + 2) * 512);
#pragma unroll
            for (int m = NWO + NPF; m < 16; m++) if (i < 3 && i == ((OL >> (2 * (15 - m))) & 3)) wo[m] = lds128(k.lw + w5 + R_WO + (m - NWO) * 4096);
            if (i == 1) { i0 = rcp(__uint2float_rn(il.x)) * 2097152.f; i1 = rcp(__uint2float_rn(il.y)) * 2097152.f; }
            if (i == 2) {
                const uint32_t po = k.po + z;
                dst = (uint4*)((char*)xregion(X, 0) + ((po & ~1u) ^ ((po & X) << 12)));
                asm volatile("" : "+l"(dst));
            }
            PIN(7);
        }
        const uint32_t tag = (s + 1) & 1;
#pragma unroll
        for (int i = 0; i < 4; i++) { r0[0][i] = (OA ? r0[0][i] + r0[1][i] : r0[0][i]) * ((i & 1) ? i1 : i0); r1[0][i] = (OA ? r1[0][i] + r1[1][i] : r1[0][i]) * ((i & 1) ? i1 : i0); }
        st_rlx128(dst, (pack2(r0[0][0], r0[0][2]) & ~1u) | tag,
                  pack2(r1[0][0], r1[0][2]), pack2(r0[0][1], r0[0][3]), pack2(r1[0][1], r1[0][3]));
        bar_arrive(NB_PART + X, 288);
#pragma unroll
        for (int t = 0; t < V_PRE; t++) if (!((VMASK >> t) & 1)) wv[t] = lds128(k.lw + w5 + R_WV + t * 4096);
        if (!EGO) arrive_if(sb + R_BAR + (RB_GO + 2 * X + (s & 1)) * 8, k.sp, X ? s + 1 < hi : s >= lo);
    }
}

__device__ __forceinline__ void rec_fetch(const Params& p, uint32_t sb, int head, uint32_t rank, int which, int dst) {
#pragma unroll 1
    for (int j = 0; j < 8; j++) tma2d(sb + dst + j * 8192, &p.tm[which], head * 128 + (j >> 2) * 64, rank * 256 + (j & 3) * 64, sb + R_BAR + RB_INIT * 8);
}

__device__ __forceinline__ void rec_weights(const Params& p, uint32_t sb, int head, uint32_t rank, int w) {
    const int lane = threadIdx.x & 31, g = lane >> 2, c = lane & 3;
    const int t = w & 3, WG = w >> 2;
    uint32_t wq[16][4], wk[16][4];
    uint4 wo[16], wv[16];
    const uint32_t woff = sb + WG * 32768 + (((lane >> 4) << 3) + (lane & 7)) * 128 + (((2 * t + ((lane >> 3) & 1)) ^ (lane & 7)) << 4);
    const uint32_t lw = sb + lane * 16;
    PROF(threadIdx.x == 0, 3501);
    {
        const __nv_bfloat16* wp = p.Wo + (size_t)(head * 128 + 2 * c) * 512 + rank * 256 + w * 32 + g * 4;
#pragma unroll
        for (int ks = 0; ks < 8; ks++) {
            const uint2 r0 = *(const uint2*)(wp + (ks * 16) * 512), r1 = *(const uint2*)(wp + (ks * 16 + 1) * 512);
            const uint2 r2 = *(const uint2*)(wp + (ks * 16 + 8) * 512), r3 = *(const uint2*)(wp + (ks * 16 + 9) * 512);
            const uint4 f[2] = {make_uint4(__byte_perm(r0.x, r1.x, 0x5410), __byte_perm(r0.x, r1.x, 0x7632), __byte_perm(r2.x, r3.x, 0x5410), __byte_perm(r2.x, r3.x, 0x7632)),
                                make_uint4(__byte_perm(r0.y, r1.y, 0x5410), __byte_perm(r0.y, r1.y, 0x7632), __byte_perm(r2.y, r3.y, 0x5410), __byte_perm(r2.y, r3.y, 0x7632))};
#pragma unroll
            for (int h = 0; h < 2; h++) {
                const int m = 2 * ks + h;
                wo[m] = f[h];
            }
        }
    }
    PROF(threadIdx.x == 0, 3502);
    mbar_wait(sb + R_BAR + RB_INIT * 8, 0);
    PROF(threadIdx.x == 0, 3503);
#pragma unroll
    for (int ks = 0; ks < 16; ks++) {
        uint4 a = ldsm4t(woff + R_STQ + ks * 2048), b = ldsm4t(woff + R_STK + ks * 2048);
        wq[ks][0] = a.x; wq[ks][1] = a.y; wq[ks][2] = a.z; wq[ks][3] = a.w;
        wk[ks][0] = b.x; wk[ks][1] = b.y; wk[ks][2] = b.z; wk[ks][3] = b.w;
    }
    bar_sync(NB_W, 256);
#pragma unroll
    for (int m = 0; m < 16; m++)
        if (m < NPF || m >= NPF + NWO) sts128(lw + w * 512 + R_WO + (m < NPF ? m : m - NWO) * 4096, wo[m].x, wo[m].y, wo[m].z, wo[m].w);
#pragma unroll
    for (int i = 0; i < 16; i++) {
        wv[i] = ldsm4t(woff + R_STV + i * 2048);
        if (!((VMASK >> i) & 1)) sts128(lw + w * 512 + R_WV + i * 4096, wv[i].x, wv[i].y, wv[i].z, wv[i].w);
    }
    fence_async_smem();
    PROF(threadIdx.x == 0, 3504);
    __syncthreads();
    cluster_sync();
    PROF(threadIdx.x == 0, 3505);
    RecW k;
    {
        const int r = (w * 4 + (lane >> 3)) * 2 + rank;
        const uint32_t sl = lds32(sb + R_SEL + r * 4);
        const int slot = HL == 0 ? head * 8 + (lane & 7) : HL == 1 ? (head >> 2) * 32 + ((lane & 7) >> 1) * 8 + (head & 3) * 2 + (lane & 1) : (head >> 1) * 16 + ((lane & 7) >> 2) * 8 + (head & 1) * 4 + (lane & 3);
        k.po = (r * 512 + slot + (sl & 1) * 256) * 16 + (((sl >> 1) ^ sl) & 1);
    }
    k.dp = mapa(sb, rank ^ 1) - sb;
    k.lw = __shfl_sync(0xffffffffu, lw, lane);
    k.sp = __shfl_sync(0xffffffffu, (lane & 7) * 656 + (lane >> 3) * 128 + w * 16 + ((g < 4 ? (w * 4 + c) * 16 + g * 4 : 512 + (w * 4 + c) * 4) << 16), lane);
    k.w = w;
    const int e0 = (p.chains & 1) ? 64 : 0, o1 = (p.chains & 2) ? p.lag : 1000, nit = (p.chains & 2) ? p.lag + 64 : e0;
    const uint32_t zero = p.zero;
    int it = 0, X = e0 ? 0 : 1;
#pragma unroll 1
    while (it < nit) {
        rec_step(k, sb, X, X ? it - o1 : it, zero, o1, e0 - o1, o1 + 1 - X, wq, wk, wv, wo);
        if (X == 0 && it >= o1) X = 1; else { it++; X = it < e0 ? 0 : 1; }
    }
}

__device__ __forceinline__ uint32_t mism(uint32_t a, uint32_t b, uint32_t t) {
    uint32_t d; asm("lop3.b32 %0,%1,%2,%3,0x7e;" : "=r"(d) : "r"(a), "r"(b), "r"(t)); return d;
}
__device__ __forceinline__ uint32_t or3(uint32_t a, uint32_t b, uint32_t c) {
    uint32_t d; asm("lop3.b32 %0,%1,%2,%3,0xfe;" : "=r"(d) : "r"(a), "r"(b), "r"(c)); return d;
}
template <bool TWO, class F>
__device__ __forceinline__ void poll8(uint4* x, const uint4* src, uint32_t tag, F&& use) {
#pragma unroll
    for (int j = 0; j < 8; j++) x[j] = ld_rlx128(src + j * 32);
    int n = 0;
    while (true) {
        use();
        uint32_t bad = or3(mism(x[0].x, x[1].x, tag), mism(x[2].x, x[3].x, tag), mism(x[4].x, x[5].x, tag));
        if (TWO) bad = or3(bad, or3(mism(x[0].z, x[1].z, tag), mism(x[2].z, x[3].z, tag), mism(x[4].z, x[5].z, tag)), mism(x[6].z, x[7].z, tag));
        if (!__any_sync(0xffffffffu, (bad | mism(x[6].x, x[7].x, tag)) & 1)) break;
#pragma unroll
        for (int j = 0; j < 8; j++)
            asm volatile("{.reg .pred p; .reg .b128 t; .reg .b32 m; lop3.b32 m,%0,%6,%5,0x7e; and.b32 m,m,1; setp.ne.u32 p,m,0; mov.b128 t,{%0,%1,%2,%3};"
                         "@p ld.relaxed.gpu.global.b128 t,[%4]; mov.b128 {%0,%1,%2,%3},t;}"
                         : "+r"(x[j].x), "+r"(x[j].y), "+r"(x[j].z), "+r"(x[j].w) : "l"(src + j * 32), "r"(tag), "r"(TWO ? x[j].z : tag) : "memory");
        if (++n > 2000000) __trap();
    }
}

__device__ __forceinline__ void rec_comm(const Params& p, uint32_t sb, int X, int head, uint32_t rank) {
    const int lane = threadIdx.x & 31, g = lane >> 2, c = lane & 3;
    const int me = head * 2 + rank;
    const uint32_t mb = sb + R_M + X * 4096 + lane * 16;
    uint4 x[8];
#pragma unroll
    for (int j = 0; j < 8; j++) x[j] = *(const uint4*)(p.mem0 + (lane & 7) * 512 + rank * 256 + (j * 4 + (lane >> 3)) * 8);
    const uint32_t sl = lds32(sb + R_SEL + me * 4);
    const uint4* src1 = xregion(X, me) + ((sl >> X) & 1) * 256 + (HL == 0 ? c * 8 + g : HL == 1 ? (g >> 1) * 8 + c * 2 + (g & 1) : (c >> 1) * 16 + (g >> 2) * 8 + (c & 1) * 4 + (g & 3));
    const uint4* src2 = xregion(X, 64 + rank) + ((sl >> (2 + X)) & 1) * 256 + lane;
    uint2* mdst = (uint2*)(xregion(X, 64 + rank) + (c >> 1) * 256 + head * 8 + (g & 3) * 2 + (c & 1)) + (g >> 2);
    const uint32_t one = (g & 1) ? 0x3f800000u : 0x00003f80u, selA = (g & 2) ? 0u : one, selB = (g & 2) ? one : 0u;
    const uint32_t qb = sb + R_BAR + (RB_QK + X * 8 + lane) * 8;
    if (lane < 8) mbar_expect(qb, 768);
    if (!XFW) mbar_wait(sb + R_BAR + (RB_XFULL + X * 2) * 8, 0);
#pragma unroll
    for (int j = 0; j < 8; j++) sts128(mb + j * 512, x[j].x, x[j].y, x[j].z, x[j].w);
#pragma unroll 1
    for (int s = 0;; s++) {
        bar_arrive(NB_MFULL + X, 288);
        PROF(lane == 0, X * 64 + s);
        bar_sync(NB_PART + X, 288);
        if (s == 63) break;
        const uint32_t tag = (s + 1) & 1;
        if (lane < 8) mbar_expect(qb, 768);
        spin(D1);
        uint32_t m0, m1;
        poll8<false>(x, src1, tag, [&]() {
            float a[RACC][4];
#pragma unroll
            for (int j = 0; j < 8; j++) {
                if (j < RACC) a[j][0] = a[j][1] = a[j][2] = a[j][3] = 0;
                mma16(a[j % RACC], x[j].x, x[j].y, x[j].z, x[j].w, selA, selB);
            }
#pragma unroll
            for (int i = 0; i < 4; i++) a[0][i] = RACC == 3 ? a[0][i] + a[1][i] + a[2 % RACC][i] : a[0][i] + a[1][i];
            m0 = (pack2(a[0][0], a[0][1]) & ~1u) | tag; m1 = pack2(a[0][2], a[0][3]);
        });
        asm volatile("st.relaxed.gpu.global.b64 [%0],%1;" ::"l"(mdst), "l"(((uint64_t)m1 << 32) | m0) : "memory");
        const uint32_t t2 = clk32();
        if (!XFW) mbar_wait(sb + R_BAR + (RB_XFULL + X * 2 + tag) * 8, ((s + 1) >> 1) & 1);
        while (clk32() - t2 < D2) {}
        poll8<true>(x, src2, tag, [&]() {
#pragma unroll
            for (int j = 0; j < 8; j++) sts128(mb + j * 512, x[j].x, x[j].y, x[j].z, x[j].w);
        });
    }
}

template <int MT>
__device__ __forceinline__ void xattn(uint32_t l16, uint32_t l8, uint32_t os, int g, int c) {
    constexpr int NT = 3 + 2 * MT, XUN = XU;
    float S[NT][4];
#pragma unroll
    for (int i = 0; i < NT; i++) S[i][0] = S[i][1] = S[i][2] = S[i][3] = 0;
#pragma unroll XUN
    for (int ks = 0; ks < 8; ks++) {
        const uint4 q = lds128(l16 + SL_Q + ks * 512);
        const uint2 u = lds64(l8 + SL_KM + ks * 256);
        mma16(S[0], q.x, q.y, q.z, q.w, u.x, u.y);
#pragma unroll
        for (int m = 0; m <= MT; m++) {
            const uint4 kk = lds128(l16 + m * 4096 + ks * 512);
            mma16(S[1 + 2 * m], q.x, q.y, q.z, q.w, kk.x, kk.z); mma16(S[2 + 2 * m], q.x, q.y, q.z, q.w, kk.y, kk.w);
        }
    }
    const float NEG = -__int_as_float(0x7f800000);
    if (2 * c > g) { S[NT - 2][0] = NEG; S[NT - 1][2] = NEG; }
    if (2 * c + 1 > g) { S[NT - 2][1] = NEG; S[NT - 1][3] = NEG; }
    S[NT - 1][0] = S[NT - 1][1] = NEG;
    float m0 = fmaxf(S[0][0], S[0][1]), m1 = fmaxf(S[0][2], S[0][3]);
#pragma unroll
    for (int i = 1; i < NT; i++) { if (i < NT - 1) m0 = fmaxf(m0, fmaxf(S[i][0], S[i][1])); m1 = fmaxf(m1, fmaxf(S[i][2], S[i][3])); }
    m0 = fmaxf(m0, __shfl_xor_sync(0xffffffffu, m0, 1)); m1 = fmaxf(m1, __shfl_xor_sync(0xffffffffu, m1, 1));
    m0 = fmaxf(m0, __shfl_xor_sync(0xffffffffu, m0, 2)); m1 = fmaxf(m1, __shfl_xor_sync(0xffffffffu, m1, 2));
    m0 *= -SC_LOG2E; m1 *= -SC_LOG2E;
    float l0 = 0, l1 = 0;
#pragma unroll
    for (int i = 0; i < NT; i++) {
        if (i < NT - 1) { S[i][0] = ex2(fmaf(S[i][0], SC_LOG2E, m0)); S[i][1] = ex2(fmaf(S[i][1], SC_LOG2E, m0)); l0 += S[i][0] + S[i][1]; }
        S[i][2] = ex2(fmaf(S[i][2], SC_LOG2E, m1)); S[i][3] = ex2(fmaf(S[i][3], SC_LOG2E, m1)); l1 += S[i][2] + S[i][3];
    }
    l0 += __shfl_xor_sync(0xffffffffu, l0, 1); l1 += __shfl_xor_sync(0xffffffffu, l1, 1);
    l0 += __shfl_xor_sync(0xffffffffu, l0, 2); l1 += __shfl_xor_sync(0xffffffffu, l1, 2);
    uint2 vm = lds64(l8 + SL_VM);
    uint4 v[2];
#pragma unroll
    for (int m = 0; m <= MT; m++) v[m] = lds128(l16 + SL_V + m * 4096);
    l0 = rcp(l0); l1 = rcp(l1);
    uint32_t P[NT][2];
#pragma unroll
    for (int i = 0; i < NT; i++) { P[i][0] = i < NT - 1 ? pack2(S[i][0] * l0, S[i][1] * l0) : 0u; P[i][1] = pack2(S[i][2] * l1, S[i][3] * l1); }
#pragma unroll
    for (int et = 0; et < 8; et++) {
        float a[4] = {0, 0, 0, 0}, b[4] = {0, 0, 0, 0};
        const uint2 um = vm;
        const uint4 u[2] = {v[0], v[MT]};
        if (et < 7) {
            vm = lds64(l8 + SL_VM + et * 256 + 256);
#pragma unroll
            for (int m = 0; m <= MT; m++) v[m] = lds128(l16 + SL_V + m * 4096 + et * 512 + 512);
            PIN(11);
        }
        mma8(a, um.x, um.y, P[0][0]); mma8(b, um.x, um.y, P[0][1]);
#pragma unroll
        for (int m = 0; m <= MT; m++) {
            mma16(a, u[m].x, u[m].y, u[m].z, u[m].w, P[1 + 2 * m][0], P[2 + 2 * m][0]); mma16(b, u[m].x, u[m].y, u[m].z, u[m].w, P[1 + 2 * m][1], P[2 + 2 * m][1]);
        }
        asm volatile("stmatrix.sync.aligned.m8n8.x4.trans.shared.b16 [%0],{%1,%2,%3,%4};" ::"r"(os + (et >> 2) * 2048 + (et & 3) * 256),
                     "r"(pack2(a[0], a[1])), "r"(pack2(a[2], a[3])), "r"(pack2(b[0], b[1])), "r"(pack2(b[2], b[3])) : "memory");
    }
}

__device__ __forceinline__ void rec_tiles(uint32_t sb, int X, int head, uint32_t rank, int& nxt, int lim, int need) {
#pragma unroll 1
    while (nxt <= lim) {
        if ((nxt & 1) == 0) {
            unsigned v; int n = 0;
            while (true) {
                asm volatile("ld.relaxed.gpu.global.u32 %0,[%1];" : "=r"(v) : "l"(cnt_ptr(C_QKV + X * 32 + (nxt >> 1))) : "memory");
                if (__all_sync(0xffffffffu, v >= 2 * NQ)) break;
                if (nxt > need) return;
                if (++n > 3000000) __trap();
            }
        }
        if (elect()) {
            const uint32_t bar = sb + R_BAR + (RB_XFULL + X * 2 + (nxt & 1)) * 8, dst = sb + R_SL + (X * 2 + (nxt & 1)) * SLOT;
            const uint4* src = g_qkv + (size_t)((X * 64 + nxt) * 32 + head) * 1536;
            mbar_expect(bar, 20480);
            bulk_g2s_mc(dst + rank * 8192, src + 512 + rank * 512, 8192, bar, POL_LAST);
            bulk_g2s(dst + SL_Q, src + (rank ^ X) * 256, 4096, bar, POL_LAST);
        }
        __syncwarp();
        nxt++;
    }
}

__device__ __forceinline__ void rec_attn(const Params& p, uint32_t sb, int X, int head, uint32_t rank) {
    const int lane = __shfl_sync(0xffffffffu, threadIdx.x & 31, threadIdx.x & 31), g = lane >> 2, c = lane & 3;
    const int mt = rank ^ X;
    const uint32_t dp = mapa(sb, rank ^ 1) - sb;
    int nxt = 0;
    rec_tiles(sb, X, head, rank, nxt, 1, 0);
#pragma unroll 1
    for (int s = 0; s < 64; s++) {
        const uint32_t so = sb + R_SL + (X * 2 + (s & 1)) * SLOT;
        while (nxt <= min(s + 1, 63)) {
            uint32_t ok;
            asm volatile("{.reg .pred p; mbarrier.test_wait.parity.shared::cta.b64 p,[%1],%2; selp.u32 %0,1,0,p;}" : "=r"(ok) : "r"(sb + R_BAR + (RB_GO + X * 2 + (s & 1)) * 8), "r"((s >> 1) & 1) : "memory");
            if (__any_sync(0xffffffffu, ok)) break;
            rec_tiles(sb, X, head, rank, nxt, s + 1, -1);
        }
        mbar_wait(sb + R_BAR + (RB_GO + X * 2 + (s & 1)) * 8, (s >> 1) & 1);
        spin(DX);
        mbar_wait(sb + R_BAR + (RB_XFULL + X * 2 + (s & 1)) * 8, (s >> 1) & 1);
        if (elect()) asm volatile("cp.async.bulk.wait_group.read 0;" ::: "memory");
        __syncwarp();
        const uint32_t os = sb + R_OS + X * 4096 + (lane >> 4) * 1024 + (lane & 15) * 16;
        if (mt) xattn<1>(so + lane * 16, so + lane * 8, os, g, c); else xattn<0>(so + lane * 16, so + lane * 8, os, g, c);
        fence_async_smem();
        __syncwarp();
        const uint32_t svb = sb + R_BAR + (RB_SV + X * 2 + (s & 1)) * 8;
        if (elect()) {
            mbar_arrive(svb); mbar_arrive_cluster(svb + dp);
            const uint64_t pol = POL_SOON;
#pragma unroll
            for (int kb = 0; kb < 2; kb++)
                asm volatile("cp.async.bulk.global.shared::cta.bulk_group.L2::cache_hint [%0],[%1],%2,%3;" ::"l"(g_o + ((X * 32 + (s >> 1)) * 64 + head * 2 + kb) * 512 + ((s & 1) * 4 + mt * 2) * 64),
                             "r"(sb + R_OS + X * 4096 + kb * 2048), "r"(2048), "l"(pol) : "memory");
            asm volatile("cp.async.bulk.commit_group;" ::: "memory");
        }
        __syncwarp();
        if (s & 1) {
            if (elect()) { asm volatile("cp.async.bulk.wait_group 0;" ::: "memory"); red_relaxed(cnt_ptr(C_O + (X * 32 + (s >> 1)) * 4 + (head >> 3)), 1); }
            __syncwarp();
        }
        rec_tiles(sb, X, head, rank, nxt, min(s + 1, 63), s + 1);
        mbar_wait(svb, (s >> 1) & 1);
        rec_tiles(sb, X, head, rank, nxt, min(s + 2, 63), -1);
    }
}

__device__ __forceinline__ uint32_t timed_clear(unsigned* r, int lane) {
    uint32_t v = 0;
    const uint32_t t0 = clk32();
    asm volatile("{.reg .pred p; setp.eq.u32 p,%2,0; @p atom.relaxed.gpu.global.exch.b32 %0,[%1],0;}" : "+r"(v) : "l"(r), "r"(lane) : "memory");
    v = __shfl_sync(0xffffffffu, v, 0);
    asm volatile("{.reg .pred p; setp.eq.u32 p,%0,0x5a5a5a5b; @p nanosleep.u32 1;}" ::"r"(v) : "memory");
    return clk32() - t0;
}
__device__ __forceinline__ void rec_slots(int me, int X) {
    const int lane = threadIdx.x & 31;
#pragma unroll 1
    for (int i = lane; i < 512; i += 32) xregion(X, me)[i] = make_uint4(0, 0, 0, 0);
    if (lane < 16) xregion(X, 64 + (me & 1))[(lane >> 3) * 256 + (me >> 1) * 8 + (lane & 7)] = make_uint4(0, 0, 0, 0);
    __syncwarp();
    uint32_t sel = 0;
#pragma unroll 1
    for (int k = 0; k < 2; k++) {
        unsigned* r = (unsigned*)xregion(X, k ? 64 + (me & 1) : me) + k * (me >> 1) * 32;
        uint32_t b0 = ~0u, b1 = ~0u;
#pragma unroll 1
        for (int i = 0; i < 4; i++) { b0 = min(b0, timed_clear(r, lane)); b1 = min(b1, timed_clear(r + 1024, lane)); }
        sel |= (b1 < b0) << (2 * k + X);
    }
    if (lane == 0) ((uint16_t*)g_sel)[me * 2 + X] = sel;
}

__device__ __forceinline__ void rec_init(uint32_t sb) {
    const uint32_t b = sb + R_BAR;
    const int i = threadIdx.x & 31;
    mbar_init(b + i * 8, i >= RB_SV ? 2 : 1);
    if (i == RB_INIT) mbar_expect(b + RB_INIT * 8, 196608);
    asm volatile("fence.mbarrier_init.release.cluster;" ::: "memory");
}
constexpr int G_BAR = B_BAR;
enum { GB_FULL = 0  , GB_EMPTY = 8  , GB_RS = 16, GB_SS = 17, GB_LAG = 18, GB_FREE = 19, GB_DONE = 20  , GB_N = 24 };
constexpr int Q_PRE = 8;
constexpr int NQRS = 2 * NQ - 64;
__device__ __forceinline__ void gemm_init(uint32_t sb, bool op) {
    const int i = threadIdx.x & 31;
    if (i < GB_N) mbar_init(sb + G_BAR + i * 8, i >= GB_DONE ? 4 : i == GB_FREE ? 8 : (i >= GB_EMPTY && i < GB_RS) ? 2 : 1);
    if (i == GB_RS) mbar_expect(sb + G_BAR + i * 8, op ? 131072 : 98304);
    if (i == GB_SS) mbar_expect(sb + G_BAR + i * 8, op ? 131072 : 163840);
    asm volatile("fence.mbarrier_init.release.cluster;" ::: "memory");
}
__device__ __forceinline__ int qkv_blk(int id, int j) { return NQRS * 4 + id * 10 + j; }
__device__ __forceinline__ void qkv_fetch(const Params& p, uint32_t sb, int id, int j0, int j1) {
#pragma unroll 1
    for (int j = j0 * 2; j < j1 * 2; j++) {
        const int blk = min(qkv_blk(id, j >> 1), 511);
        tma2d(sb + j * 8192, &p.tn[blk >> 8], (blk & 255) * 16, (j & 1) * 256, sb + G_BAR + GB_SS * 8);
    }
}
__device__ __forceinline__ void qkv_stage(const Params& p, uint32_t dst, uint32_t bar, int id, int k0, int nk) {
#pragma unroll 1
    for (int j = 0; j < 2 * nk; j++) {
        const int u = id * 2 + (j >= nk);
        tma2d(dst + j * 8192, &p.tm[u < 64 ? 2 : 0], (u & 63) * 64, (k0 + (j >= nk ? j - nk : j)) * 64, bar);
    }
}
__device__ __forceinline__ void op_fetch(const Params& p, uint32_t sb, int id, int half) {
#pragma unroll 1
    for (int j = 0; j < 16; j++) tma2d(sb + j * 8192, &p.tm[4], ((id * 2 + (j >> 3)) & 7) * 64, (id >> 2) * 1024 + (j & 7) * 128 + half * 64, sb + G_BAR + (GB_RS + half) * 8);
}
template <bool OP>
__device__ __forceinline__ void gemm_producer(const Params& p, uint32_t sb, int id) {
    constexpr int NS = OP ? 6 : 8, SB = OP ? 16384 : 8192, RING = OP ? 131072 : 163840;
    if (!elect()) return;
    mbar_wait(sb + G_BAR + GB_FREE * 8, 0);
    if (OP) op_fetch(p, sb, id, 1);
    else {
        mbar_expect(sb + G_BAR + GB_RS * 8, 32768);
        qkv_stage(p, sb + 196608, sb + G_BAR + GB_RS * 8, id, 6, 2);
        qkv_fetch(p, sb, id, Q_PRE, 10);
        mbar_wait(sb + G_BAR + GB_FREE * 8, 1);
    }
    wait_cnt(g_gate, lds32(sb + S_GATE));
    int st = 0; uint32_t ph = 1;
#pragma unroll 1
    for (int n = 0; n < p.nl[OP]; n++) {
        const int e = p.list[OP][n];
        wait_cnt(OP ? cnt_ptr(C_O + e * 4 + (id >> 2)) : cnt_ptr(C_XN + e), 16);
        PROF(true, 1024 + n * 4);
        const uint4* src = OP ? g_o + (e * 64 + (id >> 2) * 16) * 512 : g_xn + e * 4096;
#pragma unroll 1
        for (int s = 0; s < 8; s++) {
            mbar_wait(sb + G_BAR + (GB_EMPTY + st) * 8, ph);
            mbar_expect(sb + G_BAR + (GB_FULL + st) * 8, SB);
            bulk_g2s(sb + RING + st * SB, src + s * (SB / 16), SB, sb + G_BAR + (GB_FULL + st) * 8, POL_N);
            if (++st == NS) { st = 0; ph ^= 1; }
        }
    }
}
__device__ __forceinline__ void qkv_release(const Params& p, uint32_t sb) {
    if (!elect()) return;
#pragma unroll 1
    for (int n = 0; n < 2 * p.nl[0]; n++) {
        const int e = p.list[0][n >> 1];
        mbar_wait(sb + G_BAR + (GB_DONE + (n & 3)) * 8, (n >> 2) & 1);
        red_release(cnt_ptr(C_QKV + e), 1);
        PROF(n & 1, 1024 + (n >> 1) * 4 + 3);
    }
}
__device__ __forceinline__ void op_permute(uint32_t sb) {
#pragma unroll 2
    for (int i = threadIdx.x; i < 4096; i += 256) {
        const uint32_t a = sb + i * 32 + ((i >> 2) & 1) * 16, b = a ^ 16;
        const uint4 x = lds128(a), y = lds128(b);
        sts128(a, __byte_perm(x.x, x.y, 0x5410), __byte_perm(x.z, x.w, 0x5410), __byte_perm(y.x, y.y, 0x5410), __byte_perm(y.z, y.w, 0x5410));
        sts128(b, __byte_perm(x.x, x.y, 0x7632), __byte_perm(x.z, x.w, 0x7632), __byte_perm(y.x, y.y, 0x7632), __byte_perm(y.z, y.w, 0x7632));
    }
    fence_async_smem();
    bar_sync(1, 256);
}
template <bool OP>
__device__ __forceinline__ void gemm_consumer(const Params& p, uint32_t sb, int id, int w) {
    constexpr int NS = OP ? 6 : 8, SB = OP ? 16384 : 8192, RING = OP ? 131072 : 163840;
    const int lane = threadIdx.x & 31, wg = w >> 2, t = w & 3, u = id * 2 + wg;
    uint32_t a[128];
    mbar_wait(sb + G_BAR + GB_RS * 8, 0);
    PROF(threadIdx.x == 0, 3501);
    if (OP) op_permute(sb);
    const uint32_t wo = sb + (((lane >> 4) << 3) + (lane & 7)) * 128 + (((2 * t + ((lane >> 3) & 1)) ^ (lane & 7)) << 4);
#pragma unroll
    for (int ks = 0; ks < 32; ks++) {
        const uint4 v = ldsm4t(wo + ks * 2048 + (OP ? wg * 65536 : ks < 24 ? 131072 + wg * 49152 : 196608 - 49152 + wg * 16384));
        a[ks * 4] = v.x; a[ks * 4 + 1] = v.y; a[ks * 4 + 2] = v.z; a[ks * 4 + 3] = v.w;
        if (ks == 31 || (!OP && ks == 23)) {
            fence_async_smem();
            __syncwarp();
            if (lane == 0) mbar_arrive(sb + G_BAR + GB_FREE * 8);
            if (ks == 23) mbar_wait(sb + G_BAR + GB_RS * 8, 1);
        }
    }
    PROF(threadIdx.x == 0, 3502);
    mbar_wait(sb + G_BAR + GB_SS * 8, 0);
    if (OP) op_permute(sb);
    PROF(threadIdx.x == 0, 3503);
    const uint32_t tag = OP ? lds32(sb + S_TAG) : 0;
    float c0[32], c1[OP ? 32 : 40];
    int st = 0; uint32_t ph = 0;
    const bool el = (threadIdx.x & 127) == 0;
#pragma unroll 1
    for (int n = 0; n < p.nl[OP]; n++) {
        int prev = 0;
        const uint32_t wb = sb + wg * (OP ? 65536 : 81920) + (n & p.zero);
        const uint64_t dw = OP ? mkdesc(wb, 0, 1024, 1) : mkdesc(wb, 16384, 256, 3);
        if (!OP && wg) mbar_wait(sb + G_BAR + GB_LAG * 8, n & 1);
#pragma unroll
        for (int s = 0; s < 8; s++) {
            mbar_wait(sb + G_BAR + (GB_FULL + st) * 8, ph);
            const uint64_t dx = mkdesc(sb + RING + st * SB, 128, 1024, 0);
            wg_fence();
#pragma unroll
            for (int kk = 0; kk < 4; kk++) {
                const int ks = s * 4 + kk;
                if (ks == 0) { wgmma64_rs<0>(c0, a, dx); if (OP) wgmma64_ta<0>(c1, dw, dx + 512); else wgmma80_tb<0>(c1, dx, dw); }
                else { wgmma64_rs<1>(c0, a + ks * 4, dx + kk * 16); if (OP) wgmma64_ta<1>(c1, dw + ks * 128, dx + 512 + kk * 16); else wgmma80_tb<1>(c1, dx + kk * 16, dw + ks * 32); }
            }
            wg_commit();
            if (s) {
                wg_wait<1>();
                if (el) { mbar_arrive(sb + G_BAR + (GB_EMPTY + prev) * 8); if (!OP && s == QLAG && !wg) mbar_arrive(sb + G_BAR + GB_LAG * 8); }
            }
            prev = st;
            if (++st == NS) { st = 0; ph ^= 1; }
        }
        const int e = p.list[OP][n];
        wg_wait<0>();
        if (el) mbar_arrive(sb + G_BAR + (GB_EMPTY + prev) * 8);
        PROF(threadIdx.x == 128, 1024 + n * 4 + 1);
        if (OP) {
            uint4* dst = g_pp + (e * 4 + (id >> 2)) * 4096 + ((u & 7) * 32 + t * 8) * 16 + (lane >> 2) * 16 + (lane & 3);
#pragma unroll
            for (int j = 0; j < 4; j++) {
                const float* x = c0 + j * 8; const float* y = c1 + j * 8;
                st_rlx128(dst + j * 4, (pack2(x[0] + y[0], x[1] + y[1]) & ~1u) | tag, pack2(x[2] + y[2], x[3] + y[3]), (pack2(x[4] + y[4], x[5] + y[5]) & ~1u) | tag, pack2(x[6] + y[6], x[7] + y[7]));
            }
            if (lane == 0) red_relaxed(cnt_ptr(C_PP + e * 8 + (u & 7)), 1);
            PROF(threadIdx.x == 128, 1024 + n * 4 + 3);
        } else {
            uint4* dst = g_qkv + (size_t)e * 2 * 32 * 1536 + lane;
            const uint64_t pol = POL_SOON;
#pragma unroll
            for (int j = 0; j < 4; j++) {
                const float* x = c0 + j * 8;
                uint4 v = make_uint4(pack2(x[0], x[1]), pack2(x[2], x[3]), pack2(x[4], x[5]), pack2(x[6], x[7]));
                if (u >= 64) v = make_uint4(movm(v.x), movm(v.z), movm(v.y), movm(v.w));
                stg128(dst + (((j >> 1) * 32 + ((u & 63) >> 1)) * 1536 + (u < 64 ? 1024 : 0) + (j & 1) * 256 + ((u & 1) * 4 + t) * 32), v, pol);
            }
#pragma unroll
            for (int j = 0; j < 5; j++) {
                const float* x = c1 + (OP ? 0 : j * 8);
                const int blk = qkv_blk(id, wg * 5 + j);
                if (blk < 512) stg128(dst + (((t >> 1) * 32 + ((blk >> 3) & 31)) * 1536 + (blk >> 8) * 512 + (t & 1) * 256 + (blk & 7) * 32),
                                      make_uint4(pack2(x[0], x[1]), pack2(x[2], x[3]), pack2(x[4], x[5]), pack2(x[6], x[7])), pol);
            }
        }
        __syncwarp();
        if (!OP && lane == 0) mbar_arrive(sb + G_BAR + (GB_DONE + (n & 1) * 2 + wg) * 8);
        PROF(threadIdx.x == 128, 1024 + n * 4 + 2);
    }
}

template <int NP, bool MMA>
__device__ __forceinline__ void sum_partials(float* x, const uint2* src, const uint32_t* r0, const uint32_t* r1, uint32_t idm, uint32_t tag, bool on) {
    uint2 v[4][NP];
    int n = 0;
    while (true) {
        uint32_t bad = 0;
#pragma unroll
        for (int s = 0; s < 4; s++)
#pragma unroll
            for (int i = 0; i < NP; i++)
                asm volatile("{.reg .pred p; .reg .b64 t; setp.ne.u32 p,%4,0; mov.b64 t,0; @p ld.relaxed.gpu.global.L2::cache_hint.b64 t,[%2],%3; mov.b64 {%0,%1},t;}"
                             : "=r"(v[s][i].x), "=r"(v[s][i].y) : "l"(src + s * 8192 + i * 32), "l"(POL_LAST), "r"((uint32_t)on) : "memory");
#pragma unroll
        for (int s = 0; s < 4; s++) bad = or3(bad, mism(v[s][0].x, v[s][1].x, tag), mism(v[s][NP - 2].x, v[s][NP - 1].x, tag));
        if (!__any_sync(0xffffffffu, (bad & 1) && on)) break;
        if (++n > 2000000) __trap();
    }
#pragma unroll
    for (int i = 0; i < NP; i++) {
        uint32_t a, b;
        if (MMA) {
            float t[4] = {0, 0, 0, 0};
            mma16(t, v[0][i].x, v[0][i].y, v[1][i].x, v[1][i].y, idm, idm); mma16(t, v[2][i].x, v[2][i].y, v[3][i].x, v[3][i].y, idm, idm);
            a = pack2(t[0], t[2]); b = pack2(t[1], t[3]);
        } else {
            a = pack2((blo(v[0][i].x) + blo(v[1][i].x)) + (blo(v[2][i].x) + blo(v[3][i].x)), (blo(v[0][i].y) + blo(v[1][i].y)) + (blo(v[2][i].y) + blo(v[3][i].y)));
            b = pack2((bhi(v[0][i].x) + bhi(v[1][i].x)) + (bhi(v[2][i].x) + bhi(v[3][i].x)), (bhi(v[0][i].y) + bhi(v[1][i].y)) + (bhi(v[2][i].y) + bhi(v[3][i].y)));
        }
        const uint32_t s0 = hadd2(a, r0[i]), s1 = hadd2(b, r1[i]);
        x[4 * i] = blo(s0); x[4 * i + 2] = bhi(s0); x[4 * i + 1] = blo(s1); x[4 * i + 3] = bhi(s1);
    }
}
__device__ __forceinline__ const uint2* pp_src(int e, int tile, int lane) { return (const uint2*)g_pp + e * 32768 + tile * 128 + (lane >> 3) * 8 + (lane & 3) * 2 + ((lane >> 2) & 1); }

__device__ __forceinline__ void fin_warp(const Params& p, uint32_t sb, int id) {
    const int grp = (id & ~3) + (threadIdx.x & 3), tp = (id & 3) * 8 + ((threadIdx.x & 31) >> 2);
    wait_cnt_warp(g_gate, lds32(sb + S_GATE));
#pragma unroll 1
    for (int e = 32; e < 64; e++) {
        wait_cnt_warp(cnt_ptr(C_XN + e), 16);
        const uint4 r = ldcg128(g_x + ((128 + grp) * XP + (e - 32) * 32 + tp));
        if (e < 62) wait_cnt_warp(cnt_ptr(C_PP + e * 8 + (id >> 4)), 16);
        wait_flag_warp(cnt_ptr(C_PP + e * 8 + (id >> 4)), 16);
        const uint32_t a[2] = {r.x, r.y}, b[2] = {r.z, r.w};
        float x[8];
        sum_partials<2, false>(x, pp_src(e, 0, tp) + grp * 64, a, b, 0, lds32(sb + S_TAG), true);
        uint2* dst = (uint2*)p.out + ((e - 32) * 64 + tp * 2) * 128 + grp;
#pragma unroll
        for (int t = 0; t < 2; t++)
            dst[t * 128] = make_uint2(__byte_perm(__float_as_uint(x[t]), __float_as_uint(x[2 + t]), 0x7632), __byte_perm(__float_as_uint(x[4 + t]), __float_as_uint(x[6 + t]), 0x7632));
        PROF((threadIdx.x & 31) == 0, 1536 + e);
    }
}

constexpr int PROW = 272, UROW = 2304, UPRE = 256;
constexpr int C_UR = 0  , C_TB = 65536  , C_BG = C_TB + 51200,
              CB_M = 8960, CB_U = CB_M + 1792, CB_BIG = CB_U + 2560, C_ST = C_BG + 8 * CB_BIG  ;
static_assert(C_ST + 4736 <= B_BAR, "smem map");
enum { CB_TB = 0, CB_UF = 1  , CB_CF = 5  , CB_LD = 9   };
__device__ __forceinline__ void conv_init(uint32_t sb, bool spare) {
    const int i = threadIdx.x & 31;
    mbar_init(sb + B_BAR + i * 8, (i >= CB_UF && i < CB_CF && !spare) ? 2 : 1);
    if (i == CB_TB && !spare) mbar_expect(sb + B_BAR + i * 8, 51200);
    asm volatile("fence.mbarrier_init.release.cluster;" ::: "memory");
}
__device__ __forceinline__ void mma_q(float* c, const uint32_t* a, const uint4& q) {
    mma16(c, a[0], a[1], a[2], a[3], q.x, q.y); mma16(c, a[4], a[5], a[6], a[7], q.z, q.w);
}
__device__ __forceinline__ uint2 ld_acc(const uint2* p, bool on) {
    uint2 v = make_uint2(0, 0);
    asm volatile("{.reg .pred p; setp.ne.u32 p,%3,0; @p ld.global.cg.v2.u32 {%0,%1},[%2];}" : "+r"(v.x), "+r"(v.y) : "l"(p), "r"((uint32_t)on) : "memory");
    return v;
}
__device__ __forceinline__ void add_acc(float* c, uint2 v) { c[0] += blo(v.x); c[1] += bhi(v.x); c[2] += blo(v.y); c[3] += bhi(v.y); }
__device__ __forceinline__ void st_acc(uint2* p, const float* c) { *p = make_uint2(pack2(c[0], c[1]), pack2(c[2], c[3])); }
__device__ __forceinline__ float sum8(const uint4* v, int k) {
#define VK(i) __uint_as_float(k == 0 ? v[i].x : k == 1 ? v[i].y : k == 2 ? v[i].z : v[i].w)
    return ((VK(0) + VK(1)) + (VK(2) + VK(3))) + ((VK(4) + VK(5)) + (VK(6) + VK(7)));
}
template <int XW>
__device__ __forceinline__ void stats_send(uint32_t l16, const float* x, uint4* gs, int q, int w) {
    float s0 = 0, s1 = 0, m0 = 0, m1 = 0;
#pragma unroll
    for (int i = 0; i < 8; i++) { s0 += x[2 * i]; s1 += x[2 * i + 1]; m0 = fmaf(x[2 * i], x[2 * i], m0); m1 = fmaf(x[2 * i + 1], x[2 * i + 1], m1); }
    sts128(l16 + C_ST + w * 512, __float_as_uint(s0), __float_as_uint(m0), __float_as_uint(s1), __float_as_uint(m1));
    if (w == XW) {
        bar_sync(2, 256);
        uint4 v[8];
#pragma unroll
        for (int i = 0; i < 8; i++) v[i] = lds128(l16 + C_ST + i * 512);
        st_rlx128(gs + q * 32, __float_as_uint(sum8(v, 0)), __float_as_uint(sum8(v, 1)) & 0x7fffffffu, __float_as_uint(sum8(v, 2)), __float_as_uint(sum8(v, 3)));
    } else bar_arrive(2, 256);
}
template <int XW>
__device__ __forceinline__ float4 stats_recv(uint32_t l16, const uint4* gs, int w) {
    if (w == XW) {
        uint4 v[8];
        int n = 0;
        while (true) {
            uint32_t bad = 0;
#pragma unroll
            for (int i = 0; i < 8; i++) v[i] = ld_rlx128(gs + i * 32);
#pragma unroll
            for (int i = 0; i < 8; i++) bad |= v[i].y;
            if (!__any_sync(0xffffffffu, bad >> 31)) break;
            if (++n > 2000000) __trap();
        }
        const float s0 = sum8(v, 0) * (1.f / 512.f), s1 = sum8(v, 2) * (1.f / 512.f);
        const float2 l0 = ln_finish(s0, fmaxf(fmaf(sum8(v, 1), 1.f / 512.f, -s0 * s0), 0.f)), l1 = ln_finish(s1, fmaxf(fmaf(sum8(v, 3), 1.f / 512.f, -s1 * s1), 0.f));
        sts128(l16 + C_ST + 4096, __float_as_uint(l0.x), __float_as_uint(rcp(l0.y)), __float_as_uint(l1.x), __float_as_uint(rcp(l1.y)));
    }
    bar_sync(3, 256);
    const uint4 r = lds128(l16 + C_ST + 4096);
    return make_float4(__uint_as_float(r.x), __uint_as_float(r.y), __uint_as_float(r.z), __uint_as_float(r.w));
}

#define HOIST_STOP(k) asm volatile("{.reg .pred p; setp.eq.u32 p,%0,%1; @p nanosleep.u32 1;}" ::"r"(zero), "r"((k) + 1) : "memory")
__device__ __forceinline__ void conv_near(float (*acc)[4], uint32_t ta, uint32_t qa, uint32_t zero) {
#pragma unroll
    for (int k = 0; k < 8; k++) {
        uint32_t a[8];
#pragma unroll
        for (int j = 0; j < 8; j++) a[j] = lds32(ta + k * 800 + j * 32);
        mma_q(acc[k], a, ldsm4(qa + k * 1024));
        if (k % NFE == NFE - 1 && k < 7) HOIST_STOP(k);
    }
}
template <int K0>
__device__ __forceinline__ void conv_pair(float (*acc)[4], float (*pend)[4], uint32_t ta, uint32_t q0, uint32_t q1, uint32_t q2, uint32_t zero) {
#pragma unroll
    for (int i = 0; i < 4; i++) {
        const int k = K0 + i;
#pragma unroll
        for (int e = 0; e < 4; e++) { acc[4 - K0 + i][e] += pend[i][e]; pend[i][e] = 0; }
        uint32_t a[16];
#pragma unroll
        for (int j = 0; j < 16; j++) a[j] = lds32(ta + 256 + k * 800 + j * 32);
        const uint4 x1 = ldsm4(q1 + k * 1024);
        mma_q(acc[k], a, x1); mma_q(pend[i], a, ldsm4(q2 + k * 1024));
        mma_q(pend[i], a + 8, x1); mma_q(acc[k], a + 8, ldsm4(q0 + k * 1024));
        if (i % NFP == NFP - 1 && i < 3) HOIST_STOP(k);
    }
}

__device__ __forceinline__ void conv_tile(const Params& p, uint32_t sb, int q, int w) {
    const int lane = __shfl_sync(0xffffffffu, threadIdx.x & 31, threadIdx.x & 31), g = lane >> 2, c = lane & 3, tile = q * 8 + w;
    const uint32_t l16 = sb + lane * 16;
#pragma unroll
    for (int i = 0; i < 16; i++) sts128(l16 + C_UR + w * 8192 + i * 512, 0, 0, 0, 0);
    wait_cnt_warp(g_gate, lds32(sb + S_GATE));
    if (lane < 8) bulk_g2s(sb + C_TB + (w * 8 + lane) * 800, g_P + (tile * 8 + lane) * PROW + 72, 800, sb + B_BAR + CB_TB * 8, POL_N);
    uint32_t A[8][8];
#pragma unroll
    for (int k = 0; k < 8; k++)
#pragma unroll
        for (int j = 0; j < 8; j++) A[k][j] = __ldcg(g_P + (tile * 8 + k) * PROW + 16 + 8 * j + g - 2 * c);
    if (lane == 0) { const uint4 d = __ldg((const uint4*)p.Dskip + tile); sts128(sb + C_ST + 4608 + w * 16, d.x, d.y, d.z, d.w); }
    float acc[8][4], pend[4][4];
#pragma unroll
    for (int k = 0; k < 8; k++) acc[k][0] = acc[k][1] = acc[k][2] = acc[k][3] = pend[k & 3][k >> 2] = pend[k & 3][2 + (k >> 2)] = 0;
    const uint32_t row = sb + C_UR + w * 8192, ta = sb + C_TB + w * 6400 + (8 + g - 2 * c) * 4, zero = p.zero, qo = (lane & 7) * 16 - (lane >> 3) * 32;
    bar_sync(4, 384);
    mbar_wait(sb + B_BAR + CB_TB * 8, 0);
#pragma unroll 1
    for (int b = -2; b < 32; b++) {
        const int lz = lane + (b & p.zero);
        const bool on = b >= 0;
        uint4 r0 = make_uint4(0, 0, 0, 0), r1 = r0;
        asm volatile("{.reg .pred p; setp.ge.s32 p,%9,0; @p ld.global.cg.v4.u32 {%0,%1,%2,%3},[%8]; @p ld.global.cg.v4.u32 {%4,%5,%6,%7},[%8+%10];}"
                     : "+r"(r0.x), "+r"(r0.y), "+r"(r0.z), "+r"(r0.w), "+r"(r1.x), "+r"(r1.y), "+r"(r1.z), "+r"(r1.w) : "l"(g_x + (tile * 2 * XP + b * 32 + lz)), "r"(b), "n"(XP * 16) : "memory");
        const uint32_t q1 = row + ((qo + (b - 1) * 128) & 1023);
        if (w == 0) conv_near(acc, ta, q1, zero);
        PROF(threadIdx.x == 0 && on, 2048 + b * 8);
        const uint2* pps = pp_src(b, tile, lz);
        asm volatile("" : "+l"(pps));
        const uint32_t tag = lds32(sb + S_TAG);
        wait_flag_warp(cnt_ptr(C_PP + b * 8 + q), on ? 16 : 0);
        PROF(threadIdx.x == 0 && on, 2048 + b * 8 + 1);
        float x[16];
        {
            const uint32_t a[4] = {r0.x, r0.y, r1.x, r1.y}, bb[4] = {r0.z, r0.w, r1.z, r1.w};
            sum_partials<4, true>(x, pps, a, bb, (2 * (lz & 3) == lz >> 2) ? 0x00003f80u : (2 * (lz & 3) + 1 == lz >> 2) ? 0x3f800000u : 0u, tag, on);
        }
        stats_send<0>(l16, x, g_st + (b + 2) * 256 + lz, q, w);
        {
            PROF(threadIdx.x == 0 && on, 2048 + b * 8 + 2);
            if (on) mbar_wait(sb + B_BAR + (CB_CF + (w >> 1)) * 8, b & 1);
            const uint2* cb = g_carry + ((tile * 320 + b) * 32 + lz);
            uint2 cr[8];
#pragma unroll
            for (int k = 0; k < 8; k++) cr[k] = ld_acc(cb + k * 1280, b >= 4);
            if (w && b) conv_near(acc, ta, q1, zero);
#pragma unroll
            for (int k = 0; k < 8; k++) add_acc(acc[k], cr[k]);
        }
        float4 ln = stats_recv<0>(l16, g_st + (b + 2) * 256 + lz, w);
        PROF(threadIdx.x == 0 && on, 2048 + b * 8 + 3);
        uint32_t u[8];
#pragma unroll
        for (int k = 0; k < 8; k++) {
            u[k] = pack2(rbf(x[2 * k] - ln.x) * ln.y, rbf(x[2 * k + 1] - ln.z) * ln.w);
            sts32(row + k * 1024 + (b & 7) * 128 + lane * 4, u[k]);
        }
        __syncwarp();
        const uint32_t qa = row + ((qo + b * 128) & 1023);
#pragma unroll
        for (int k = 0; k < 8; k++) mma_q(acc[k], A[k], ldsm4(qa + k * 1024));
        const uint4 dk = lds128(sb + C_ST + 4608 + w * 16);
#pragma unroll
        for (int k = 0; k < 8; k++) {
            const float t = __shfl_sync(0xffffffffu, acc[k][3], (lz & ~3) | ((lz - 1) & 3));
            const uint32_t y = movm(pack2(acc[k][0] + (c ? t : 0.f), acc[k][1] + acc[k][2]));
            acc[k][0] = c ? 0.f : t; acc[k][1] = acc[k][2] = acc[k][3] = 0;
            const uint32_t dw = k >> 1 == 0 ? dk.x : k >> 1 == 1 ? dk.y : k >> 1 == 2 ? dk.z : dk.w;
            const uint32_t s = hadd2(hadd2(y, hmul2(u[k], __byte_perm(dw, 0, (k & 1) ? 0x3232 : 0x1010))), __byte_perm(__float_as_uint(x[2 * k]), __float_as_uint(x[2 * k + 1]), 0x7632));
            x[2 * k] = blo(s); x[2 * k + 1] = bhi(s);
        }
        arrive_if(sb + B_BAR + (CB_UF + (w >> 1)) * 8, lz, b < -1 ? 32 : 0);
        stats_send<1>(l16, x, g_st + (36 + b) * 256 + lz, q, w);
        {
            PROF(threadIdx.x == 0 && on, 2048 + b * 8 + 4);
            uint4* dst = g_x + ((128 + tile * 2) * XP + b * 32 + lz);
#pragma unroll
            for (int e = 0; e < 2; e++) {
                const float* y = x + e * 8;
                if (on) dst[e * XP] = make_uint4(__byte_perm(__float_as_uint(y[0]), __float_as_uint(y[2]), 0x7632), __byte_perm(__float_as_uint(y[4]), __float_as_uint(y[6]), 0x7632),
                                           __byte_perm(__float_as_uint(y[1]), __float_as_uint(y[3]), 0x7632), __byte_perm(__float_as_uint(y[5]), __float_as_uint(y[7]), 0x7632));
            }
            uint32_t* du = g_u + (tile * 8 * (UROW / 2) + UPRE / 2 + b * 32 + lz);
#pragma unroll
            for (int k = 0; k < 8; k++) if (on) du[k * (UROW / 2)] = u[k];
        }
#pragma unroll 1
        for (int pass = 0; pass < 2; pass++) {
            if (pass == (w == 1 || b < NLATE)) {
                const uint32_t q0 = row + ((qo + (b - 2) * 128) & 1023);
                if (b & 1) conv_pair<4>(acc, pend, ta, q0, q1, qa, zero); else conv_pair<0>(acc, pend, ta, q0, q1, qa, zero);
            }
            if (pass) break;
            ln = stats_recv<1>(l16, g_st + (36 + b) * 256 + lz, w);
            PROF(threadIdx.x == 0 && on, 2048 + b * 8 + 5);
            uint32_t o[2][4];
#pragma unroll
            for (int e = 0; e < 2; e++) {
                const float mu = e ? ln.z : ln.x, rs = e ? ln.w : ln.y;
#pragma unroll
                for (int i = 0; i < 4; i++) o[e][i] = pack2(rbf(x[4 * i + e] - mu) * rs, rbf(x[4 * i + 2 + e] - mu) * rs);
            }
#pragma unroll
            for (int i = 0; i < 4; i++) {
                const uint32_t t = __shfl_xor_sync(0xffffffffu, (lz & 1) ? o[0][i] : o[1][i], 1);
                if (lz & 1) o[0][i] = t; else o[1][i] = t;
            }
            uint4* dst = g_xn + ((32 + b) * 4096 + q * 512 + (lz >> 2) * 64 + w * 8 + (lz & 2) * 2 + (lz & 1));
            if (on) { dst[0] = make_uint4(o[0][0], o[0][1], o[0][2], o[0][3]); dst[2] = make_uint4(o[1][0], o[1][1], o[1][2], o[1][3]); }
            if (w == 7) {
                bar_sync(5, 256);
                if (elect()) red_release(cnt_ptr(on ? C_XN + 32 + b : C_FAR + 2), 2);
                PROF(lane == 0 && on, 2048 + b * 8 + 6);
                __syncwarp();
            } else bar_arrive(5, 256);
        }
    }
}

template <int P0, bool TRI = false>
__device__ __forceinline__ void bg_half(float (*acc)[4], uint4* win, uint32_t ta, uint32_t qa, uint32_t mask, uint32_t row) {
#pragma unroll
    for (int i = 0; i < 4; i++) {
        win[P0 + i] = ldsm4(((qa + i * 128) & mask) + row);
        const uint4 a = lds128(ta + (3 - i) * 448), e = lds128(ta + (3 - i) * 448 + 224);
#pragma unroll
        for (int r = TRI ? 7 - P0 - i : 0; r < 8; r++) mma16(acc[r], a.x, a.y, a.z, a.w, win[(P0 + i + 1 + r) & 7].x, win[(P0 + i + 1 + r) & 7].y);
#pragma unroll
        for (int r = TRI ? 7 - P0 - i : 0; r < 8; r++) mma16(acc[r], e.x, e.y, e.z, e.w, win[(P0 + i + 1 + r) & 7].z, win[(P0 + i + 1 + r) & 7].w);
    }
}
__device__ __forceinline__ void bg_fetch(uint32_t sb, int q, int j, int n, int lane) {
    const int b0 = n >> 1, ch = q * 64 + j * 16 + (n & 1) * 8 + (b0 & 7), lo = max(b0 - 24, -4), nu = b0 > 4 ? (b0 - 4 - lo) * 128 : 0;
    const uint32_t bar = sb + B_BAR + (CB_LD + j * 2 + (n & 1)) * 8, buf = sb + C_BG + (j * 2 + (n & 1)) * CB_BIG;
    const int nt = min(max((b0 + 7) >> 2, 2), 5) * 1792;
    if (elect()) {
        mbar_expect(bar, nt + nu + 1792);
        bulk_g2s(buf, g_W + ch * 784, nt, bar, POL_N);
        bulk_g2s(buf + CB_M, g_W + (ch ^ 4) * 784, 1792, bar, POL_N);
        if (nu) bulk_g2s(buf + CB_U + (lo - b0 + 24) * 128, g_u + ch * (UROW / 2) + UPRE / 2 + lo * 32, nu, bar, POL_N);
    }
    __syncwarp();
}
__device__ __forceinline__ void conv_back(uint32_t sb, int q, int j) {
    const int lane = __shfl_sync(0xffffffffu, threadIdx.x & 31, threadIdx.x & 31), g = lane >> 2, c = lane & 3;
    wait_cnt_warp(g_gate, lds32(sb + S_GATE));
    bg_fetch(sb, q, j, 0, lane);
    bar_sync(4, 384);
    const uint32_t to = (6 + g - 2 * c) * 16, qo = (lane & 7) * 16 - (lane >> 3) * 32;
#pragma unroll 1
    for (int n = 0; n < 64; n++) {
        const int b0 = n >> 1, i = n & 1, chl = j * 16 + i * 8 + (b0 & 7), hm = (b0 + 7) >> 2;
        const uint32_t buf = sb + C_BG + (j * 2 + i) * CB_BIG, ta = buf + to;
        float acc[8][4];
        uint4 win[8];
        if (n < 63) bg_fetch(sb, q, j, n + 1, lane);
        if (n == 34 || n == 42) wait_flag_warp(cnt_ptr(C_FAR + (n == 42)), 12);
        mbar_wait(sb + B_BAR + (CB_LD + j * 2 + i) * 8, b0 & 1);
#pragma unroll
        for (int r = 0; r < 8; r++) {
            acc[r][0] = acc[r][1] = acc[r][2] = acc[r][3] = 0;
            win[r] = make_uint4(0, 0, 0, 0);
            if (r) asm volatile("{.reg .pred p; setp.ge.s32 p,%5,24; @p ldmatrix.sync.aligned.m8n8.x4.shared.b16 {%0,%1,%2,%3},[%4];}"
                                : "+r"(win[r].x), "+r"(win[r].y), "+r"(win[r].z), "+r"(win[r].w) : "r"(buf + CB_U + qo + r * 128), "r"(b0 + r) : "memory");
        }
        const uint2* fr = g_far + (((q * 64 + chl) * 8 + b0 - 24) * 32 + lane);
        uint2* cr = g_carry + (((q * 64 + chl) * 40 + b0) * 32 + lane);
        uint2* cm = g_carry + (((q * 64 + (chl ^ 4)) * 40 + b0) * 32 + lane);
        const uint32_t fm = 0xff000000u >> b0;
        uint2 pf[8], pm[4];
#pragma unroll
        for (int r = 0; r < 8; r++) pf[r] = ld_acc(fr + r * 32, (fm >> r) & 1);
#pragma unroll
        for (int r = 0; r < 4; r++) pm[r] = ld_acc(cm + r * 32, b0 > 4);
#pragma unroll 1
        for (int h = hm > 3 ? 5 : 3; h >= 3; h -= 2) {
            if (h <= hm) bg_half<0>(acc, win, ta + (h - 1) * 1792, qo + (28 - 4 * h) * 128, ~0u, buf + CB_U);
            if (h == 3 && i == 0) mbar_wait(sb + B_BAR + (CB_UF + j) * 8, b0 & 1);
            bg_half<4>(acc, win, ta + (h - 2) * 1792, qo + (h == 3 ? b0 - 4 : 12) * 128, h == 3 ? 1023u : ~0u, h == 3 ? sb + C_UR + chl * 1024 : buf + CB_U);
        }
        uint4 wm[8];
#pragma unroll
        for (int r = 1; r < 8; r++) wm[r] = ldsm4(sb + C_UR + (chl ^ 4) * 1024 + ((qo + (b0 + r) * 128) & 1023));
#pragma unroll
        for (int r = 0; r < 8; r++) add_acc(acc[r], pf[r]);
#pragma unroll
        for (int r = 4; r < 8; r++) { st_acc(cr + r * 32, acc[r]); acc[r][0] = blo(pm[r - 4].x); acc[r][1] = bhi(pm[r - 4].x); acc[r][2] = blo(pm[r - 4].y); acc[r][3] = bhi(pm[r - 4].y); }
#pragma unroll
        for (int t = 7; t >= 0; t--) {
            const uint4 a = lds128(ta + t * 224), e = lds128(ta + CB_M + t * 224);
#pragma unroll
            for (int r = 0; r < 4; r++) { const uint4& x = win[4 + r - (t >> 1)]; mma16(acc[r], a.x, a.y, a.z, a.w, (t & 1) ? x.z : x.x, (t & 1) ? x.w : x.y); }
#pragma unroll
            for (int r = 0; r < 4; r++) { const uint4& x = wm[4 + r - (t >> 1)]; mma16(acc[4 + r], e.x, e.y, e.z, e.w, (t & 1) ? x.z : x.x, (t & 1) ? x.w : x.y); }
        }
#pragma unroll
        for (int r = 0; r < 4; r++) { st_acc(cr + r * 32, acc[r]); st_acc(cm + r * 32, acc[4 + r]); }
        __syncwarp();
        if (lane == 0 && i) mbar_arrive(sb + B_BAR + (CB_CF + j) * 8);
        PROF(j == 0 && lane == 0 && i, 2048 + b0 * 8 + 7);
    }
}
__device__ __forceinline__ void conv_far(uint32_t sb, int w) {
    const int lane = __shfl_sync(0xffffffffu, threadIdx.x & 31, threadIdx.x & 31), g = lane >> 2, c = lane & 3;
    wait_cnt_warp(g_gate, lds32(sb + S_GATE));
    wait_cnt_warp(cnt_ptr(C_XN + 39), 16);
    const uint32_t to = (6 + g - 2 * c) * 16, qo = (lane & 7) * 16 - (lane >> 3) * 32;
#pragma unroll 1
    for (int n = -1; n * 12 + w < 512; n++) {
        const int t = n * 12 + w, ch = (t & 63) * 8 + (((t >> 6) + 1) & 7), cn = ((t + 12) & 63) * 8 + ((((t + 12) >> 6) + 1) & 7);
        const uint32_t bar = sb + B_BAR + (w * 2 + (n & 1)) * 8, buf = sb + (w * 2 + (n & 1)) * 5120;
        if (t + 12 < 512 && elect()) {
            const uint32_t nb = sb + (w * 2 + (~n & 1)) * 5120;
            mbar_expect(bar ^ 8, 3584 + 1152);
            bulk_g2s(nb, g_W + cn * 784 + 560, 3584, bar ^ 8, POL_N);
            bulk_g2s(nb + 3584, g_u + cn * (UROW / 2) + UPRE / 2 - 32, 1152, bar ^ 8, POL_N);
        }
        __syncwarp();
        if (n < 0) continue;
        float acc[8][4];
        uint4 win[8];
#pragma unroll
        for (int r = 0; r < 8; r++) { acc[r][0] = acc[r][1] = acc[r][2] = acc[r][3] = 0; win[r] = make_uint4(0, 0, 0, 0); }
        mbar_wait(bar, (n >> 1) & 1);
        bg_half<0, true>(acc, win, buf + to + 1792, qo + 128, ~0u, buf + 3584);
        bg_half<4, true>(acc, win, buf + to, qo + 640, ~0u, buf + 3584);
#pragma unroll
        for (int r = 0; r < 8; r++) st_acc(g_far + (ch * 256 + lane) + r * 32, acc[r]);
        __syncwarp();
        if (((t + 12) ^ t) >= 256 && elect()) red_release(cnt_ptr(C_FAR + (t >> 8)), 1);
        __syncwarp();
    }
    PROF(threadIdx.x == 0, 2048);
}

constexpr int P_X = 131072  , P_K6 = P_X + 32768  , P_P = P_K6 + 10496  , P_U = P_P + 33280  ,
              P_END = P_U + 17408, P_PRM = P_P + 8192  , P_Y = P_P  ;
static_assert(P_END <= B_BAR && P_END <= R_SEL, "prologue scratch");
#define KGUN 2
constexpr int KGU = KGUN;
__device__ __forceinline__ void csq(float& r, float& i) { const float t = r * i; r = fmaf(r, r, -(i * i)); i = t + t; }
__device__ __forceinline__ void cpow(float ar, float ph, float p, float& r, float& i) {
    const float e = ex2(ar * p);
    const float u = ph * p, n = fabsf(u) < 4194304.f ? (u + 12582912.f) - 12582912.f : u;
    const float t = (u - n) * 6.283185307179586f;
    r = e * __cosf(t); i = e * __sinf(t);
}
__device__ __forceinline__ void mma_tf32(float* c, float a0, float a1, float a2, float a3, float b0, float b1) {
    asm volatile("mma.sync.aligned.m16n8k8.row.col.f32.tf32.tf32.f32 {%0,%1,%2,%3},{%4,%5,%6,%7},{%8,%9},{%0,%1,%2,%3};"
                 : "+f"(c[0]), "+f"(c[1]), "+f"(c[2]), "+f"(c[3])
                 : "r"(__float_as_uint(a0)), "r"(__float_as_uint(a1)), "r"(__float_as_uint(a2)), "r"(__float_as_uint(a3)), "r"(__float_as_uint(b0)), "r"(__float_as_uint(b1)));
}

__device__ __forceinline__ void early_fetch(const Params& p, uint32_t sb) {
    const int v = blockIdx.x;
    if (elect()) {
        if (v >= V_QKV) { if (v < V_QKV + NQ && (p.roles & 8)) qkv_fetch(p, sb, v - V_QKV, 0, Q_PRE); }
        else if (v >= V_OP) { if (p.roles & 4) op_fetch(p, sb, v - V_OP, 0); }
        else if (v >= V_REC && (p.roles & 2)) { rec_fetch(p, sb, (v - V_REC) >> 1, v & 1, 0, R_STQ); rec_fetch(p, sb, (v - V_REC) >> 1, v & 1, 2, R_STV); }
    }
    __syncwarp();
}
struct ProRegs { uint32_t v[2][4], ldt[2]; };
__device__ __forceinline__ void prologue_load(const ProArgs& a, int b, ProRegs& pr) {
    const int w = threadIdx.x >> 5;
#pragma unroll
    for (int i = 0; i < 2; i++) {
        const int gi = b * 512 + (w & 3) * 128 + ((w >> 2) & 1) * 64 + i * 32 + (threadIdx.x & 31);
        pr.ldt[i] = __ldg((const uint16_t*)a.ldt + b * 4 + (w & 3));
        pr.v[i][0] = __ldg((const uint16_t*)a.lAr + gi); pr.v[i][1] = __ldg((const uint16_t*)a.Ai + gi);
        pr.v[i][2] = __ldg((const uint16_t*)a.Cr + gi); pr.v[i][3] = __ldg((const uint16_t*)a.Ci + gi);
    }
}
__device__ __forceinline__ void prologue(const Params& p, uint32_t sb, int b, int w, const ProRegs& pr) {
    const ProArgs& a = p.pa;
    const int tid = threadIdx.x, lane = tid & 31, g = lane >> 2, c = lane & 3;
    const int d0 = b * 4;
    if (w >= 8) {
        const int t2 = tid - 256;
        if (w < 10) {
            const int row = b * 16 + (w - 8) * 8 + g;
            uint4 v[16];
            const float2 r = row_stats512(v, (const uint4*)(a.x + (size_t)row * 512) + c, 8, 4);
            const float2 l = ln_finish(r.x * (1.f / 512.f), r.y * (1.f / 512.f));
            if (c == (g >> 1)) asm volatile("st.relaxed.gpu.global.u32 [%0],%1;" ::"l"(g_ln0 + row), "r"(pack2(l.x, l.y)) : "memory");
        }
        else if (b + 4 >= V_REC && b + 4 < V_OP) rec_slots(b + 4 - V_REC, w - 10);
        PROF(t2 == 0, 3516);
        const int gi = b * 128 + t2;
        g_st[gi] = make_uint4(~0u, ~0u, ~0u, ~0u);
        if (gi < 1024) g_st[16384 + gi] = make_uint4(~0u, ~0u, ~0u, ~0u);
        if (gi < 900 * 8) g_cnt[gi] = 0;
        bar_sync(6, 384);
        if (lane < 4 && ((PFM >> (w - 8)) & 1)) asm volatile("cp.async.bulk.prefetch.L2.global [%0],%1;" ::"l"(a.W[w - 8] + (b * 4 + lane) * 4096), "r"(8192) : "memory");
        bar_sync(9, 384);
        if (w == 10) early_fetch(p, sb);
#pragma unroll 2
        for (int i = t2; i < 4 * 784; i += 128) {
            const int ch = i / 784, k = i - ch * 784;
            const uint32_t o = sb + P_P + (ch * 2080 + 266 + (k / 14) * 18 + k) * 4;
            g_W[d0 * 784 + i] = make_uint4(lds32(o), lds32(o + 32), lds32(o + 64), lds32(o + 96));
        }
        bar_arrive(10, 384);
        PROF(t2 == 0, 3517);
        return;
    }
#pragma unroll
    for (int i = 0; i < 2; i++) {
        const float dt = rbf(expf(blo(pr.ldt[i])));
        const float ar = -rbf(expf(blo(pr.v[i][0]))) * dt, ai = blo(pr.v[i][1]) * dt;
        sts128(sb + P_PRM + (w * 64 + i * 32 + lane) * 16, __float_as_uint(ar * 1.4426950408889634f), __float_as_uint(ai * 0.15915494309189535f),
               __float_as_uint(2.f * (blo(pr.v[i][2]) * dt)), __float_as_uint(2.f * (blo(pr.v[i][3]) * dt)));
    }
    if (tid < 64) sts128(sb + P_U + (tid >> 3) * 2176 + (tid & 7) * 16, 0, 0, 0, 0);
    bar_arrive(6, 384);
    __syncwarp();
    PROF(tid == 0, 3510);
    const int ch = w & 3, hf = w >> 2;
    {
        float k0[4] = {0, 0, 0, 0}, k1[4] = {0, 0, 0, 0}, k2[4] = {0, 0, 0, 0}, k3[4] = {0, 0, 0, 0}, k4[4] = {0, 0, 0, 0}, kl = 0;
#pragma unroll KGU
        for (int j = 0; j < 16; j++) {
            const uint4 q = lds128(sb + P_PRM + (w * 64 + j * 4 + c) * 16);
            const float cr = __uint_as_float(q.z), ci = __uint_as_float(q.w);
            float wr[4], wi[4], vr[4], vi[4];
            cpow(__uint_as_float(q.x), __uint_as_float(q.y), (float)g, wr[0], wi[0]);
            cpow(__uint_as_float(q.x), __uint_as_float(q.y), (float)(g + 8), vr[0], vi[0]);
#pragma unroll
            for (int i = 1; i < 4; i++) { wr[i] = wr[i - 1]; wi[i] = wi[i - 1]; csq(wr[i], wi[i]); vr[i] = vr[i - 1]; vi[i] = vi[i - 1]; csq(vr[i], vi[i]); }
            float hr = wr[3], hi = wi[3];
            csq(hr, hi);
            mma_tf32(k0, wr[0], vr[0], wi[0], vi[0], cr * hr - ci * hi, -(cr * hi + ci * hr));
            hr = vr[3]; hi = vi[3]; csq(hr, hi);
            mma_tf32(k1, wr[0], vr[0], wi[0], vi[0], cr * hr - ci * hi, -(cr * hi + ci * hr));
            csq(hr, hi);
            mma_tf32(k2, wr[1], vr[1], wi[1], vi[1], cr * hr - ci * hi, -(cr * hi + ci * hr));
            csq(hr, hi);
            mma_tf32(k3, wr[2], vr[2], wi[2], vi[2], cr * hr - ci * hi, -(cr * hi + ci * hr));
            csq(hr, hi);
            mma_tf32(k4, wr[3], vr[3], wi[3], vi[3], cr * hr - ci * hi, -(cr * hi + ci * hr));
            csq(hr, hi);
            kl += cr * hr - ci * hi;
        }
        kl += __shfl_xor_sync(0xffffffffu, kl, 1); kl += __shfl_xor_sync(0xffffffffu, kl, 2);
        const uint32_t o = sb + P_K6 + (ch * 656 + c * 32 + g) * 4, ol = sb + P_K6 + (ch * 656 + 640) * 4;
#define KST(k, base) sts32(o + (base) * 4, __float_as_uint(k[0])); sts32(o + (base) * 4 + 64, __float_as_uint(k[1])); \
                     sts32(o + (base) * 4 + 32, __float_as_uint(k[2])); sts32(o + (base) * 4 + 96, __float_as_uint(k[3]))
#define KAD(k, base) k[0] += __uint_as_float(lds32(o + (base) * 4)); k[1] += __uint_as_float(lds32(o + (base) * 4 + 64)); \
                     k[2] += __uint_as_float(lds32(o + (base) * 4 + 32)); k[3] += __uint_as_float(lds32(o + (base) * 4 + 96))
        if (hf == 0) {
            bar_sync(2 + ch, 64);
            KAD(k0, 0); KAD(k1, 128); KAD(k2, 256); KAD(k3, 384); KAD(k4, 512);
            kl += __uint_as_float(lds32(ol));
            __syncwarp();
        }
        KST(k0, 0); KST(k1, 128); KST(k2, 256); KST(k3, 384); KST(k4, 512);
        if (lane == 0) sts32(ol, __float_as_uint(kl));
        if (hf == 1) { __syncwarp(); bar_arrive(2 + ch, 64); }
    }
    PROF(tid == 0, 3511);
    {
        uint4 l0, l1;
        int n = 0;
        while (true) {
            l0 = ld_rlx128((const uint4*)g_ln0 + tid * 2); l1 = ld_rlx128((const uint4*)g_ln0 + tid * 2 + 1);
            if (__all_sync(0xffffffffu, l0.x && l0.y && l0.z && l0.w && l1.x && l1.y && l1.z && l1.w)) break;
            if (++n > 2000000) __trap();
        }
        sts128(sb + P_P + tid * 32, l0.x, l0.y, l0.z, l0.w); sts128(sb + P_P + tid * 32 + 16, l1.x, l1.y, l1.z, l1.w);
        bar_sync(8, 384);
        mbar_wait(sb + S_XBAR, 0);
        __syncwarp();
#pragma unroll 2
        for (int i = 0; i < 8; i++) {
            const int t = w * 256 + i * 32 + lane;
            const uint32_t ln = lds32(sb + P_P + t * 4);
            const uint2 x = lds64(sb + P_X + t * 16 + (b & 1) * 8);
            const float m = blo(ln), rs = rcp(bhi(ln));
            const uint32_t u0 = pack2(rbf(blo(x.x) - m) * rs, rbf(bhi(x.x) - m) * rs), u1 = pack2(rbf(blo(x.y) - m) * rs, rbf(bhi(x.y) - m) * rs);
            sts128(sb + P_X + t * 16, x.x, x.y, u0, u1);
            const uint32_t o = sb + P_U + ((t >> 3) & 1) * 2176 + ((t >> 4) + 8) * 16 + (t & 7) * 2;
            asm volatile("st.shared.u16 [%0],%1;" ::"r"(o), "h"((uint16_t)u0) : "memory");
            asm volatile("st.shared.u16 [%0],%1;" ::"r"(o + 4352), "h"((uint16_t)(u0 >> 16)) : "memory");
            asm volatile("st.shared.u16 [%0],%1;" ::"r"(o + 8704), "h"((uint16_t)u1) : "memory");
            asm volatile("st.shared.u16 [%0],%1;" ::"r"(o + 13056), "h"((uint16_t)(u1 >> 16)) : "memory");
        }
    }
    bar_sync(1, 256);
    PROF(tid == 0, 3512);
    if (tid < 64) sts32(sb + P_P + ((tid >> 4) * 2080 + (tid & 15)) * 4, 0);
#pragma unroll 1
    for (int x = tid; x < 2048; x += 512) {
        uint32_t pw[2][4];
#pragma unroll
        for (int h = 0; h < 2; h++) {
            const int y = x + h * 256;
            const int i0 = y <= 256 ? y : 256 + (int)((pack2((float)y, 0.f) & 0xffff) - 0x4380);
            const int i1 = y <= 256 ? max(y - 1, 0) : 256 + (int)((pack2((float)(y - 1), 0.f) & 0xffff) - 0x4380);
#pragma unroll
            for (int k = 0; k < 4; k++) {
                const float lo = __uint_as_float(lds32(sb + P_K6 + k * 2624 + i0 * 4)), hi = __uint_as_float(lds32(sb + P_K6 + k * 2624 + i1 * 4));
                pw[h][k] = pack2(lo, y ? hi : 0.f);
            }
        }
#pragma unroll
        for (int h = 0; h < 2; h++)
#pragma unroll
            for (int k = 0; k < 4; k++) sts32(sb + P_P + (k * 2080 + x + h * 256 + 16) * 4, pw[h][k]);
    }
    fence_async_smem();
    bar_arrive(9, 384);
    bar_sync(1, 256);
    if (tid < 4) {
        asm volatile("cp.async.bulk.global.shared::cta.bulk_group [%0],[%1],%2;" ::"l"(g_P + (d0 + tid) * PROW), "r"(sb + P_P + tid * 8320), "r"(PROW * 4) : "memory");
        asm volatile("cp.async.bulk.commit_group;" ::: "memory");
    }
    __syncwarp();
    PROF(tid == 0, 3513);
    {
        float acc[16][4];
#pragma unroll
        for (int j = 0; j < 16; j++) acc[j][0] = acc[j][1] = acc[j][2] = acc[j][3] = 0;
#pragma unroll 1
        for (int e = hf * 4; e < hf * 4 + 4; e++) {
            uint32_t B[16][2];
            const uint32_t ua = sb + P_U + ch * 4352 + ((lane >> 3) & 1) * 2176 + (8 + (lane >> 4) * 8 + (lane & 7) - e) * 16;
#pragma unroll
            for (int j = 0; j < 8; j++) { const uint4 v = ldsm4(ua + j * 256); B[2 * j][0] = v.x; B[2 * j][1] = v.y; B[2 * j + 1][0] = v.z; B[2 * j + 1][1] = v.w; }
            const uint32_t pa = sb + P_P + (ch * 2080 + 16 + e * 16 + g - 2 * c) * 4;
#pragma unroll
            for (int d = 0; d < 16; d++) {
                const uint32_t a0 = lds32(pa + d * 512), a1 = lds32(pa + d * 512 + 32), a2 = lds32(pa + d * 512 - 32);
#pragma unroll
                for (int j = d; j < 16; j++) mma16(acc[j], a0, a1, a2, a0, B[j - d][0], B[j - d][1]);
            }
        }
        PROF(tid == 0, 3514);
        const uint32_t o = sb + P_Y + (ch * 2560 + c * 40 + g) * 4;
        if (tid < 4) asm volatile("cp.async.bulk.wait_group 0;" ::: "memory");
        __syncwarp();
        bar_sync(10, 384);
        if (hf == 0) {
            bar_sync(2 + ch, 64);
#pragma unroll
            for (int j = 0; j < 16; j++) {
                acc[j][0] += __uint_as_float(lds32(o + j * 640)); acc[j][1] += __uint_as_float(lds32(o + j * 640 + 80));
                acc[j][2] += __uint_as_float(lds32(o + j * 640 + 32)); acc[j][3] += __uint_as_float(lds32(o + j * 640 + 112));
            }
        }
#pragma unroll
        for (int j = 0; j < 16; j++) {
            sts32(o + j * 640, __float_as_uint(acc[j][0])); sts32(o + j * 640 + 80, __float_as_uint(acc[j][1]));
            sts32(o + j * 640 + 32, __float_as_uint(acc[j][2])); sts32(o + j * 640 + 112, __float_as_uint(acc[j][3]));
        }
        if (hf == 1) bar_arrive(2 + ch, 64);
    }
    const uint2 dk = __ldg((const uint2*)(a.Dk + d0));
    bar_sync(1, 256);
#pragma unroll 2
    for (int i = 0; i < 8; i++) {
        const int t = i * 256 + tid;
        const uint32_t o = sb + P_Y + (t + 4 * (t >> 4)) * 4;
        const uint4 xu = lds128(sb + P_X + t * 16);
        float y[4];
#pragma unroll
        for (int k = 0; k < 4; k++) y[k] = rbf(__uint_as_float(lds32(o + k * 10240)));
        uint2 r;
        r.x = pack2(blo(xu.x) + rbf(y[0] + rbf(blo(xu.z) * blo(dk.x))), bhi(xu.x) + rbf(y[1] + rbf(bhi(xu.z) * bhi(dk.x))));
        r.y = pack2(blo(xu.y) + rbf(y[2] + rbf(blo(xu.w) * blo(dk.y))), bhi(xu.y) + rbf(y[3] + rbf(bhi(xu.w) * bhi(dk.y))));
        ((uint2*)g_x)[b * 2 * XP + t] = r;
    }
    PROF(tid == 0, 3515);
}

__global__ void __cluster_dims__(2, 1, 1) __launch_bounds__(384, 1) main_kernel(const __grid_constant__ Params p) {
    extern __shared__ __align__(1024) uint8_t smem[];
    const uint32_t sb = smem_u32(smem);
    uint32_t rank; asm("mov.u32 %0,%%cluster_ctarank;" : "=r"(rank));
    const int wi = __shfl_sync(0xffffffffu, threadIdx.x >> 5, 0);
    const int v = blockIdx.x, cl = v >> 1, wg = wi >> 2;
    PROF(threadIdx.x == 0, 3500);
    ProRegs pr;
    prologue_load(p.pa, max((int)blockIdx.x - 4, 0), pr);
    if (wi == 11 && p.dopro && cl >= 2 && elect()) {
        mbar_init(sb + S_XBAR, 1);
        asm volatile("fence.mbarrier_init.release.cluster;" ::: "memory");
        mbar_expect(sb + S_XBAR, 32768);
        for (int j = 0; j < 8; j++) tma2d(sb + P_X + j * 4096, &p.tm[3], ((blockIdx.x - 4) >> 1) * 8, j * 256, sb + S_XBAR);
    }
    if (threadIdx.x == 320) {
        unsigned n;
        asm volatile("ld.relaxed.gpu.global.u32 %0,[%1];" : "=r"(n) : "l"(g_gate) : "memory");
        n = n / (4 * NCL) + p.dopro;
        sts64(sb + S_GATE, n * (4 * NCL), n & 1);
    }
    __syncwarp();
    if (wi == 10) {
        if (v < V_REC || v == 131) conv_init(sb, v == 131); else if (v < V_OP) rec_init(sb); else gemm_init(sb, v < V_QKV);
        __syncwarp();
    }
    if (wg == 2) bar_arrive(8, 384);
    asm volatile("barrier.cluster.arrive.relaxed.aligned;" ::: "memory");
    if (p.dopro && cl >= 2) prologue(p, sb, blockIdx.x - 4, wi, pr); else if (wg < 2) bar_sync(8, 384); else if (wi == 10) early_fetch(p, sb);
    asm volatile("barrier.cluster.wait.aligned;" ::: "memory");
    const int role = (v < V_REC ? 1 : v < V_OP ? 2 : v < V_QKV ? 20 : v < V_QKV + NQ ? 24 : 1) & p.roles;
    fence_async_smem();
    bar_sync(wg == 2 ? 7 : 1, wg == 2 ? 128 : 256);
    if (p.dopro && (threadIdx.x == 32 || threadIdx.x == 352)) red_release(g_gate, 1);
    PROF(threadIdx.x == 32, 3509);
    if (wi == 0 && (role & 8) && elect()) qkv_stage(p, sb + 131072, sb + G_BAR + GB_RS * 8, v - V_QKV, 0, 6);
    PROF(threadIdx.x == 0, 3506);
    __syncwarp();
    if (p.dopro && v >= V_REC && v < V_QKV && (v < V_OP ? wi == 8 : wi < 8)) {
        bool on = v >= V_OP;
#pragma unroll 1
        for (int r = on ? 64 + (v - V_OP) * 8 + wi : v - V_REC; r < 512;) {
            if (on) wait_flag_warp(g_gate, lds32(sb + S_GATE));
            PROF(threadIdx.x == 256 && on, 3507);
            x1_norm(on ? (const uint2*)g_x : (const uint2*)p.pa.W[0], r, on);
            __syncwarp();
            if (on && elect()) red_release(cnt_ptr(C_XN + (r >> 4)), 1);
            __syncwarp();
            PROF(threadIdx.x == 256, on ? 3508 : 3499);
            if (on) r += v < V_OP ? 512 : 128;
            on = true;
        }
    }
    if (role == 2) {
        const int head = (v - V_REC) >> 1;
        if (wi == 0 && elect()) rec_fetch(p, sb, head, rank, 1, R_STK);
        __syncwarp();
        if (wg == 2) {
            reg_dec<RH>();
            const int w = wi & 3;
            wait_cnt_warp(g_gate, lds32(sb + S_GATE));
            if (w < 2) { const uint32_t x = __ldcg(g_sel + (threadIdx.x & 63)); sts32(sb + R_SEL + (threadIdx.x & 63) * 4, (x | x >> 16) & 15); }
            __syncthreads();
            cluster_sync();
            if ((p.chains >> (w & 1)) & 1) { if (w < 2) rec_comm(p, sb, w, head, rank); else rec_attn(p, sb, w & 1, head, rank); }
        } else {
            reg_inc<RW0>();
            rec_weights(p, sb, head, rank, wi);
        }
    } else if (role == 1) {
        if (v == 131) conv_far(sb, wi); else if (wg == 2) { reg_dec<RCB>(); conv_back(sb, v, wi & 3); } else { reg_inc<RCU>(); conv_tile(p, sb, v, wi); }
    } else if (role && v < V_QKV) {
        if (wg == 2) {
            reg_dec<40>();
            if (wi == 8) { if (role & 4) gemm_producer<true>(p, sb, v - V_OP); }
            else if (v < V_OP + 14 && (role & 16)) fin_warp(p, sb, 2 * NQ + (v - V_OP) * 3 + wi - 9);
        } else { reg_inc<232>(); if (role & 4) gemm_consumer<true>(p, sb, v - V_OP, wi); }
    } else if (role) {
        if (wg == 2) {
            reg_dec<40>();
            if (wi < 10) {
                if (role & 8) { if (wi == 8) gemm_producer<false>(p, sb, v - V_QKV); else qkv_release(p, sb); }
            } else if (role & 16) fin_warp(p, sb, (v - V_QKV) * 2 + wi - 10);
        } else { reg_inc<232>(); if (role & 8) gemm_consumer<false>(p, sb, v - V_QKV, wi); }
    }
    __syncwarp();
    cluster_sync();
}

typedef CUresult (*EncFn)(CUtensorMap*, CUtensorMapDataType, cuuint32_t, void*, const cuuint64_t*, const cuuint64_t*, const cuuint32_t*, const cuuint32_t*,
                          CUtensorMapInterleave, CUtensorMapSwizzle, CUtensorMapL2promotion, CUtensorMapFloatOOBfill);
constexpr int SMEM_BYTES = 232448;
#define LAG 8
#define QLEAD 6
#define OLEAD (LAG / 2 + 2)
void plan(Params& P) {
    P.roles = 31; P.chains = 3; P.lag = LAG; P.dopro = 1;
    for (int r = 0; r < 2; r++) {
        const int lead = r ? OLEAD : QLEAD;
        int n = 0;
        for (int i = 0; i < 32 + lead; i++) {
            if (i >= lead) P.list[r][n++] = 32 + i - lead;
            if (i < 32) P.list[r][n++] = i;
        }
        P.nl[r] = n;
    }
}

#define TK() do {} while (0)
}

extern "C" void kernel_launch(void* const* d_in, const int* in_sizes, int n_in, void* d_out, int out_size) {
    typedef const __nv_bfloat16* BP;
    static EncFn enc = nullptr;
    if (!enc) {
        void* fn = nullptr; cudaDriverEntryPointQueryResult qr;
        cudaGetDriverEntryPoint("cuTensorMapEncodeTiled", &fn, cudaEnableDefault, &qr);
        enc = (EncFn)fn;
        cudaFuncSetAttribute(main_kernel, cudaFuncAttributeMaxDynamicSharedMemorySize, SMEM_BYTES);
    }
    static Params P;
    for (int i = 0; i < 4; i++) {
        const cuuint64_t cols = i < 3 ? 4096 : 512, rows = i < 3 ? 512 : 4096;
        cuuint64_t d2[2] = {cols, rows}, str[1] = {cols * 2};
        cuuint32_t box[2] = {64, 64}, bn[2] = {16, 256}, es[2] = {1, 1};
        enc(&P.tm[i < 3 ? i : 4], CU_TENSOR_MAP_DATA_TYPE_BFLOAT16, 2, d_in[9 + i], d2, str, box, es, CU_TENSOR_MAP_INTERLEAVE_NONE, CU_TENSOR_MAP_SWIZZLE_128B,
            CU_TENSOR_MAP_L2_PROMOTION_L2_128B, CU_TENSOR_MAP_FLOAT_OOB_FILL_NONE);
        if (i < 2) enc(&P.tn[i], CU_TENSOR_MAP_DATA_TYPE_BFLOAT16, 2, d_in[9 + i], d2, str, bn, es, CU_TENSOR_MAP_INTERLEAVE_NONE, CU_TENSOR_MAP_SWIZZLE_32B,
                       CU_TENSOR_MAP_L2_PROMOTION_L2_128B, CU_TENSOR_MAP_FLOAT_OOB_FILL_NONE);
    }
    {
        cuuint64_t dims[2] = {512, 2048}, str[1] = {1024};
        cuuint32_t box[2] = {8, 256}, es[2] = {1, 1};
        enc(&P.tm[3], CU_TENSOR_MAP_DATA_TYPE_BFLOAT16, 2, d_in[0], dims, str, box, es, CU_TENSOR_MAP_INTERLEAVE_NONE, CU_TENSOR_MAP_SWIZZLE_NONE,
            CU_TENSOR_MAP_L2_PROMOTION_NONE, CU_TENSOR_MAP_FLOAT_OOB_FILL_NONE);
    }
    P.mem0 = (BP)d_in[8]; P.Wo = (BP)d_in[12]; P.Dskip = (BP)d_in[6]; P.out = (__nv_bfloat16*)d_out;
    cudaStream_t s = cudaStreamPerThread;
    P.pa = {(BP)d_in[0], (BP)d_in[1], (BP)d_in[2], (BP)d_in[3], (BP)d_in[4], (BP)d_in[5], (BP)d_in[6], {(BP)d_in[9], (BP)d_in[10], (BP)d_in[11], (BP)d_in[12]}};
    plan(P);
    TK(); main_kernel<<<2 * NCL, 384, SMEM_BYTES, s>>>(P); TK();
}
```

```cpp
#include <cuda_runtime.h>
#include <cuda_bf16.h>
#include <cuda.h>
#include <stdint.h>
#include <string.h>
#include <math.h>

namespace {

constexpr int NCL = 66;
constexpr int NQ = 43;
constexpr int V_REC = 8, V_OP = 72, V_QKV = 88;
static_assert(2 * NQ + 3 * 14 == 128, "warps of the final residual");

#define XP 1024
__device__ uint4 g_x[2 * 128 * XP];
__device__ uint4 g_xn[64 * 4096];
__device__ uint4 g_st[68 * 256];
__device__ uint4 g_qkv[128 * 32 * 1536];
__device__ uint4 g_o[64 * 64 * 512];
__device__ uint4 g_pp[64 * 4 * 4096];
__device__ uint4 g_xch[133 * 512];
__device__ unsigned g_sel[64];
__device__ unsigned g_gate[32];
__device__ __align__(16) uint32_t g_P[512 * 272];
__device__ uint4 g_W[512 * 784];
__device__ __align__(16) uint32_t g_u[512 * 1152];
__device__ uint2 g_carry[512 * 40 * 32];
__device__ uint2 g_far[512 * 8 * 32];
__device__ unsigned g_cnt[900 * 8];
__device__ uint32_t g_ln0[2048];

enum { C_XN = 0  , C_QKV = 64  , C_O = 128  , C_PP = 384  , C_FAR = 896 };
__device__ __forceinline__ unsigned* cnt_ptr(int i) { return g_cnt + i * 8; }

struct ProArgs { const __nv_bfloat16 *x, *lAr, *Ai, *Cr, *Ci, *ldt, *Dk, *W[4]; };
struct Params {
    CUtensorMap tm[5];
    CUtensorMap tn[2];
    ProArgs pa;
    int dopro;
    const __nv_bfloat16* mem0;
    const __nv_bfloat16* Wo;
    const __nv_bfloat16* Dskip;
    __nv_bfloat16* out;
    int roles;
    int chains;
    int lag;
    int zero;
    int nl[2];
    uint8_t list[2][64];
};

__device__ __forceinline__ uint32_t smem_u32(const void* p) { return (uint32_t)__cvta_generic_to_shared(p); }
__device__ __forceinline__ uint32_t mapa(uint32_t a, uint32_t r) {
    uint32_t o; asm("mapa.shared::cluster.u32 %0,%1,%2;" : "=r"(o) : "r"(a), "r"(r)); return o;
}
__device__ __forceinline__ void mbar_init(uint32_t b, int c) { asm volatile("mbarrier.init.shared::cta.b64 [%0],%1;" ::"r"(b), "r"(c) : "memory"); }
__device__ __forceinline__ void mbar_expect(uint32_t b, int bytes) { asm volatile("mbarrier.arrive.expect_tx.shared::cta.b64 _,[%0],%1;" ::"r"(b), "r"(bytes) : "memory"); }
__device__ __forceinline__ void mbar_arrive(uint32_t b) { asm volatile("mbarrier.arrive.shared::cta.b64 _,[%0];" ::"r"(b) : "memory"); }
__device__ __forceinline__ void mbar_arrive_cluster(uint32_t b) { asm volatile("mbarrier.arrive.shared::cluster.b64 _,[%0];" ::"r"(b) : "memory"); }
__device__ __forceinline__ void mbar_wait(uint32_t b, uint32_t ph) {
    asm volatile(
        "{.reg .pred p; .reg .u32 n; mov.u32 n,0;\n"
        "W%=: mbarrier.try_wait.parity.shared::cta.b64 p,[%0],%1;\n"
        "@p bra D%=;\n"
        "add.u32 n,n,1; setp.lt.u32 p,n,2000000; @p bra W%=;\n"
        "trap;\n"
        "D%=: }" ::"r"(b), "r"(ph) : "memory");
}
__device__ __forceinline__ bool wait_lds128(uint32_t b, uint32_t ph, uint32_t a, uint4& v) {
    uint32_t ok;
    asm volatile("{.reg .pred p; mbarrier.try_wait.parity.shared::cta.b64 p,[%5],%6,20000; ld.shared.v4.u32 {%0,%1,%2,%3},[%7]; selp.u32 %4,1,0,p;}"
                 : "=r"(v.x), "=r"(v.y), "=r"(v.z), "=r"(v.w), "=r"(ok) : "r"(b), "r"(ph), "r"(a) : "memory");
    return ok;
}
__device__ __forceinline__ bool wait_lds64(uint32_t b, uint32_t ph, uint32_t a, uint2& v) {
    uint32_t ok;
    asm volatile("{.reg .pred p; mbarrier.try_wait.parity.shared::cta.b64 p,[%3],%4,20000; ld.shared.v2.u32 {%0,%1},[%5]; selp.u32 %2,1,0,p;}"
                 : "=r"(v.x), "=r"(v.y), "=r"(ok) : "r"(b), "r"(ph), "r"(a) : "memory");
    return ok;
}
template <int PH> __device__ __forceinline__ void mbar_wait_c(uint32_t b) {
    asm volatile(
        "{.reg .pred p; .reg .u32 n; mov.u32 n,%2;\n"
        "W%=: mbarrier.try_wait.parity.shared::cta.b64 p,[%0],%1;\n"
        "@p bra D%=;\n"
        "add.u32 n,n,1; setp.lt.u32 p,n,2000000; @p bra W%=;\n"
        "trap;\n"
        "D%=: }" ::"r"(b), "n"(PH), "n"(PH) : "memory");
}
__device__ __forceinline__ bool elect() {
    uint32_t r; asm volatile("{.reg .pred p; elect.sync _|p,0xffffffff; selp.u32 %0,1,0,p;}" : "=r"(r)); return r;
}
__device__ __forceinline__ void bar_sync(int id, int n) { asm volatile("bar.sync %0,%1;" ::"r"(id), "r"(n) : "memory"); }
__device__ __forceinline__ void bar_arrive(int id, int n) { asm volatile("bar.arrive %0,%1;" ::"r"(id), "r"(n) : "memory"); }
__device__ __forceinline__ void cluster_sync() { asm volatile("barrier.cluster.arrive.relaxed.aligned; barrier.cluster.wait.aligned;" ::: "memory"); }
__device__ __forceinline__ void fence_async() { asm volatile("fence.proxy.async;" ::: "memory"); }
__device__ __forceinline__ void fence_async_smem() { asm volatile("fence.proxy.async.shared::cta;" ::: "memory"); }
#define EFR 1
#define EFW 2
constexpr uint64_t POL_N = 0x1000000000000000ull, POL_F = 0x12F0000000000000ull;
constexpr uint64_t POL_LAST = EFR ? POL_F : POL_N  , POL_LATE = EFW ? POL_F : POL_N  , POL_SOON = EFW > 1 ? POL_F : POL_N;
__device__ __forceinline__ void bulk_g2s(uint32_t dst, const void* src, int bytes, uint32_t bar, uint64_t pol) {
    asm volatile("cp.async.bulk.shared::cluster.global.mbarrier::complete_tx::bytes.L2::cache_hint [%0],[%1],%2,[%3],%4;" ::"r"(dst), "l"(src), "r"(bytes), "r"(bar), "l"(pol) : "memory");
}
__device__ __forceinline__ void bulk_g2s_mc(uint32_t dst, const void* src, int bytes, uint32_t bar, uint64_t pol) {
    asm volatile("cp.async.bulk.shared::cluster.global.mbarrier::complete_tx::bytes.multicast::cluster.L2::cache_hint [%0],[%1],%2,[%3],%4,%5;" ::"r"(dst), "l"(src), "r"(bytes), "r"(bar), "h"((uint16_t)3), "l"(pol) : "memory");
}
__device__ __forceinline__ void stg128(uint4* p, uint4 v, uint64_t pol) {
    asm volatile("st.global.L2::cache_hint.v4.u32 [%0],{%1,%2,%3,%4},%5;" ::"l"(p), "r"(v.x), "r"(v.y), "r"(v.z), "r"(v.w), "l"(pol));
}
__device__ __forceinline__ void stg32(uint32_t* p, uint32_t v, uint64_t pol) { asm volatile("st.global.L2::cache_hint.u32 [%0],%1,%2;" ::"l"(p), "r"(v), "l"(pol)); }
__device__ __forceinline__ uint4 ldcg128_last(const uint4* p) {
    uint4 v; asm volatile("ld.global.cg.L2::cache_hint.v4.u32 {%0,%1,%2,%3},[%4],%5;" : "=r"(v.x), "=r"(v.y), "=r"(v.z), "=r"(v.w) : "l"(p), "l"(POL_LAST) : "memory"); return v;
}
__device__ __forceinline__ void tma2d(uint32_t dst, const CUtensorMap* tm, int x, int y, uint32_t bar) {
    asm volatile("cp.async.bulk.tensor.2d.shared::cluster.global.mbarrier::complete_tx::bytes [%0],[%1,{%2,%3}],[%4];" ::"r"(dst), "l"(tm), "r"(x), "r"(y), "r"(bar) : "memory");
}
__device__ __forceinline__ void tma3d(uint32_t dst, const CUtensorMap* tm, int y, int z, uint32_t bar) {
    asm volatile("cp.async.bulk.tensor.3d.shared::cluster.global.mbarrier::complete_tx::bytes [%0],[%1,{0,%2,%3}],[%4];" ::"r"(dst), "l"(tm), "r"(y), "r"(z), "r"(bar) : "memory");
}
__device__ __forceinline__ void st_async4(uint32_t a, uint32_t x, uint32_t y, uint32_t z, uint32_t w, uint32_t mb) {
    asm volatile("st.async.shared::cluster.mbarrier::complete_tx::bytes.v4.b32 [%0],{%1,%2,%3,%4},[%5];" ::"r"(a), "r"(x), "r"(y), "r"(z), "r"(w), "r"(mb) : "memory");
}
__device__ __forceinline__ void st_async2(uint32_t a, uint32_t x, uint32_t y, uint32_t mb) {
    asm volatile("st.async.shared::cluster.mbarrier::complete_tx::bytes.v2.b32 [%0],{%1,%2},[%3];" ::"r"(a), "r"(x), "r"(y), "r"(mb) : "memory");
}
#define LDSQ "ld.shared"
__device__ __forceinline__ uint4 lds128(uint32_t a) { uint4 v; asm volatile(LDSQ ".v4.u32 {%0,%1,%2,%3},[%4];" : "=r"(v.x), "=r"(v.y), "=r"(v.z), "=r"(v.w) : "r"(a) : "memory"); return v; }
__device__ __forceinline__ uint4 lds128v(uint32_t a) { uint4 v; asm volatile("ld.volatile.shared.v4.u32 {%0,%1,%2,%3},[%4];" : "=r"(v.x), "=r"(v.y), "=r"(v.z), "=r"(v.w) : "r"(a) : "memory"); return v; }
__device__ __forceinline__ uint2 lds64(uint32_t a) { uint2 v; asm volatile(LDSQ ".v2.u32 {%0,%1},[%2];" : "=r"(v.x), "=r"(v.y) : "r"(a) : "memory"); return v; }
__device__ __forceinline__ uint32_t lds32(uint32_t a) { uint32_t v; asm volatile(LDSQ ".u32 %0,[%1];" : "=r"(v) : "r"(a) : "memory"); return v; }
__device__ __forceinline__ void sts128(uint32_t a, uint32_t x, uint32_t y, uint32_t z, uint32_t w) { asm volatile("st.shared.v4.u32 [%0],{%1,%2,%3,%4};" ::"r"(a), "r"(x), "r"(y), "r"(z), "r"(w) : "memory"); }
__device__ __forceinline__ void sts64(uint32_t a, uint32_t x, uint32_t y) { asm volatile("st.shared.v2.u32 [%0],{%1,%2};" ::"r"(a), "r"(x), "r"(y) : "memory"); }
__device__ __forceinline__ void sts32(uint32_t a, uint32_t x) { asm volatile("st.shared.u32 [%0],%1;" ::"r"(a), "r"(x) : "memory"); }
__device__ __forceinline__ uint4 ldsm4(uint32_t a) { uint4 v; asm volatile("ldmatrix.sync.aligned.m8n8.x4.shared.b16 {%0,%1,%2,%3},[%4];" : "=r"(v.x), "=r"(v.y), "=r"(v.z), "=r"(v.w) : "r"(a) : "memory"); return v; }
__device__ __forceinline__ uint4 ldsm4t(uint32_t a) { uint4 v; asm volatile("ldmatrix.sync.aligned.m8n8.x4.trans.shared.b16 {%0,%1,%2,%3},[%4];" : "=r"(v.x), "=r"(v.y), "=r"(v.z), "=r"(v.w) : "r"(a) : "memory"); return v; }
__device__ __forceinline__ uint32_t movm(uint32_t a) { uint32_t d; asm volatile("movmatrix.sync.aligned.m8n8.trans.b16 %0,%1;" : "=r"(d) : "r"(a)); return d; }
__device__ __forceinline__ uint32_t pack2(float lo, float hi) { uint32_t d; asm("cvt.rn.bf16x2.f32 %0,%1,%2;" : "=r"(d) : "f"(hi), "f"(lo)); return d; }
__device__ __forceinline__ uint32_t hadd2(uint32_t a, uint32_t b) { uint32_t d; asm("add.rn.bf16x2 %0,%1,%2;" : "=r"(d) : "r"(a), "r"(b)); return d; }
__device__ __forceinline__ uint32_t hmul2(uint32_t a, uint32_t b) { uint32_t d; asm("mul.rn.bf16x2 %0,%1,%2;" : "=r"(d) : "r"(a), "r"(b)); return d; }
__device__ __forceinline__ float blo(uint32_t v) { return __uint_as_float(v << 16); }
__device__ __forceinline__ float bhi(uint32_t v) { return __uint_as_float(v & 0xffff0000u); }
__device__ __forceinline__ float rbf(float x) { return __uint_as_float(pack2(0.f, x)); }
__device__ __forceinline__ float ex2(float x) { float y; asm("ex2.approx.ftz.f32 %0,%1;" : "=f"(y) : "f"(x)); return y; }
__device__ __forceinline__ float rcp(float x) { float y; asm("rcp.approx.ftz.f32 %0,%1;" : "=f"(y) : "f"(x)); return y; }
__device__ __forceinline__ void mma16(float* c, uint32_t a0, uint32_t a1, uint32_t a2, uint32_t a3, uint32_t b0, uint32_t b1) {
    asm volatile("mma.sync.aligned.m16n8k16.row.col.f32.bf16.bf16.f32 {%0,%1,%2,%3},{%4,%5,%6,%7},{%8,%9},{%0,%1,%2,%3};"
                 : "+f"(c[0]), "+f"(c[1]), "+f"(c[2]), "+f"(c[3]) : "r"(a0), "r"(a1), "r"(a2), "r"(a3), "r"(b0), "r"(b1));
}
__device__ __forceinline__ void mma16_top(float& d0, float& d1, uint32_t a0, uint32_t a2, uint32_t b0, uint32_t b1) {
    asm volatile("{.reg .b32 j; .reg .f32 e,f; mma.sync.aligned.m16n8k16.row.col.f32.bf16.bf16.f32 {%0,%1,e,f},{%2,j,%3,j},{%4,%5},{0f00000000,0f00000000,0f00000000,0f00000000};}"
                 : "=f"(d0), "=f"(d1) : "r"(a0), "r"(a2), "r"(b0), "r"(b1));
}
__device__ __forceinline__ void mma8(float* c, uint32_t a0, uint32_t a1, uint32_t b0) {
    asm volatile("mma.sync.aligned.m16n8k8.row.col.f32.bf16.bf16.f32 {%0,%1,%2,%3},{%4,%5},{%6},{%0,%1,%2,%3};"
                 : "+f"(c[0]), "+f"(c[1]), "+f"(c[2]), "+f"(c[3]) : "r"(a0), "r"(a1), "r"(b0));
}
__device__ __forceinline__ uint4 ld_rlx128(const uint4* p) {
    uint4 v;
    asm volatile("{.reg .b128 t; ld.relaxed.gpu.global.b128 t,[%4]; mov.b128 {%0,%1,%2,%3},t;}" : "=r"(v.x), "=r"(v.y), "=r"(v.z), "=r"(v.w) : "l"(p) : "memory");
    return v;
}
__device__ __forceinline__ void st_rlx128(uint4* p, uint32_t x, uint32_t y, uint32_t z, uint32_t w) {
    asm volatile("{.reg .b128 t; mov.b128 t,{%1,%2,%3,%4}; st.relaxed.gpu.global.b128 [%0],t;}" ::"l"(p), "r"(x), "r"(y), "r"(z), "r"(w) : "memory");
}
__device__ __forceinline__ uint4 ldcg128(const uint4* p) { uint4 v; asm volatile("ld.global.cg.v4.u32 {%0,%1,%2,%3},[%4];" : "=r"(v.x), "=r"(v.y), "=r"(v.z), "=r"(v.w) : "l"(p) : "memory"); return v; }
__device__ __forceinline__ void red_release(unsigned* p, unsigned v) {
    asm volatile("fence.proxy.async; red.relaxed.gpu.global.add.u32 [%0],%1;" ::"l"(p), "r"(v) : "memory");
}
__device__ __forceinline__ void red_relaxed(unsigned* p, unsigned v) { asm volatile("red.relaxed.gpu.global.add.u32 [%0],%1;" ::"l"(p), "r"(v) : "memory"); }
__device__ __forceinline__ void wait_cnt(const unsigned* p, unsigned target) {
    asm volatile(
        "{.reg .pred p; .reg .u32 n,v; mov.u32 n,0;\n"
        "W%=: ld.acquire.gpu.global.u32 v,[%0]; setp.ge.u32 p,v,%1; @p bra D%=;\n"
        "nanosleep.u32 20; add.u32 n,n,1; setp.lt.u32 p,n,4000000; @p bra W%=;\n"
        "trap;\n"
        "D%=: }" ::"l"(p), "r"(target) : "memory");
}
__device__ __forceinline__ void wait_cnt_warp(const unsigned* p, unsigned target) {
    asm volatile(
        "{.reg .pred p; .reg .u32 n,v; mov.u32 n,0;\n"
        "W%=: ld.acquire.gpu.global.u32 v,[%0]; setp.ge.u32 p,v,%1; vote.sync.all.pred p,p,0xffffffff; @p bra.uni D%=;\n"
        "nanosleep.u32 20; add.u32 n,n,1; setp.lt.u32 p,n,4000000; @p bra.uni W%=;\n"
        "trap;\n"
        "D%=: }" ::"l"(p), "r"(target) : "memory");
}
__device__ __forceinline__ void wait_slow_warp(const unsigned* p, unsigned target) {
    asm volatile(
        "{.reg .pred p; .reg .u32 n,v; mov.u32 n,0;\n"
        "W%=: ld.relaxed.gpu.global.u32 v,[%0]; setp.ge.u32 p,v,%1; vote.sync.all.pred p,p,0xffffffff; @p bra.uni D%=;\n"
        "nanosleep.u32 400; add.u32 n,n,1; setp.lt.u32 p,n,1000000; @p bra.uni W%=;\n"
        "trap;\n"
        "D%=: }" ::"l"(p), "r"(target) : "memory");
}
__device__ __forceinline__ void wait_flag_warp(const unsigned* p, unsigned target) {
    asm volatile(
        "{.reg .pred p; .reg .u32 n,v; mov.u32 n,0;\n"
        "W%=: ld.relaxed.gpu.global.u32 v,[%0]; setp.ge.u32 p,v,%1; vote.sync.all.pred p,p,0xffffffff; @p bra.uni D%=;\n"
        "add.u32 n,n,1; setp.lt.u32 p,n,10000000; @p bra.uni W%=;\n"
        "trap;\n"
        "D%=: }" ::"l"(p), "r"(target) : "memory");
}
__device__ __forceinline__ uint64_t mkdesc(uint32_t addr, uint32_t lbo, uint32_t sbo, uint32_t sw) {
    return (uint64_t)((addr & 0x3FFFF) >> 4) | ((uint64_t)(lbo >> 4) << 16) | ((uint64_t)(sbo >> 4) << 32) | ((uint64_t)sw << 62);
}
__device__ __forceinline__ void wg_fence() { asm volatile("wgmma.fence.sync.aligned;" ::: "memory"); }
__device__ __forceinline__ void wg_commit() { asm volatile("wgmma.commit_group.sync.aligned;" ::: "memory"); }
template <int N> __device__ __forceinline__ void wg_wait() { asm volatile("wgmma.wait_group.sync.aligned %0;" ::"n"(N) : "memory"); }
#define R8(c, o) "+f"(c[o]), "+f"(c[o + 1]), "+f"(c[o + 2]), "+f"(c[o + 3]), "+f"(c[o + 4]), "+f"(c[o + 5]), "+f"(c[o + 6]), "+f"(c[o + 7])
#define R32(c, o) R8(c, o), R8(c, o + 8), R8(c, o + 16), R8(c, o + 24)
#define S32A "%0,%1,%2,%3,%4,%5,%6,%7,%8,%9,%10,%11,%12,%13,%14,%15,%16,%17,%18,%19,%20,%21,%22,%23,%24,%25,%26,%27,%28,%29,%30,%31"
template <int ACC> __device__ __forceinline__ void wgmma64_rs(float* c, const uint32_t* a, uint64_t db) {
    asm volatile("wgmma.mma_async.sync.aligned.m64n64k16.f32.bf16.bf16 {" S32A "},{%32,%33,%34,%35},%36,%37,1,1,0;"
                 : R32(c, 0) : "r"(a[0]), "r"(a[1]), "r"(a[2]), "r"(a[3]), "l"(db), "n"(ACC));
}
template <int ACC> __device__ __forceinline__ void wgmma64_ta(float* c, uint64_t da, uint64_t db) {
    asm volatile("wgmma.mma_async.sync.aligned.m64n64k16.f32.bf16.bf16 {" S32A "},%32,%33,%34,1,1,1,0;" : R32(c, 0) : "l"(da), "l"(db), "n"(ACC));
}
template <int ACC> __device__ __forceinline__ void wgmma80_tb(float* c, uint64_t da, uint64_t db) {
    asm volatile("wgmma.mma_async.sync.aligned.m64n80k16.f32.bf16.bf16 {" S32A ",%32,%33,%34,%35,%36,%37,%38,%39},%40,%41,%42,1,1,0,1;"
                 : R32(c, 0), R8(c, 32) : "l"(da), "l"(db), "n"(ACC));
}
template <int N> __device__ __forceinline__ void reg_inc() { asm volatile("setmaxnreg.inc.sync.aligned.u32 %0;" ::"n"(N)); }
template <int N> __device__ __forceinline__ void reg_dec() { asm volatile("setmaxnreg.dec.sync.aligned.u32 %0;" ::"n"(N)); }

#define PROF(cond, idx) do {} while (0)
#define CPROF(k) do {} while (0)

constexpr int S_GATE = 232440, S_TAG = 232444, S_XBAR = 232432, B_BAR = 231936;
#define RCB 136
#define RCU 184
#define NTOP 1
#define PLATE 2
#define PFM 12
#define QLAG 3
constexpr float SC_LOG2E = 0.08838834764831845f * 1.4426950408889634f;

__device__ __forceinline__ float2 ln_finish(float mean, float var) {
    float sd; asm("sqrt.approx.f32 %0,%1;" : "=f"(sd) : "f"(rbf(rbf(var) + 1e-5f)));
    sd = rbf(sd);
    return make_float2(rbf(mean), sd);
}

__device__ __forceinline__ float2 row_stats512(uint4* v, const uint4* src, int s1, int s2) {
    const int g = (threadIdx.x & 31) >> 2;
#pragma unroll
    for (int i = 0; i < 16; i++) v[i] = ldcg128(src + (i >> 1) * s1 + (i & 1) * s2);
    float a[4] = {0, 0, 0, 0}, q0[4] = {0, 0, 0, 0}, q1[4] = {0, 0, 0, 0};
#pragma unroll
    for (int i = 0; i < 16; i++) {
        mma16(a, v[i].x, v[i].y, v[i].z, v[i].w, 0x3f803f80u, 0x3f803f80u);
        mma8(q0, v[i].x, v[i].y, v[i].x); mma8(q1, v[i].x, v[i].y, v[i].y);
        mma8(q0, v[i].z, v[i].w, v[i].z); mma8(q1, v[i].z, v[i].w, v[i].w);
    }
    const float sum = a[0] + a[2], sq = (g & 1) ? q0[1] + q1[3] : q0[0] + q1[2];
    return make_float2(sum, fmaxf(sq - sum * sum * (1.f / 512.f), 0.f));
}
__device__ __forceinline__ void x1_norm(const uint2* src, int r, bool on) {
    const int lane = threadIdx.x & 31, g = lane >> 2, t = r * 4 + (lane & 3);
    constexpr int xp = XP;
    uint2 v[16];
#pragma unroll
    for (int i = 0; i < 16; i++) asm volatile("ld.global.cg.v2.u32 {%0,%1},[%2];" : "=r"(v[i].x), "=r"(v[i].y) : "l"(src + (g * 4 * xp + t) + ((i >> 1) * 16 + (i & 1)) * 2 * xp) : "memory");
    float s = 0, q = 0;
#pragma unroll
    for (int i = 0; i < 32; i++) {
        const uint32_t w = (i & 1) ? v[i >> 1].y : v[i >> 1].x;
        s += blo(w) + bhi(w); q = fmaf(blo(w), blo(w), fmaf(bhi(w), bhi(w), q));
    }
#pragma unroll
    for (int d = 4; d < 32; d *= 2) { s += __shfl_xor_sync(0xffffffffu, s, d); q += __shfl_xor_sync(0xffffffffu, q, d); }
    if (g == 0 && on) g_ln0[t] = 0;
    s *= 1.f / 512.f;
    const float2 l = ln_finish(s, fmaxf(fmaf(q, 1.f / 512.f, -s * s), 0.f));
    const float rs = rcp(l.y);
    const uint32_t mm = pack2(-l.x, -l.x);
    uint4* dst = g_xn + ((t >> 6) * 4096 + ((t >> 3) & 7) * 64 + g * 8 + (t & 7));
#define NRM(w) pack2(blo(hadd2(w, mm)) * rs, bhi(hadd2(w, mm)) * rs)
#pragma unroll
    for (int i = 0; i < 8; i++)
        asm volatile("{.reg .pred p; setp.ne.u32 p,%5,0; @p st.global.v4.u32 [%0],{%1,%2,%3,%4};}" ::"l"(dst + i * 512), "r"(NRM(v[2 * i].x)), "r"(NRM(v[2 * i].y)),
                     "r"(NRM(v[2 * i + 1].x)), "r"(NRM(v[2 * i + 1].y)), "r"((uint32_t)on) : "memory");
}

#define NWO 10
#define VMASK 0x4444
#define VPRE 2
#define VFIRST 1
#define OA 0
#define OL 0x16
#define PINS 0x2ae1
#define NPX 2
#define NPF 2
constexpr int SLOT = 24576, SL_V = 8192, SL_Q = 16384, SL_KM = 20480, SL_VM = 22528;
constexpr int R_SL = 0, R_WV = 4 * SLOT  , R_WO = R_WV + 65536, R_M = 196608  , R_U = R_M + 8192  ,
              R_OS = R_U + 8192  , R_SB = R_OS + 8192  , R_OB = R_SB + 5248  , R_PB = R_OB + 2048  ,
              R_IL = R_PB + 1024  , R_SEL = 231680, R_BAR = R_SEL + 256, R_STV = 0, R_STQ = 65536, R_STK = 131072;
static_assert(R_WO + (16 - NWO) * 4096 <= R_M && R_IL + 64 <= R_SEL && R_BAR + 512 <= 232448, "smem map");
enum { RB_XFULL = 0  , RB_GO = 4  , RB_QK = 8  , RB_INIT = 24, RB_SV = 25   };

enum { NB_MFULL = 1  , NB_PART = 3  , NB_S = 5, NB_P = 6, NB_O = 7, NB_W = 10 };
#define HL 2
#define XU 8
#define EGO 0
#define NPRB 3
#define REARLY 1
#define RFW 8
#define EFS V_QKV
#define RACC 2
#define WDEP 1
#define RH 56
#define RW0 224
#define D1 350
#define D2 350
__device__ __forceinline__ uint32_t clk32() { uint32_t c; asm volatile("mov.u32 %0,%%clock;" : "=r"(c)::"memory"); return c; }
__device__ __forceinline__ void spin(int cycles) {
    if (cycles <= 0) return;
    asm volatile("{.reg .pred p; .reg .u32 a,b; mov.u32 a,%%clock; add.u32 a,a,%0;\nS%=: mov.u32 b,%%clock; sub.u32 b,b,a; setp.lt.s32 p,b,0; @p bra.uni S%=;}" ::"r"(cycles) : "memory");
}
__device__ __forceinline__ uint4* xregion(int X, int r) { return (uint4*)(((size_t)g_xch + 8191) & ~(size_t)8191) + (X * 66 + r) * 512; }

__device__ __forceinline__ void arrive_if(uint32_t bar, uint32_t a, uint32_t b) {
    asm volatile("{.reg .pred p; setp.eq.u32 p,%1,%2; @p mbarrier.arrive.shared::cta.b64 _,[%0];}" ::"r"(bar), "r"(a), "r"(b) : "memory");
}
struct RecW { uint32_t po, dp, lw, sp  , w; };
#define PIN(n) if ((PINS >> (n)) & 1) asm volatile("griddepcontrol.launch_dependents;" ::: "memory")
constexpr int v_stream(int n) {
    int ks = 0;
    for (; ks < 16; ks++) if (!((VMASK >> ks) & 1) && n-- == 0) break;
    return ks;
}
constexpr uint64_t v_next() {
    uint64_t r = 0;
    for (int n = 0; v_stream(n + VPRE) < 16; n++) r |= (uint64_t)v_stream(n + VPRE) << (4 * v_stream(n));
    return r;
}
constexpr uint64_t V_NEXT = v_next();
constexpr int V_PRE = v_stream(VPRE);

__device__ __forceinline__ void rec_step(const RecW& k, uint32_t sb, const int X, int s, uint32_t zero, int lo, int hi, int d, const uint32_t (*wq)[4], const uint32_t (*wk)[4], uint4* wv, uint4* wo) {
    const int SL = R_SL + X * 2 * SLOT;
    uint4 mk[8];
    bar_sync(NB_MFULL + X, 288);
    mk[0] = ldsm4(k.lw + X * 4096 + R_M);
    PIN(0);
    mk[1] = ldsm4(k.lw + X * 4096 + R_M + 512);
    PIN(0);
    asm volatile("" : "+r"(s));
    const uint32_t z = s & zero, wz = k.w + z, w5 = wz * 512, so = (s & 1) * SLOT + w5;
    const uint32_t qb = sb + R_BAR + (RB_QK + X * 8) * 8 + wz * 8;
    uint32_t x[4], vv[2], l8;
    {
        float aq[4] = {0, 0, 0, 0}, ak[4] = {0, 0, 0, 0}, av[4] = {0, 0, 0, 0};
#pragma unroll
        for (int t = 0; t < 16; t++) {
            const uint32_t b0 = (t & 1) ? mk[t >> 1].z : mk[t >> 1].x, b1 = (t & 1) ? mk[t >> 1].w : mk[t >> 1].y;
            mma16(aq, wq[t][0], wq[t][1], wq[t][2], wq[t][3], b0, b1);
            PIN(8);
            mma16(ak, wk[t][0], wk[t][1], wk[t][2], wk[t][3], b0, b1);
            PIN(9);
            mma16(av, wv[t].x, wv[t].y, wv[t].z, wv[t].w, b0, b1);
            PIN(10);
            if ((t & 1) && t < 13) mk[(t >> 1) + 2] = ldsm4(k.lw + X * 4096 + R_M + (t >> 1) * 512 + 1024);
            const int nx = (V_NEXT >> (4 * t)) & 15;
            if (nx) wv[nx] = lds128(k.lw + w5 + R_WV + nx * 4096);
            if (t == 14) l8 = ((k.lw + z) >> 1) + (sb - (sb >> 1) + SL + (s & 1) * SLOT + wz * 256);
            if (t < 15) PIN(1);
        }
        x[0] = movm(pack2(aq[0], aq[1])); x[1] = movm(pack2(aq[2], aq[3]));
        x[2] = movm(pack2(ak[0], ak[1])); x[3] = movm(pack2(ak[2], ak[3]));
        vv[0] = pack2(av[0], av[1]); vv[1] = pack2(av[2], av[3]);
        if (VFIRST) st_async2(l8 + (SL_VM + k.dp), vv[0], vv[1], qb + k.dp);
        st_async4(k.lw + (R_U + X * 4096 + w5 + k.dp), x[0], x[1], x[2], x[3], qb + k.dp);
        if (!VFIRST) st_async2(l8 + (SL_VM + k.dp), vv[0], vv[1], qb + k.dp);
    }
    {
        arrive_if(sb + R_BAR + (RB_GO + 2 - 2 * X + ((s + d) & 1)) * 8, k.sp, X ? s >= hi : s <= lo);
        const uint32_t swr = ((k.sp + z) & 0xffff) + (sb + R_SB);
        mbar_wait(sb + R_BAR + (RB_XFULL + X * 2) * 8 + (s & 1) * 8, (s >> 1) & 1);
        const uint4 k0 = lds128(k.lw + so + SL), k1 = lds128(k.lw + so + SL + 4096);
#pragma unroll
        for (int i = 0; i < NPX; i++) wo[i] = lds128(k.lw + w5 + R_WO + i * 4096);
        mbar_wait(qb, s & 1);
        const uint4 u = lds128(k.lw + w5 + R_U + X * 4096);
        const uint32_t q0 = hadd2(x[0], u.x), q1 = hadd2(x[1], u.y);
        x[2] = hadd2(x[2], u.z); x[3] = hadd2(x[3], u.w);
        float sa[4] = {0, 0, 0, 0}, sc[4] = {0, 0, 0, 0}, sm0, sm1;
        mma16(sa, k0.x, k0.y, k0.z, k0.w, q0, q1);
        mma16(sc, k1.x, k1.y, k1.z, k1.w, q0, q1);
        mma16_top(sm0, sm1, x[2], x[3], q0, q1);
        asm volatile("stmatrix.sync.aligned.m8n8.x4.trans.shared.b16 [%0],{%1,%2,%3,%4};" ::"r"(swr), "r"(pack2(sa[0], sa[1])), "r"(pack2(sa[2], sa[3])),
                     "r"(pack2(sc[0], sc[1])), "r"(pack2(sc[2], sc[3])) : "memory");
        asm volatile("stmatrix.sync.aligned.m8n8.x1.trans.shared.b16 [%0],{%1};" ::"r"(swr + 512), "r"(pack2(sm0, sm1)) : "memory");
    }
    bar_sync(NB_S, 256);
    uint4 v0, v1;
    uint32_t ls;
    {
        const uint4 y = ldsm4t(k.lw + wz * 656 + R_SB);
        PIN(2);
        uint32_t y4; asm volatile("ldmatrix.sync.aligned.m8n8.x1.trans.shared.b16 {%0},[%1];" : "=r"(y4) : "r"(k.lw + wz * 656 + R_SB + 512) : "memory");
        PIN(2);
        const uint2 vp = lds64(l8 + SL_VM);
        sts64(l8 + SL_KM, x[2], x[3]);
        const uint32_t ONE = 0x3f803f80u + z;
        float a[4] = {0, 0, 0, 0}, b[4] = {0, 0, 0, 0}, e[4] = {0, 0, 0, 0};
        mma16(a, ONE, z, z, ONE, y.x, y.y); mma16(b, ONE, z, z, ONE, y.z, y.w); mma8(e, ONE, z, y4);
        vv[0] = hadd2(vv[0], vp.x); vv[1] = hadd2(vv[1], vp.y);
        sts64(l8 + SL_VM, vv[0], vv[1]);
        float s0, s1;
        asm("{.reg .pred p1,p2,p4; .reg .f32 t0,t1,u0,u1; .reg .b32 m; and.b32 m,%12,64; setp.ne.u32 p1,m,0; and.b32 m,%12,128; setp.ne.u32 p2,m,0; and.b32 m,%12,256; setp.ne.u32 p4,m,0;"
            "selp.f32 t0,%4,%2,p1; selp.f32 t1,%5,%3,p1; selp.f32 u0,%8,%6,p1; selp.f32 u1,%9,%7,p1; selp.f32 t0,u0,t0,p2; selp.f32 t1,u1,t1,p2; selp.f32 %0,%10,t0,p4; selp.f32 %1,%11,t1,p4;}"
            : "=f"(s0), "=f"(s1) : "f"(a[0]), "f"(a[1]), "f"(a[2]), "f"(a[3]), "f"(b[0]), "f"(b[1]), "f"(b[2]), "f"(b[3]), "f"(e[0]), "f"(e[1]), "r"(k.lw));
        const int mi = __float_as_int(fmaxf(s0, s1));
        const int mp = __reduce_max_sync(0xffffffffu, mi), mn = (int)__reduce_min_sync(0xffffffffu, (unsigned)mi);
        PIN(3);
        v0 = lds128(k.lw + so + SL + SL_V); v1 = lds128(k.lw + so + SL + SL_V + 4096);
#pragma unroll
        for (int i = NPX; i < NPF; i++) wo[i] = lds128(k.lw + w5 + R_WO + i * 4096);
        PIN(4);
        const float mo = -__int_as_float(mp >= 0 ? mp : mn) * SC_LOG2E;
        s0 = ex2(fmaf(s0, SC_LOG2E, mo)); s1 = ex2(fmaf(s1, SC_LOG2E, mo));
        sts32(((k.sp + z) >> 16) + (sb + R_PB), pack2(s0, s1));
        ls = k.lw < sb + 320 ? __float_as_uint((s0 + s1) + 4.f) : 0;
    }
    bar_sync(NB_P, 256);
    {
        const uint4 pp = lds128(k.lw + R_PB);
        PIN(5);
        const uint32_t pm = lds32(((k.lw + z) >> 2) + (sb - (sb >> 2) + R_PB + 512));
        PIN(5);
        if (EGO) arrive_if(sb + R_BAR + (RB_GO + 2 * X + (s & 1)) * 8, k.sp, X ? s + 1 < hi : s >= lo);
        sts32(sb + R_IL + (wz >> 1) * 16 + (wz & 1) * 4, __reduce_add_sync(0xffffffffu, ls) - 20u * 0x40800000u);
        float o0[4] = {0, 0, 0, 0}, o1[4] = {0, 0, 0, 0}, o2[4] = {0, 0, 0, 0};
        mma16(o0, v0.x, v0.y, v0.z, v0.w, pp.x, pp.y);
        mma16(o1, v1.x, v1.y, v1.z, v1.w, pp.z, pp.w);
        mma8(o2, vv[0], vv[1], pm);
        asm volatile("stmatrix.sync.aligned.m8n8.x2.trans.shared.b16 [%0],{%1,%2};" ::"r"(k.lw + wz * 256 + R_OB),
                     "r"(pack2(o0[0] + o1[0] + o2[0], o0[1] + o1[1] + o2[1])), "r"(pack2(o0[2] + o1[2] + o2[2], o0[3] + o1[3] + o2[3])) : "memory");
    }
    bar_sync(NB_O, 256);
    {
        float r0[2][4] = {{0, 0, 0, 0}, {0, 0, 0, 0}}, r1[2][4] = {{0, 0, 0, 0}, {0, 0, 0, 0}};
        uint4 b[4];
        b[0] = ldsm4(k.lw + R_OB);
        PIN(6);
        b[1] = ldsm4(k.lw + R_OB + 512);
        PIN(6);
#pragma unroll
        for (int m = NWO + NPF; m < 16; m++) if (((OL >> (2 * (15 - m))) & 3) == 3) wo[m] = lds128(k.lw + w5 + R_WO + (m - NWO) * 4096);
        const uint2 il = lds64(sb + R_IL + ((k.lw + z) & 48));
        PIN(6);
        float i0, i1;
        uint4* dst;
#pragma unroll
        for (int i = 0; i < 4; i++) {
            mma16(r0[0], wo[4 * i].x, wo[4 * i].y, wo[4 * i].z, wo[4 * i].w, b[i].x, b[i].y);
            mma16(r1[0], wo[4 * i + 1].x, wo[4 * i + 1].y, wo[4 * i + 1].z, wo[4 * i + 1].w, b[i].x, b[i].y);
            mma16(r0[OA], wo[4 * i + 2].x, wo[4 * i + 2].y, wo[4 * i + 2].z, wo[4 * i + 2].w, b[i].z, b[i].w);
            mma16(r1[OA], wo[4 * i + 3].x, wo[4 * i + 3].y, wo[4 * i + 3].z, wo[4 * i + 3].w, b[i].z, b[i].w);
            if (i < 2) b[i + 2] = ldsm4(k.lw + R_OB + (i + 2) * 512);
#pragma unroll
            for (int m = NWO + NPF; m < 16; m++) if (i < 3 && i == ((OL >> (2 * (15 - m))) & 3)) wo[m] = lds128(k.lw + w5 + R_WO + (m - NWO) * 4096);
            if (i == 1) { i0 = rcp(__uint2float_rn(il.x)) * 2097152.f; i1 = rcp(__uint2float_rn(il.y)) * 2097152.f; }
            if (i == 2) {
                const uint32_t po = k.po + z;
                dst = (uint4*)((char*)xregion(X, 0) + ((po & ~1u) ^ ((po & X) << 12)));
                asm volatile("" : "+l"(dst));
            }
            PIN(7);
        }
        const uint32_t tag = (s + 1) & 1;
#pragma unroll
        for (int i = 0; i < 4; i++) { r0[0][i] = (OA ? r0[0][i] + r0[1][i] : r0[0][i]) * ((i & 1) ? i1 : i0); r1[0][i] = (OA ? r1[0][i] + r1[1][i] : r1[0][i]) * ((i & 1) ? i1 : i0); }
        st_rlx128(dst, (pack2(r0[0][0], r0[0][2]) & ~1u) | tag,
                  pack2(r1[0][0], r1[0][2]), pack2(r0[0][1], r0[0][3]), pack2(r1[0][1], r1[0][3]));
        bar_arrive(NB_PART + X, 288);
#pragma unroll
        for (int t = 0; t < V_PRE; t++) if (!((VMASK >> t) & 1)) wv[t] = lds128(k.lw + w5 + R_WV + t * 4096);
        if (!EGO) arrive_if(sb + R_BAR + (RB_GO + 2 * X + (s & 1)) * 8, k.sp, X ? s + 1 < hi : s >= lo);
    }
}

__device__ __forceinline__ void rec_fetch(const Params& p, uint32_t sb, int head, uint32_t rank, int which, int dst) {
#pragma unroll 1
    for (int j = 0; j < 8; j++) tma2d(sb + dst + j * 8192, &p.tm[which], head * 128 + (j >> 2) * 64, rank * 256 + (j & 3) * 64, sb + R_BAR + RB_INIT * 8);
}

__device__ __forceinline__ void rec_weights(const Params& p, uint32_t sb, int head, uint32_t rank, int w) {
    const int lane = threadIdx.x & 31, g = lane >> 2, c = lane & 3;
    const int t = w & 3, WG = w >> 2;
    uint32_t wq[16][4], wk[16][4];
    uint4 wo[16], wv[16];
    const uint32_t woff = sb + WG * 32768 + (((lane >> 4) << 3) + (lane & 7)) * 128 + (((2 * t + ((lane >> 3) & 1)) ^ (lane & 7)) << 4);
    const uint32_t lw = sb + lane * 16;
    PROF(threadIdx.x == 0, 3501);
    {
        const __nv_bfloat16* wp = p.Wo + (size_t)(head * 128 + 2 * c) * 512 + rank * 256 + w * 32 + g * 4;
#pragma unroll
        for (int ks = 0; ks < 8; ks++) {
            const uint2 r0 = *(const uint2*)(wp + (ks * 16) * 512), r1 = *(const uint2*)(wp + (ks * 16 + 1) * 512);
            const uint2 r2 = *(const uint2*)(wp + (ks * 16 + 8) * 512), r3 = *(const uint2*)(wp + (ks * 16 + 9) * 512);
            const uint4 f[2] = {make_uint4(__byte_perm(r0.x, r1.x, 0x5410), __byte_perm(r0.x, r1.x, 0x7632), __byte_perm(r2.x, r3.x, 0x5410), __byte_perm(r2.x, r3.x, 0x7632)),
                                make_uint4(__byte_perm(r0.y, r1.y, 0x5410), __byte_perm(r0.y, r1.y, 0x7632), __byte_perm(r2.y, r3.y, 0x5410), __byte_perm(r2.y, r3.y, 0x7632))};
#pragma unroll
            for (int h = 0; h < 2; h++) {
                const int m = 2 * ks + h;
                wo[m] = f[h];
            }
        }
    }
    PROF(threadIdx.x == 0, 3502);
    mbar_wait(sb + R_BAR + RB_INIT * 8, 0);
    PROF(threadIdx.x == 0, 3503);
#pragma unroll
    for (int ks = 0; ks < 16; ks++) {
        uint4 a = ldsm4t(woff + R_STQ + ks * 2048), b = ldsm4t(woff + R_STK + ks * 2048);
        wq[ks][0] = a.x; wq[ks][1] = a.y; wq[ks][2] = a.z; wq[ks][3] = a.w;
        wk[ks][0] = b.x; wk[ks][1] = b.y; wk[ks][2] = b.z; wk[ks][3] = b.w;
    }
    bar_sync(NB_W, 256);
#pragma unroll
    for (int m = 0; m < 16; m++)
        if (m < NPF || m >= NPF + NWO) sts128(lw + w * 512 + R_WO + (m < NPF ? m : m - NWO) * 4096, wo[m].x, wo[m].y, wo[m].z, wo[m].w);
#pragma unroll
    for (int i = 0; i < 16; i++) {
        wv[i] = ldsm4t(woff + R_STV + i * 2048);
        if (!((VMASK >> i) & 1)) sts128(lw + w * 512 + R_WV + i * 4096, wv[i].x, wv[i].y, wv[i].z, wv[i].w);
    }
    fence_async_smem();
    PROF(threadIdx.x == 0, 3504);
    __syncthreads();
    cluster_sync();
    PROF(threadIdx.x == 0, 3505);
    RecW k;
    {
        const int r = (w * 4 + (lane >> 3)) * 2 + rank;
        const uint32_t sl = lds32(sb + R_SEL + r * 4);
        const int slot = HL == 0 ? head * 8 + (lane & 7) : HL == 1 ? (head >> 2) * 32 + ((lane & 7) >> 1) * 8 + (head & 3) * 2 + (lane & 1) : (head >> 1) * 16 + ((lane & 7) >> 2) * 8 + (head & 1) * 4 + (lane & 3);
        k.po = (r * 512 + slot + (sl & 1) * 256) * 16 + (((sl >> 1) ^ sl) & 1);
    }
    k.dp = mapa(sb, rank ^ 1) - sb;
    k.lw = __shfl_sync(0xffffffffu, lw, lane);
    k.sp = __shfl_sync(0xffffffffu, (lane & 7) * 656 + (lane >> 3) * 128 + w * 16 + ((g < 4 ? (w * 4 + c) * 16 + g * 4 : 512 + (w * 4 + c) * 4) << 16), lane);
    k.w = w;
    const int e0 = (p.chains & 1) ? 64 : 0, o1 = (p.chains & 2) ? p.lag : 1000, nit = (p.chains & 2) ? p.lag + 64 : e0;
    const uint32_t zero = p.zero;
    int it = 0, X = e0 ? 0 : 1;
#pragma unroll 1
    while (it < nit) {
        rec_step(k, sb, X, X ? it - o1 : it, zero, o1, e0 - o1, o1 + 1 - X, wq, wk, wv, wo);
        if (X == 0 && it >= o1) X = 1; else { it++; X = it < e0 ? 0 : 1; }
    }
}

__device__ __forceinline__ uint32_t mism(uint32_t a, uint32_t b, uint32_t t) {
    uint32_t d; asm("lop3.b32 %0,%1,%2,%3,0x7e;" : "=r"(d) : "r"(a), "r"(b), "r"(t)); return d;
}
__device__ __forceinline__ uint32_t or3(uint32_t a, uint32_t b, uint32_t c) {
    uint32_t d; asm("lop3.b32 %0,%1,%2,%3,0xfe;" : "=r"(d) : "r"(a), "r"(b), "r"(c)); return d;
}
template <bool TWO, class F>
__device__ __forceinline__ void poll8(uint4* x, const uint4* src, uint32_t tag, F&& use) {
#pragma unroll
    for (int j = 0; j < 8; j++) x[j] = ld_rlx128(src + j * 32);
    int n = 0;
    while (true) {
        use();
        uint32_t bad = or3(mism(x[0].x, x[1].x, tag), mism(x[2].x, x[3].x, tag), mism(x[4].x, x[5].x, tag));
        if (TWO) bad = or3(bad, or3(mism(x[0].z, x[1].z, tag), mism(x[2].z, x[3].z, tag), mism(x[4].z, x[5].z, tag)), mism(x[6].z, x[7].z, tag));
        if (!__any_sync(0xffffffffu, (bad | mism(x[6].x, x[7].x, tag)) & 1)) break;
#pragma unroll
        for (int j = 0; j < 8; j++)
            asm volatile("{.reg .pred p; .reg .b128 t; .reg .b32 m; lop3.b32 m,%0,%6,%5,0x7e; and.b32 m,m,1; setp.ne.u32 p,m,0; mov.b128 t,{%0,%1,%2,%3};"
                         "@p ld.relaxed.gpu.global.b128 t,[%4]; mov.b128 {%0,%1,%2,%3},t;}"
                         : "+r"(x[j].x), "+r"(x[j].y), "+r"(x[j].z), "+r"(x[j].w) : "l"(src + j * 32), "r"(tag), "r"(TWO ? x[j].z : tag) : "memory");
        if (++n > 2000000) __trap();
    }
}

__device__ __forceinline__ void rec_comm(const Params& p, uint32_t sb, int X, int head, uint32_t rank) {
    const int lane = threadIdx.x & 31, g = lane >> 2, c = lane & 3;
    const int me = head * 2 + rank;
    const uint32_t mb = sb + R_M + X * 4096 + lane * 16;
    uint4 x[8];
#pragma unroll
    for (int j = 0; j < 8; j++) x[j] = *(const uint4*)(p.mem0 + (lane & 7) * 512 + rank * 256 + (j * 4 + (lane >> 3)) * 8);
    const uint32_t sl = lds32(sb + R_SEL + me * 4);
    const uint4* src1 = xregion(X, me) + ((sl >> X) & 1) * 256 + (HL == 0 ? c * 8 + g : HL == 1 ? (g >> 1) * 8 + c * 2 + (g & 1) : (c >> 1) * 16 + (g >> 2) * 8 + (c & 1) * 4 + (g & 3));
    const uint4* src2 = xregion(X, 64 + rank) + ((sl >> (2 + X)) & 1) * 256 + lane;
    uint2* mdst = (uint2*)(xregion(X, 64 + rank) + (c >> 1) * 256 + head * 8 + (g & 3) * 2 + (c & 1)) + (g >> 2);
    const uint32_t one = (g & 1) ? 0x3f800000u : 0x00003f80u, selA = (g & 2) ? 0u : one, selB = (g & 2) ? one : 0u;
    const uint32_t qb = sb + R_BAR + (RB_QK + X * 8 + lane) * 8;
    if (lane < 8) mbar_expect(qb, 768);
#pragma unroll
    for (int j = 0; j < 8; j++) sts128(mb + j * 512, x[j].x, x[j].y, x[j].z, x[j].w);
#pragma unroll 1
    for (int s = 0;; s++) {
        bar_arrive(NB_MFULL + X, 288);
        PROF(lane == 0, X * 64 + s);
        bar_sync(NB_PART + X, 288);
        if (s == 63) break;
        const uint32_t tag = (s + 1) & 1;
        if (lane < 8) mbar_expect(qb, 768);
        spin(D1);
        uint32_t m0, m1;
        poll8<false>(x, src1, tag, [&]() {
            float a[RACC][4];
#pragma unroll
            for (int j = 0; j < 8; j++) {
                if (j < RACC) a[j][0] = a[j][1] = a[j][2] = a[j][3] = 0;
                mma16(a[j % RACC], x[j].x, x[j].y, x[j].z, x[j].w, selA, selB);
            }
#pragma unroll
            for (int i = 0; i < 4; i++) a[0][i] = RACC == 3 ? a[0][i] + a[1][i] + a[2 % RACC][i] : a[0][i] + a[1][i];
            m0 = (pack2(a[0][0], a[0][1]) & ~1u) | tag; m1 = pack2(a[0][2], a[0][3]);
        });
        asm volatile("st.relaxed.gpu.global.b64 [%0],%1;" ::"l"(mdst), "l"(((uint64_t)m1 << 32) | m0) : "memory");
        spin(D2);
        poll8<true>(x, src2, tag, [&]() {
#pragma unroll
            for (int j = 0; j < 8; j++) sts128(mb + j * 512, x[j].x, x[j].y, x[j].z, x[j].w);
        });
    }
}

template <int MT>
__device__ __forceinline__ void xattn(uint32_t l16, uint32_t l8, uint32_t os, int g, int c) {
    constexpr int NT = 3 + 2 * MT, XUN = XU;
    float S[NT][4];
#pragma unroll
    for (int i = 0; i < NT; i++) S[i][0] = S[i][1] = S[i][2] = S[i][3] = 0;
#pragma unroll XUN
    for (int ks = 0; ks < 8; ks++) {
        const uint4 q = lds128(l16 + SL_Q + ks * 512);
        const uint2 u = lds64(l8 + SL_KM + ks * 256);
        mma16(S[0], q.x, q.y, q.z, q.w, u.x, u.y);
#pragma unroll
        for (int m = 0; m <= MT; m++) {
            const uint4 kk = lds128(l16 + m * 4096 + ks * 512);
            mma16(S[1 + 2 * m], q.x, q.y, q.z, q.w, kk.x, kk.z); mma16(S[2 + 2 * m], q.x, q.y, q.z, q.w, kk.y, kk.w);
        }
    }
    const float NEG = -__int_as_float(0x7f800000);
    if (2 * c > g) { S[NT - 2][0] = NEG; S[NT - 1][2] = NEG; }
    if (2 * c + 1 > g) { S[NT - 2][1] = NEG; S[NT - 1][3] = NEG; }
    S[NT - 1][0] = S[NT - 1][1] = NEG;
    float m0 = fmaxf(S[0][0], S[0][1]), m1 = fmaxf(S[0][2], S[0][3]);
#pragma unroll
    for (int i = 1; i < NT; i++) { if (i < NT - 1) m0 = fmaxf(m0, fmaxf(S[i][0], S[i][1])); m1 = fmaxf(m1, fmaxf(S[i][2], S[i][3])); }
    m0 = fmaxf(m0, __shfl_xor_sync(0xffffffffu, m0, 1)); m1 = fmaxf(m1, __shfl_xor_sync(0xffffffffu, m1, 1));
    m0 = fmaxf(m0, __shfl_xor_sync(0xffffffffu, m0, 2)); m1 = fmaxf(m1, __shfl_xor_sync(0xffffffffu, m1, 2));
    m0 *= -SC_LOG2E; m1 *= -SC_LOG2E;
    float l0 = 0, l1 = 0;
#pragma unroll
    for (int i = 0; i < NT; i++) {
        if (i < NT - 1) { S[i][0] = ex2(fmaf(S[i][0], SC_LOG2E, m0)); S[i][1] = ex2(fmaf(S[i][1], SC_LOG2E, m0)); l0 += S[i][0] + S[i][1]; }
        S[i][2] = ex2(fmaf(S[i][2], SC_LOG2E, m1)); S[i][3] = ex2(fmaf(S[i][3], SC_LOG2E, m1)); l1 += S[i][2] + S[i][3];
    }
    l0 += __shfl_xor_sync(0xffffffffu, l0, 1); l1 += __shfl_xor_sync(0xffffffffu, l1, 1);
    l0 += __shfl_xor_sync(0xffffffffu, l0, 2); l1 += __shfl_xor_sync(0xffffffffu, l1, 2);
    uint2 vm = lds64(l8 + SL_VM);
    uint4 v[2];
#pragma unroll
    for (int m = 0; m <= MT; m++) v[m] = lds128(l16 + SL_V + m * 4096);
    l0 = rcp(l0); l1 = rcp(l1);
    uint32_t P[NT][2];
#pragma unroll
    for (int i = 0; i < NT; i++) { P[i][0] = i < NT - 1 ? pack2(S[i][0] * l0, S[i][1] * l0) : 0u; P[i][1] = pack2(S[i][2] * l1, S[i][3] * l1); }
#pragma unroll
    for (int et = 0; et < 8; et++) {
        float a[4] = {0, 0, 0, 0}, b[4] = {0, 0, 0, 0};
        const uint2 um = vm;
        const uint4 u[2] = {v[0], v[MT]};
        if (et < 7) {
            vm = lds64(l8 + SL_VM + et * 256 + 256);
#pragma unroll
            for (int m = 0; m <= MT; m++) v[m] = lds128(l16 + SL_V + m * 4096 + et * 512 + 512);
            PIN(11);
        }
        mma8(a, um.x, um.y, P[0][0]); mma8(b, um.x, um.y, P[0][1]);
#pragma unroll
        for (int m = 0; m <= MT; m++) {
            mma16(a, u[m].x, u[m].y, u[m].z, u[m].w, P[1 + 2 * m][0], P[2 + 2 * m][0]); mma16(b, u[m].x, u[m].y, u[m].z, u[m].w, P[1 + 2 * m][1], P[2 + 2 * m][1]);
        }
        asm volatile("stmatrix.sync.aligned.m8n8.x4.trans.shared.b16 [%0],{%1,%2,%3,%4};" ::"r"(os + (et >> 2) * 2048 + (et & 3) * 256),
                     "r"(pack2(a[0], a[1])), "r"(pack2(a[2], a[3])), "r"(pack2(b[0], b[1])), "r"(pack2(b[2], b[3])) : "memory");
    }
}

__device__ __forceinline__ void rec_tiles(uint32_t sb, int X, int head, uint32_t rank, int& nxt, int lim, int need) {
#pragma unroll 1
    while (nxt <= lim) {
        if ((nxt & 1) == 0) {
            unsigned v; int n = 0;
            while (true) {
                asm volatile("ld.relaxed.gpu.global.u32 %0,[%1];" : "=r"(v) : "l"(cnt_ptr(C_QKV + X * 32 + (nxt >> 1))) : "memory");
                if (__all_sync(0xffffffffu, v >= 2 * NQ)) break;
                if (nxt > need) return;
                if (++n > 3000000) __trap();
            }
        }
        if (elect()) {
            const uint32_t bar = sb + R_BAR + (RB_XFULL + X * 2 + (nxt & 1)) * 8, dst = sb + R_SL + (X * 2 + (nxt & 1)) * SLOT;
            const uint4* src = g_qkv + (size_t)((X * 64 + nxt) * 32 + head) * 1536;
            mbar_expect(bar, 20480);
            bulk_g2s_mc(dst + rank * 8192, src + 512 + rank * 512, 8192, bar, POL_LAST);
            bulk_g2s(dst + SL_Q, src + (rank ^ X) * 256, 4096, bar, POL_LAST);
        }
        __syncwarp();
        nxt++;
    }
}

__device__ __forceinline__ void rec_attn(const Params& p, uint32_t sb, int X, int head, uint32_t rank) {
    const int lane = __shfl_sync(0xffffffffu, threadIdx.x & 31, threadIdx.x & 31), g = lane >> 2, c = lane & 3;
    const int mt = rank ^ X;
    const uint32_t dp = mapa(sb, rank ^ 1) - sb;
    int nxt = 0;
    rec_tiles(sb, X, head, rank, nxt, 1, 0);
#pragma unroll 1
    for (int s = 0; s < 64; s++) {
        const uint32_t so = sb + R_SL + (X * 2 + (s & 1)) * SLOT;
        while (nxt <= min(s + 1, 63)) {
            uint32_t ok;
            asm volatile("{.reg .pred p; mbarrier.test_wait.parity.shared::cta.b64 p,[%1],%2; selp.u32 %0,1,0,p;}" : "=r"(ok) : "r"(sb + R_BAR + (RB_GO + X * 2 + (s & 1)) * 8), "r"((s >> 1) & 1) : "memory");
            if (__any_sync(0xffffffffu, ok)) break;
            rec_tiles(sb, X, head, rank, nxt, s + 1, -1);
        }
        mbar_wait(sb + R_BAR + (RB_GO + X * 2 + (s & 1)) * 8, (s >> 1) & 1);
        if (elect()) asm volatile("cp.async.bulk.wait_group.read 0;" ::: "memory");
        __syncwarp();
        const uint32_t os = sb + R_OS + X * 4096 + (lane >> 4) * 1024 + (lane & 15) * 16;
        if (mt) xattn<1>(so + lane * 16, so + lane * 8, os, g, c); else xattn<0>(so + lane * 16, so + lane * 8, os, g, c);
        fence_async_smem();
        __syncwarp();
        const uint32_t svb = sb + R_BAR + (RB_SV + X * 2 + (s & 1)) * 8;
        if (elect()) {
            mbar_arrive(svb); mbar_arrive_cluster(svb + dp);
            const uint64_t pol = POL_SOON;
#pragma unroll
            for (int kb = 0; kb < 2; kb++)
                asm volatile("cp.async.bulk.global.shared::cta.bulk_group.L2::cache_hint [%0],[%1],%2,%3;" ::"l"(g_o + ((X * 32 + (s >> 1)) * 64 + head * 2 + kb) * 512 + ((s & 1) * 4 + mt * 2) * 64),
                             "r"(sb + R_OS + X * 4096 + kb * 2048), "r"(2048), "l"(pol) : "memory");
            asm volatile("cp.async.bulk.commit_group;" ::: "memory");
        }
        __syncwarp();
        if (s & 1) {
            if (elect()) { asm volatile("cp.async.bulk.wait_group 0;" ::: "memory"); red_relaxed(cnt_ptr(C_O + (X * 32 + (s >> 1)) * 4 + (head >> 3)), 1); }
            __syncwarp();
        }
        rec_tiles(sb, X, head, rank, nxt, min(s + 1, 63), s + 1);
        mbar_wait(svb, (s >> 1) & 1);
        rec_tiles(sb, X, head, rank, nxt, min(s + 2, 63), -1);
    }
}

__device__ __forceinline__ uint32_t timed_clear(unsigned* r, int lane) {
    uint32_t v = 0;
    const uint32_t t0 = clk32();
    asm volatile("{.reg .pred p; setp.eq.u32 p,%2,0; @p atom.relaxed.gpu.global.exch.b32 %0,[%1],0;}" : "+r"(v) : "l"(r), "r"(lane) : "memory");
    v = __shfl_sync(0xffffffffu, v, 0);
    asm volatile("{.reg .pred p; setp.eq.u32 p,%0,0x5a5a5a5b; @p nanosleep.u32 1;}" ::"r"(v) : "memory");
    return clk32() - t0;
}
__device__ __forceinline__ void rec_slots(int me, int w) {
    const int lane = threadIdx.x & 31;
    uint4* r = xregion(w & 1, (w & 2) ? 64 + (me & 1) : me) + ((w & 2) ? (me >> 1) * 8 : 0);
#pragma unroll 1
    for (int i = lane; i < ((w & 2) ? 8 : 256); i += 32) r[i] = r[i + 256] = make_uint4(0, 0, 0, 0);
    __syncwarp();
    uint32_t b0 = ~0u, b1 = ~0u;
#pragma unroll 1
    for (int i = 0; i < NPRB; i++) { b0 = min(b0, timed_clear((unsigned*)r, lane)); b1 = min(b1, timed_clear((unsigned*)(r + 256), lane)); }
    if (lane == 0) ((uint8_t*)g_sel)[me * 4 + w] = (b1 < b0) << w;
}

__device__ __forceinline__ void rec_init(uint32_t sb) {
    const uint32_t b = sb + R_BAR;
    const int i = threadIdx.x & 31;
    mbar_init(b + i * 8, i >= RB_SV ? 2 : 1);
    if (i == RB_INIT) mbar_expect(b + RB_INIT * 8, 196608);
    asm volatile("fence.mbarrier_init.release.cluster;" ::: "memory");
}
constexpr int G_BAR = B_BAR;
enum { GB_FULL = 0  , GB_EMPTY = 8  , GB_RS = 16, GB_SS = 17, GB_LAG = 18, GB_FREE = 19, GB_DONE = 20  , GB_N = 24 };
constexpr int Q_PRE = 8;
constexpr int NQRS = 2 * NQ - 64;
__device__ __forceinline__ void gemm_init(uint32_t sb, bool op) {
    const int i = threadIdx.x & 31;
    if (i < GB_N) mbar_init(sb + G_BAR + i * 8, i >= GB_DONE ? 4 : i == GB_FREE ? 8 : (i >= GB_EMPTY && i < GB_RS) ? 2 : 1);
    if (i == GB_RS) mbar_expect(sb + G_BAR + i * 8, op ? 131072 : 98304);
    if (i == GB_SS) mbar_expect(sb + G_BAR + i * 8, op ? 131072 : 163840);
    asm volatile("fence.mbarrier_init.release.cluster;" ::: "memory");
}
__device__ __forceinline__ int qkv_blk(int id, int j) { return NQRS * 4 + id * 10 + j; }
__device__ __forceinline__ void qkv_fetch(const Params& p, uint32_t sb, int id, int j0, int j1) {
#pragma unroll 1
    for (int j = j0 * 2; j < j1 * 2; j++) {
        const int blk = min(qkv_blk(id, j >> 1), 511);
        tma2d(sb + j * 8192, &p.tn[blk >> 8], (blk & 255) * 16, (j & 1) * 256, sb + G_BAR + GB_SS * 8);
    }
}
__device__ __forceinline__ void qkv_stage(const Params& p, uint32_t dst, uint32_t bar, int id, int k0, int nk) {
#pragma unroll 1
    for (int j = 0; j < 2 * nk; j++) {
        const int u = id * 2 + (j >= nk);
        tma2d(dst + j * 8192, &p.tm[u < 64 ? 2 : 0], (u & 63) * 64, (k0 + (j >= nk ? j - nk : j)) * 64, bar);
    }
}
__device__ __forceinline__ void op_fetch(const Params& p, uint32_t sb, int id, int half) {
#pragma unroll 1
    for (int j = 0; j < 16; j++) tma2d(sb + j * 8192, &p.tm[4], ((id * 2 + (j >> 3)) & 7) * 64, (id >> 2) * 1024 + (j & 7) * 128 + half * 64, sb + G_BAR + (GB_RS + half) * 8);
}
template <bool OP>
__device__ __forceinline__ void gemm_producer(const Params& p, uint32_t sb, int id) {
    constexpr int NS = OP ? 6 : 8, SB = OP ? 16384 : 8192, RING = OP ? 131072 : 163840;
    if (!elect()) return;
    mbar_wait(sb + G_BAR + GB_FREE * 8, 0);
    if (OP) op_fetch(p, sb, id, 1);
    else {
        mbar_expect(sb + G_BAR + GB_RS * 8, 32768);
        qkv_stage(p, sb + 196608, sb + G_BAR + GB_RS * 8, id, 6, 2);
        qkv_fetch(p, sb, id, Q_PRE, 10);
        mbar_wait(sb + G_BAR + GB_FREE * 8, 1);
    }
    wait_cnt(g_gate, lds32(sb + S_GATE));
    int st = 0; uint32_t ph = 1;
#pragma unroll 1
    for (int n = 0; n < p.nl[OP]; n++) {
        const int e = p.list[OP][n];
        wait_cnt(OP ? cnt_ptr(C_O + e * 4 + (id >> 2)) : cnt_ptr(C_XN + e), 16);
        PROF(true, 1024 + n * 4);
        const uint4* src = OP ? g_o + (e * 64 + (id >> 2) * 16) * 512 : g_xn + e * 4096;
#pragma unroll 1
        for (int s = 0; s < 8; s++) {
            mbar_wait(sb + G_BAR + (GB_EMPTY + st) * 8, ph);
            mbar_expect(sb + G_BAR + (GB_FULL + st) * 8, SB);
            bulk_g2s(sb + RING + st * SB, src + s * (SB / 16), SB, sb + G_BAR + (GB_FULL + st) * 8, POL_N);
            if (++st == NS) { st = 0; ph ^= 1; }
        }
    }
}
__device__ __forceinline__ void qkv_release(const Params& p, uint32_t sb) {
    if (!elect()) return;
#pragma unroll 1
    for (int n = 0; n < 2 * p.nl[0]; n++) {
        const int e = p.list[0][n >> 1];
        mbar_wait(sb + G_BAR + (GB_DONE + (n & 3)) * 8, (n >> 2) & 1);
        red_release(cnt_ptr(C_QKV + e), 1);
        PROF(n & 1, 1024 + (n >> 1) * 4 + 3);
    }
}
__device__ __forceinline__ void op_permute(uint32_t sb) {
#pragma unroll 2
    for (int i = threadIdx.x; i < 4096; i += 256) {
        const uint32_t a = sb + i * 32 + ((i >> 2) & 1) * 16, b = a ^ 16;
        const uint4 x = lds128(a), y = lds128(b);
        sts128(a, __byte_perm(x.x, x.y, 0x5410), __byte_perm(x.z, x.w, 0x5410), __byte_perm(y.x, y.y, 0x5410), __byte_perm(y.z, y.w, 0x5410));
        sts128(b, __byte_perm(x.x, x.y, 0x7632), __byte_perm(x.z, x.w, 0x7632), __byte_perm(y.x, y.y, 0x7632), __byte_perm(y.z, y.w, 0x7632));
    }
    fence_async_smem();
    bar_sync(1, 256);
}
template <bool OP>
__device__ __forceinline__ void gemm_consumer(const Params& p, uint32_t sb, int id, int w) {
    constexpr int NS = OP ? 6 : 8, SB = OP ? 16384 : 8192, RING = OP ? 131072 : 163840;
    const int lane = threadIdx.x & 31, wg = w >> 2, t = w & 3, u = id * 2 + wg;
    uint32_t a[128];
    mbar_wait(sb + G_BAR + GB_RS * 8, 0);
    PROF(threadIdx.x == 0, 3501);
    if (OP) op_permute(sb);
    const uint32_t wo = sb + (((lane >> 4) << 3) + (lane & 7)) * 128 + (((2 * t + ((lane >> 3) & 1)) ^ (lane & 7)) << 4);
#pragma unroll
    for (int ks = 0; ks < 32; ks++) {
        const uint4 v = ldsm4t(wo + ks * 2048 + (OP ? wg * 65536 : ks < 24 ? 131072 + wg * 49152 : 196608 - 49152 + wg * 16384));
        a[ks * 4] = v.x; a[ks * 4 + 1] = v.y; a[ks * 4 + 2] = v.z; a[ks * 4 + 3] = v.w;
        if (ks == 31 || (!OP && ks == 23)) {
            fence_async_smem();
            __syncwarp();
            if (lane == 0) mbar_arrive(sb + G_BAR + GB_FREE * 8);
            if (ks == 23) mbar_wait(sb + G_BAR + GB_RS * 8, 1);
        }
    }
    PROF(threadIdx.x == 0, 3502);
    mbar_wait(sb + G_BAR + GB_SS * 8, 0);
    if (OP) op_permute(sb);
    PROF(threadIdx.x == 0, 3503);
    const uint32_t tag = OP ? lds32(sb + S_TAG) : 0;
    float c0[32], c1[OP ? 32 : 40];
    int st = 0; uint32_t ph = 0;
    const bool el = (threadIdx.x & 127) == 0;
#pragma unroll 1
    for (int n = 0; n < p.nl[OP]; n++) {
        int prev = 0;
        const uint32_t wb = sb + wg * (OP ? 65536 : 81920) + (n & p.zero);
        const uint64_t dw = OP ? mkdesc(wb, 0, 1024, 1) : mkdesc(wb, 16384, 256, 3);
        if (!OP && wg) mbar_wait(sb + G_BAR + GB_LAG * 8, n & 1);
#pragma unroll
        for (int s = 0; s < 8; s++) {
            mbar_wait(sb + G_BAR + (GB_FULL + st) * 8, ph);
            const uint64_t dx = mkdesc(sb + RING + st * SB, 128, 1024, 0);
            wg_fence();
#pragma unroll
            for (int kk = 0; kk < 4; kk++) {
                const int ks = s * 4 + kk;
                if (ks == 0) { wgmma64_rs<0>(c0, a, dx); if (OP) wgmma64_ta<0>(c1, dw, dx + 512); else wgmma80_tb<0>(c1, dx, dw); }
                else { wgmma64_rs<1>(c0, a + ks * 4, dx + kk * 16); if (OP) wgmma64_ta<1>(c1, dw + ks * 128, dx + 512 + kk * 16); else wgmma80_tb<1>(c1, dx + kk * 16, dw + ks * 32); }
            }
            wg_commit();
            if (s) {
                wg_wait<1>();
                if (el) { mbar_arrive(sb + G_BAR + (GB_EMPTY + prev) * 8); if (!OP && s == QLAG && !wg) mbar_arrive(sb + G_BAR + GB_LAG * 8); }
            }
            prev = st;
            if (++st == NS) { st = 0; ph ^= 1; }
        }
        const int e = p.list[OP][n];
        wg_wait<0>();
        if (el) mbar_arrive(sb + G_BAR + (GB_EMPTY + prev) * 8);
        PROF(threadIdx.x == 128, 1024 + n * 4 + 1);
        if (OP) {
            uint4* dst = g_pp + (e * 4 + (id >> 2)) * 4096 + ((u & 7) * 32 + t * 8) * 16 + (lane >> 2) * 16 + (lane & 3);
#pragma unroll
            for (int j = 0; j < 4; j++) {
                const float* x = c0 + j * 8; const float* y = c1 + j * 8;
                st_rlx128(dst + j * 4, (pack2(x[0] + y[0], x[1] + y[1]) & ~1u) | tag, pack2(x[2] + y[2], x[3] + y[3]), (pack2(x[4] + y[4], x[5] + y[5]) & ~1u) | tag, pack2(x[6] + y[6], x[7] + y[7]));
            }
            if (lane == 0) red_relaxed(cnt_ptr(C_PP + e * 8 + (u & 7)), 1);
            PROF(threadIdx.x == 128, 1024 + n * 4 + 3);
        } else {
            uint4* dst = g_qkv + (size_t)e * 2 * 32 * 1536 + lane;
            const uint64_t pol = POL_SOON;
#pragma unroll
            for (int j = 0; j < 4; j++) {
                const float* x = c0 + j * 8;
                uint4 v = make_uint4(pack2(x[0], x[1]), pack2(x[2], x[3]), pack2(x[4], x[5]), pack2(x[6], x[7]));
                if (u >= 64) v = make_uint4(movm(v.x), movm(v.z), movm(v.y), movm(v.w));
                stg128(dst + (((j >> 1) * 32 + ((u & 63) >> 1)) * 1536 + (u < 64 ? 1024 : 0) + (j & 1) * 256 + ((u & 1) * 4 + t) * 32), v, pol);
            }
#pragma unroll
            for (int j = 0; j < 5; j++) {
                const float* x = c1 + (OP ? 0 : j * 8);
                const int blk = qkv_blk(id, wg * 5 + j);
                if (blk < 512) stg128(dst + (((t >> 1) * 32 + ((blk >> 3) & 31)) * 1536 + (blk >> 8) * 512 + (t & 1) * 256 + (blk & 7) * 32),
                                      make_uint4(pack2(x[0], x[1]), pack2(x[2], x[3]), pack2(x[4], x[5]), pack2(x[6], x[7])), pol);
            }
        }
        __syncwarp();
        if (!OP && lane == 0) mbar_arrive(sb + G_BAR + (GB_DONE + (n & 1) * 2 + wg) * 8);
        PROF(threadIdx.x == 128, 1024 + n * 4 + 2);
    }
}

template <int NP, bool MMA>
__device__ __forceinline__ void sum_partials(float* x, const uint2* src, const uint32_t* r0, const uint32_t* r1, uint32_t idm, uint32_t tag, bool on) {
    uint2 v[4][NP];
    int n = 0;
    while (true) {
        uint32_t bad = 0;
#pragma unroll
        for (int s = 0; s < 4; s++)
#pragma unroll
            for (int i = 0; i < NP; i++)
                asm volatile("{.reg .pred p; .reg .b64 t; setp.ne.u32 p,%4,0; mov.b64 t,0; @p ld.relaxed.gpu.global.L2::cache_hint.b64 t,[%2],%3; mov.b64 {%0,%1},t;}"
                             : "=r"(v[s][i].x), "=r"(v[s][i].y) : "l"(src + s * 8192 + i * 32), "l"(POL_LAST), "r"((uint32_t)on) : "memory");
#pragma unroll
        for (int s = 0; s < 4; s++) bad = or3(bad, mism(v[s][0].x, v[s][1].x, tag), mism(v[s][NP - 2].x, v[s][NP - 1].x, tag));
        if (!__any_sync(0xffffffffu, (bad & 1) && on)) break;
        if (++n > 2000000) __trap();
    }
#pragma unroll
    for (int i = 0; i < NP; i++) {
        uint32_t a, b;
        if (MMA) {
            float t[4] = {0, 0, 0, 0};
            mma16(t, v[0][i].x, v[0][i].y, v[1][i].x, v[1][i].y, idm, idm); mma16(t, v[2][i].x, v[2][i].y, v[3][i].x, v[3][i].y, idm, idm);
            a = pack2(t[0], t[2]); b = pack2(t[1], t[3]);
        } else {
            a = pack2((blo(v[0][i].x) + blo(v[1][i].x)) + (blo(v[2][i].x) + blo(v[3][i].x)), (blo(v[0][i].y) + blo(v[1][i].y)) + (blo(v[2][i].y) + blo(v[3][i].y)));
            b = pack2((bhi(v[0][i].x) + bhi(v[1][i].x)) + (bhi(v[2][i].x) + bhi(v[3][i].x)), (bhi(v[0][i].y) + bhi(v[1][i].y)) + (bhi(v[2][i].y) + bhi(v[3][i].y)));
        }
        const uint32_t s0 = hadd2(a, r0[i]), s1 = hadd2(b, r1[i]);
        x[4 * i] = blo(s0); x[4 * i + 2] = bhi(s0); x[4 * i + 1] = blo(s1); x[4 * i + 3] = bhi(s1);
    }
}
__device__ __forceinline__ const uint2* pp_src(int e, int tile, int lane) { return (const uint2*)g_pp + e * 32768 + tile * 128 + (lane >> 3) * 8 + (lane & 3) * 2 + ((lane >> 2) & 1); }

__device__ __forceinline__ void fin_warp(const Params& p, uint32_t sb, int id) {
    const int grp = (id & ~3) + (threadIdx.x & 3), tp = (id & 3) * 8 + ((threadIdx.x & 31) >> 2);
    wait_slow_warp(g_gate, lds32(sb + S_GATE));
#pragma unroll 1
    for (int e = 32; e < 64; e++) {
        wait_slow_warp(cnt_ptr(C_XN + e), 16);
        const uint4 r = ldcg128(g_x + ((128 + grp) * XP + (e - 32) * 32 + tp));
        if (e < 63) wait_slow_warp(cnt_ptr(C_PP + e * 8 + (id >> 4)), 16); else wait_slow_warp(cnt_ptr(C_O + 63 * 4), 16);
        wait_flag_warp(cnt_ptr(C_PP + e * 8 + (id >> 4)), 16);
        const uint32_t a[2] = {r.x, r.y}, b[2] = {r.z, r.w};
        float x[8];
        sum_partials<2, false>(x, pp_src(e, 0, tp) + grp * 64, a, b, 0, lds32(sb + S_TAG), true);
        uint2* dst = (uint2*)p.out + ((e - 32) * 64 + tp * 2) * 128 + grp;
#pragma unroll
        for (int t = 0; t < 2; t++)
            dst[t * 128] = make_uint2(__byte_perm(__float_as_uint(x[t]), __float_as_uint(x[2 + t]), 0x7632), __byte_perm(__float_as_uint(x[4 + t]), __float_as_uint(x[6 + t]), 0x7632));
        PROF((threadIdx.x & 31) == 0, 1536 + e);
    }
}

constexpr int PROW = 272, UROW = 2304, UPRE = 256;
constexpr int C_UR = 0  , C_TB = 65536  , C_BG = C_TB + 51200,
              CB_M = 8960, CB_U = CB_M + 1792, CB_BIG = CB_U + 2560, C_ST = C_BG + 8 * CB_BIG  ;
static_assert(C_ST + 4736 <= B_BAR, "smem map");
enum { CB_TB = 0, CB_UF = 1  , CB_CF = 5  , CB_LD = 9   };
__device__ __forceinline__ void conv_init(uint32_t sb, bool spare) {
    const int i = threadIdx.x & 31;
    mbar_init(sb + B_BAR + i * 8, (i >= CB_UF && i < CB_CF && !spare) ? 2 : 1);
    if (i == CB_TB && !spare) mbar_expect(sb + B_BAR + i * 8, 51200);
    asm volatile("fence.mbarrier_init.release.cluster;" ::: "memory");
}
__device__ __forceinline__ void mma_q(float* c, const uint32_t* a, const uint4& q) {
    mma16(c, a[0], a[1], a[2], a[3], q.x, q.y); mma16(c, a[4], a[5], a[6], a[7], q.z, q.w);
}
__device__ __forceinline__ uint2 ld_acc(const uint2* p, bool on) {
    uint2 v = make_uint2(0, 0);
    asm volatile("{.reg .pred p; setp.ne.u32 p,%3,0; @p ld.global.cg.v2.u32 {%0,%1},[%2];}" : "+r"(v.x), "+r"(v.y) : "l"(p), "r"((uint32_t)on) : "memory");
    return v;
}
__device__ __forceinline__ void add_acc(float* c, uint2 v) { c[0] += blo(v.x); c[1] += bhi(v.x); c[2] += blo(v.y); c[3] += bhi(v.y); }
__device__ __forceinline__ void st_acc(uint2* p, const float* c) { *p = make_uint2(pack2(c[0], c[1]), pack2(c[2], c[3])); }
__device__ __forceinline__ float sum8(const uint4* v, int k) {
#define VK(i) __uint_as_float(k == 0 ? v[i].x : k == 1 ? v[i].y : k == 2 ? v[i].z : v[i].w)
    return ((VK(0) + VK(1)) + (VK(2) + VK(3))) + ((VK(4) + VK(5)) + (VK(6) + VK(7)));
}
template <int XW>
__device__ __forceinline__ void stats_send(uint32_t l16, const float* x, uint4* gs, int q, int w) {
    float s0 = 0, s1 = 0, m0 = 0, m1 = 0;
#pragma unroll
    for (int i = 0; i < 8; i++) { s0 += x[2 * i]; s1 += x[2 * i + 1]; m0 = fmaf(x[2 * i], x[2 * i], m0); m1 = fmaf(x[2 * i + 1], x[2 * i + 1], m1); }
    sts128(l16 + C_ST + w * 512, __float_as_uint(s0), __float_as_uint(m0), __float_as_uint(s1), __float_as_uint(m1));
    if (w == XW) {
        bar_sync(2, 256);
        uint4 v[8];
#pragma unroll
        for (int i = 0; i < 8; i++) v[i] = lds128(l16 + C_ST + i * 512);
        st_rlx128(gs + q * 32, __float_as_uint(sum8(v, 0)), __float_as_uint(sum8(v, 1)) & 0x7fffffffu, __float_as_uint(sum8(v, 2)), __float_as_uint(sum8(v, 3)));
    } else bar_arrive(2, 256);
}
template <int XW>
__device__ __forceinline__ float4 stats_recv(uint32_t l16, const uint4* gs, int w) {
    if (w == XW) {
        uint4 v[8];
        int n = 0;
        while (true) {
            uint32_t bad = 0;
#pragma unroll
            for (int i = 0; i < 8; i++) v[i] = ld_rlx128(gs + i * 32);
#pragma unroll
            for (int i = 0; i < 8; i++) bad |= v[i].y;
            if (!__any_sync(0xffffffffu, bad >> 31)) break;
            if (++n > 2000000) __trap();
        }
        const float s0 = sum8(v, 0) * (1.f / 512.f), s1 = sum8(v, 2) * (1.f / 512.f);
        const float2 l0 = ln_finish(s0, fmaxf(fmaf(sum8(v, 1), 1.f / 512.f, -s0 * s0), 0.f)), l1 = ln_finish(s1, fmaxf(fmaf(sum8(v, 3), 1.f / 512.f, -s1 * s1), 0.f));
        sts128(l16 + C_ST + 4096, __float_as_uint(l0.x), __float_as_uint(rcp(l0.y)), __float_as_uint(l1.x), __float_as_uint(rcp(l1.y)));
    }
    bar_sync(3, 256);
    const uint4 r = lds128(l16 + C_ST + 4096);
    return make_float4(__uint_as_float(r.x), __uint_as_float(r.y), __uint_as_float(r.z), __uint_as_float(r.w));
}

__device__ __forceinline__ void conv_near(float (*acc)[4], uint32_t ta, uint32_t qa) {
    uint32_t a[9][8];
    uint4 x[9];
#pragma unroll
    for (int k = 0; k < 9; k++) {
        if (k < 8) {
            x[k] = ldsm4(qa + k * 1024);
#pragma unroll
            for (int j = 0; j < 8; j++) a[k][j] = lds32(ta + k * 800 + j * 32);
        }
        if (k) mma_q(acc[k - 1], a[k - 1], x[k - 1]);
        PIN(13);
    }
}
template <int K0>
__device__ __forceinline__ void conv_pair(float (*acc)[4], float (*pend)[4], uint32_t ta, uint32_t q0, uint32_t q1, uint32_t q2) {
    uint32_t a[9][8];
    uint4 x[9], y[5];
#pragma unroll
    for (int n = 0; n < 9; n++) {
        if (n < 8) {
            const int k = K0 + (n >> 1);
            if (!(n & 1)) y[n >> 1] = ldsm4(q1 + k * 1024);
            x[n] = ldsm4(((n & 1) ? q0 : q2) + k * 1024);
#pragma unroll
            for (int j = 0; j < 8; j++) a[n][j] = lds32(ta + 256 + (n & 1) * 256 + k * 800 + j * 32);
        }
        if (n == 0) {
#pragma unroll
            for (int i = 0; i < 16; i++) { acc[4 - K0 + (i >> 2)][i & 3] += pend[i >> 2][i & 3]; pend[i >> 2][i & 3] = 0; }
        } else {
            const int m = n - 1, i = m >> 1;
            mma_q(acc[K0 + i], a[m], (m & 1) ? x[m] : y[i]); mma_q(pend[i], a[m], (m & 1) ? y[i] : x[m]);
        }
        PIN(13);
    }
}

__device__ __forceinline__ void conv_tile(const Params& p, uint32_t sb, int q, int w) {
    const int lane = __shfl_sync(0xffffffffu, threadIdx.x & 31, threadIdx.x & 31), g = lane >> 2, c = lane & 3, tile = q * 8 + w;
    const uint32_t l16 = sb + lane * 16;
#pragma unroll
    for (int i = 0; i < 16; i++) sts128(l16 + C_UR + w * 8192 + i * 512, 0, 0, 0, 0);
    wait_slow_warp(g_gate, lds32(sb + S_GATE));
    if (lane < 8) bulk_g2s(sb + C_TB + (w * 8 + lane) * 800, g_P + (tile * 8 + lane) * PROW + 72, 800, sb + B_BAR + CB_TB * 8, POL_N);
    uint32_t A[8][8];
#pragma unroll
    for (int k = 0; k < 8; k++)
#pragma unroll
        for (int j = 0; j < 8; j++) A[k][j] = __ldcg(g_P + (tile * 8 + k) * PROW + 16 + 8 * j + g - 2 * c);
    if (lane == 0) { const uint4 d = __ldg((const uint4*)p.Dskip + tile); sts128(sb + C_ST + 4608 + w * 16, d.x, d.y, d.z, d.w); }
    float acc[8][4], pend[4][4];
#pragma unroll
    for (int k = 0; k < 8; k++) acc[k][0] = acc[k][1] = acc[k][2] = acc[k][3] = pend[k & 3][k >> 2] = pend[k & 3][2 + (k >> 2)] = 0;
    const uint32_t row = sb + C_UR + w * 8192, ta = sb + C_TB + w * 6400 + (8 + g - 2 * c) * 4, qo = (lane & 7) * 16 - (lane >> 3) * 32;
    bar_sync(4, 384);
    mbar_wait(sb + B_BAR + CB_TB * 8, 0);
#pragma unroll 1
    for (int b = -2; b < 32; b++) {
        const int lz = lane + (b & p.zero);
        const bool on = b >= 0;
        uint4 r0 = make_uint4(0, 0, 0, 0), r1 = r0;
        asm volatile("{.reg .pred p; setp.ge.s32 p,%9,0; @p ld.global.cg.v4.u32 {%0,%1,%2,%3},[%8]; @p ld.global.cg.v4.u32 {%4,%5,%6,%7},[%8+%10];}"
                     : "+r"(r0.x), "+r"(r0.y), "+r"(r0.z), "+r"(r0.w), "+r"(r1.x), "+r"(r1.y), "+r"(r1.z), "+r"(r1.w) : "l"(g_x + (tile * 2 * XP + b * 32 + lz)), "r"(b), "n"(XP * 16) : "memory");
        const uint32_t q1 = row + ((qo + (b - 1) * 128) & 1023);
        if ((NTOP >> w) & 1) conv_near(acc, ta, q1);
        PROF(threadIdx.x == 0 && on, 2048 + b * 8);
        const uint2* pps = pp_src(b, tile, lz);
        asm volatile("" : "+l"(pps));
        const uint32_t tag = lds32(sb + S_TAG);
        wait_flag_warp(cnt_ptr(C_PP + b * 8 + q), on ? 16 : 0);
        PROF(threadIdx.x == 0 && on, 2048 + b * 8 + 1);
        float x[16];
        {
            const uint32_t a[4] = {r0.x, r0.y, r1.x, r1.y}, bb[4] = {r0.z, r0.w, r1.z, r1.w};
            sum_partials<4, true>(x, pps, a, bb, (2 * (lz & 3) == lz >> 2) ? 0x00003f80u : (2 * (lz & 3) + 1 == lz >> 2) ? 0x3f800000u : 0u, tag, on);
        }
        stats_send<0>(l16, x, g_st + (b + 2) * 256 + lz, q, w);
        {
            PROF(threadIdx.x == 0 && on, 2048 + b * 8 + 2);
            if (on) mbar_wait(sb + B_BAR + (CB_CF + (w >> 1)) * 8, b & 1);
            const uint2* cb = g_carry + ((tile * 320 + b) * 32 + lz);
            uint2 cr[8];
#pragma unroll
            for (int k = 0; k < 8; k++) cr[k] = ld_acc(cb + k * 1280, b >= 4);
            if (NTOP != 255 && !((NTOP >> w) & 1) && b) conv_near(acc, ta, q1);
#pragma unroll
            for (int k = 0; k < 8; k++) add_acc(acc[k], cr[k]);
        }
        PIN(13);
        float4 ln = stats_recv<0>(l16, g_st + (b + 2) * 256 + lz, w);
        PROF(threadIdx.x == 0 && on, 2048 + b * 8 + 3);
        uint32_t u[8];
#pragma unroll
        for (int k = 0; k < 8; k++) {
            u[k] = pack2(rbf(x[2 * k] - ln.x) * ln.y, rbf(x[2 * k + 1] - ln.z) * ln.w);
            sts32(row + k * 1024 + (b & 7) * 128 + lane * 4, u[k]);
        }
        __syncwarp();
        const uint32_t qa = row + ((qo + b * 128) & 1023);
#pragma unroll
        for (int k = 0; k < 8; k++) mma_q(acc[k], A[k], ldsm4(qa + k * 1024));
        const uint4 dk = lds128(sb + C_ST + 4608 + w * 16);
#pragma unroll
        for (int k = 0; k < 8; k++) {
            const float t = __shfl_sync(0xffffffffu, acc[k][3], (lz & ~3) | ((lz - 1) & 3));
            const uint32_t y = movm(pack2(acc[k][0] + (c ? t : 0.f), acc[k][1] + acc[k][2]));
            acc[k][0] = c ? 0.f : t; acc[k][1] = acc[k][2] = acc[k][3] = 0;
            const uint32_t dw = k >> 1 == 0 ? dk.x : k >> 1 == 1 ? dk.y : k >> 1 == 2 ? dk.z : dk.w;
            const uint32_t s = hadd2(hadd2(y, hmul2(u[k], __byte_perm(dw, 0, (k & 1) ? 0x3232 : 0x1010))), __byte_perm(__float_as_uint(x[2 * k]), __float_as_uint(x[2 * k + 1]), 0x7632));
            x[2 * k] = blo(s); x[2 * k + 1] = bhi(s);
        }
        arrive_if(sb + B_BAR + (CB_UF + (w >> 1)) * 8, lz, b < -1 ? 32 : 0);
        stats_send<1>(l16, x, g_st + (36 + b) * 256 + lz, q, w);
        {
            PROF(threadIdx.x == 0 && on, 2048 + b * 8 + 4);
            uint4* dst = g_x + ((128 + tile * 2) * XP + b * 32 + lz);
#pragma unroll
            for (int e = 0; e < 2; e++) {
                const float* y = x + e * 8;
                if (on) dst[e * XP] = make_uint4(__byte_perm(__float_as_uint(y[0]), __float_as_uint(y[2]), 0x7632), __byte_perm(__float_as_uint(y[4]), __float_as_uint(y[6]), 0x7632),
                                           __byte_perm(__float_as_uint(y[1]), __float_as_uint(y[3]), 0x7632), __byte_perm(__float_as_uint(y[5]), __float_as_uint(y[7]), 0x7632));
            }
            uint32_t* du = g_u + (tile * 8 * (UROW / 2) + UPRE / 2 + b * 32 + lz);
#pragma unroll
            for (int k = 0; k < 8; k++) if (on) du[k * (UROW / 2)] = u[k];
        }
#pragma unroll 1
        for (int pass = 0; pass < 2; pass++) {
            if (pass == ((PLATE >> w) & 1)) {
                const uint32_t q0 = row + ((qo + (b - 2) * 128) & 1023);
                if (b & 1) conv_pair<4>(acc, pend, ta, q0, q1, qa); else conv_pair<0>(acc, pend, ta, q0, q1, qa);
            }
            if (pass) break;
            ln = stats_recv<1>(l16, g_st + (36 + b) * 256 + lz, w);
            PROF(threadIdx.x == 0 && on, 2048 + b * 8 + 5);
            uint32_t o[2][4];
#pragma unroll
            for (int e = 0; e < 2; e++) {
                const float mu = e ? ln.z : ln.x, rs = e ? ln.w : ln.y;
#pragma unroll
                for (int i = 0; i < 4; i++) o[e][i] = pack2(rbf(x[4 * i + e] - mu) * rs, rbf(x[4 * i + 2 + e] - mu) * rs);
            }
#pragma unroll
            for (int i = 0; i < 4; i++) {
                const uint32_t t = __shfl_xor_sync(0xffffffffu, (lz & 1) ? o[0][i] : o[1][i], 1);
                if (lz & 1) o[0][i] = t; else o[1][i] = t;
            }
            uint4* dst = g_xn + ((32 + b) * 4096 + q * 512 + (lz >> 2) * 64 + w * 8 + (lz & 2) * 2 + (lz & 1));
            if (on) { dst[0] = make_uint4(o[0][0], o[0][1], o[0][2], o[0][3]); dst[2] = make_uint4(o[1][0], o[1][1], o[1][2], o[1][3]); }
            if (w == 7) {
                bar_sync(5, 256);
                if (elect()) red_release(cnt_ptr(on ? C_XN + 32 + b : C_FAR + 2), 2);
                PROF(lane == 0 && on, 2048 + b * 8 + 6);
                __syncwarp();
            } else bar_arrive(5, 256);
        }
    }
}

template <int P0, bool TRI = false>
__device__ __forceinline__ void bg_half(float (*acc)[4], uint4* win, uint32_t ta, uint32_t qa, uint32_t mask, uint32_t row) {
#pragma unroll
    for (int i = 0; i < 4; i++) {
        win[P0 + i] = ldsm4(((qa + i * 128) & mask) + row);
        const uint4 a = lds128(ta + (3 - i) * 448), e = lds128(ta + (3 - i) * 448 + 224);
#pragma unroll
        for (int r = TRI ? 7 - P0 - i : 0; r < 8; r++) mma16(acc[r], a.x, a.y, a.z, a.w, win[(P0 + i + 1 + r) & 7].x, win[(P0 + i + 1 + r) & 7].y);
#pragma unroll
        for (int r = TRI ? 7 - P0 - i : 0; r < 8; r++) mma16(acc[r], e.x, e.y, e.z, e.w, win[(P0 + i + 1 + r) & 7].z, win[(P0 + i + 1 + r) & 7].w);
    }
}
__device__ __forceinline__ void bg_fetch(uint32_t sb, int q, int j, int n, int lane) {
    const int b0 = n >> 1, ch = q * 64 + j * 16 + (n & 1) * 8 + (b0 & 7), lo = max(b0 - 24, -4), nu = b0 > 4 ? (b0 - 4 - lo) * 128 : 0;
    const uint32_t bar = sb + B_BAR + (CB_LD + j * 2 + (n & 1)) * 8, buf = sb + C_BG + (j * 2 + (n & 1)) * CB_BIG;
    const int nt = min(max((b0 + 7) >> 2, 2), 5) * 1792;
    if (elect()) {
        mbar_expect(bar, nt + nu + 1792);
        bulk_g2s(buf, g_W + ch * 784, nt, bar, POL_N);
        bulk_g2s(buf + CB_M, g_W + (ch ^ 4) * 784, 1792, bar, POL_N);
        if (nu) bulk_g2s(buf + CB_U + (lo - b0 + 24) * 128, g_u + ch * (UROW / 2) + UPRE / 2 + lo * 32, nu, bar, POL_N);
    }
    __syncwarp();
}
__device__ __forceinline__ void conv_back(uint32_t sb, int q, int j) {
    const int lane = __shfl_sync(0xffffffffu, threadIdx.x & 31, threadIdx.x & 31), g = lane >> 2, c = lane & 3;
    wait_slow_warp(g_gate, lds32(sb + S_GATE));
    bg_fetch(sb, q, j, 0, lane);
    bar_sync(4, 384);
    const uint32_t to = (6 + g - 2 * c) * 16, qo = (lane & 7) * 16 - (lane >> 3) * 32;
#pragma unroll 1
    for (int n = 0; n < 64; n++) {
        const int b0 = n >> 1, i = n & 1, chl = j * 16 + i * 8 + (b0 & 7), hm = (b0 + 7) >> 2;
        const uint32_t buf = sb + C_BG + (j * 2 + i) * CB_BIG, ta = buf + to;
        float acc[8][4];
        uint4 win[8];
        if (n < 63) bg_fetch(sb, q, j, n + 1, lane);
        if (n == 34 || n == 42) wait_flag_warp(cnt_ptr(C_FAR + (n == 42)), 12);
        mbar_wait(sb + B_BAR + (CB_LD + j * 2 + i) * 8, b0 & 1);
#pragma unroll
        for (int r = 0; r < 8; r++) {
            acc[r][0] = acc[r][1] = acc[r][2] = acc[r][3] = 0;
            win[r] = make_uint4(0, 0, 0, 0);
            if (r) asm volatile("{.reg .pred p; setp.ge.s32 p,%5,24; @p ldmatrix.sync.aligned.m8n8.x4.shared.b16 {%0,%1,%2,%3},[%4];}"
                                : "+r"(win[r].x), "+r"(win[r].y), "+r"(win[r].z), "+r"(win[r].w) : "r"(buf + CB_U + qo + r * 128), "r"(b0 + r) : "memory");
        }
        const uint2* fr = g_far + (((q * 64 + chl) * 8 + b0 - 24) * 32 + lane);
        uint2* cr = g_carry + (((q * 64 + chl) * 40 + b0) * 32 + lane);
        uint2* cm = g_carry + (((q * 64 + (chl ^ 4)) * 40 + b0) * 32 + lane);
        const uint32_t fm = 0xff000000u >> b0;
        uint2 pf[8], pm[4];
#pragma unroll
        for (int r = 0; r < 8; r++) pf[r] = ld_acc(fr + r * 32, (fm >> r) & 1);
#pragma unroll
        for (int r = 0; r < 4; r++) pm[r] = ld_acc(cm + r * 32, b0 > 4);
#pragma unroll 1
        for (int h = hm > 3 ? 5 : 3; h >= 3; h -= 2) {
            if (h <= hm) bg_half<0>(acc, win, ta + (h - 1) * 1792, qo + (28 - 4 * h) * 128, ~0u, buf + CB_U);
            if (h == 3 && i == 0) mbar_wait(sb + B_BAR + (CB_UF + j) * 8, b0 & 1);
            bg_half<4>(acc, win, ta + (h - 2) * 1792, qo + (h == 3 ? b0 - 4 : 12) * 128, h == 3 ? 1023u : ~0u, h == 3 ? sb + C_UR + chl * 1024 : buf + CB_U);
        }
        uint4 wm[8];
#pragma unroll
        for (int r = 1; r < 8; r++) wm[r] = ldsm4(sb + C_UR + (chl ^ 4) * 1024 + ((qo + (b0 + r) * 128) & 1023));
#pragma unroll
        for (int r = 0; r < 8; r++) add_acc(acc[r], pf[r]);
#pragma unroll
        for (int r = 4; r < 8; r++) { st_acc(cr + r * 32, acc[r]); acc[r][0] = blo(pm[r - 4].x); acc[r][1] = bhi(pm[r - 4].x); acc[r][2] = blo(pm[r - 4].y); acc[r][3] = bhi(pm[r - 4].y); }
#pragma unroll
        for (int t = 7; t >= 0; t--) {
            const uint4 a = lds128(ta + t * 224), e = lds128(ta + CB_M + t * 224);
#pragma unroll
            for (int r = 0; r < 4; r++) { const uint4& x = win[4 + r - (t >> 1)]; mma16(acc[r], a.x, a.y, a.z, a.w, (t & 1) ? x.z : x.x, (t & 1) ? x.w : x.y); }
#pragma unroll
            for (int r = 0; r < 4; r++) { const uint4& x = wm[4 + r - (t >> 1)]; mma16(acc[4 + r], e.x, e.y, e.z, e.w, (t & 1) ? x.z : x.x, (t & 1) ? x.w : x.y); }
        }
#pragma unroll
        for (int r = 0; r < 4; r++) { st_acc(cr + r * 32, acc[r]); st_acc(cm + r * 32, acc[4 + r]); }
        __syncwarp();
        if (lane == 0 && i) mbar_arrive(sb + B_BAR + (CB_CF + j) * 8);
        PROF(j == 0 && lane == 0 && i, 2048 + b0 * 8 + 7);
    }
}
__device__ __forceinline__ void conv_far(uint32_t sb, int w) {
    const int lane = __shfl_sync(0xffffffffu, threadIdx.x & 31, threadIdx.x & 31), g = lane >> 2, c = lane & 3;
    wait_slow_warp(g_gate, lds32(sb + S_GATE));
    wait_slow_warp(cnt_ptr(C_XN + 39), 16);
    const uint32_t to = (6 + g - 2 * c) * 16, qo = (lane & 7) * 16 - (lane >> 3) * 32;
#pragma unroll 1
    for (int n = -1; n * 12 + w < 512; n++) {
        const int t = n * 12 + w, ch = (t & 63) * 8 + (((t >> 6) + 1) & 7), cn = ((t + 12) & 63) * 8 + ((((t + 12) >> 6) + 1) & 7);
        const uint32_t bar = sb + B_BAR + (w * 2 + (n & 1)) * 8, buf = sb + (w * 2 + (n & 1)) * 5120;
        if (t + 12 < 512 && elect()) {
            const uint32_t nb = sb + (w * 2 + (~n & 1)) * 5120;
            mbar_expect(bar ^ 8, 3584 + 1152);
            bulk_g2s(nb, g_W + cn * 784 + 560, 3584, bar ^ 8, POL_N);
            bulk_g2s(nb + 3584, g_u + cn * (UROW / 2) + UPRE / 2 - 32, 1152, bar ^ 8, POL_N);
        }
        __syncwarp();
        if (n < 0) continue;
        float acc[8][4];
        uint4 win[8];
#pragma unroll
        for (int r = 0; r < 8; r++) { acc[r][0] = acc[r][1] = acc[r][2] = acc[r][3] = 0; win[r] = make_uint4(0, 0, 0, 0); }
        mbar_wait(bar, (n >> 1) & 1);
        bg_half<0, true>(acc, win, buf + to + 1792, qo + 128, ~0u, buf + 3584);
        bg_half<4, true>(acc, win, buf + to, qo + 640, ~0u, buf + 3584);
#pragma unroll
        for (int r = 0; r < 8; r++) st_acc(g_far + (ch * 256 + lane) + r * 32, acc[r]);
        __syncwarp();
        if (((t + 12) ^ t) >= 256 && elect()) red_release(cnt_ptr(C_FAR + (t >> 8)), 1);
        __syncwarp();
    }
    PROF(threadIdx.x == 0, 2048);
}

constexpr int P_X = 131072  , P_K6 = P_X + 32768  , P_P = P_K6 + 10496  , P_U = P_P + 33280  ,
              P_END = P_U + 17408, P_PRM = P_P + 8192  , P_Y = P_P  ;
static_assert(P_END <= B_BAR && P_END <= R_SEL, "prologue scratch");
#define KGUN 2
constexpr int KGU = KGUN;
__device__ __forceinline__ void csq(float& r, float& i) { const float t = r * i; r = fmaf(r, r, -(i * i)); i = t + t; }
__device__ __forceinline__ void cpow(float ar, float ph, float p, float& r, float& i) {
    const float e = ex2(ar * p);
    const float u = ph * p, n = fabsf(u) < 4194304.f ? (u + 12582912.f) - 12582912.f : u;
    const float t = (u - n) * 6.283185307179586f;
    r = e * __cosf(t); i = e * __sinf(t);
}
__device__ __forceinline__ void mma_tf32(float* c, float a0, float a1, float a2, float a3, float b0, float b1) {
    asm volatile("mma.sync.aligned.m16n8k8.row.col.f32.tf32.tf32.f32 {%0,%1,%2,%3},{%4,%5,%6,%7},{%8,%9},{%0,%1,%2,%3};"
                 : "+f"(c[0]), "+f"(c[1]), "+f"(c[2]), "+f"(c[3])
                 : "r"(__float_as_uint(a0)), "r"(__float_as_uint(a1)), "r"(__float_as_uint(a2)), "r"(__float_as_uint(a3)), "r"(__float_as_uint(b0)), "r"(__float_as_uint(b1)));
}

__device__ __forceinline__ void early_fetch(const Params& p, uint32_t sb) {
    const int v = blockIdx.x;
    if (elect()) {
        if (v >= V_QKV) { if (v < V_QKV + NQ && (p.roles & 8)) qkv_fetch(p, sb, v - V_QKV, 0, Q_PRE); }
        else if (v >= V_OP) { if (p.roles & 4) op_fetch(p, sb, v - V_OP, 0); }
        else if (REARLY && v >= V_REC && (p.roles & 2)) { rec_fetch(p, sb, (v - V_REC) >> 1, v & 1, 0, R_STQ); rec_fetch(p, sb, (v - V_REC) >> 1, v & 1, 2, R_STV); }
    }
    __syncwarp();
}
struct ProRegs { uint32_t v[2][4], ldt[2]; };
__device__ __forceinline__ void prologue_load(const ProArgs& a, int b, ProRegs& pr) {
    const int w = threadIdx.x >> 5;
#pragma unroll
    for (int i = 0; i < 2; i++) {
        const int gi = b * 512 + (w & 3) * 128 + ((w >> 2) & 1) * 64 + i * 32 + (threadIdx.x & 31);
        pr.ldt[i] = __ldg((const uint16_t*)a.ldt + b * 4 + (w & 3));
        pr.v[i][0] = __ldg((const uint16_t*)a.lAr + gi); pr.v[i][1] = __ldg((const uint16_t*)a.Ai + gi);
        pr.v[i][2] = __ldg((const uint16_t*)a.Cr + gi); pr.v[i][3] = __ldg((const uint16_t*)a.Ci + gi);
    }
}
__device__ __forceinline__ void prologue(const Params& p, uint32_t sb, int b, int w, const ProRegs& pr) {
    const ProArgs& a = p.pa;
    const int tid = threadIdx.x, lane = tid & 31, g = lane >> 2, c = lane & 3;
    const int d0 = b * 4;
    if (w >= 8) {
        const int t2 = tid - 256;
        if (w < 10) {
            const int row = b * 16 + (w - 8) * 8 + g;
            uint4 v[16];
            const float2 r = row_stats512(v, (const uint4*)(a.x + (size_t)row * 512) + c, 8, 4);
            const float2 l = ln_finish(r.x * (1.f / 512.f), r.y * (1.f / 512.f));
            if (c == (g >> 1)) asm volatile("st.relaxed.gpu.global.u32 [%0],%1;" ::"l"(g_ln0 + row), "r"(pack2(l.x, l.y)) : "memory");
        }
        if (b + 4 >= V_REC && b + 4 < V_OP) rec_slots(b + 4 - V_REC, (w & 3) ^ 2);
        PROF(t2 == 0, 3516);
        const int gi = b * 128 + t2;
        g_st[gi] = make_uint4(~0u, ~0u, ~0u, ~0u);
        if (gi < 1024) g_st[16384 + gi] = make_uint4(~0u, ~0u, ~0u, ~0u);
        if (gi < 900 * 8) g_cnt[gi] = 0;
        bar_sync(6, 384);
        if (lane < 4 && ((PFM >> (w - 8)) & 1)) asm volatile("cp.async.bulk.prefetch.L2.global [%0],%1;" ::"l"(a.W[w - 8] + (b * 4 + lane) * 4096), "r"(8192) : "memory");
        bar_sync(9, 384);
#pragma unroll 1
        for (int pass = 0; pass < 2; pass++) {
        if (w == 10 && pass == (b + 4 < EFS)) early_fetch(p, sb);
        if (pass) break;
#pragma unroll 2
        for (int i = t2; i < 4 * 784; i += 128) {
            const int ch = i / 784, k = i - ch * 784;
            const uint32_t o = sb + P_P + (ch * 2080 + 266 + (k / 14) * 18 + k) * 4;
            g_W[d0 * 784 + i] = make_uint4(lds32(o), lds32(o + 32), lds32(o + 64), lds32(o + 96));
        }
        bar_arrive(10, 384);
        }
        PROF(t2 == 0, 3517);
        return;
    }
#pragma unroll
    for (int i = 0; i < 2; i++) {
        const float dt = rbf(expf(blo(pr.ldt[i])));
        const float ar = -rbf(expf(blo(pr.v[i][0]))) * dt, ai = blo(pr.v[i][1]) * dt;
        sts128(sb + P_PRM + (w * 64 + i * 32 + lane) * 16, __float_as_uint(ar * 1.4426950408889634f), __float_as_uint(ai * 0.15915494309189535f),
               __float_as_uint(2.f * (blo(pr.v[i][2]) * dt)), __float_as_uint(2.f * (blo(pr.v[i][3]) * dt)));
    }
    if (tid < 64) sts128(sb + P_U + (tid >> 3) * 2176 + (tid & 7) * 16, 0, 0, 0, 0);
    bar_arrive(6, 384);
    __syncwarp();
    PROF(tid == 0, 3510);
    const int ch = w & 3, hf = w >> 2;
    {
        float k0[4] = {0, 0, 0, 0}, k1[4] = {0, 0, 0, 0}, k2[4] = {0, 0, 0, 0}, k3[4] = {0, 0, 0, 0}, k4[4] = {0, 0, 0, 0}, kl = 0;
#pragma unroll KGU
        for (int j = 0; j < 16; j++) {
            const uint4 q = lds128(sb + P_PRM + (w * 64 + j * 4 + c) * 16);
            const float cr = __uint_as_float(q.z), ci = __uint_as_float(q.w);
            float wr[4], wi[4], vr[4], vi[4];
            cpow(__uint_as_float(q.x), __uint_as_float(q.y), (float)g, wr[0], wi[0]);
            cpow(__uint_as_float(q.x), __uint_as_float(q.y), (float)(g + 8), vr[0], vi[0]);
#pragma unroll
            for (int i = 1; i < 4; i++) { wr[i] = wr[i - 1]; wi[i] = wi[i - 1]; csq(wr[i], wi[i]); vr[i] = vr[i - 1]; vi[i] = vi[i - 1]; csq(vr[i], vi[i]); }
            float hr = wr[3], hi = wi[3];
            csq(hr, hi);
            mma_tf32(k0, wr[0], vr[0], wi[0], vi[0], cr * hr - ci * hi, -(cr * hi + ci * hr));
            hr = vr[3]; hi = vi[3]; csq(hr, hi);
            mma_tf32(k1, wr[0], vr[0], wi[0], vi[0], cr * hr - ci * hi, -(cr * hi + ci * hr));
            csq(hr, hi);
            mma_tf32(k2, wr[1], vr[1], wi[1], vi[1], cr * hr - ci * hi, -(cr * hi + ci * hr));
            csq(hr, hi);
            mma_tf32(k3, wr[2], vr[2], wi[2], vi[2], cr * hr - ci * hi, -(cr * hi + ci * hr));
            csq(hr, hi);
            mma_tf32(k4, wr[3], vr[3], wi[3], vi[3], cr * hr - ci * hi, -(cr * hi + ci * hr));
            csq(hr, hi);
            kl += cr * hr - ci * hi;
        }
        kl += __shfl_xor_sync(0xffffffffu, kl, 1); kl += __shfl_xor_sync(0xffffffffu, kl, 2);
        const uint32_t o = sb + P_K6 + (ch * 656 + c * 32 + g) * 4, ol = sb + P_K6 + (ch * 656 + 640) * 4;
#define KST(k, base) sts32(o + (base) * 4, __float_as_uint(k[0])); sts32(o + (base) * 4 + 64, __float_as_uint(k[1])); \
                     sts32(o + (base) * 4 + 32, __float_as_uint(k[2])); sts32(o + (base) * 4 + 96, __float_as_uint(k[3]))
#define KAD(k, base) k[0] += __uint_as_float(lds32(o + (base) * 4)); k[1] += __uint_as_float(lds32(o + (base) * 4 + 64)); \
                     k[2] += __uint_as_float(lds32(o + (base) * 4 + 32)); k[3] += __uint_as_float(lds32(o + (base) * 4 + 96))
        if (hf == 0) {
            bar_sync(2 + ch, 64);
            KAD(k0, 0); KAD(k1, 128); KAD(k2, 256); KAD(k3, 384); KAD(k4, 512);
            kl += __uint_as_float(lds32(ol));
            __syncwarp();
        }
        KST(k0, 0); KST(k1, 128); KST(k2, 256); KST(k3, 384); KST(k4, 512);
        if (lane == 0) sts32(ol, __float_as_uint(kl));
        if (hf == 1) { __syncwarp(); bar_arrive(2 + ch, 64); }
    }
    PROF(tid == 0, 3511);
    {
        uint4 l0, l1;
        int n = 0;
        while (true) {
            l0 = ld_rlx128((const uint4*)g_ln0 + tid * 2); l1 = ld_rlx128((const uint4*)g_ln0 + tid * 2 + 1);
            if (__all_sync(0xffffffffu, l0.x && l0.y && l0.z && l0.w && l1.x && l1.y && l1.z && l1.w)) break;
            if (++n > 2000000) __trap();
        }
        sts128(sb + P_P + tid * 32, l0.x, l0.y, l0.z, l0.w); sts128(sb + P_P + tid * 32 + 16, l1.x, l1.y, l1.z, l1.w);
        bar_sync(8, 384);
        mbar_wait(sb + S_XBAR, 0);
        __syncwarp();
#pragma unroll 2
        for (int i = 0; i < 8; i++) {
            const int t = w * 256 + i * 32 + lane;
            const uint32_t ln = lds32(sb + P_P + t * 4);
            const uint2 x = lds64(sb + P_X + t * 16 + (b & 1) * 8);
            const float m = blo(ln), rs = rcp(bhi(ln));
            const uint32_t u0 = pack2(rbf(blo(x.x) - m) * rs, rbf(bhi(x.x) - m) * rs), u1 = pack2(rbf(blo(x.y) - m) * rs, rbf(bhi(x.y) - m) * rs);
            sts128(sb + P_X + t * 16, x.x, x.y, u0, u1);
            const uint32_t o = sb + P_U + ((t >> 3) & 1) * 2176 + ((t >> 4) + 8) * 16 + (t & 7) * 2;
            asm volatile("st.shared.u16 [%0],%1;" ::"r"(o), "h"((uint16_t)u0) : "memory");
            asm volatile("st.shared.u16 [%0],%1;" ::"r"(o + 4352), "h"((uint16_t)(u0 >> 16)) : "memory");
            asm volatile("st.shared.u16 [%0],%1;" ::"r"(o + 8704), "h"((uint16_t)u1) : "memory");
            asm volatile("st.shared.u16 [%0],%1;" ::"r"(o + 13056), "h"((uint16_t)(u1 >> 16)) : "memory");
        }
    }
    bar_sync(1, 256);
    PROF(tid == 0, 3512);
    if (tid < 64) sts32(sb + P_P + ((tid >> 4) * 2080 + (tid & 15)) * 4, 0);
#pragma unroll 1
    for (int x = tid; x < 2048; x += 512) {
        uint32_t pw[2][4];
#pragma unroll
        for (int h = 0; h < 2; h++) {
            const int y = x + h * 256;
            const int i0 = y <= 256 ? y : 256 + (int)((pack2((float)y, 0.f) & 0xffff) - 0x4380);
            const int i1 = y <= 256 ? max(y - 1, 0) : 256 + (int)((pack2((float)(y - 1), 0.f) & 0xffff) - 0x4380);
#pragma unroll
            for (int k = 0; k < 4; k++) {
                const float lo = __uint_as_float(lds32(sb + P_K6 + k * 2624 + i0 * 4)), hi = __uint_as_float(lds32(sb + P_K6 + k * 2624 + i1 * 4));
                pw[h][k] = pack2(lo, y ? hi : 0.f);
            }
        }
#pragma unroll
        for (int h = 0; h < 2; h++)
#pragma unroll
            for (int k = 0; k < 4; k++) sts32(sb + P_P + (k * 2080 + x + h * 256 + 16) * 4, pw[h][k]);
    }
    fence_async_smem();
    bar_arrive(9, 384);
    bar_sync(1, 256);
    if (tid < 4) {
        asm volatile("cp.async.bulk.global.shared::cta.bulk_group [%0],[%1],%2;" ::"l"(g_P + (d0 + tid) * PROW), "r"(sb + P_P + tid * 8320), "r"(PROW * 4) : "memory");
        asm volatile("cp.async.bulk.commit_group;" ::: "memory");
    }
    __syncwarp();
    PROF(tid == 0, 3513);
    {
        float acc[16][4];
#pragma unroll
        for (int j = 0; j < 16; j++) acc[j][0] = acc[j][1] = acc[j][2] = acc[j][3] = 0;
#pragma unroll 1
        for (int e = hf * 4; e < hf * 4 + 4; e++) {
            uint32_t B[16][2];
            const uint32_t ua = sb + P_U + ch * 4352 + ((lane >> 3) & 1) * 2176 + (8 + (lane >> 4) * 8 + (lane & 7) - e) * 16;
#pragma unroll
            for (int j = 0; j < 8; j++) { const uint4 v = ldsm4(ua + j * 256); B[2 * j][0] = v.x; B[2 * j][1] = v.y; B[2 * j + 1][0] = v.z; B[2 * j + 1][1] = v.w; }
            const uint32_t pa = sb + P_P + (ch * 2080 + 16 + e * 16 + g - 2 * c) * 4;
#pragma unroll
            for (int d = 0; d < 16; d++) {
                const uint32_t a0 = lds32(pa + d * 512), a1 = lds32(pa + d * 512 + 32), a2 = lds32(pa + d * 512 - 32);
#pragma unroll
                for (int j = d; j < 16; j++) mma16(acc[j], a0, a1, a2, a0, B[j - d][0], B[j - d][1]);
            }
        }
        PROF(tid == 0, 3514);
        if (tid < 4) asm volatile("cp.async.bulk.wait_group 0;" ::: "memory");
        __syncwarp();
        bar_sync(10, 384);
#pragma unroll
        for (int j = 0; j < 8; j++) {
#pragma unroll
            for (int i = 0; i < 4; i++) { const float t = hf ? acc[j][i] : acc[j + 8][i]; acc[j][i] = hf ? acc[j + 8][i] : acc[j][i]; acc[j + 8][i] = t; }
            sts128(sb + P_Y + w * 4096 + j * 512 + lane * 16, __float_as_uint(acc[j + 8][0]), __float_as_uint(acc[j + 8][1]), __float_as_uint(acc[j + 8][2]), __float_as_uint(acc[j + 8][3]));
        }
        bar_sync(2 + ch, 64);
        uint32_t yp[16];
#pragma unroll
        for (int j = 0; j < 8; j++) {
            const uint4 t = lds128(sb + P_Y + (w ^ 4) * 4096 + j * 512 + lane * 16);
            yp[2 * j] = pack2(acc[j][0] + __uint_as_float(t.x), acc[j][1] + __uint_as_float(t.y)); yp[2 * j + 1] = pack2(acc[j][2] + __uint_as_float(t.z), acc[j][3] + __uint_as_float(t.w));
        }
#pragma unroll
        for (int j = 0; j < 4; j++)
            asm volatile("stmatrix.sync.aligned.m8n8.x4.trans.shared.b16 [%0],{%1,%2,%3,%4};" ::"r"(sb + P_Y + 32768 + ch * 4096 + hf * 2048 + j * 512 + (lane >> 4) * 256 + (lane & 7) * 32 + (lane & 8) * 2),
                         "r"(yp[4 * j]), "r"(yp[4 * j + 1]), "r"(yp[4 * j + 2]), "r"(yp[4 * j + 3]) : "memory");
    }
    const uint2 dk = __ldg((const uint2*)(a.Dk + d0));
    bar_sync(1, 256);
#pragma unroll 2
    for (int i = 0; i < 4; i++) {
        const int t = i * 256 + tid;
        const uint4 x0 = lds128(sb + P_X + t * 32), x1 = lds128(sb + P_X + t * 32 + 16);
        uint32_t y[4];
#pragma unroll
        for (int k = 0; k < 4; k++) y[k] = lds32(sb + P_Y + 32768 + k * 4096 + t * 4);
        g_x[b * XP + t] = make_uint4(hadd2(x0.x, hadd2(__byte_perm(y[0], y[1], 0x5410), hmul2(x0.z, dk.x))), hadd2(x0.y, hadd2(__byte_perm(y[2], y[3], 0x5410), hmul2(x0.w, dk.y))),
                                     hadd2(x1.x, hadd2(__byte_perm(y[0], y[1], 0x7632), hmul2(x1.z, dk.x))), hadd2(x1.y, hadd2(__byte_perm(y[2], y[3], 0x7632), hmul2(x1.w, dk.y))));
    }
    PROF(tid == 0, 3515);
}

__global__ void __cluster_dims__(2, 1, 1) __launch_bounds__(384, 1) main_kernel(const __grid_constant__ Params p) {
    extern __shared__ __align__(1024) uint8_t smem[];
    const uint32_t sb = smem_u32(smem);
    uint32_t rank; asm("mov.u32 %0,%%cluster_ctarank;" : "=r"(rank));
    const int wi = __shfl_sync(0xffffffffu, threadIdx.x >> 5, 0);
    const int v = blockIdx.x, cl = v >> 1, wg = wi >> 2;
    PROF(threadIdx.x == 0, 3500);
    ProRegs pr;
    prologue_load(p.pa, max((int)blockIdx.x - 4, 0), pr);
    if (wi == 11 && p.dopro && cl >= 2 && elect()) {
        mbar_init(sb + S_XBAR, 1);
        asm volatile("fence.mbarrier_init.release.cluster;" ::: "memory");
        mbar_expect(sb + S_XBAR, 32768);
        for (int j = 0; j < 8; j++) tma2d(sb + P_X + j * 4096, &p.tm[3], ((blockIdx.x - 4) >> 1) * 8, j * 256, sb + S_XBAR);
    }
    if (threadIdx.x == 320) {
        unsigned n;
        asm volatile("ld.relaxed.gpu.global.u32 %0,[%1];" : "=r"(n) : "l"(g_gate) : "memory");
        n = n / (4 * NCL) + p.dopro;
        sts64(sb + S_GATE, n * (4 * NCL), n & 1);
    }
    __syncwarp();
    if (wi == 10) {
        if (v < V_REC || v == 131) conv_init(sb, v == 131); else if (v < V_OP) rec_init(sb); else gemm_init(sb, v < V_QKV);
        __syncwarp();
    }
    if (wg == 2) bar_arrive(8, 384);
    asm volatile("barrier.cluster.arrive.relaxed.aligned;" ::: "memory");
    if (p.dopro && cl >= 2) prologue(p, sb, blockIdx.x - 4, wi, pr); else if (wg < 2) bar_sync(8, 384); else if (wi == 10) early_fetch(p, sb);
    asm volatile("barrier.cluster.wait.aligned;" ::: "memory");
    const int role = (v < V_REC ? 1 : v < V_OP ? 2 : v < V_QKV ? 20 : v < V_QKV + NQ ? 24 : 1) & p.roles;
    fence_async_smem();
    bar_sync(wg == 2 ? 7 : 1, wg == 2 ? 128 : 256);
    if (p.dopro && (threadIdx.x == 32 || threadIdx.x == 352)) red_release(g_gate, 1);
    PROF(threadIdx.x == 32, 3509);
    if (wi == 0 && (role & 8) && elect()) qkv_stage(p, sb + 131072, sb + G_BAR + GB_RS * 8, v - V_QKV, 0, 6);
    PROF(threadIdx.x == 0, 3506);
    __syncwarp();
    if (p.dopro && (v == 131 || (v >= V_REC && v < V_QKV && (v < V_OP ? wi == 8 : wi < 8)))) {
        bool on = v >= V_OP;
#pragma unroll 1
        for (int r = v == 131 ? 448 + wi : on ? 64 + (v - V_OP) * 8 + wi : v - V_REC; r < (v == 131 ? 512 : 448);) {
            if (v >= V_OP) wait_slow_warp(g_gate, lds32(sb + S_GATE)); else if (on) wait_flag_warp(g_gate, lds32(sb + S_GATE));
            PROF(threadIdx.x == 256 && on, 3507);
            x1_norm(on ? (const uint2*)g_x : (const uint2*)p.pa.x, r, on);
            __syncwarp();
            if (on && elect()) red_release(cnt_ptr(C_XN + (r >> 4)), 1);
            __syncwarp();
            PROF(threadIdx.x == 256, on ? 3508 : 3499);
            if (on) r += v < V_OP ? 512 : v == 131 ? 12 : 128;
            on = true;
        }
    }
    if (role == 2) {
        const int head = (v - V_REC) >> 1;
        if (wi == RFW && elect()) {
            if (!REARLY) { rec_fetch(p, sb, head, rank, 0, R_STQ); }
            rec_fetch(p, sb, head, rank, 1, R_STK);
            if (!REARLY) { rec_fetch(p, sb, head, rank, 2, R_STV); }
        }
        __syncwarp();
        if (wg == 2) {
            reg_dec<RH>();
            const int w = wi & 3;
            wait_slow_warp(g_gate, lds32(sb + S_GATE));
            if (w < 2) { const uint32_t x = __ldcg(g_sel + (threadIdx.x & 63)); sts32(sb + R_SEL + (threadIdx.x & 63) * 4, (x * 0x01010101u) >> 24); }
            __syncthreads();
            cluster_sync();
            if ((p.chains >> (w & 1)) & 1) { if (w < 2) rec_comm(p, sb, w, head, rank); else rec_attn(p, sb, w & 1, head, rank); }
        } else {
            reg_inc<RW0>();
            rec_weights(p, sb, head, rank, wi);
        }
    } else if (role == 1) {
        if (v == 131) conv_far(sb, wi); else if (wg == 2) { reg_dec<RCB>(); conv_back(sb, v, wi & 3); } else { reg_inc<RCU>(); conv_tile(p, sb, v, wi); }
    } else if (role && v < V_QKV) {
        if (wg == 2) {
            reg_dec<40>();
            if (wi == 8) { if (role & 4) gemm_producer<true>(p, sb, v - V_OP); }
            else if (v < V_OP + 14 && (role & 16)) fin_warp(p, sb, 2 * NQ + (v - V_OP) * 3 + wi - 9);
        } else { reg_inc<232>(); if (role & 4) gemm_consumer<true>(p, sb, v - V_OP, wi); }
    } else if (role) {
        if (wg == 2) {
            reg_dec<40>();
            if (wi < 10) {
                if (role & 8) { if (wi == 8) gemm_producer<false>(p, sb, v - V_QKV); else qkv_release(p, sb); }
            } else if (role & 16) fin_warp(p, sb, (v - V_QKV) * 2 + wi - 10);
        } else { reg_inc<232>(); if (role & 8) gemm_consumer<false>(p, sb, v - V_QKV, wi); }
    }
    __syncwarp();
    cluster_sync();
}

typedef CUresult (*EncFn)(CUtensorMap*, CUtensorMapDataType, cuuint32_t, void*, const cuuint64_t*, const cuuint64_t*, const cuuint32_t*, const cuuint32_t*,
                          CUtensorMapInterleave, CUtensorMapSwizzle, CUtensorMapL2promotion, CUtensorMapFloatOOBfill);
constexpr int SMEM_BYTES = 232448;
#define LAG 8
#define QLEAD 6
#define OLEAD (LAG / 2 + 2)
void plan(Params& P) {
    P.roles = 31; P.chains = 3; P.lag = LAG; P.dopro = 1;
    for (int r = 0; r < 2; r++) {
        const int lead = r ? OLEAD : QLEAD;
        int n = 0;
        for (int i = 0; i < 32 + lead; i++) {
            if (i >= lead) P.list[r][n++] = 32 + i - lead;
            if (i < 32) P.list[r][n++] = i;
        }
        P.nl[r] = n;
    }
}

#define TK() do {} while (0)
}

extern "C" void kernel_launch(void* const* d_in, const int* in_sizes, int n_in, void* d_out, int out_size) {
    typedef const __nv_bfloat16* BP;
    static EncFn enc = nullptr;
    if (!enc) {
        void* fn = nullptr; cudaDriverEntryPointQueryResult qr;
        cudaGetDriverEntryPoint("cuTensorMapEncodeTiled", &fn, cudaEnableDefault, &qr);
        enc = (EncFn)fn;
        cudaFuncSetAttribute(main_kernel, cudaFuncAttributeMaxDynamicSharedMemorySize, SMEM_BYTES);
    }
    static Params P;
    for (int i = 0; i < 4; i++) {
        const cuuint64_t cols = i < 3 ? 4096 : 512, rows = i < 3 ? 512 : 4096;
        cuuint64_t d2[2] = {cols, rows}, str[1] = {cols * 2};
        cuuint32_t box[2] = {64, 64}, bn[2] = {16, 256}, es[2] = {1, 1};
        enc(&P.tm[i < 3 ? i : 4], CU_TENSOR_MAP_DATA_TYPE_BFLOAT16, 2, d_in[9 + i], d2, str, box, es, CU_TENSOR_MAP_INTERLEAVE_NONE, CU_TENSOR_MAP_SWIZZLE_128B,
            CU_TENSOR_MAP_L2_PROMOTION_L2_128B, CU_TENSOR_MAP_FLOAT_OOB_FILL_NONE);
        if (i < 2) enc(&P.tn[i], CU_TENSOR_MAP_DATA_TYPE_BFLOAT16, 2, d_in[9 + i], d2, str, bn, es, CU_TENSOR_MAP_INTERLEAVE_NONE, CU_TENSOR_MAP_SWIZZLE_32B,
                       CU_TENSOR_MAP_L2_PROMOTION_L2_128B, CU_TENSOR_MAP_FLOAT_OOB_FILL_NONE);
    }
    {
        cuuint64_t dims[2] = {512, 2048}, str[1] = {1024};
        cuuint32_t box[2] = {8, 256}, es[2] = {1, 1};
        enc(&P.tm[3], CU_TENSOR_MAP_DATA_TYPE_BFLOAT16, 2, d_in[0], dims, str, box, es, CU_TENSOR_MAP_INTERLEAVE_NONE, CU_TENSOR_MAP_SWIZZLE_NONE,
            CU_TENSOR_MAP_L2_PROMOTION_NONE, CU_TENSOR_MAP_FLOAT_OOB_FILL_NONE);
    }
    P.mem0 = (BP)d_in[8]; P.Wo = (BP)d_in[12]; P.Dskip = (BP)d_in[6]; P.out = (__nv_bfloat16*)d_out;
    cudaStream_t s = cudaStreamPerThread;
    P.pa = {(BP)d_in[0], (BP)d_in[1], (BP)d_in[2], (BP)d_in[3], (BP)d_in[4], (BP)d_in[5], (BP)d_in[6], {(BP)d_in[9], (BP)d_in[10], (BP)d_in[11], (BP)d_in[12]}};
    plan(P);
    TK(); main_kernel<<<2 * NCL, 384, SMEM_BYTES, s>>>(P); TK();
}
```

```cpp
#include <cuda_runtime.h>
#include <cuda_bf16.h>
#include <cuda.h>
#include <stdint.h>
#include <string.h>
#include <math.h>

namespace {

constexpr int NCL = 66;
constexpr int NQ = 43;
constexpr int V_REC = 8, V_OP = 72, V_QKV = 88;
static_assert(2 * NQ + 3 * 14 == 128, "warps of the final residual");

#define XP 1024
__device__ uint4 g_x[2 * 128 * XP];
__device__ uint4 g_xn[64 * 4096];
__device__ uint4 g_st[68 * 256];
__device__ uint4 g_qkv[128 * 32 * 1536];
__device__ uint4 g_o[64 * 64 * 512];
__device__ uint4 g_pp[64 * 4 * 4096];
__device__ uint4 g_xch[133 * 512];
__device__ unsigned g_sel[64];
__device__ unsigned g_gate[32];
__device__ __align__(16) uint32_t g_P[512 * 272];
__device__ uint4 g_W[512 * 784];
__device__ __align__(16) uint32_t g_u[512 * 1152];
__device__ uint2 g_carry[512 * 40 * 32];
__device__ uint2 g_far[512 * 8 * 32];
__device__ unsigned g_cnt[900 * 8];
__device__ uint32_t g_ln0[2048];

enum { C_XN = 0  , C_QKV = 64  , C_O = 128  , C_PP = 384  , C_FAR = 896 };
__device__ __forceinline__ unsigned* cnt_ptr(int i) { return g_cnt + i * 8; }

struct ProArgs { const __nv_bfloat16 *x, *lAr, *Ai, *Cr, *Ci, *ldt, *Dk, *W[4]; };
struct Params {
    CUtensorMap tm[5];
    CUtensorMap tn[2];
    ProArgs pa;
    int dopro;
    const __nv_bfloat16* mem0;
    const __nv_bfloat16* Wo;
    const __nv_bfloat16* Dskip;
    __nv_bfloat16* out;
    int roles;
    int chains;
    int lag;
    int zero;
    int nl[2];
    uint8_t list[2][64];
};

__device__ __forceinline__ uint32_t smem_u32(const void* p) { return (uint32_t)__cvta_generic_to_shared(p); }
__device__ __forceinline__ uint32_t mapa(uint32_t a, uint32_t r) {
    uint32_t o; asm("mapa.shared::cluster.u32 %0,%1,%2;" : "=r"(o) : "r"(a), "r"(r)); return o;
}
__device__ __forceinline__ void mbar_init(uint32_t b, int c) { asm volatile("mbarrier.init.shared::cta.b64 [%0],%1;" ::"r"(b), "r"(c) : "memory"); }
__device__ __forceinline__ void mbar_expect(uint32_t b, int bytes) { asm volatile("mbarrier.arrive.expect_tx.shared::cta.b64 _,[%0],%1;" ::"r"(b), "r"(bytes) : "memory"); }
__device__ __forceinline__ void mbar_arrive(uint32_t b) { asm volatile("mbarrier.arrive.shared::cta.b64 _,[%0];" ::"r"(b) : "memory"); }
__device__ __forceinline__ void mbar_arrive_cluster(uint32_t b) { asm volatile("mbarrier.arrive.shared::cluster.b64 _,[%0];" ::"r"(b) : "memory"); }
__device__ __forceinline__ void mbar_wait(uint32_t b, uint32_t ph) {
    asm volatile(
        "{.reg .pred p; .reg .u32 n; mov.u32 n,0;\n"
        "W%=: mbarrier.try_wait.parity.shared::cta.b64 p,[%0],%1;\n"
        "@p bra D%=;\n"
        "add.u32 n,n,1; setp.lt.u32 p,n,2000000; @p bra W%=;\n"
        "trap;\n"
        "D%=: }" ::"r"(b), "r"(ph) : "memory");
}
__device__ __forceinline__ bool wait_lds128(uint32_t b, uint32_t ph, uint32_t a, uint4& v) {
    uint32_t ok;
    asm volatile("{.reg .pred p; mbarrier.try_wait.parity.shared::cta.b64 p,[%5],%6,20000; ld.shared.v4.u32 {%0,%1,%2,%3},[%7]; selp.u32 %4,1,0,p;}"
                 : "=r"(v.x), "=r"(v.y), "=r"(v.z), "=r"(v.w), "=r"(ok) : "r"(b), "r"(ph), "r"(a) : "memory");
    return ok;
}
__device__ __forceinline__ bool wait_lds64(uint32_t b, uint32_t ph, uint32_t a, uint2& v) {
    uint32_t ok;
    asm volatile("{.reg .pred p; mbarrier.try_wait.parity.shared::cta.b64 p,[%3],%4,20000; ld.shared.v2.u32 {%0,%1},[%5]; selp.u32 %2,1,0,p;}"
                 : "=r"(v.x), "=r"(v.y), "=r"(ok) : "r"(b), "r"(ph), "r"(a) : "memory");
    return ok;
}
template <int PH> __device__ __forceinline__ void mbar_wait_c(uint32_t b) {
    asm volatile(
        "{.reg .pred p; .reg .u32 n; mov.u32 n,%2;\n"
        "W%=: mbarrier.try_wait.parity.shared::cta.b64 p,[%0],%1;\n"
        "@p bra D%=;\n"
        "add.u32 n,n,1; setp.lt.u32 p,n,2000000; @p bra W%=;\n"
        "trap;\n"
        "D%=: }" ::"r"(b), "n"(PH), "n"(PH) : "memory");
}
__device__ __forceinline__ bool elect() {
    uint32_t r; asm volatile("{.reg .pred p; elect.sync _|p,0xffffffff; selp.u32 %0,1,0,p;}" : "=r"(r)); return r;
}
__device__ __forceinline__ void bar_sync(int id, int n) { asm volatile("bar.sync %0,%1;" ::"r"(id), "r"(n) : "memory"); }
__device__ __forceinline__ void bar_arrive(int id, int n) { asm volatile("bar.arrive %0,%1;" ::"r"(id), "r"(n) : "memory"); }
__device__ __forceinline__ void cluster_sync() { asm volatile("barrier.cluster.arrive.relaxed.aligned; barrier.cluster.wait.aligned;" ::: "memory"); }
__device__ __forceinline__ void fence_async() { asm volatile("fence.proxy.async;" ::: "memory"); }
__device__ __forceinline__ void fence_async_smem() { asm volatile("fence.proxy.async.shared::cta;" ::: "memory"); }
#define EFR 1
#define EFW 0
constexpr uint64_t POL_N = 0x1000000000000000ull, POL_F = 0x12F0000000000000ull;
constexpr uint64_t POL_LAST = EFR ? POL_F : POL_N  , POL_LATE = EFW ? POL_F : POL_N  , POL_SOON = EFW > 1 ? POL_F : POL_N;
__device__ __forceinline__ void bulk_g2s(uint32_t dst, const void* src, int bytes, uint32_t bar, uint64_t pol) {
    asm volatile("cp.async.bulk.shared::cluster.global.mbarrier::complete_tx::bytes.L2::cache_hint [%0],[%1],%2,[%3],%4;" ::"r"(dst), "l"(src), "r"(bytes), "r"(bar), "l"(pol) : "memory");
}
__device__ __forceinline__ void bulk_g2s_mc(uint32_t dst, const void* src, int bytes, uint32_t bar, uint64_t pol) {
    asm volatile("cp.async.bulk.shared::cluster.global.mbarrier::complete_tx::bytes.multicast::cluster.L2::cache_hint [%0],[%1],%2,[%3],%4,%5;" ::"r"(dst), "l"(src), "r"(bytes), "r"(bar), "h"((uint16_t)3), "l"(pol) : "memory");
}
__device__ __forceinline__ void stg128(uint4* p, uint4 v, uint64_t pol) {
    asm volatile("st.global.L2::cache_hint.v4.u32 [%0],{%1,%2,%3,%4},%5;" ::"l"(p), "r"(v.x), "r"(v.y), "r"(v.z), "r"(v.w), "l"(pol));
}
__device__ __forceinline__ void stg32(uint32_t* p, uint32_t v, uint64_t pol) { asm volatile("st.global.L2::cache_hint.u32 [%0],%1,%2;" ::"l"(p), "r"(v), "l"(pol)); }
__device__ __forceinline__ uint4 ldcg128_last(const uint4* p) {
    uint4 v; asm volatile("ld.global.cg.L2::cache_hint.v4.u32 {%0,%1,%2,%3},[%4],%5;" : "=r"(v.x), "=r"(v.y), "=r"(v.z), "=r"(v.w) : "l"(p), "l"(POL_LAST) : "memory"); return v;
}
__device__ __forceinline__ void tma2d(uint32_t dst, const CUtensorMap* tm, int x, int y, uint32_t bar) {
    asm volatile("cp.async.bulk.tensor.2d.shared::cluster.global.mbarrier::complete_tx::bytes [%0],[%1,{%2,%3}],[%4];" ::"r"(dst), "l"(tm), "r"(x), "r"(y), "r"(bar) : "memory");
}
__device__ __forceinline__ void tma3d(uint32_t dst, const CUtensorMap* tm, int y, int z, uint32_t bar) {
    asm volatile("cp.async.bulk.tensor.3d.shared::cluster.global.mbarrier::complete_tx::bytes [%0],[%1,{0,%2,%3}],[%4];" ::"r"(dst), "l"(tm), "r"(y), "r"(z), "r"(bar) : "memory");
}
__device__ __forceinline__ void st_async4(uint32_t a, uint32_t x, uint32_t y, uint32_t z, uint32_t w, uint32_t mb) {
    asm volatile("st.async.shared::cluster.mbarrier::complete_tx::bytes.v4.b32 [%0],{%1,%2,%3,%4},[%5];" ::"r"(a), "r"(x), "r"(y), "r"(z), "r"(w), "r"(mb) : "memory");
}
__device__ __forceinline__ void st_async2(uint32_t a, uint32_t x, uint32_t y, uint32_t mb) {
    asm volatile("st.async.shared::cluster.mbarrier::complete_tx::bytes.v2.b32 [%0],{%1,%2},[%3];" ::"r"(a), "r"(x), "r"(y), "r"(mb) : "memory");
}
#define LDSQ "ld.shared"
__device__ __forceinline__ uint4 lds128(uint32_t a) { uint4 v; asm volatile(LDSQ ".v4.u32 {%0,%1,%2,%3},[%4];" : "=r"(v.x), "=r"(v.y), "=r"(v.z), "=r"(v.w) : "r"(a) : "memory"); return v; }
__device__ __forceinline__ uint4 lds128v(uint32_t a) { uint4 v; asm volatile("ld.volatile.shared.v4.u32 {%0,%1,%2,%3},[%4];" : "=r"(v.x), "=r"(v.y), "=r"(v.z), "=r"(v.w) : "r"(a) : "memory"); return v; }
__device__ __forceinline__ uint2 lds64(uint32_t a) { uint2 v; asm volatile(LDSQ ".v2.u32 {%0,%1},[%2];" : "=r"(v.x), "=r"(v.y) : "r"(a) : "memory"); return v; }
__device__ __forceinline__ uint32_t lds32(uint32_t a) { uint32_t v; asm volatile(LDSQ ".u32 %0,[%1];" : "=r"(v) : "r"(a) : "memory"); return v; }
__device__ __forceinline__ void sts128(uint32_t a, uint32_t x, uint32_t y, uint32_t z, uint32_t w) { asm volatile("st.shared.v4.u32 [%0],{%1,%2,%3,%4};" ::"r"(a), "r"(x), "r"(y), "r"(z), "r"(w) : "memory"); }
__device__ __forceinline__ void sts64(uint32_t a, uint32_t x, uint32_t y) { asm volatile("st.shared.v2.u32 [%0],{%1,%2};" ::"r"(a), "r"(x), "r"(y) : "memory"); }
__device__ __forceinline__ void sts32(uint32_t a, uint32_t x) { asm volatile("st.shared.u32 [%0],%1;" ::"r"(a), "r"(x) : "memory"); }
__device__ __forceinline__ uint4 ldsm4(uint32_t a) { uint4 v; asm volatile("ldmatrix.sync.aligned.m8n8.x4.shared.b16 {%0,%1,%2,%3},[%4];" : "=r"(v.x), "=r"(v.y), "=r"(v.z), "=r"(v.w) : "r"(a) : "memory"); return v; }
__device__ __forceinline__ uint4 ldsm4t(uint32_t a) { uint4 v; asm volatile("ldmatrix.sync.aligned.m8n8.x4.trans.shared.b16 {%0,%1,%2,%3},[%4];" : "=r"(v.x), "=r"(v.y), "=r"(v.z), "=r"(v.w) : "r"(a) : "memory"); return v; }
__device__ __forceinline__ uint32_t movm(uint32_t a) { uint32_t d; asm volatile("movmatrix.sync.aligned.m8n8.trans.b16 %0,%1;" : "=r"(d) : "r"(a)); return d; }
__device__ __forceinline__ uint32_t pack2(float lo, float hi) { uint32_t d; asm("cvt.rn.bf16x2.f32 %0,%1,%2;" : "=r"(d) : "f"(hi), "f"(lo)); return d; }
__device__ __forceinline__ uint32_t hadd2(uint32_t a, uint32_t b) { uint32_t d; asm("add.rn.bf16x2 %0,%1,%2;" : "=r"(d) : "r"(a), "r"(b)); return d; }
__device__ __forceinline__ uint32_t hmul2(uint32_t a, uint32_t b) { uint32_t d; asm("mul.rn.bf16x2 %0,%1,%2;" : "=r"(d) : "r"(a), "r"(b)); return d; }
__device__ __forceinline__ float blo(uint32_t v) { return __uint_as_float(v << 16); }
__device__ __forceinline__ float bhi(uint32_t v) { return __uint_as_float(v & 0xffff0000u); }
__device__ __forceinline__ float rbf(float x) { return __uint_as_float(pack2(0.f, x)); }
__device__ __forceinline__ float ex2(float x) { float y; asm("ex2.approx.ftz.f32 %0,%1;" : "=f"(y) : "f"(x)); return y; }
__device__ __forceinline__ float rcp(float x) { float y; asm("rcp.approx.ftz.f32 %0,%1;" : "=f"(y) : "f"(x)); return y; }
__device__ __forceinline__ void mma16(float* c, uint32_t a0, uint32_t a1, uint32_t a2, uint32_t a3, uint32_t b0, uint32_t b1) {
    asm volatile("mma.sync.aligned.m16n8k16.row.col.f32.bf16.bf16.f32 {%0,%1,%2,%3},{%4,%5,%6,%7},{%8,%9},{%0,%1,%2,%3};"
                 : "+f"(c[0]), "+f"(c[1]), "+f"(c[2]), "+f"(c[3]) : "r"(a0), "r"(a1), "r"(a2), "r"(a3), "r"(b0), "r"(b1));
}
__device__ __forceinline__ void mma16_top(float& d0, float& d1, uint32_t a0, uint32_t a2, uint32_t b0, uint32_t b1) {
    asm volatile("{.reg .b32 j; .reg .f32 e,f; mma.sync.aligned.m16n8k16.row.col.f32.bf16.bf16.f32 {%0,%1,e,f},{%2,j,%3,j},{%4,%5},{0f00000000,0f00000000,0f00000000,0f00000000};}"
                 : "=f"(d0), "=f"(d1) : "r"(a0), "r"(a2), "r"(b0), "r"(b1));
}
__device__ __forceinline__ void mma8(float* c, uint32_t a0, uint32_t a1, uint32_t b0) {
    asm volatile("mma.sync.aligned.m16n8k8.row.col.f32.bf16.bf16.f32 {%0,%1,%2,%3},{%4,%5},{%6},{%0,%1,%2,%3};"
                 : "+f"(c[0]), "+f"(c[1]), "+f"(c[2]), "+f"(c[3]) : "r"(a0), "r"(a1), "r"(b0));
}
__device__ __forceinline__ uint4 ld_rlx128(const uint4* p) {
    uint4 v;
    asm volatile("{.reg .b128 t; ld.relaxed.gpu.global.b128 t,[%4]; mov.b128 {%0,%1,%2,%3},t;}" : "=r"(v.x), "=r"(v.y), "=r"(v.z), "=r"(v.w) : "l"(p) : "memory");
    return v;
}
__device__ __forceinline__ void st_rlx128(uint4* p, uint32_t x, uint32_t y, uint32_t z, uint32_t w) {
    asm volatile("{.reg .b128 t; mov.b128 t,{%1,%2,%3,%4}; st.relaxed.gpu.global.b128 [%0],t;}" ::"l"(p), "r"(x), "r"(y), "r"(z), "r"(w) : "memory");
}
__device__ __forceinline__ uint4 ldcg128(const uint4* p) { uint4 v; asm volatile("ld.global.cg.v4.u32 {%0,%1,%2,%3},[%4];" : "=r"(v.x), "=r"(v.y), "=r"(v.z), "=r"(v.w) : "l"(p) : "memory"); return v; }
__device__ __forceinline__ void red_release(unsigned* p, unsigned v) {
    asm volatile("fence.proxy.async; red.relaxed.gpu.global.add.u32 [%0],%1;" ::"l"(p), "r"(v) : "memory");
}
__device__ __forceinline__ void red_relaxed(unsigned* p, unsigned v) { asm volatile("red.relaxed.gpu.global.add.u32 [%0],%1;" ::"l"(p), "r"(v) : "memory"); }
__device__ __forceinline__ void wait_cnt(const unsigned* p, unsigned target) {
    asm volatile(
        "{.reg .pred p; .reg .u32 n,v; mov.u32 n,0;\n"
        "W%=: ld.acquire.gpu.global.u32 v,[%0]; setp.ge.u32 p,v,%1; @p bra D%=;\n"
        "nanosleep.u32 20; add.u32 n,n,1; setp.lt.u32 p,n,4000000; @p bra W%=;\n"
        "trap;\n"
        "D%=: }" ::"l"(p), "r"(target) : "memory");
}
__device__ __forceinline__ void wait_cnt_warp(const unsigned* p, unsigned target) {
    asm volatile(
        "{.reg .pred p; .reg .u32 n,v; mov.u32 n,0;\n"
        "W%=: ld.acquire.gpu.global.u32 v,[%0]; setp.ge.u32 p,v,%1; vote.sync.all.pred p,p,0xffffffff; @p bra.uni D%=;\n"
        "nanosleep.u32 20; add.u32 n,n,1; setp.lt.u32 p,n,4000000; @p bra.uni W%=;\n"
        "trap;\n"
        "D%=: }" ::"l"(p), "r"(target) : "memory");
}
__device__ __forceinline__ void wait_slow_warp(const unsigned* p, unsigned target) {
    asm volatile(
        "{.reg .pred p; .reg .u32 n,v; mov.u32 n,0;\n"
        "W%=: ld.relaxed.gpu.global.u32 v,[%0]; setp.ge.u32 p,v,%1; vote.sync.all.pred p,p,0xffffffff; @p bra.uni D%=;\n"
        "nanosleep.u32 400; add.u32 n,n,1; setp.lt.u32 p,n,1000000; @p bra.uni W%=;\n"
        "trap;\n"
        "D%=: }" ::"l"(p), "r"(target) : "memory");
}
__device__ __forceinline__ void wait_flag_warp(const unsigned* p, unsigned target) {
    asm volatile(
        "{.reg .pred p; .reg .u32 n,v; mov.u32 n,0;\n"
        "W%=: ld.relaxed.gpu.global.u32 v,[%0]; setp.ge.u32 p,v,%1; vote.sync.all.pred p,p,0xffffffff; @p bra.uni D%=;\n"
        "add.u32 n,n,1; setp.lt.u32 p,n,10000000; @p bra.uni W%=;\n"
        "trap;\n"
        "D%=: }" ::"l"(p), "r"(target) : "memory");
}
__device__ __forceinline__ uint64_t mkdesc(uint32_t addr, uint32_t lbo, uint32_t sbo, uint32_t sw) {
    return (uint64_t)((addr & 0x3FFFF) >> 4) | ((uint64_t)(lbo >> 4) << 16) | ((uint64_t)(sbo >> 4) << 32) | ((uint64_t)sw << 62);
}
__device__ __forceinline__ void wg_fence() { asm volatile("wgmma.fence.sync.aligned;" ::: "memory"); }
__device__ __forceinline__ void wg_commit() { asm volatile("wgmma.commit_group.sync.aligned;" ::: "memory"); }
template <int N> __device__ __forceinline__ void wg_wait() { asm volatile("wgmma.wait_group.sync.aligned %0;" ::"n"(N) : "memory"); }
#define R8(c, o) "+f"(c[o]), "+f"(c[o + 1]), "+f"(c[o + 2]), "+f"(c[o + 3]), "+f"(c[o + 4]), "+f"(c[o + 5]), "+f"(c[o + 6]), "+f"(c[o + 7])
#define R32(c, o) R8(c, o), R8(c, o + 8), R8(c, o + 16), R8(c, o + 24)
#define S32A "%0,%1,%2,%3,%4,%5,%6,%7,%8,%9,%10,%11,%12,%13,%14,%15,%16,%17,%18,%19,%20,%21,%22,%23,%24,%25,%26,%27,%28,%29,%30,%31"
template <int ACC> __device__ __forceinline__ void wgmma64_rs(float* c, const uint32_t* a, uint64_t db) {
    asm volatile("wgmma.mma_async.sync.aligned.m64n64k16.f32.bf16.bf16 {" S32A "},{%32,%33,%34,%35},%36,%37,1,1,0;"
                 : R32(c, 0) : "r"(a[0]), "r"(a[1]), "r"(a[2]), "r"(a[3]), "l"(db), "n"(ACC));
}
template <int ACC> __device__ __forceinline__ void wgmma64_ta(float* c, uint64_t da, uint64_t db) {
    asm volatile("wgmma.mma_async.sync.aligned.m64n64k16.f32.bf16.bf16 {" S32A "},%32,%33,%34,1,1,1,0;" : R32(c, 0) : "l"(da), "l"(db), "n"(ACC));
}
template <int ACC> __device__ __forceinline__ void wgmma80_tb(float* c, uint64_t da, uint64_t db) {
    asm volatile("wgmma.mma_async.sync.aligned.m64n80k16.f32.bf16.bf16 {" S32A ",%32,%33,%34,%35,%36,%37,%38,%39},%40,%41,%42,1,1,0,1;"
                 : R32(c, 0), R8(c, 32) : "l"(da), "l"(db), "n"(ACC));
}
template <int N> __device__ __forceinline__ void reg_inc() { asm volatile("setmaxnreg.inc.sync.aligned.u32 %0;" ::"n"(N)); }
template <int N> __device__ __forceinline__ void reg_dec() { asm volatile("setmaxnreg.dec.sync.aligned.u32 %0;" ::"n"(N)); }

#define PROF(cond, idx) do {} while (0)
#define PROF2(cond, idx) do {} while (0)

constexpr int S_GATE = 232440, S_TAG = 232444, S_XBAR = 232432, B_BAR = 231936;
#define RCB 136
#define RCU 184
#define NTOP 1
#define PLATE 2
#define PFM 12
#define QLAG 3
constexpr float SC_LOG2E = 0.08838834764831845f * 1.4426950408889634f;

__device__ __forceinline__ float2 ln_finish(float mean, float var) {
    float sd; asm("sqrt.approx.f32 %0,%1;" : "=f"(sd) : "f"(rbf(rbf(var) + 1e-5f)));
    sd = rbf(sd);
    return make_float2(rbf(mean), sd);
}

__device__ __forceinline__ float2 row_stats512(uint4* v, const uint4* src, int s1, int s2) {
    const int g = (threadIdx.x & 31) >> 2;
#pragma unroll
    for (int i = 0; i < 16; i++) v[i] = ldcg128(src + (i >> 1) * s1 + (i & 1) * s2);
    float a[4] = {0, 0, 0, 0}, q0[4] = {0, 0, 0, 0}, q1[4] = {0, 0, 0, 0};
#pragma unroll
    for (int i = 0; i < 16; i++) {
        mma16(a, v[i].x, v[i].y, v[i].z, v[i].w, 0x3f803f80u, 0x3f803f80u);
        mma8(q0, v[i].x, v[i].y, v[i].x); mma8(q1, v[i].x, v[i].y, v[i].y);
        mma8(q0, v[i].z, v[i].w, v[i].z); mma8(q1, v[i].z, v[i].w, v[i].w);
    }
    const float sum = a[0] + a[2], sq = (g & 1) ? q0[1] + q1[3] : q0[0] + q1[2];
    return make_float2(sum, fmaxf(sq - sum * sum * (1.f / 512.f), 0.f));
}
__device__ __forceinline__ void x1_norm(const uint2* src, int r, bool on) {
    const int lane = threadIdx.x & 31, g = lane >> 2, t = r * 4 + (lane & 3);
    constexpr int xp = XP;
    uint2 v[16];
#pragma unroll
    for (int i = 0; i < 16; i++) asm volatile("ld.global.cg.v2.u32 {%0,%1},[%2];" : "=r"(v[i].x), "=r"(v[i].y) : "l"(src + (g * 4 * xp + t) + ((i >> 1) * 16 + (i & 1)) * 2 * xp) : "memory");
    float s = 0, q = 0;
#pragma unroll
    for (int i = 0; i < 32; i++) {
        const uint32_t w = (i & 1) ? v[i >> 1].y : v[i >> 1].x;
        s += blo(w) + bhi(w); q = fmaf(blo(w), blo(w), fmaf(bhi(w), bhi(w), q));
    }
#pragma unroll
    for (int d = 4; d < 32; d *= 2) { s += __shfl_xor_sync(0xffffffffu, s, d); q += __shfl_xor_sync(0xffffffffu, q, d); }
    if (g == 0 && on) g_ln0[t] = 0;
    s *= 1.f / 512.f;
    const float2 l = ln_finish(s, fmaxf(fmaf(q, 1.f / 512.f, -s * s), 0.f));
    const float rs = rcp(l.y);
    const uint32_t mm = pack2(-l.x, -l.x);
    uint4* dst = g_xn + ((t >> 6) * 4096 + ((t >> 3) & 7) * 64 + g * 8 + (t & 7));
#define NRM(w) pack2(blo(hadd2(w, mm)) * rs, bhi(hadd2(w, mm)) * rs)
#pragma unroll
    for (int i = 0; i < 8; i++)
        asm volatile("{.reg .pred p; setp.ne.u32 p,%5,0; @p st.global.v4.u32 [%0],{%1,%2,%3,%4};}" ::"l"(dst + i * 512), "r"(NRM(v[2 * i].x)), "r"(NRM(v[2 * i].y)),
                     "r"(NRM(v[2 * i + 1].x)), "r"(NRM(v[2 * i + 1].y)), "r"((uint32_t)on) : "memory");
}

#define NWO 10
#define VMASK 0x4444
#define VPRE 2
#define VFIRST 1
#define OA 0
#define OL 0x16
#define PINS 0x2ae1
#define NPX 2
#define NPF 2
constexpr int SLOT = 24576, SL_V = 8192, SL_Q = 16384, SL_KM = 20480, SL_VM = 22528;
constexpr int R_SL = 0, R_WV = 4 * SLOT  , R_WO = R_WV + 65536, R_M = 196608  , R_U = R_M + 8192  ,
              R_OS = R_U + 8192  , R_SB = R_OS + 8192  , R_OB = R_SB + 5248  , R_PB = R_OB + 2048  ,
              R_IL = R_PB + 1024  , R_SEL = 231680, R_BAR = R_SEL + 256, R_STV = 0, R_STQ = 65536, R_STK = 131072;
static_assert(R_WO + (16 - NWO) * 4096 <= R_M && R_IL + 64 <= R_SEL && R_BAR + 512 <= 232448, "smem map");
enum { RB_XFULL = 0  , RB_GO = 4  , RB_QK = 8  , RB_INIT = 24, RB_SV = 25   };

enum { NB_MFULL = 1  , NB_PART = 3  , NB_S = 5, NB_P = 6, NB_O = 7, NB_W = 10 };
#define XU 4
#define GOP 0
#define WOF 1
#define EGO 0
#define NPRB 3
#define REARLY 1
#define RFW 8
#define PF0 0
#define PFD 1500
#define EFS V_QKV
#define RACC 2
#define WDEP 1
#define RH 56
#define RW0 224
#define D1 350
#define D2 350
__device__ __forceinline__ uint32_t clk32() { uint32_t c; asm volatile("mov.u32 %0,%%clock;" : "=r"(c)::"memory"); return c; }
__device__ __forceinline__ void spin(int cycles) {
    if (cycles <= 0) return;
    asm volatile("{.reg .pred p; .reg .u32 a,b; mov.u32 a,%%clock; add.u32 a,a,%0;\nS%=: mov.u32 b,%%clock; sub.u32 b,b,a; setp.lt.s32 p,b,0; @p bra.uni S%=;}" ::"r"(cycles) : "memory");
}
__device__ __forceinline__ uint4* xregion(int X, int r) { return (uint4*)(((size_t)g_xch + 8191) & ~(size_t)8191) + (X * 66 + r) * 512; }

__device__ __forceinline__ void arrive_if(uint32_t bar, uint32_t a, uint32_t b) {
    asm volatile("{.reg .pred p; setp.eq.u32 p,%1,%2; @p mbarrier.arrive.shared::cta.b64 _,[%0];}" ::"r"(bar), "r"(a), "r"(b) : "memory");
}
struct RecW { uint32_t po, dp, lw, sp, w; };
#define PIN(n) if ((PINS >> (n)) & 1) asm volatile("griddepcontrol.launch_dependents;" ::: "memory")
constexpr int v_stream(int n) {
    int ks = 0;
    for (; ks < 16; ks++) if (!((VMASK >> ks) & 1) && n-- == 0) break;
    return ks;
}
constexpr uint64_t v_next() {
    uint64_t r = 0;
    for (int n = 0; v_stream(n + VPRE) < 16; n++) r |= (uint64_t)v_stream(n + VPRE) << (4 * v_stream(n));
    return r;
}
constexpr uint64_t V_NEXT = v_next();
constexpr int V_PRE = v_stream(VPRE);

__device__ __forceinline__ void rec_step(const RecW& k, uint32_t sb, const int X, int s, uint32_t zero, int lo, int hi, int d, const uint32_t (*wq)[4], const uint32_t (*wk)[4], uint4* wv, uint4* wo) {
    const int SL = R_SL + X * 2 * SLOT;
    uint4 mk[8];
    bar_sync(NB_MFULL + X, 288);
    mk[0] = ldsm4(k.lw + X * 4096 + R_M);
    PIN(0);
    mk[1] = ldsm4(k.lw + X * 4096 + R_M + 512);
    PIN(0);
    asm volatile("" : "+r"(s));
    const uint32_t z = s & zero, wz = k.w + z, w5 = wz * 512, so = (s & 1) * SLOT + w5;
    const uint32_t qb = sb + R_BAR + (RB_QK + X * 8) * 8 + wz * 8;
    uint32_t x[4], vv[2], l8;
    {
        float aq[4] = {0, 0, 0, 0}, ak[4] = {0, 0, 0, 0}, av[4] = {0, 0, 0, 0};
#pragma unroll
        for (int t = 0; t < 16; t++) {
            const uint32_t b0 = (t & 1) ? mk[t >> 1].z : mk[t >> 1].x, b1 = (t & 1) ? mk[t >> 1].w : mk[t >> 1].y;
            mma16(aq, wq[t][0], wq[t][1], wq[t][2], wq[t][3], b0, b1);
            PIN(8);
            mma16(ak, wk[t][0], wk[t][1], wk[t][2], wk[t][3], b0, b1);
            PIN(9);
            mma16(av, wv[t].x, wv[t].y, wv[t].z, wv[t].w, b0, b1);
            PIN(10);
            if ((t & 1) && t < 13) mk[(t >> 1) + 2] = ldsm4(k.lw + X * 4096 + R_M + (t >> 1) * 512 + 1024);
            const int nx = (V_NEXT >> (4 * t)) & 15;
            if (nx) wv[nx] = lds128(k.lw + w5 + R_WV + nx * 4096);
            if (t == 14) l8 = ((k.lw + z) >> 1) + (sb - (sb >> 1) + SL + (s & 1) * SLOT + wz * 256);
            if (t < 15) PIN(1);
        }
        x[0] = movm(pack2(aq[0], aq[1])); x[1] = movm(pack2(aq[2], aq[3]));
        x[2] = movm(pack2(ak[0], ak[1])); x[3] = movm(pack2(ak[2], ak[3]));
        vv[0] = pack2(av[0], av[1]); vv[1] = pack2(av[2], av[3]);
        if (VFIRST) st_async2(l8 + (SL_VM + k.dp), vv[0], vv[1], qb + k.dp);
        st_async4(k.lw + (R_U + X * 4096 + w5 + k.dp), x[0], x[1], x[2], x[3], qb + k.dp);
        if (!VFIRST) st_async2(l8 + (SL_VM + k.dp), vv[0], vv[1], qb + k.dp);
    }
    {
#define GO_OTHER arrive_if(sb + R_BAR + (RB_GO + 2 - 2 * X + ((s + d) & 1)) * 8, (k.sp + z) & 0x1ff0, X ? s >= hi : s <= lo)
        if (GOP == 0) GO_OTHER;
        const uint32_t swr = ((k.sp + z) & 0x1ff0) + (sb + R_SB);
        if (WOF) {
#pragma unroll
            for (int i = 0; i < NPX; i++) wo[i] = lds128v(k.lw + w5 + R_WO + i * 4096);
        }
        mbar_wait(sb + R_BAR + (RB_XFULL + X * 2) * 8 + (s & 1) * 8, (s >> 1) & 1);
        const uint4 k0 = lds128(k.lw + so + SL), k1 = lds128(k.lw + so + SL + 4096);
        if (!WOF) {
#pragma unroll
            for (int i = 0; i < NPX; i++) wo[i] = lds128(k.lw + w5 + R_WO + i * 4096);
        }
        if (GOP == 1) GO_OTHER;
        mbar_wait(qb, s & 1);
        const uint4 u = lds128(k.lw + w5 + R_U + X * 4096);
        if (GOP == 2) GO_OTHER;
        const uint32_t q0 = hadd2(x[0], u.x), q1 = hadd2(x[1], u.y);
        x[2] = hadd2(x[2], u.z); x[3] = hadd2(x[3], u.w);
        float sa[4] = {0, 0, 0, 0}, sc[4] = {0, 0, 0, 0}, sm0, sm1;
        mma16(sa, k0.x, k0.y, k0.z, k0.w, q0, q1);
        mma16(sc, k1.x, k1.y, k1.z, k1.w, q0, q1);
        mma16_top(sm0, sm1, x[2], x[3], q0, q1);
        asm volatile("stmatrix.sync.aligned.m8n8.x4.trans.shared.b16 [%0],{%1,%2,%3,%4};" ::"r"(swr), "r"(pack2(sa[0], sa[1])), "r"(pack2(sa[2], sa[3])),
                     "r"(pack2(sc[0], sc[1])), "r"(pack2(sc[2], sc[3])) : "memory");
        asm volatile("stmatrix.sync.aligned.m8n8.x1.trans.shared.b16 [%0],{%1};" ::"r"(swr + 512), "r"(pack2(sm0, sm1)) : "memory");
    }
    if (GOP == 3) GO_OTHER;
    bar_sync(NB_S, 256);
    uint4 v0, v1;
    uint32_t ls;
    {
        const uint4 y = ldsm4t(k.lw + wz * 656 + R_SB);
        PIN(2);
        uint32_t y4; asm volatile("ldmatrix.sync.aligned.m8n8.x1.trans.shared.b16 {%0},[%1];" : "=r"(y4) : "r"(k.lw + wz * 656 + R_SB + 512) : "memory");
        PIN(2);
        const uint2 vp = lds64(l8 + SL_VM);
        sts64(l8 + SL_KM, x[2], x[3]);
        const uint32_t z1 = k.lw & z, z2 = k.sp & z, ONE = 0x3f803f80u | z2, ONF = 0x3f803f80u | z1;
        float a[4] = {0, 0, 0, 0}, b[4] = {0, 0, 0, 0}, e[4] = {0, 0, 0, 0};
        mma8(e, ONE, z1, y4); mma16(a, ONE, z1, z2, ONF, y.x, y.y); mma16(b, ONE, z1, z2, ONF, y.z, y.w);
        vv[0] = hadd2(vv[0], vp.x); vv[1] = hadd2(vv[1], vp.y);
        sts64(l8 + SL_VM, vv[0], vv[1]);
        float s0, s1;
        asm("{.reg .pred p1,p2,p4; .reg .f32 t0,t1,u0,u1; .reg .b32 m; and.b32 m,%12,64; setp.ne.u32 p1,m,0; and.b32 m,%12,128; setp.ne.u32 p2,m,0; and.b32 m,%12,256; setp.ne.u32 p4,m,0;"
            "selp.f32 t0,%4,%2,p1; selp.f32 t1,%5,%3,p1; selp.f32 u0,%8,%6,p1; selp.f32 u1,%9,%7,p1; selp.f32 t0,u0,t0,p2; selp.f32 t1,u1,t1,p2; selp.f32 %0,%10,t0,p4; selp.f32 %1,%11,t1,p4;}"
            : "=f"(s0), "=f"(s1) : "f"(a[0]), "f"(a[1]), "f"(a[2]), "f"(a[3]), "f"(b[0]), "f"(b[1]), "f"(b[2]), "f"(b[3]), "f"(e[0]), "f"(e[1]), "r"(k.lw));
        const int mi = __float_as_int(fmaxf(s0, s1));
        const int mp = __reduce_max_sync(0xffffffffu, mi), mn = (int)__reduce_min_sync(0xffffffffu, (unsigned)mi);
        PIN(3);
        v0 = lds128(k.lw + so + SL + SL_V); v1 = lds128(k.lw + so + SL + SL_V + 4096);
#pragma unroll
        for (int i = NPX; i < NPF; i++) wo[i] = lds128(k.lw + w5 + R_WO + i * 4096);
        PIN(4);
        const float mo = -__int_as_float(mp >= 0 ? mp : mn) * SC_LOG2E;
        s0 = ex2(fmaf(s0, SC_LOG2E, mo)); s1 = ex2(fmaf(s1, SC_LOG2E, mo));
        sts32((((k.sp + z) >> 11) & 0x1fc) + (k.lw & 256) * 2 + (sb + R_PB), pack2(s0, s1));
        ls = k.lw < sb + 320 ? __float_as_uint((s0 + s1) + 4.f) : 0;
    }
    bar_sync(NB_P, 256);
    {
        const uint4 pp = lds128(k.lw + R_PB);
        PIN(5);
        const uint32_t pm = lds32(((k.lw + z) >> 2) + (sb - (sb >> 2) + R_PB + 512));
        PIN(5);
        if (EGO) arrive_if(sb + R_BAR + (RB_GO + 2 * X + (s & 1)) * 8, (k.sp + z) & 0x1ff0, X ? s + 1 < hi : s >= lo);
        sts32(sb + R_IL + (wz >> 1) * 16 + (wz & 1) * 4, __reduce_add_sync(0xffffffffu, ls) - 20u * 0x40800000u);
        float o0[4] = {0, 0, 0, 0}, o1[4] = {0, 0, 0, 0}, o2[4] = {0, 0, 0, 0};
        mma16(o0, v0.x, v0.y, v0.z, v0.w, pp.x, pp.y);
        mma16(o1, v1.x, v1.y, v1.z, v1.w, pp.z, pp.w);
        mma8(o2, vv[0], vv[1], pm);
        asm volatile("stmatrix.sync.aligned.m8n8.x2.trans.shared.b16 [%0],{%1,%2};" ::"r"(k.lw + wz * 256 + R_OB),
                     "r"(pack2(o0[0] + o1[0] + o2[0], o0[1] + o1[1] + o2[1])), "r"(pack2(o0[2] + o1[2] + o2[2], o0[3] + o1[3] + o2[3])) : "memory");
    }
    bar_sync(NB_O, 256);
    {
        float r0[2][4] = {{0, 0, 0, 0}, {0, 0, 0, 0}}, r1[2][4] = {{0, 0, 0, 0}, {0, 0, 0, 0}};
        uint4 b[4];
        b[0] = ldsm4(k.lw + R_OB);
        PIN(6);
        b[1] = ldsm4(k.lw + R_OB + 512);
        PIN(6);
#pragma unroll
        for (int m = NWO + NPF; m < 16; m++) if (((OL >> (2 * (15 - m))) & 3) == 3) wo[m] = lds128(k.lw + w5 + R_WO + (m - NWO) * 4096);
        const uint2 il = lds64(sb + R_IL + ((k.lw + z) & 48));
        PIN(6);
        float i0, i1;
        uint4* dst;
#pragma unroll
        for (int i = 0; i < 4; i++) {
            mma16(r0[0], wo[4 * i].x, wo[4 * i].y, wo[4 * i].z, wo[4 * i].w, b[i].x, b[i].y);
            mma16(r1[0], wo[4 * i + 1].x, wo[4 * i + 1].y, wo[4 * i + 1].z, wo[4 * i + 1].w, b[i].x, b[i].y);
            mma16(r0[OA], wo[4 * i + 2].x, wo[4 * i + 2].y, wo[4 * i + 2].z, wo[4 * i + 2].w, b[i].z, b[i].w);
            mma16(r1[OA], wo[4 * i + 3].x, wo[4 * i + 3].y, wo[4 * i + 3].z, wo[4 * i + 3].w, b[i].z, b[i].w);
            if (i < 2) b[i + 2] = ldsm4(k.lw + R_OB + (i + 2) * 512);
#pragma unroll
            for (int m = NWO + NPF; m < 16; m++) if (i < 3 && i == ((OL >> (2 * (15 - m))) & 3)) wo[m] = lds128(k.lw + w5 + R_WO + (m - NWO) * 4096);
            if (i == 1) { i0 = rcp(__uint2float_rn(il.x)) * 2097152.f; i1 = rcp(__uint2float_rn(il.y)) * 2097152.f; }
            if (i == 2) {
                const uint32_t po = k.sp + z;
                dst = xregion(X, 0) + k.po + ((po >> 20) ^ ((po & X) << 8));
                asm volatile("" : "+l"(dst));
            }
            PIN(7);
        }
        const uint32_t tag = (s + 1) & 1;
#pragma unroll
        for (int i = 0; i < 4; i++) { r0[0][i] = (OA ? r0[0][i] + r0[1][i] : r0[0][i]) * ((i & 1) ? i1 : i0); r1[0][i] = (OA ? r1[0][i] + r1[1][i] : r1[0][i]) * ((i & 1) ? i1 : i0); }
        st_rlx128(dst, (pack2(r0[0][0], r0[0][2]) & ~1u) | tag,
                  pack2(r1[0][0], r1[0][2]), pack2(r0[0][1], r0[0][3]), pack2(r1[0][1], r1[0][3]));
        bar_arrive(NB_PART + X, 288);
#pragma unroll
        for (int t = 0; t < V_PRE; t++) if (!((VMASK >> t) & 1)) wv[t] = lds128(k.lw + w5 + R_WV + t * 4096);
        if (!EGO) arrive_if(sb + R_BAR + (RB_GO + 2 * X + (s & 1)) * 8, (k.sp + z) & 0x1ff0, X ? s + 1 < hi : s >= lo);
    }
}

__device__ __forceinline__ void rec_fetch(const Params& p, uint32_t sb, int head, uint32_t rank, int which, int dst) {
#pragma unroll 1
    for (int j = 0; j < 8; j++) tma2d(sb + dst + j * 8192, &p.tm[which], head * 128 + (j >> 2) * 64, rank * 256 + (j & 3) * 64, sb + R_BAR + RB_INIT * 8);
}

__device__ __forceinline__ void rec_weights(const Params& p, uint32_t sb, int head, uint32_t rank, int w) {
    const int lane = __shfl_sync(0xffffffffu, threadIdx.x & 31, threadIdx.x & 31),
        g = lane >> 2, c = lane & 3;
    const int t = w & 3, WG = w >> 2;
    uint32_t wq[16][4], wk[16][4];
    uint4 wo[16], wv[16];
    const uint32_t woff = sb + WG * 32768 + (((lane >> 4) << 3) + (lane & 7)) * 128 + (((2 * t + ((lane >> 3) & 1)) ^ (lane & 7)) << 4);
    const uint32_t lw = sb + lane * 16;
    PROF2(threadIdx.x == 0, 3501);
    {
        const __nv_bfloat16* wp = p.Wo + (size_t)(head * 128 + 2 * c) * 512 + rank * 256 + w * 32 + g * 4;
#pragma unroll
        for (int ks = 0; ks < 8; ks++) {
            const uint2 r0 = *(const uint2*)(wp + (ks * 16) * 512), r1 = *(const uint2*)(wp + (ks * 16 + 1) * 512);
            const uint2 r2 = *(const uint2*)(wp + (ks * 16 + 8) * 512), r3 = *(const uint2*)(wp + (ks * 16 + 9) * 512);
            const uint4 f[2] = {make_uint4(__byte_perm(r0.x, r1.x, 0x5410), __byte_perm(r0.x, r1.x, 0x7632), __byte_perm(r2.x, r3.x, 0x5410), __byte_perm(r2.x, r3.x, 0x7632)),
                                make_uint4(__byte_perm(r0.y, r1.y, 0x5410), __byte_perm(r0.y, r1.y, 0x7632), __byte_perm(r2.y, r3.y, 0x5410), __byte_perm(r2.y, r3.y, 0x7632))};
#pragma unroll
            for (int h = 0; h < 2; h++) {
                const int m = 2 * ks + h;
                wo[m] = f[h];
            }
        }
    }
    PROF2(threadIdx.x == 0, 3502);
    mbar_wait(sb + R_BAR + RB_INIT * 8, 0);
    PROF2(threadIdx.x == 0, 3503);
#pragma unroll
    for (int ks = 0; ks < 16; ks++) {
        uint4 a = ldsm4t(woff + R_STQ + ks * 2048), b = ldsm4t(woff + R_STK + ks * 2048);
        wq[ks][0] = a.x; wq[ks][1] = a.y; wq[ks][2] = a.z; wq[ks][3] = a.w;
        wk[ks][0] = b.x; wk[ks][1] = b.y; wk[ks][2] = b.z; wk[ks][3] = b.w;
    }
    bar_sync(NB_W, 256);
#pragma unroll
    for (int m = 0; m < 16; m++)
        if (m < NPF || m >= NPF + NWO) sts128(lw + w * 512 + R_WO + (m < NPF ? m : m - NWO) * 4096, wo[m].x, wo[m].y, wo[m].z, wo[m].w);
#pragma unroll
    for (int i = 0; i < 16; i++) {
        wv[i] = ldsm4t(woff + R_STV + i * 2048);
        if (!((VMASK >> i) & 1)) sts128(lw + w * 512 + R_WV + i * 4096, wv[i].x, wv[i].y, wv[i].z, wv[i].w);
    }
    fence_async_smem();
    PROF2(threadIdx.x == 0, 3504);
    __syncthreads();
    cluster_sync();
    PROF2(threadIdx.x == 0, 3505);
    RecW k;
    {
        const int r = (w * 4 + (lane >> 3)) * 2 + rank;
        const uint32_t sl = lds32(sb + R_SEL + r * 4);
        k.po = (w * 8 + rank) * 512 + (head >> 1) * 16 + (head & 1) * 4;
        k.sp = (((lane >> 3) * 1024 + (sl & 1) * 256 + (lane & 4) * 2 + (lane & 3)) << 20) + (((sl >> 1) ^ sl) & 1) + (lane & 7) * 656 + (lane >> 3) * 128 + w * 16 +
               ((g < 4 ? (w * 4 + c) * 4 + g : w * 4 + c) << 13);
    }
    k.dp = mapa(sb, rank ^ 1) - sb;
    k.lw = lw;
    asm volatile("" : "+r"(k.lw));
    k.w = w;
    const int e0 = (p.chains & 1) ? 64 : 0, o1 = (p.chains & 2) ? p.lag : 1000, nit = (p.chains & 2) ? p.lag + 64 : e0;
    const uint32_t zero = p.zero;
    int it = 0, X = e0 ? 0 : 1;
#pragma unroll 1
    while (it < nit) {
        rec_step(k, sb, X, X ? it - o1 : it, zero, o1, e0 - o1, o1 + 1 - X, wq, wk, wv, wo);
        if (X == 0 && it >= o1) X = 1; else { it++; X = it < e0 ? 0 : 1; }
    }
}

__device__ __forceinline__ uint32_t mism(uint32_t a, uint32_t b, uint32_t t) {
    uint32_t d; asm("lop3.b32 %0,%1,%2,%3,0x7e;" : "=r"(d) : "r"(a), "r"(b), "r"(t)); return d;
}
__device__ __forceinline__ uint32_t or3(uint32_t a, uint32_t b, uint32_t c) {
    uint32_t d; asm("lop3.b32 %0,%1,%2,%3,0xfe;" : "=r"(d) : "r"(a), "r"(b), "r"(c)); return d;
}
template <bool TWO, class F>
__device__ __forceinline__ void poll8(uint4* x, const uint4* src, uint32_t tag, F&& use) {
#pragma unroll
    for (int j = 0; j < 8; j++) x[j] = ld_rlx128(src + j * 32);
    int n = 0;
    while (true) {
        use();
        uint32_t bad = or3(mism(x[0].x, x[1].x, tag), mism(x[2].x, x[3].x, tag), mism(x[4].x, x[5].x, tag));
        if (TWO) bad = or3(bad, or3(mism(x[0].z, x[1].z, tag), mism(x[2].z, x[3].z, tag), mism(x[4].z, x[5].z, tag)), mism(x[6].z, x[7].z, tag));
        if (!__any_sync(0xffffffffu, (bad | mism(x[6].x, x[7].x, tag)) & 1)) break;
#pragma unroll
        for (int j = 0; j < 8; j++)
            asm volatile("{.reg .pred p; .reg .b128 t; .reg .b32 m; lop3.b32 m,%0,%6,%5,0x7e; and.b32 m,m,1; setp.ne.u32 p,m,0; mov.b128 t,{%0,%1,%2,%3};"
                         "@p ld.relaxed.gpu.global.b128 t,[%4]; mov.b128 {%0,%1,%2,%3},t;}"
                         : "+r"(x[j].x), "+r"(x[j].y), "+r"(x[j].z), "+r"(x[j].w) : "l"(src + j * 32), "r"(tag), "r"(TWO ? x[j].z : tag) : "memory");
        if (++n > 2000000) __trap();
    }
}

__device__ __forceinline__ void rec_comm(const Params& p, uint32_t sb, int X, int head, uint32_t rank) {
    const int lane = threadIdx.x & 31, g = lane >> 2, c = lane & 3;
    const int me = head * 2 + rank;
    const uint32_t mb = sb + R_M + X * 4096 + lane * 16;
    uint4 x[8];
#pragma unroll
    for (int j = 0; j < 8; j++) x[j] = *(const uint4*)(p.mem0 + (lane & 7) * 512 + rank * 256 + (j * 4 + (lane >> 3)) * 8);
    const uint32_t sl = lds32(sb + R_SEL + me * 4);
    const uint4* src1 = xregion(X, me) + ((sl >> X) & 1) * 256 + (c >> 1) * 16 + (g >> 2) * 8 + (c & 1) * 4 + (g & 3);
    const uint4* src2 = xregion(X, 64 + rank) + ((sl >> (2 + X)) & 1) * 256 + lane;
    uint2* mdst = (uint2*)(xregion(X, 64 + rank) + (c >> 1) * 256 + head * 8 + (g & 3) * 2 + (c & 1)) + (g >> 2);
    const uint32_t one = (g & 1) ? 0x3f800000u : 0x00003f80u, selA = (g & 2) ? 0u : one, selB = (g & 2) ? one : 0u;
    const uint32_t qb = sb + R_BAR + (RB_QK + X * 8) * 8;
    if (lane < 8) mbar_expect(qb + lane * 8, 768);
    __syncwarp();
#pragma unroll
    for (int j = 0; j < 8; j++) sts128(mb + j * 512, x[j].x, x[j].y, x[j].z, x[j].w);
#pragma unroll 1
    for (int s = 0;; s++) {
        bar_arrive(NB_MFULL + X, 288);
        PROF(lane == 0, X * 64 + s);
        bar_sync(NB_PART + X, 288);
        if (s == 63) break;
        const uint32_t tag = (s + 1) & 1;
        asm volatile("{.reg .pred p; setp.lt.u32 p,%0,%1; @p mbarrier.arrive.expect_tx.shared::cta.b64 _,[%0],768;}"
                     ::"r"(((mb + (s & p.zero)) >> 1) + (qb - ((sb + R_M + X * 4096) >> 1))), "r"(qb + 64) : "memory");
        spin(D1);
        uint32_t m0, m1;
        poll8<false>(x, src1, tag, [&]() {
            float a[RACC][4];
#pragma unroll
            for (int j = 0; j < 8; j++) {
                if (j < RACC) a[j][0] = a[j][1] = a[j][2] = a[j][3] = 0;
                mma16(a[j % RACC], x[j].x, x[j].y, x[j].z, x[j].w, selA, selB);
            }
#pragma unroll
            for (int i = 0; i < 4; i++) a[0][i] = RACC == 3 ? a[0][i] + a[1][i] + a[2 % RACC][i] : a[0][i] + a[1][i];
            m0 = (pack2(a[0][0], a[0][1]) & ~1u) | tag; m1 = pack2(a[0][2], a[0][3]);
        });
        asm volatile("st.relaxed.gpu.global.b64 [%0],%1;" ::"l"(mdst), "l"(((uint64_t)m1 << 32) | m0) : "memory");
        spin(D2);
        poll8<true>(x, src2, tag, [&]() {
#pragma unroll
            for (int j = 0; j < 8; j++) sts128(mb + j * 512, x[j].x, x[j].y, x[j].z, x[j].w);
        });
    }
}

template <int MT>
__device__ __forceinline__ void xattn(uint32_t l16, uint32_t l8, uint32_t os, int g, int c) {
    constexpr int NT = 3 + 2 * MT, XUN = XU;
    float S[NT][4];
#pragma unroll
    for (int i = 0; i < NT; i++) S[i][0] = S[i][1] = S[i][2] = S[i][3] = 0;
#pragma unroll XUN
    for (int ks = 0; ks < 8; ks++) {
        const uint4 q = lds128(l16 + SL_Q + ks * 512);
        const uint2 u = lds64(l8 + SL_KM + ks * 256);
        mma16(S[0], q.x, q.y, q.z, q.w, u.x, u.y);
#pragma unroll
        for (int m = 0; m <= MT; m++) {
            const uint4 kk = lds128(l16 + m * 4096 + ks * 512);
            mma16(S[1 + 2 * m], q.x, q.y, q.z, q.w, kk.x, kk.z); mma16(S[2 + 2 * m], q.x, q.y, q.z, q.w, kk.y, kk.w);
        }
    }
    const float NEG = -__int_as_float(0x7f800000);
    if (2 * c > g) { S[NT - 2][0] = NEG; S[NT - 1][2] = NEG; }
    if (2 * c + 1 > g) { S[NT - 2][1] = NEG; S[NT - 1][3] = NEG; }
    S[NT - 1][0] = S[NT - 1][1] = NEG;
    float m0 = fmaxf(S[0][0], S[0][1]), m1 = fmaxf(S[0][2], S[0][3]);
#pragma unroll
    for (int i = 1; i < NT; i++) { if (i < NT - 1) m0 = fmaxf(m0, fmaxf(S[i][0], S[i][1])); m1 = fmaxf(m1, fmaxf(S[i][2], S[i][3])); }
    m0 = fmaxf(m0, __shfl_xor_sync(0xffffffffu, m0, 1)); m1 = fmaxf(m1, __shfl_xor_sync(0xffffffffu, m1, 1));
    m0 = fmaxf(m0, __shfl_xor_sync(0xffffffffu, m0, 2)); m1 = fmaxf(m1, __shfl_xor_sync(0xffffffffu, m1, 2));
    m0 *= -SC_LOG2E; m1 *= -SC_LOG2E;
    float l0 = 0, l1 = 0;
#pragma unroll
    for (int i = 0; i < NT; i++) {
        if (i < NT - 1) { S[i][0] = ex2(fmaf(S[i][0], SC_LOG2E, m0)); S[i][1] = ex2(fmaf(S[i][1], SC_LOG2E, m0)); l0 += S[i][0] + S[i][1]; }
        S[i][2] = ex2(fmaf(S[i][2], SC_LOG2E, m1)); S[i][3] = ex2(fmaf(S[i][3], SC_LOG2E, m1)); l1 += S[i][2] + S[i][3];
    }
    l0 += __shfl_xor_sync(0xffffffffu, l0, 1); l1 += __shfl_xor_sync(0xffffffffu, l1, 1);
    l0 += __shfl_xor_sync(0xffffffffu, l0, 2); l1 += __shfl_xor_sync(0xffffffffu, l1, 2);
    uint2 vm = lds64(l8 + SL_VM);
    uint4 v[2];
#pragma unroll
    for (int m = 0; m <= MT; m++) v[m] = lds128(l16 + SL_V + m * 4096);
    l0 = rcp(l0); l1 = rcp(l1);
    uint32_t P[NT][2];
#pragma unroll
    for (int i = 0; i < NT; i++) { P[i][0] = i < NT - 1 ? pack2(S[i][0] * l0, S[i][1] * l0) : 0u; P[i][1] = pack2(S[i][2] * l1, S[i][3] * l1); }
#pragma unroll
    for (int et = 0; et < 8; et++) {
        float a[4] = {0, 0, 0, 0}, b[4] = {0, 0, 0, 0};
        const uint2 um = vm;
        const uint4 u[2] = {v[0], v[MT]};
        if (et < 7) {
            vm = lds64(l8 + SL_VM + et * 256 + 256);
#pragma unroll
            for (int m = 0; m <= MT; m++) v[m] = lds128(l16 + SL_V + m * 4096 + et * 512 + 512);
            PIN(11);
        }
        mma8(a, um.x, um.y, P[0][0]); mma8(b, um.x, um.y, P[0][1]);
#pragma unroll
        for (int m = 0; m <= MT; m++) {
            mma16(a, u[m].x, u[m].y, u[m].z, u[m].w, P[1 + 2 * m][0], P[2 + 2 * m][0]); mma16(b, u[m].x, u[m].y, u[m].z, u[m].w, P[1 + 2 * m][1], P[2 + 2 * m][1]);
        }
        asm volatile("stmatrix.sync.aligned.m8n8.x4.trans.shared.b16 [%0],{%1,%2,%3,%4};" ::"r"(os + (et >> 2) * 2048 + (et & 3) * 256),
                     "r"(pack2(a[0], a[1])), "r"(pack2(a[2], a[3])), "r"(pack2(b[0], b[1])), "r"(pack2(b[2], b[3])) : "memory");
    }
}

__device__ __forceinline__ void rec_tiles(uint32_t sb, int X, int head, uint32_t rank, int& nxt, int lim, int need) {
#pragma unroll 1
    while (nxt <= lim) {
        if ((nxt & 1) == 0) {
            unsigned v; int n = 0;
            while (true) {
                asm volatile("ld.relaxed.gpu.global.u32 %0,[%1];" : "=r"(v) : "l"(cnt_ptr(C_QKV + X * 32 + (nxt >> 1))) : "memory");
                if (__all_sync(0xffffffffu, v >= 2 * NQ)) break;
                if (nxt > need) return;
                if (++n > 3000000) __trap();
            }
        }
        if (elect()) {
            const uint32_t bar = sb + R_BAR + (RB_XFULL + X * 2 + (nxt & 1)) * 8, dst = sb + R_SL + (X * 2 + (nxt & 1)) * SLOT;
            const uint4* src = g_qkv + (size_t)((X * 64 + nxt) * 32 + head) * 1536;
            mbar_expect(bar, 20480);
            bulk_g2s_mc(dst + rank * 8192, src + 512 + rank * 512, 8192, bar, POL_LAST);
            bulk_g2s(dst + SL_Q, src + (rank ^ X) * 256, 4096, bar, POL_LAST);
        }
        __syncwarp();
        nxt++;
    }
}

__device__ __forceinline__ void rec_attn(const Params& p, uint32_t sb, int X, int head, uint32_t rank) {
    const int lane = __shfl_sync(0xffffffffu, threadIdx.x & 31, threadIdx.x & 31), g = lane >> 2, c = lane & 3;
    const int mt = rank ^ X;
    const uint32_t dp = mapa(sb, rank ^ 1) - sb;
    int nxt = 0;
    rec_tiles(sb, X, head, rank, nxt, 1, 0);
#pragma unroll 1
    for (int s = 0; s < 64; s++) {
        const uint32_t so = sb + R_SL + (X * 2 + (s & 1)) * SLOT;
        while (nxt <= min(s + 1, 63)) {
            uint32_t ok;
            asm volatile("{.reg .pred p; mbarrier.test_wait.parity.shared::cta.b64 p,[%1],%2; selp.u32 %0,1,0,p;}" : "=r"(ok) : "r"(sb + R_BAR + (RB_GO + X * 2 + (s & 1)) * 8), "r"((s >> 1) & 1) : "memory");
            if (__any_sync(0xffffffffu, ok)) break;
            rec_tiles(sb, X, head, rank, nxt, s + 1, -1);
        }
        mbar_wait(sb + R_BAR + (RB_GO + X * 2 + (s & 1)) * 8, (s >> 1) & 1);
        if (elect()) asm volatile("cp.async.bulk.wait_group.read 0;" ::: "memory");
        __syncwarp();
        const uint32_t os = sb + R_OS + X * 4096 + (lane >> 4) * 1024 + (lane & 15) * 16;
        if (mt) xattn<1>(so + lane * 16, so + lane * 8, os, g, c); else xattn<0>(so + lane * 16, so + lane * 8, os, g, c);
        fence_async_smem();
        __syncwarp();
        const uint32_t svb = sb + R_BAR + (RB_SV + X * 2 + (s & 1)) * 8;
        if (elect()) {
            mbar_arrive(svb); mbar_arrive_cluster(svb + dp);
            const uint64_t pol = POL_SOON;
#pragma unroll
            for (int kb = 0; kb < 2; kb++)
                asm volatile("cp.async.bulk.global.shared::cta.bulk_group.L2::cache_hint [%0],[%1],%2,%3;" ::"l"(g_o + ((X * 32 + (s >> 1)) * 64 + head * 2 + kb) * 512 + ((s & 1) * 4 + mt * 2) * 64),
                             "r"(sb + R_OS + X * 4096 + kb * 2048), "r"(2048), "l"(pol) : "memory");
            asm volatile("cp.async.bulk.commit_group;" ::: "memory");
        }
        __syncwarp();
        if (s & 1) {
            if (elect()) { asm volatile("cp.async.bulk.wait_group 0;" ::: "memory"); red_relaxed(cnt_ptr(C_O + (X * 32 + (s >> 1)) * 4 + (head >> 3)), 1); }
            __syncwarp();
        }
        rec_tiles(sb, X, head, rank, nxt, min(s + 1, 63), s + 1);
        mbar_wait(svb, (s >> 1) & 1);
        rec_tiles(sb, X, head, rank, nxt, min(s + 2, 63), -1);
    }
}

__device__ __forceinline__ uint32_t timed_clear(unsigned* r, int lane) {
    uint32_t v = 0;
    const uint32_t t0 = clk32();
    asm volatile("{.reg .pred p; setp.eq.u32 p,%2,0; @p atom.relaxed.gpu.global.exch.b32 %0,[%1],0;}" : "+r"(v) : "l"(r), "r"(lane) : "memory");
    v = __shfl_sync(0xffffffffu, v, 0);
    asm volatile("{.reg .pred p; setp.eq.u32 p,%0,0x5a5a5a5b; @p nanosleep.u32 1;}" ::"r"(v) : "memory");
    return clk32() - t0;
}
__device__ __forceinline__ void rec_slots(int me, int w) {
    const int lane = threadIdx.x & 31;
    uint4* r = xregion(w & 1, (w & 2) ? 64 + (me & 1) : me) + ((w & 2) ? (me >> 1) * 8 : 0);
#pragma unroll 1
    for (int i = lane; i < ((w & 2) ? 8 : 256); i += 32) r[i] = r[i + 256] = make_uint4(0, 0, 0, 0);
    __syncwarp();
    uint32_t b0 = ~0u, b1 = ~0u;
#pragma unroll 1
    for (int i = 0; i < NPRB; i++) { b0 = min(b0, timed_clear((unsigned*)r, lane)); b1 = min(b1, timed_clear((unsigned*)(r + 256), lane)); }
    if (lane == 0) ((uint8_t*)g_sel)[me * 4 + w] = (b1 < b0) << w;
}

__device__ __forceinline__ void rec_init(uint32_t sb) {
    const uint32_t b = sb + R_BAR;
    const int i = threadIdx.x & 31;
    mbar_init(b + i * 8, i >= RB_SV ? 2 : 1);
    if (i == RB_INIT) mbar_expect(b + RB_INIT * 8, 196608);
    asm volatile("fence.mbarrier_init.release.cluster;" ::: "memory");
}
constexpr int G_BAR = B_BAR;
enum { GB_FULL = 0  , GB_EMPTY = 8  , GB_RS = 16, GB_SS = 17, GB_LAG = 18, GB_FREE = 19, GB_DONE = 20  , GB_N = 24 };
constexpr int Q_PRE = 8;
constexpr int NQRS = 2 * NQ - 64;
__device__ __forceinline__ void gemm_init(uint32_t sb, bool op) {
    const int i = threadIdx.x & 31;
    if (i < GB_N) mbar_init(sb + G_BAR + i * 8, i >= GB_DONE ? 4 : i == GB_FREE ? 8 : (i >= GB_EMPTY && i < GB_RS) ? 2 : 1);
    if (i == GB_RS) mbar_expect(sb + G_BAR + i * 8, op ? 131072 : 98304);
    if (i == GB_SS) mbar_expect(sb + G_BAR + i * 8, op ? 131072 : 163840);
    asm volatile("fence.mbarrier_init.release.cluster;" ::: "memory");
}
__device__ __forceinline__ int qkv_blk(int id, int j) { return NQRS * 4 + id * 10 + j; }
__device__ __forceinline__ void qkv_fetch(const Params& p, uint32_t sb, int id, int j0, int j1) {
#pragma unroll 1
    for (int j = j0 * 2; j < j1 * 2; j++) {
        const int blk = min(qkv_blk(id, j >> 1), 511);
        tma2d(sb + j * 8192, &p.tn[blk >> 8], (blk & 255) * 16, (j & 1) * 256, sb + G_BAR + GB_SS * 8);
    }
}
__device__ __forceinline__ void qkv_stage(const Params& p, uint32_t dst, uint32_t bar, int id, int k0, int nk) {
#pragma unroll 1
    for (int j = 0; j < 2 * nk; j++) {
        const int u = id * 2 + (j >= nk);
        tma2d(dst + j * 8192, &p.tm[u < 64 ? 2 : 0], (u & 63) * 64, (k0 + (j >= nk ? j - nk : j)) * 64, bar);
    }
}
__device__ __forceinline__ void op_fetch(const Params& p, uint32_t sb, int id, int half) {
#pragma unroll 1
    for (int j = 0; j < 16; j++) tma2d(sb + j * 8192, &p.tm[4], ((id * 2 + (j >> 3)) & 7) * 64, (id >> 2) * 1024 + (j & 7) * 128 + half * 64, sb + G_BAR + (GB_RS + half) * 8);
}
template <bool OP>
__device__ __forceinline__ void gemm_producer(const Params& p, uint32_t sb, int id) {
    constexpr int NS = OP ? 6 : 8, SB = OP ? 16384 : 8192, RB = OP ? 131072 : 163840;
    if (!elect()) return;
    mbar_wait(sb + G_BAR + GB_FREE * 8, 0);
    if (OP) op_fetch(p, sb, id, 1);
    else {
        mbar_expect(sb + G_BAR + GB_RS * 8, 32768);
        qkv_stage(p, sb + 196608, sb + G_BAR + GB_RS * 8, id, 6, 2);
        qkv_fetch(p, sb, id, Q_PRE, 10);
        mbar_wait(sb + G_BAR + GB_FREE * 8, 1);
    }
    wait_cnt(g_gate, lds32(sb + S_GATE));
    int st = 0; uint32_t ph = 1;
#pragma unroll 1
    for (int n = 0; n < p.nl[OP]; n++) {
        const int e = p.list[OP][n];
        wait_cnt(OP ? cnt_ptr(C_O + e * 4 + (id >> 2)) : cnt_ptr(C_XN + e), 16);
        PROF(true, 1024 + n * 4);
        const uint4* src = OP ? g_o + (e * 64 + (id >> 2) * 16) * 512 : g_xn + e * 4096;
#pragma unroll 1
        for (int s = 0; s < 8; s++) {
            mbar_wait(sb + G_BAR + (GB_EMPTY + st) * 8, ph);
            mbar_expect(sb + G_BAR + (GB_FULL + st) * 8, SB);
            bulk_g2s(sb + RB + st * SB, src + s * (SB / 16), SB, sb + G_BAR + (GB_FULL + st) * 8, POL_N);
            if (++st == NS) { st = 0; ph ^= 1; }
        }
    }
}
__device__ __forceinline__ void qkv_release(const Params& p, uint32_t sb) {
    if (!elect()) return;
#pragma unroll 1
    for (int n = 0; n < 2 * p.nl[0]; n++) {
        const int e = p.list[0][n >> 1];
        mbar_wait(sb + G_BAR + (GB_DONE + (n & 3)) * 8, (n >> 2) & 1);
        red_release(cnt_ptr(C_QKV + e), 1);
        PROF(n & 1, 1024 + (n >> 1) * 4 + 3);
    }
}
__device__ __forceinline__ void op_permute(uint32_t sb) {
#pragma unroll 2
    for (int i = threadIdx.x; i < 4096; i += 256) {
        const uint32_t a = sb + i * 32 + ((i >> 2) & 1) * 16, b = a ^ 16;
        const uint4 x = lds128(a), y = lds128(b);
        sts128(a, __byte_perm(x.x, x.y, 0x5410), __byte_perm(x.z, x.w, 0x5410), __byte_perm(y.x, y.y, 0x5410), __byte_perm(y.z, y.w, 0x5410));
        sts128(b, __byte_perm(x.x, x.y, 0x7632), __byte_perm(x.z, x.w, 0x7632), __byte_perm(y.x, y.y, 0x7632), __byte_perm(y.z, y.w, 0x7632));
    }
    fence_async_smem();
    bar_sync(1, 256);
}
template <bool OP>
__device__ __forceinline__ void gemm_consumer(const Params& p, uint32_t sb, int id, int w) {
    constexpr int NS = OP ? 6 : 8, SB = OP ? 16384 : 8192, RB = OP ? 131072 : 163840;
    const int lane = threadIdx.x & 31, wg = w >> 2, t = w & 3, u = id * 2 + wg;
    uint32_t a[128];
    mbar_wait(sb + G_BAR + GB_RS * 8, 0);
    PROF2(threadIdx.x == 0, 3501);
    if (OP) op_permute(sb);
    const uint32_t wo = sb + (((lane >> 4) << 3) + (lane & 7)) * 128 + (((2 * t + ((lane >> 3) & 1)) ^ (lane & 7)) << 4);
#pragma unroll
    for (int ks = 0; ks < 32; ks++) {
        const uint4 v = ldsm4t(wo + ks * 2048 + (OP ? wg * 65536 : ks < 24 ? 131072 + wg * 49152 : 196608 - 49152 + wg * 16384));
        a[ks * 4] = v.x; a[ks * 4 + 1] = v.y; a[ks * 4 + 2] = v.z; a[ks * 4 + 3] = v.w;
        if (ks == 31 || (!OP && ks == 23)) {
            fence_async_smem();
            __syncwarp();
            if (lane == 0) mbar_arrive(sb + G_BAR + GB_FREE * 8);
            if (ks == 23) mbar_wait(sb + G_BAR + GB_RS * 8, 1);
        }
    }
    PROF2(threadIdx.x == 0, 3502);
    mbar_wait(sb + G_BAR + GB_SS * 8, 0);
    if (OP) op_permute(sb);
    PROF2(threadIdx.x == 0, 3503);
    const uint32_t tag = OP ? lds32(sb + S_TAG) : 0;
    float c0[32], c1[OP ? 32 : 40];
    int st = 0; uint32_t ph = 0;
    const bool el = (threadIdx.x & 127) == 0;
#pragma unroll 1
    for (int n = 0; n < p.nl[OP]; n++) {
        int prev = 0;
        const uint32_t wb = sb + wg * (OP ? 65536 : 81920) + (n & p.zero);
        const uint64_t dw = OP ? mkdesc(wb, 0, 1024, 1) : mkdesc(wb, 16384, 256, 3);
        if (!OP && wg) mbar_wait(sb + G_BAR + GB_LAG * 8, n & 1);
#pragma unroll
        for (int s = 0; s < 8; s++) {
            mbar_wait(sb + G_BAR + (GB_FULL + st) * 8, ph);
            const uint64_t dx = mkdesc(sb + RB + st * SB, 128, 1024, 0);
            wg_fence();
#pragma unroll
            for (int kk = 0; kk < 4; kk++) {
                const int ks = s * 4 + kk;
                if (ks == 0) { wgmma64_rs<0>(c0, a, dx); if (OP) wgmma64_ta<0>(c1, dw, dx + 512); else wgmma80_tb<0>(c1, dx, dw); }
                else { wgmma64_rs<1>(c0, a + ks * 4, dx + kk * 16); if (OP) wgmma64_ta<1>(c1, dw + ks * 128, dx + 512 + kk * 16); else wgmma80_tb<1>(c1, dx + kk * 16, dw + ks * 32); }
            }
            wg_commit();
            if (s) {
                wg_wait<1>();
                if (el) { mbar_arrive(sb + G_BAR + (GB_EMPTY + prev) * 8); if (!OP && s == QLAG && !wg) mbar_arrive(sb + G_BAR + GB_LAG * 8); }
            }
            prev = st;
            if (++st == NS) { st = 0; ph ^= 1; }
        }
        const int e = p.list[OP][n];
        wg_wait<0>();
        if (el) mbar_arrive(sb + G_BAR + (GB_EMPTY + prev) * 8);
        PROF(threadIdx.x == 128, 1024 + n * 4 + 1);
        if (OP) {
            uint4* dst = g_pp + (e * 4 + (id >> 2)) * 4096 + ((u & 7) * 32 + t * 8) * 16 + (lane >> 2) * 16 + (lane & 3);
#pragma unroll
            for (int j = 0; j < 4; j++) {
                const float* x = c0 + j * 8; const float* y = c1 + j * 8;
                st_rlx128(dst + j * 4, (pack2(x[0] + y[0], x[1] + y[1]) & ~1u) | tag, pack2(x[2] + y[2], x[3] + y[3]), (pack2(x[4] + y[4], x[5] + y[5]) & ~1u) | tag, pack2(x[6] + y[6], x[7] + y[7]));
            }
            if (lane == 0) red_relaxed(cnt_ptr(C_PP + e * 8 + (u & 7)), 1);
            PROF(threadIdx.x == 128, 1024 + n * 4 + 3);
        } else {
            uint4* dst = g_qkv + (size_t)e * 2 * 32 * 1536 + lane;
            const uint64_t pol = POL_SOON;
#pragma unroll
            for (int j = 0; j < 4; j++) {
                const float* x = c0 + j * 8;
                uint4 v = make_uint4(pack2(x[0], x[1]), pack2(x[2], x[3]), pack2(x[4], x[5]), pack2(x[6], x[7]));
                if (u >= 64) v = make_uint4(movm(v.x), movm(v.z), movm(v.y), movm(v.w));
                stg128(dst + (((j >> 1) * 32 + ((u & 63) >> 1)) * 1536 + (u < 64 ? 1024 : 0) + (j & 1) * 256 + ((u & 1) * 4 + t) * 32), v, pol);
            }
#pragma unroll
            for (int j = 0; j < 5; j++) {
                const float* x = c1 + (OP ? 0 : j * 8);
                const int blk = qkv_blk(id, wg * 5 + j);
                if (blk < 512) stg128(dst + (((t >> 1) * 32 + ((blk >> 3) & 31)) * 1536 + (blk >> 8) * 512 + (t & 1) * 256 + (blk & 7) * 32),
                                      make_uint4(pack2(x[0], x[1]), pack2(x[2], x[3]), pack2(x[4], x[5]), pack2(x[6], x[7])), pol);
            }
        }
        __syncwarp();
        if (!OP && lane == 0) mbar_arrive(sb + G_BAR + (GB_DONE + (n & 1) * 2 + wg) * 8);
        PROF(threadIdx.x == 128, 1024 + n * 4 + 2);
    }
}

template <int NP, bool MMA>
__device__ __forceinline__ void sum_partials(float* x, const uint2* src, const uint32_t* r0, const uint32_t* r1, uint32_t idm, uint32_t tag, bool on) {
    uint2 v[4][NP];
    int n = 0;
    while (true) {
        uint32_t bad = 0;
#pragma unroll
        for (int s = 0; s < 4; s++)
#pragma unroll
            for (int i = 0; i < NP; i++)
                asm volatile("{.reg .pred p; .reg .b64 t; setp.ne.u32 p,%4,0; mov.b64 t,0; @p ld.relaxed.gpu.global.L2::cache_hint.b64 t,[%2],%3; mov.b64 {%0,%1},t;}"
                             : "=r"(v[s][i].x), "=r"(v[s][i].y) : "l"(src + s * 8192 + i * 32), "l"(POL_LAST), "r"((uint32_t)on) : "memory");
#pragma unroll
        for (int s = 0; s < 4; s++) bad = or3(bad, mism(v[s][0].x, v[s][1].x, tag), mism(v[s][NP - 2].x, v[s][NP - 1].x, tag));
        if (!__any_sync(0xffffffffu, (bad & 1) && on)) break;
        if (++n > 2000000) __trap();
    }
#pragma unroll
    for (int i = 0; i < NP; i++) {
        uint32_t a, b;
        if (MMA) {
            float t[4] = {0, 0, 0, 0};
            mma16(t, v[0][i].x, v[0][i].y, v[1][i].x, v[1][i].y, idm, idm); mma16(t, v[2][i].x, v[2][i].y, v[3][i].x, v[3][i].y, idm, idm);
            a = pack2(t[0], t[2]); b = pack2(t[1], t[3]);
        } else {
            a = pack2((blo(v[0][i].x) + blo(v[1][i].x)) + (blo(v[2][i].x) + blo(v[3][i].x)), (blo(v[0][i].y) + blo(v[1][i].y)) + (blo(v[2][i].y) + blo(v[3][i].y)));
            b = pack2((bhi(v[0][i].x) + bhi(v[1][i].x)) + (bhi(v[2][i].x) + bhi(v[3][i].x)), (bhi(v[0][i].y) + bhi(v[1][i].y)) + (bhi(v[2][i].y) + bhi(v[3][i].y)));
        }
        const uint32_t s0 = hadd2(a, r0[i]), s1 = hadd2(b, r1[i]);
        x[4 * i] = blo(s0); x[4 * i + 2] = bhi(s0); x[4 * i + 1] = blo(s1); x[4 * i + 3] = bhi(s1);
    }
}
__device__ __forceinline__ const uint2* pp_src(int e, int tile, int lane) { return (const uint2*)g_pp + e * 32768 + tile * 128 + (lane >> 3) * 8 + (lane & 3) * 2 + ((lane >> 2) & 1); }

__device__ __forceinline__ void fin_warp(const Params& p, uint32_t sb, int id) {
    const int grp = (id & ~3) + (threadIdx.x & 3), tp = (id & 3) * 8 + ((threadIdx.x & 31) >> 2);
    wait_slow_warp(g_gate, lds32(sb + S_GATE));
#pragma unroll 1
    for (int e = 32; e < 64; e++) {
        wait_slow_warp(cnt_ptr(C_XN + e), 16);
        const uint4 r = ldcg128(g_x + ((128 + grp) * XP + (e - 32) * 32 + tp));
        if (e < 63) wait_slow_warp(cnt_ptr(C_PP + e * 8 + (id >> 4)), 16); else wait_slow_warp(cnt_ptr(C_O + 63 * 4), 16);
        wait_flag_warp(cnt_ptr(C_PP + e * 8 + (id >> 4)), 16);
        const uint32_t a[2] = {r.x, r.y}, b[2] = {r.z, r.w};
        float x[8];
        sum_partials<2, false>(x, pp_src(e, 0, tp) + grp * 64, a, b, 0, lds32(sb + S_TAG), true);
        uint2* dst = (uint2*)p.out + ((e - 32) * 64 + tp * 2) * 128 + grp;
#pragma unroll
        for (int t = 0; t < 2; t++)
            dst[t * 128] = make_uint2(__byte_perm(__float_as_uint(x[t]), __float_as_uint(x[2 + t]), 0x7632), __byte_perm(__float_as_uint(x[4 + t]), __float_as_uint(x[6 + t]), 0x7632));
        PROF((threadIdx.x & 31) == 0, 1536 + e);
    }
}

constexpr int PROW = 272, UROW = 2304, UPRE = 256;
constexpr int C_UR = 0  , C_TB = 65536  , C_BG = C_TB + 51200,
              CB_M = 8960, CB_U = CB_M + 1792, CB_BIG = CB_U + 2560, C_ST = C_BG + 8 * CB_BIG  ;
static_assert(C_ST + 4736 <= B_BAR, "smem map");
enum { CB_TB = 0, CB_UF = 1  , CB_CF = 5  , CB_LD = 9   };
__device__ __forceinline__ void conv_init(uint32_t sb, bool spare) {
    const int i = threadIdx.x & 31;
    mbar_init(sb + B_BAR + i * 8, (i >= CB_UF && i < CB_CF && !spare) ? 2 : 1);
    if (i == CB_TB && !spare) mbar_expect(sb + B_BAR + i * 8, 51200);
    asm volatile("fence.mbarrier_init.release.cluster;" ::: "memory");
}
__device__ __forceinline__ void mma_q(float* c, const uint32_t* a, const uint4& q) {
    mma16(c, a[0], a[1], a[2], a[3], q.x, q.y); mma16(c, a[4], a[5], a[6], a[7], q.z, q.w);
}
__device__ __forceinline__ uint2 ld_acc(const uint2* p, bool on) {
    uint2 v = make_uint2(0, 0);
    asm volatile("{.reg .pred p; setp.ne.u32 p,%3,0; @p ld.global.cg.v2.u32 {%0,%1},[%2];}" : "+r"(v.x), "+r"(v.y) : "l"(p), "r"((uint32_t)on) : "memory");
    return v;
}
__device__ __forceinline__ void add_acc(float* c, uint2 v) { c[0] += blo(v.x); c[1] += bhi(v.x); c[2] += blo(v.y); c[3] += bhi(v.y); }
__device__ __forceinline__ void st_acc(uint2* p, const float* c) { *p = make_uint2(pack2(c[0], c[1]), pack2(c[2], c[3])); }
__device__ __forceinline__ float sum8(const uint4* v, int k) {
#define VK(i) __uint_as_float(k == 0 ? v[i].x : k == 1 ? v[i].y : k == 2 ? v[i].z : v[i].w)
    return ((VK(0) + VK(1)) + (VK(2) + VK(3))) + ((VK(4) + VK(5)) + (VK(6) + VK(7)));
}
template <int XW>
__device__ __forceinline__ void stats_send(uint32_t l16, const float* x, uint4* gs, int q, int w) {
    float s0 = 0, s1 = 0, m0 = 0, m1 = 0;
#pragma unroll
    for (int i = 0; i < 8; i++) { s0 += x[2 * i]; s1 += x[2 * i + 1]; m0 = fmaf(x[2 * i], x[2 * i], m0); m1 = fmaf(x[2 * i + 1], x[2 * i + 1], m1); }
    sts128(l16 + C_ST + w * 512, __float_as_uint(s0), __float_as_uint(m0), __float_as_uint(s1), __float_as_uint(m1));
    if (w == XW) {
        bar_sync(2, 256);
        uint4 v[8];
#pragma unroll
        for (int i = 0; i < 8; i++) v[i] = lds128(l16 + C_ST + i * 512);
        st_rlx128(gs + q * 32, __float_as_uint(sum8(v, 0)), __float_as_uint(sum8(v, 1)) & 0x7fffffffu, __float_as_uint(sum8(v, 2)), __float_as_uint(sum8(v, 3)));
    } else bar_arrive(2, 256);
}
template <int XW>
__device__ __forceinline__ float4 stats_recv(uint32_t l16, const uint4* gs, int w) {
    if (w == XW) {
        uint4 v[8];
        int n = 0;
        while (true) {
            uint32_t bad = 0;
#pragma unroll
            for (int i = 0; i < 8; i++) v[i] = ld_rlx128(gs + i * 32);
#pragma unroll
            for (int i = 0; i < 8; i++) bad |= v[i].y;
            if (!__any_sync(0xffffffffu, bad >> 31)) break;
            if (++n > 2000000) __trap();
        }
        const float s0 = sum8(v, 0) * (1.f / 512.f), s1 = sum8(v, 2) * (1.f / 512.f);
        const float2 l0 = ln_finish(s0, fmaxf(fmaf(sum8(v, 1), 1.f / 512.f, -s0 * s0), 0.f)), l1 = ln_finish(s1, fmaxf(fmaf(sum8(v, 3), 1.f / 512.f, -s1 * s1), 0.f));
        sts128(l16 + C_ST + 4096, __float_as_uint(l0.x), __float_as_uint(rcp(l0.y)), __float_as_uint(l1.x), __float_as_uint(rcp(l1.y)));
    }
    bar_sync(3, 256);
    const uint4 r = lds128(l16 + C_ST + 4096);
    return make_float4(__uint_as_float(r.x), __uint_as_float(r.y), __uint_as_float(r.z), __uint_as_float(r.w));
}

__device__ __forceinline__ void conv_near(float (*acc)[4], uint32_t ta, uint32_t qa) {
    uint32_t a[9][8];
    uint4 x[9];
#pragma unroll
    for (int k = 0; k < 9; k++) {
        if (k < 8) {
            x[k] = ldsm4(qa + k * 1024);
#pragma unroll
            for (int j = 0; j < 8; j++) a[k][j] = lds32(ta + k * 800 + j * 32);
        }
        if (k) mma_q(acc[k - 1], a[k - 1], x[k - 1]);
        PIN(13);
    }
}
template <int K0>
__device__ __forceinline__ void conv_pair(float (*acc)[4], float (*pend)[4], uint32_t ta, uint32_t q0, uint32_t q1, uint32_t q2) {
    uint32_t a[9][8];
    uint4 x[9], y[5];
#pragma unroll
    for (int n = 0; n < 9; n++) {
        if (n < 8) {
            const int k = K0 + (n >> 1);
            if (!(n & 1)) y[n >> 1] = ldsm4(q1 + k * 1024);
            x[n] = ldsm4(((n & 1) ? q0 : q2) + k * 1024);
#pragma unroll
            for (int j = 0; j < 8; j++) a[n][j] = lds32(ta + 256 + (n & 1) * 256 + k * 800 + j * 32);
        }
        if (n == 0) {
#pragma unroll
            for (int i = 0; i < 16; i++) { acc[4 - K0 + (i >> 2)][i & 3] += pend[i >> 2][i & 3]; pend[i >> 2][i & 3] = 0; }
        } else {
            const int m = n - 1, i = m >> 1;
            mma_q(acc[K0 + i], a[m], (m & 1) ? x[m] : y[i]); mma_q(pend[i], a[m], (m & 1) ? y[i] : x[m]);
        }
        PIN(13);
    }
}

__device__ __forceinline__ void conv_tile(const Params& p, uint32_t sb, int q, int w) {
    const int lane = __shfl_sync(0xffffffffu, threadIdx.x & 31, threadIdx.x & 31), g = lane >> 2, c = lane & 3, tile = q * 8 + w;
    const uint32_t l16 = sb + lane * 16;
#pragma unroll
    for (int i = 0; i < 16; i++) sts128(l16 + C_UR + w * 8192 + i * 512, 0, 0, 0, 0);
    wait_slow_warp(g_gate, lds32(sb + S_GATE));
    if (lane < 8) bulk_g2s(sb + C_TB + (w * 8 + lane) * 800, g_P + (tile * 8 + lane) * PROW + 72, 800, sb + B_BAR + CB_TB * 8, POL_N);
    uint32_t A[8][8];
#pragma unroll
    for (int k = 0; k < 8; k++)
#pragma unroll
        for (int j = 0; j < 8; j++) A[k][j] = __ldcg(g_P + (tile * 8 + k) * PROW + 16 + 8 * j + g - 2 * c);
    if (lane == 0) { const uint4 d = __ldg((const uint4*)p.Dskip + tile); sts128(sb + C_ST + 4608 + w * 16, d.x, d.y, d.z, d.w); }
    float acc[8][4], pend[4][4];
#pragma unroll
    for (int k = 0; k < 8; k++) acc[k][0] = acc[k][1] = acc[k][2] = acc[k][3] = pend[k & 3][k >> 2] = pend[k & 3][2 + (k >> 2)] = 0;
    const uint32_t row = sb + C_UR + w * 8192, ta = sb + C_TB + w * 6400 + (8 + g - 2 * c) * 4, qo = (lane & 7) * 16 - (lane >> 3) * 32;
    bar_sync(4, 384);
    mbar_wait(sb + B_BAR + CB_TB * 8, 0);
#pragma unroll 1
    for (int b = -2; b < 32; b++) {
        const int lz = lane + (b & p.zero);
        const bool on = b >= 0;
        uint4 r0 = make_uint4(0, 0, 0, 0), r1 = r0;
        asm volatile("{.reg .pred p; setp.ge.s32 p,%9,0; @p ld.global.cg.v4.u32 {%0,%1,%2,%3},[%8]; @p ld.global.cg.v4.u32 {%4,%5,%6,%7},[%8+%10];}"
                     : "+r"(r0.x), "+r"(r0.y), "+r"(r0.z), "+r"(r0.w), "+r"(r1.x), "+r"(r1.y), "+r"(r1.z), "+r"(r1.w) : "l"(g_x + (tile * 2 * XP + b * 32 + lz)), "r"(b), "n"(XP * 16) : "memory");
        const uint32_t q1 = row + ((qo + (b - 1) * 128) & 1023);
        if ((NTOP >> w) & 1) conv_near(acc, ta, q1);
        PROF2(threadIdx.x == 0 && on, 2048 + b * 8);
        const uint2* pps = pp_src(b, tile, lz);
        asm volatile("" : "+l"(pps));
        const uint32_t tag = lds32(sb + S_TAG);
        wait_flag_warp(cnt_ptr(C_PP + b * 8 + q), on ? 16 : 0);
        PROF2(threadIdx.x == 0 && on, 2048 + b * 8 + 1);
        float x[16];
        {
            const uint32_t a[4] = {r0.x, r0.y, r1.x, r1.y}, bb[4] = {r0.z, r0.w, r1.z, r1.w};
            sum_partials<4, true>(x, pps, a, bb, (2 * (lz & 3) == lz >> 2) ? 0x00003f80u : (2 * (lz & 3) + 1 == lz >> 2) ? 0x3f800000u : 0u, tag, on);
        }
        stats_send<0>(l16, x, g_st + (b + 2) * 256 + lz, q, w);
        {
            PROF2(threadIdx.x == 0 && on, 2048 + b * 8 + 2);
            if (on) mbar_wait(sb + B_BAR + (CB_CF + (w >> 1)) * 8, b & 1);
            const uint2* cb = g_carry + ((tile * 320 + b) * 32 + lz);
            uint2 cr[8];
#pragma unroll
            for (int k = 0; k < 8; k++) cr[k] = ld_acc(cb + k * 1280, b >= 4);
            if (NTOP != 255 && !((NTOP >> w) & 1) && b) conv_near(acc, ta, q1);
#pragma unroll
            for (int k = 0; k < 8; k++) add_acc(acc[k], cr[k]);
        }
        PIN(13);
        float4 ln = stats_recv<0>(l16, g_st + (b + 2) * 256 + lz, w);
        PROF2(threadIdx.x == 0 && on, 2048 + b * 8 + 3);
        uint32_t u[8];
#pragma unroll
        for (int k = 0; k < 8; k++) {
            u[k] = pack2(rbf(x[2 * k] - ln.x) * ln.y, rbf(x[2 * k + 1] - ln.z) * ln.w);
            sts32(row + k * 1024 + (b & 7) * 128 + lane * 4, u[k]);
        }
        __syncwarp();
        const uint32_t qa = row + ((qo + b * 128) & 1023);
#pragma unroll
        for (int k = 0; k < 8; k++) mma_q(acc[k], A[k], ldsm4(qa + k * 1024));
        const uint4 dk = lds128(sb + C_ST + 4608 + w * 16);
#pragma unroll
        for (int k = 0; k < 8; k++) {
            const float t = __shfl_sync(0xffffffffu, acc[k][3], (lz & ~3) | ((lz - 1) & 3));
            const uint32_t y = movm(pack2(acc[k][0] + (c ? t : 0.f), acc[k][1] + acc[k][2]));
            acc[k][0] = c ? 0.f : t; acc[k][1] = acc[k][2] = acc[k][3] = 0;
            const uint32_t dw = k >> 1 == 0 ? dk.x : k >> 1 == 1 ? dk.y : k >> 1 == 2 ? dk.z : dk.w;
            const uint32_t s = hadd2(hadd2(y, hmul2(u[k], __byte_perm(dw, 0, (k & 1) ? 0x3232 : 0x1010))), __byte_perm(__float_as_uint(x[2 * k]), __float_as_uint(x[2 * k + 1]), 0x7632));
            x[2 * k] = blo(s); x[2 * k + 1] = bhi(s);
        }
        arrive_if(sb + B_BAR + (CB_UF + (w >> 1)) * 8, lz, b < -1 ? 32 : 0);
        stats_send<1>(l16, x, g_st + (36 + b) * 256 + lz, q, w);
        {
            PROF2(threadIdx.x == 0 && on, 2048 + b * 8 + 4);
            uint4* dst = g_x + ((128 + tile * 2) * XP + b * 32 + lz);
#pragma unroll
            for (int e = 0; e < 2; e++) {
                const float* y = x + e * 8;
                if (on) dst[e * XP] = make_uint4(__byte_perm(__float_as_uint(y[0]), __float_as_uint(y[2]), 0x7632), __byte_perm(__float_as_uint(y[4]), __float_as_uint(y[6]), 0x7632),
                                           __byte_perm(__float_as_uint(y[1]), __float_as_uint(y[3]), 0x7632), __byte_perm(__float_as_uint(y[5]), __float_as_uint(y[7]), 0x7632));
            }
            uint32_t* du = g_u + (tile * 8 * (UROW / 2) + UPRE / 2 + b * 32 + lz);
#pragma unroll
            for (int k = 0; k < 8; k++) if (on) du[k * (UROW / 2)] = u[k];
        }
#pragma unroll 1
        for (int pass = 0; pass < 2; pass++) {
            if (pass == ((PLATE >> w) & 1)) {
                const uint32_t q0 = row + ((qo + (b - 2) * 128) & 1023);
                if (b & 1) conv_pair<4>(acc, pend, ta, q0, q1, qa); else conv_pair<0>(acc, pend, ta, q0, q1, qa);
            }
            if (pass) break;
            ln = stats_recv<1>(l16, g_st + (36 + b) * 256 + lz, w);
            PROF2(threadIdx.x == 0 && on, 2048 + b * 8 + 5);
            uint32_t o[2][4];
#pragma unroll
            for (int e = 0; e < 2; e++) {
                const float mu = e ? ln.z : ln.x, rs = e ? ln.w : ln.y;
#pragma unroll
                for (int i = 0; i < 4; i++) o[e][i] = pack2(rbf(x[4 * i + e] - mu) * rs, rbf(x[4 * i + 2 + e] - mu) * rs);
            }
#pragma unroll
            for (int i = 0; i < 4; i++) {
                const uint32_t t = __shfl_xor_sync(0xffffffffu, (lz & 1) ? o[0][i] : o[1][i], 1);
                if (lz & 1) o[0][i] = t; else o[1][i] = t;
            }
            uint4* dst = g_xn + ((32 + b) * 4096 + q * 512 + (lz >> 2) * 64 + w * 8 + (lz & 2) * 2 + (lz & 1));
            if (on) { dst[0] = make_uint4(o[0][0], o[0][1], o[0][2], o[0][3]); dst[2] = make_uint4(o[1][0], o[1][1], o[1][2], o[1][3]); }
            if (w == 7) {
                bar_sync(5, 256);
                if (elect()) red_release(cnt_ptr(on ? C_XN + 32 + b : C_FAR + 2), 2);
                PROF(lane == 0 && on, 2048 + b * 8 + 6);
                __syncwarp();
            } else bar_arrive(5, 256);
        }
    }
}

template <int P0, bool TRI = false>
__device__ __forceinline__ void bg_half(float (*acc)[4], uint4* win, uint32_t ta, uint32_t qa, uint32_t mask, uint32_t row) {
#pragma unroll
    for (int i = 0; i < 4; i++) {
        win[P0 + i] = ldsm4(((qa + i * 128) & mask) + row);
        const uint4 a = lds128(ta + (3 - i) * 448), e = lds128(ta + (3 - i) * 448 + 224);
#pragma unroll
        for (int r = TRI ? 7 - P0 - i : 0; r < 8; r++) mma16(acc[r], a.x, a.y, a.z, a.w, win[(P0 + i + 1 + r) & 7].x, win[(P0 + i + 1 + r) & 7].y);
#pragma unroll
        for (int r = TRI ? 7 - P0 - i : 0; r < 8; r++) mma16(acc[r], e.x, e.y, e.z, e.w, win[(P0 + i + 1 + r) & 7].z, win[(P0 + i + 1 + r) & 7].w);
    }
}
__device__ __forceinline__ void bg_fetch(uint32_t sb, int q, int j, int n, int lane) {
    const int b0 = n >> 1, ch = q * 64 + j * 16 + (n & 1) * 8 + (b0 & 7), lo = max(b0 - 24, -4), nu = b0 > 4 ? (b0 - 4 - lo) * 128 : 0;
    const uint32_t bar = sb + B_BAR + (CB_LD + j * 2 + (n & 1)) * 8, buf = sb + C_BG + (j * 2 + (n & 1)) * CB_BIG;
    const int nt = min(max((b0 + 7) >> 2, 2), 5) * 1792;
    if (elect()) {
        mbar_expect(bar, nt + nu + 1792);
        bulk_g2s(buf, g_W + ch * 784, nt, bar, POL_N);
        bulk_g2s(buf + CB_M, g_W + (ch ^ 4) * 784, 1792, bar, POL_N);
        if (nu) bulk_g2s(buf + CB_U + (lo - b0 + 24) * 128, g_u + ch * (UROW / 2) + UPRE / 2 + lo * 32, nu, bar, POL_N);
    }
    __syncwarp();
}
__device__ __forceinline__ void conv_back(uint32_t sb, int q, int j) {
    const int lane = __shfl_sync(0xffffffffu, threadIdx.x & 31, threadIdx.x & 31), g = lane >> 2, c = lane & 3;
    wait_slow_warp(g_gate, lds32(sb + S_GATE));
    bg_fetch(sb, q, j, 0, lane);
    bar_sync(4, 384);
    const uint32_t to = (6 + g - 2 * c) * 16, qo = (lane & 7) * 16 - (lane >> 3) * 32;
#pragma unroll 1
    for (int n = 0; n < 64; n++) {
        const int b0 = n >> 1, i = n & 1, chl = j * 16 + i * 8 + (b0 & 7), hm = (b0 + 7) >> 2;
        const uint32_t buf = sb + C_BG + (j * 2 + i) * CB_BIG, ta = buf + to;
        float acc[8][4];
        uint4 win[8];
        if (n < 63) bg_fetch(sb, q, j, n + 1, lane);
        if (n == 34 || n == 42) wait_flag_warp(cnt_ptr(C_FAR + (n == 42)), 12);
        mbar_wait(sb + B_BAR + (CB_LD + j * 2 + i) * 8, b0 & 1);
#pragma unroll
        for (int r = 0; r < 8; r++) {
            acc[r][0] = acc[r][1] = acc[r][2] = acc[r][3] = 0;
            win[r] = make_uint4(0, 0, 0, 0);
            if (r) asm volatile("{.reg .pred p; setp.ge.s32 p,%5,24; @p ldmatrix.sync.aligned.m8n8.x4.shared.b16 {%0,%1,%2,%3},[%4];}"
                                : "+r"(win[r].x), "+r"(win[r].y), "+r"(win[r].z), "+r"(win[r].w) : "r"(buf + CB_U + qo + r * 128), "r"(b0 + r) : "memory");
        }
        const uint2* fr = g_far + (((q * 64 + chl) * 8 + b0 - 24) * 32 + lane);
        uint2* cr = g_carry + (((q * 64 + chl) * 40 + b0) * 32 + lane);
        uint2* cm = g_carry + (((q * 64 + (chl ^ 4)) * 40 + b0) * 32 + lane);
        const uint32_t fm = 0xff000000u >> b0;
        uint2 pf[8], pm[4];
#pragma unroll
        for (int r = 0; r < 8; r++) pf[r] = ld_acc(fr + r * 32, (fm >> r) & 1);
#pragma unroll
        for (int r = 0; r < 4; r++) pm[r] = ld_acc(cm + r * 32, b0 > 4);
#pragma unroll 1
        for (int h = hm > 3 ? 5 : 3; h >= 3; h -= 2) {
            if (h <= hm) bg_half<0>(acc, win, ta + (h - 1) * 1792, qo + (28 - 4 * h) * 128, ~0u, buf + CB_U);
            if (h == 3 && i == 0) mbar_wait(sb + B_BAR + (CB_UF + j) * 8, b0 & 1);
            bg_half<4>(acc, win, ta + (h - 2) * 1792, qo + (h == 3 ? b0 - 4 : 12) * 128, h == 3 ? 1023u : ~0u, h == 3 ? sb + C_UR + chl * 1024 : buf + CB_U);
        }
        uint4 wm[8];
#pragma unroll
        for (int r = 1; r < 8; r++) wm[r] = ldsm4(sb + C_UR + (chl ^ 4) * 1024 + ((qo + (b0 + r) * 128) & 1023));
#pragma unroll
        for (int r = 0; r < 8; r++) add_acc(acc[r], pf[r]);
#pragma unroll
        for (int r = 4; r < 8; r++) { st_acc(cr + r * 32, acc[r]); acc[r][0] = blo(pm[r - 4].x); acc[r][1] = bhi(pm[r - 4].x); acc[r][2] = blo(pm[r - 4].y); acc[r][3] = bhi(pm[r - 4].y); }
#pragma unroll
        for (int t = 7; t >= 0; t--) {
            const uint4 a = lds128(ta + t * 224), e = lds128(ta + CB_M + t * 224);
#pragma unroll
            for (int r = 0; r < 4; r++) { const uint4& x = win[4 + r - (t >> 1)]; mma16(acc[r], a.x, a.y, a.z, a.w, (t & 1) ? x.z : x.x, (t & 1) ? x.w : x.y); }
#pragma unroll
            for (int r = 0; r < 4; r++) { const uint4& x = wm[4 + r - (t >> 1)]; mma16(acc[4 + r], e.x, e.y, e.z, e.w, (t & 1) ? x.z : x.x, (t & 1) ? x.w : x.y); }
        }
#pragma unroll
        for (int r = 0; r < 4; r++) { st_acc(cr + r * 32, acc[r]); st_acc(cm + r * 32, acc[4 + r]); }
        __syncwarp();
        if (lane == 0 && i) mbar_arrive(sb + B_BAR + (CB_CF + j) * 8);
        PROF(j == 0 && lane == 0 && i, 2048 + b0 * 8 + 7);
    }
}
__device__ __forceinline__ void conv_far(uint32_t sb, int w) {
    const int lane = __shfl_sync(0xffffffffu, threadIdx.x & 31, threadIdx.x & 31), g = lane >> 2, c = lane & 3;
    wait_slow_warp(g_gate, lds32(sb + S_GATE));
    wait_slow_warp(cnt_ptr(C_XN + 39), 16);
    const uint32_t to = (6 + g - 2 * c) * 16, qo = (lane & 7) * 16 - (lane >> 3) * 32;
#pragma unroll 1
    for (int n = -1; n * 12 + w < 512; n++) {
        const int t = n * 12 + w, ch = (t & 63) * 8 + (((t >> 6) + 1) & 7), cn = ((t + 12) & 63) * 8 + ((((t + 12) >> 6) + 1) & 7);
        const uint32_t bar = sb + B_BAR + (w * 2 + (n & 1)) * 8, buf = sb + (w * 2 + (n & 1)) * 5120;
        if (t + 12 < 512 && elect()) {
            const uint32_t nb = sb + (w * 2 + (~n & 1)) * 5120;
            mbar_expect(bar ^ 8, 3584 + 1152);
            bulk_g2s(nb, g_W + cn * 784 + 560, 3584, bar ^ 8, POL_N);
            bulk_g2s(nb + 3584, g_u + cn * (UROW / 2) + UPRE / 2 - 32, 1152, bar ^ 8, POL_N);
        }
        __syncwarp();
        if (n < 0) continue;
        float acc[8][4];
        uint4 win[8];
#pragma unroll
        for (int r = 0; r < 8; r++) { acc[r][0] = acc[r][1] = acc[r][2] = acc[r][3] = 0; win[r] = make_uint4(0, 0, 0, 0); }
        mbar_wait(bar, (n >> 1) & 1);
        bg_half<0, true>(acc, win, buf + to + 1792, qo + 128, ~0u, buf + 3584);
        bg_half<4, true>(acc, win, buf + to, qo + 640, ~0u, buf + 3584);
#pragma unroll
        for (int r = 0; r < 8; r++) st_acc(g_far + (ch * 256 + lane) + r * 32, acc[r]);
        __syncwarp();
        if (((t + 12) ^ t) >= 256 && elect()) red_release(cnt_ptr(C_FAR + (t >> 8)), 1);
        __syncwarp();
    }
    PROF(threadIdx.x == 0, 2048);
}

constexpr int P_X = 131072  , P_K6 = P_X + 32768  , P_P = P_K6 + 10496  , P_U = P_P + 33280  ,
              P_END = P_U + 17408, P_PRM = P_P + 8192  , P_Y = P_P  ;
static_assert(P_END <= B_BAR && P_END <= R_SEL, "prologue scratch");
#define KGUN 2
constexpr int KGU = KGUN;
__device__ __forceinline__ void csq(float& r, float& i) { const float t = r * i; r = fmaf(r, r, -(i * i)); i = t + t; }
__device__ __forceinline__ void cpow(float ar, float ph, float p, float& r, float& i) {
    const float e = ex2(ar * p);
    const float u = ph * p, n = fabsf(u) < 4194304.f ? (u + 12582912.f) - 12582912.f : u;
    const float t = (u - n) * 6.283185307179586f;
    r = e * __cosf(t); i = e * __sinf(t);
}
__device__ __forceinline__ void mma_tf32(float* c, float a0, float a1, float a2, float a3, float b0, float b1) {
    asm volatile("mma.sync.aligned.m16n8k8.row.col.f32.tf32.tf32.f32 {%0,%1,%2,%3},{%4,%5,%6,%7},{%8,%9},{%0,%1,%2,%3};"
                 : "+f"(c[0]), "+f"(c[1]), "+f"(c[2]), "+f"(c[3])
                 : "r"(__float_as_uint(a0)), "r"(__float_as_uint(a1)), "r"(__float_as_uint(a2)), "r"(__float_as_uint(a3)), "r"(__float_as_uint(b0)), "r"(__float_as_uint(b1)));
}

__device__ __forceinline__ void early_fetch(const Params& p, uint32_t sb) {
    const int v = blockIdx.x;
    if (elect()) {
        if (v >= V_QKV) { if (v < V_QKV + NQ && (p.roles & 8)) qkv_fetch(p, sb, v - V_QKV, 0, Q_PRE); }
        else if (v >= V_OP) { if (p.roles & 4) op_fetch(p, sb, v - V_OP, 0); }
        else if (REARLY && v >= V_REC && (p.roles & 2)) { rec_fetch(p, sb, (v - V_REC) >> 1, v & 1, 0, R_STQ); rec_fetch(p, sb, (v - V_REC) >> 1, v & 1, 2, R_STV); }
    }
    __syncwarp();
}
struct ProRegs { uint32_t v[2][4], ldt[2]; };
__device__ __forceinline__ void prologue_load(const ProArgs& a, int b, ProRegs& pr) {
    const int w = threadIdx.x >> 5;
#pragma unroll
    for (int i = 0; i < 2; i++) {
        const int gi = b * 512 + (w & 3) * 128 + ((w >> 2) & 1) * 64 + i * 32 + (threadIdx.x & 31);
        pr.ldt[i] = __ldg((const uint16_t*)a.ldt + b * 4 + (w & 3));
        pr.v[i][0] = __ldg((const uint16_t*)a.lAr + gi); pr.v[i][1] = __ldg((const uint16_t*)a.Ai + gi);
        pr.v[i][2] = __ldg((const uint16_t*)a.Cr + gi); pr.v[i][3] = __ldg((const uint16_t*)a.Ci + gi);
    }
}
__device__ __forceinline__ void prologue(const Params& p, uint32_t sb, int b, int w, const ProRegs& pr) {
    const ProArgs& a = p.pa;
    const int tid = threadIdx.x, lane = tid & 31, g = lane >> 2, c = lane & 3;
    const int d0 = b * 4;
    if (w >= 8) {
        const int t2 = tid - 256;
        if (w < 10) {
            const int row = b * 16 + (w - 8) * 8 + g;
            uint4 v[16];
            const float2 r = row_stats512(v, (const uint4*)(a.x + (size_t)row * 512) + c, 8, 4);
            const float2 l = ln_finish(r.x * (1.f / 512.f), r.y * (1.f / 512.f));
            if (c == (g >> 1)) asm volatile("st.relaxed.gpu.global.u32 [%0],%1;" ::"l"(g_ln0 + row), "r"(pack2(l.x, l.y)) : "memory");
            __syncwarp();
        } else if (PF0) {
            spin(PFD);
            if (elect()) {
#pragma unroll 1
                for (int i = w - 10; i < 4; i += 2) if ((PF0 >> i) & 1) asm volatile("cp.async.bulk.prefetch.L2.global [%0],%1;" ::"l"(a.W[i] + b * 16384), "r"(32768) : "memory");
            }
            __syncwarp();
        }
        if (b + 4 >= V_REC && b + 4 < V_OP) rec_slots(b + 4 - V_REC, (w & 3) ^ 2);
        PROF(t2 == 0, 3516);
        const int gi = b * 128 + t2;
        g_st[gi] = make_uint4(~0u, ~0u, ~0u, ~0u);
        if (gi < 1024) g_st[16384 + gi] = make_uint4(~0u, ~0u, ~0u, ~0u);
        if (gi < 900 * 8) g_cnt[gi] = 0;
        bar_sync(6, 384);
        if (lane < 4 && ((PFM >> (w - 8)) & 1)) asm volatile("cp.async.bulk.prefetch.L2.global [%0],%1;" ::"l"(a.W[w - 8] + (b * 4 + lane) * 4096), "r"(8192) : "memory");
        bar_sync(9, 384);
#pragma unroll 1
        for (int pass = 0; pass < 2; pass++) {
        if (w == 10 && pass == (b + 4 < EFS)) early_fetch(p, sb);
        if (pass) break;
#pragma unroll 2
        for (int i = t2; i < 4 * 784; i += 128) {
            const int ch = i / 784, k = i - ch * 784;
            const uint32_t o = sb + P_P + (ch * 2080 + 266 + (k / 14) * 18 + k) * 4;
            g_W[d0 * 784 + i] = make_uint4(lds32(o), lds32(o + 32), lds32(o + 64), lds32(o + 96));
        }
        bar_arrive(10, 384);
        }
        PROF(t2 == 0, 3517);
        return;
    }
#pragma unroll
    for (int i = 0; i < 2; i++) {
        const float dt = rbf(expf(blo(pr.ldt[i])));
        const float ar = -rbf(expf(blo(pr.v[i][0]))) * dt, ai = blo(pr.v[i][1]) * dt;
        sts128(sb + P_PRM + (w * 64 + i * 32 + lane) * 16, __float_as_uint(ar * 1.4426950408889634f), __float_as_uint(ai * 0.15915494309189535f),
               __float_as_uint(2.f * (blo(pr.v[i][2]) * dt)), __float_as_uint(2.f * (blo(pr.v[i][3]) * dt)));
    }
    if (tid < 64) sts128(sb + P_U + (tid >> 3) * 2176 + (tid & 7) * 16, 0, 0, 0, 0);
    bar_arrive(6, 384);
    __syncwarp();
    PROF(tid == 0, 3510);
    const int ch = w & 3, hf = w >> 2;
    {
        float k0[4] = {0, 0, 0, 0}, k1[4] = {0, 0, 0, 0}, k2[4] = {0, 0, 0, 0}, k3[4] = {0, 0, 0, 0}, k4[4] = {0, 0, 0, 0}, kl = 0;
#pragma unroll KGU
        for (int j = 0; j < 16; j++) {
            const uint4 q = lds128(sb + P_PRM + (w * 64 + j * 4 + c) * 16);
            const float cr = __uint_as_float(q.z), ci = __uint_as_float(q.w);
            float wr[4], wi[4], vr[4], vi[4];
            cpow(__uint_as_float(q.x), __uint_as_float(q.y), (float)g, wr[0], wi[0]);
            cpow(__uint_as_float(q.x), __uint_as_float(q.y), (float)(g + 8), vr[0], vi[0]);
#pragma unroll
            for (int i = 1; i < 4; i++) { wr[i] = wr[i - 1]; wi[i] = wi[i - 1]; csq(wr[i], wi[i]); vr[i] = vr[i - 1]; vi[i] = vi[i - 1]; csq(vr[i], vi[i]); }
            float hr = wr[3], hi = wi[3];
            csq(hr, hi);
            mma_tf32(k0, wr[0], vr[0], wi[0], vi[0], cr * hr - ci * hi, -(cr * hi + ci * hr));
            hr = vr[3]; hi = vi[3]; csq(hr, hi);
            mma_tf32(k1, wr[0], vr[0], wi[0], vi[0], cr * hr - ci * hi, -(cr * hi + ci * hr));
            csq(hr, hi);
            mma_tf32(k2, wr[1], vr[1], wi[1], vi[1], cr * hr - ci * hi, -(cr * hi + ci * hr));
            csq(hr, hi);
            mma_tf32(k3, wr[2], vr[2], wi[2], vi[2], cr * hr - ci * hi, -(cr * hi + ci * hr));
            csq(hr, hi);
            mma_tf32(k4, wr[3], vr[3], wi[3], vi[3], cr * hr - ci * hi, -(cr * hi + ci * hr));
            csq(hr, hi);
            kl += cr * hr - ci * hi;
        }
        kl += __shfl_xor_sync(0xffffffffu, kl, 1); kl += __shfl_xor_sync(0xffffffffu, kl, 2);
        const uint32_t o = sb + P_K6 + (ch * 656 + c * 32 + g) * 4, ol = sb + P_K6 + (ch * 656 + 640) * 4;
#define KST(k, base) sts32(o + (base) * 4, __float_as_uint(k[0])); sts32(o + (base) * 4 + 64, __float_as_uint(k[1])); \
                     sts32(o + (base) * 4 + 32, __float_as_uint(k[2])); sts32(o + (base) * 4 + 96, __float_as_uint(k[3]))
#define KAD(k, base) k[0] += __uint_as_float(lds32(o + (base) * 4)); k[1] += __uint_as_float(lds32(o + (base) * 4 + 64)); \
                     k[2] += __uint_as_float(lds32(o + (base) * 4 + 32)); k[3] += __uint_as_float(lds32(o + (base) * 4 + 96))
        if (hf == 0) {
            bar_sync(2 + ch, 64);
            KAD(k0, 0); KAD(k1, 128); KAD(k2, 256); KAD(k3, 384); KAD(k4, 512);
            kl += __uint_as_float(lds32(ol));
            __syncwarp();
        }
        KST(k0, 0); KST(k1, 128); KST(k2, 256); KST(k3, 384); KST(k4, 512);
        if (lane == 0) sts32(ol, __float_as_uint(kl));
        if (hf == 1) { __syncwarp(); bar_arrive(2 + ch, 64); }
    }
    PROF(tid == 0, 3511);
    {
        uint4 l0, l1;
        int n = 0;
        while (true) {
            l0 = ld_rlx128((const uint4*)g_ln0 + tid * 2); l1 = ld_rlx128((const uint4*)g_ln0 + tid * 2 + 1);
            if (__all_sync(0xffffffffu, l0.x && l0.y && l0.z && l0.w && l1.x && l1.y && l1.z && l1.w)) break;
            if (++n > 2000000) __trap();
        }
        sts128(sb + P_P + tid * 32, l0.x, l0.y, l0.z, l0.w); sts128(sb + P_P + tid * 32 + 16, l1.x, l1.y, l1.z, l1.w);
        bar_sync(8, 384);
        mbar_wait(sb + S_XBAR, 0);
        __syncwarp();
#pragma unroll 2
        for (int i = 0; i < 8; i++) {
            const int t = w * 256 + i * 32 + lane;
            const uint32_t ln = lds32(sb + P_P + t * 4);
            const uint2 x = lds64(sb + P_X + t * 16 + (b & 1) * 8);
            const float m = blo(ln), rs = rcp(bhi(ln));
            const uint32_t u0 = pack2(rbf(blo(x.x) - m) * rs, rbf(bhi(x.x) - m) * rs), u1 = pack2(rbf(blo(x.y) - m) * rs, rbf(bhi(x.y) - m) * rs);
            sts128(sb + P_X + t * 16, x.x, x.y, u0, u1);
            const uint32_t o = sb + P_U + ((t >> 3) & 1) * 2176 + ((t >> 4) + 8) * 16 + (t & 7) * 2;
            asm volatile("st.shared.u16 [%0],%1;" ::"r"(o), "h"((uint16_t)u0) : "memory");
            asm volatile("st.shared.u16 [%0],%1;" ::"r"(o + 4352), "h"((uint16_t)(u0 >> 16)) : "memory");
            asm volatile("st.shared.u16 [%0],%1;" ::"r"(o + 8704), "h"((uint16_t)u1) : "memory");
            asm volatile("st.shared.u16 [%0],%1;" ::"r"(o + 13056), "h"((uint16_t)(u1 >> 16)) : "memory");
        }
    }
    bar_sync(1, 256);
    PROF(tid == 0, 3512);
    if (tid < 64) sts32(sb + P_P + ((tid >> 4) * 2080 + (tid & 15)) * 4, 0);
#pragma unroll 1
    for (int x = tid; x < 2048; x += 512) {
        uint32_t pw[2][4];
#pragma unroll
        for (int h = 0; h < 2; h++) {
            const int y = x + h * 256;
            const int i0 = y <= 256 ? y : 256 + (int)((pack2((float)y, 0.f) & 0xffff) - 0x4380);
            const int i1 = y <= 256 ? max(y - 1, 0) : 256 + (int)((pack2((float)(y - 1), 0.f) & 0xffff) - 0x4380);
#pragma unroll
            for (int k = 0; k < 4; k++) {
                const float lo = __uint_as_float(lds32(sb + P_K6 + k * 2624 + i0 * 4)), hi = __uint_as_float(lds32(sb + P_K6 + k * 2624 + i1 * 4));
                pw[h][k] = pack2(lo, y ? hi : 0.f);
            }
        }
#pragma unroll
        for (int h = 0; h < 2; h++)
#pragma unroll
            for (int k = 0; k < 4; k++) sts32(sb + P_P + (k * 2080 + x + h * 256 + 16) * 4, pw[h][k]);
    }
    fence_async_smem();
    bar_arrive(9, 384);
    bar_sync(1, 256);
    if (tid < 4) {
        asm volatile("cp.async.bulk.global.shared::cta.bulk_group [%0],[%1],%2;" ::"l"(g_P + (d0 + tid) * PROW), "r"(sb + P_P + tid * 8320), "r"(PROW * 4) : "memory");
        asm volatile("cp.async.bulk.commit_group;" ::: "memory");
    }
    __syncwarp();
    PROF(tid == 0, 3513);
    {
        float acc[16][4];
#pragma unroll
        for (int j = 0; j < 16; j++) acc[j][0] = acc[j][1] = acc[j][2] = acc[j][3] = 0;
#pragma unroll 1
        for (int e = hf * 4; e < hf * 4 + 4; e++) {
            uint32_t B[16][2];
            const uint32_t ua = sb + P_U + ch * 4352 + ((lane >> 3) & 1) * 2176 + (8 + (lane >> 4) * 8 + (lane & 7) - e) * 16;
#pragma unroll
            for (int j = 0; j < 8; j++) { const uint4 v = ldsm4(ua + j * 256); B[2 * j][0] = v.x; B[2 * j][1] = v.y; B[2 * j + 1][0] = v.z; B[2 * j + 1][1] = v.w; }
            const uint32_t pa = sb + P_P + (ch * 2080 + 16 + e * 16 + g - 2 * c) * 4;
#pragma unroll
            for (int dd = 0; dd < 16; dd++) {
                const int d = (dd & 1) ? 15 - (dd >> 1) : dd >> 1;
                const uint32_t a0 = lds32(pa + d * 512), a1 = lds32(pa + d * 512 + 32), a2 = lds32(pa + d * 512 - 32), a3 = a0 + p.zero;
#pragma unroll
                for (int j = 0; j < 16; j++) if (j >= d) mma16(acc[j], a0, a1, a2, a3, B[(j - d) & 15][0], B[(j - d) & 15][1]);
            }
        }
        PROF(tid == 0, 3514);
        if (tid < 4) asm volatile("cp.async.bulk.wait_group 0;" ::: "memory");
        __syncwarp();
        bar_sync(10, 384);
#pragma unroll
        for (int j = 0; j < 8; j++) {
#pragma unroll
            for (int i = 0; i < 4; i++) { const float t = hf ? acc[j][i] : acc[j + 8][i]; acc[j][i] = hf ? acc[j + 8][i] : acc[j][i]; acc[j + 8][i] = t; }
            sts128(sb + P_Y + w * 4096 + j * 512 + lane * 16, __float_as_uint(acc[j + 8][0]), __float_as_uint(acc[j + 8][1]), __float_as_uint(acc[j + 8][2]), __float_as_uint(acc[j + 8][3]));
        }
        bar_sync(2 + ch, 64);
        uint32_t yp[16];
#pragma unroll
        for (int j = 0; j < 8; j++) {
            const uint4 t = lds128(sb + P_Y + (w ^ 4) * 4096 + j * 512 + lane * 16);
            yp[2 * j] = pack2(acc[j][0] + __uint_as_float(t.x), acc[j][1] + __uint_as_float(t.y)); yp[2 * j + 1] = pack2(acc[j][2] + __uint_as_float(t.z), acc[j][3] + __uint_as_float(t.w));
        }
#pragma unroll
        for (int j = 0; j < 4; j++)
            asm volatile("stmatrix.sync.aligned.m8n8.x4.trans.shared.b16 [%0],{%1,%2,%3,%4};" ::"r"(sb + P_Y + 32768 + ch * 4096 + hf * 2048 + j * 512 + (lane >> 4) * 256 + (lane & 7) * 32 + (lane & 8) * 2),
                         "r"(yp[4 * j]), "r"(yp[4 * j + 1]), "r"(yp[4 * j + 2]), "r"(yp[4 * j + 3]) : "memory");
    }
    const uint2 dk = __ldg((const uint2*)(a.Dk + d0));
    bar_sync(1, 256);
#pragma unroll 2
    for (int i = 0; i < 4; i++) {
        const int t = i * 256 + tid;
        const uint4 x0 = lds128(sb + P_X + t * 32), x1 = lds128(sb + P_X + t * 32 + 16);
        uint32_t y[4];
#pragma unroll
        for (int k = 0; k < 4; k++) y[k] = lds32(sb + P_Y + 32768 + k * 4096 + t * 4);
        g_x[b * XP + t] = make_uint4(hadd2(x0.x, hadd2(__byte_perm(y[0], y[1], 0x5410), hmul2(x0.z, dk.x))), hadd2(x0.y, hadd2(__byte_perm(y[2], y[3], 0x5410), hmul2(x0.w, dk.y))),
                                     hadd2(x1.x, hadd2(__byte_perm(y[0], y[1], 0x7632), hmul2(x1.z, dk.x))), hadd2(x1.y, hadd2(__byte_perm(y[2], y[3], 0x7632), hmul2(x1.w, dk.y))));
    }
    PROF(tid == 0, 3515);
}

__global__ void __cluster_dims__(2, 1, 1) __launch_bounds__(384, 1) main_kernel(const __grid_constant__ Params p) {
    extern __shared__ __align__(1024) uint8_t smem[];
    const uint32_t sb = smem_u32(smem);
    uint32_t rank; asm("mov.u32 %0,%%cluster_ctarank;" : "=r"(rank));
    const int wi = __shfl_sync(0xffffffffu, threadIdx.x >> 5, 0);
    const int v = blockIdx.x, cl = v >> 1, wg = wi >> 2;
    PROF(threadIdx.x == 0, 3500);
    ProRegs pr;
    prologue_load(p.pa, max((int)blockIdx.x - 4, 0), pr);
    if (wi == 11 && p.dopro && cl >= 2 && elect()) {
        mbar_init(sb + S_XBAR, 1);
        asm volatile("fence.mbarrier_init.release.cluster;" ::: "memory");
        mbar_expect(sb + S_XBAR, 32768);
        for (int j = 0; j < 8; j++) tma2d(sb + P_X + j * 4096, &p.tm[3], ((blockIdx.x - 4) >> 1) * 8, j * 256, sb + S_XBAR);
    }
    if (threadIdx.x == 320) {
        unsigned n;
        asm volatile("ld.relaxed.gpu.global.u32 %0,[%1];" : "=r"(n) : "l"(g_gate) : "memory");
        n = n / (4 * NCL) + p.dopro;
        sts64(sb + S_GATE, n * (4 * NCL), n & 1);
    }
    __syncwarp();
    if (wi == 10) {
        if (v < V_REC || v == 131) conv_init(sb, v == 131); else if (v < V_OP) rec_init(sb); else gemm_init(sb, v < V_QKV);
        __syncwarp();
    }
    if (wg == 2) bar_arrive(8, 384);
    asm volatile("barrier.cluster.arrive.relaxed.aligned;" ::: "memory");
    if (p.dopro && cl >= 2) prologue(p, sb, blockIdx.x - 4, wi, pr); else if (wg < 2) bar_sync(8, 384); else if (wi == 10) early_fetch(p, sb);
    asm volatile("barrier.cluster.wait.aligned;" ::: "memory");
    const int role = (v < V_REC ? 1 : v < V_OP ? 2 : v < V_QKV ? 20 : v < V_QKV + NQ ? 24 : 1) & p.roles;
    fence_async_smem();
    bar_sync(wg == 2 ? 7 : 1, wg == 2 ? 128 : 256);
    if (p.dopro && (threadIdx.x == 32 || threadIdx.x == 352)) red_release(g_gate, 1);
    PROF(threadIdx.x == 32, 3509);
    if (wi == 0 && (role & 8) && elect()) qkv_stage(p, sb + 131072, sb + G_BAR + GB_RS * 8, v - V_QKV, 0, 6);
    PROF(threadIdx.x == 0, 3506);
    __syncwarp();
    if (p.dopro && (v == 131 || (v >= V_REC && v < V_QKV && (v < V_OP ? wi == 8 : wi < 8)))) {
        bool on = v >= V_OP;
#pragma unroll 1
        for (int r = v == 131 ? 448 + wi : on ? 64 + (v - V_OP) * 8 + wi : v - V_REC; r < (v == 131 ? 512 : 448);) {
            if (v >= V_OP) wait_slow_warp(g_gate, lds32(sb + S_GATE)); else if (on) wait_flag_warp(g_gate, lds32(sb + S_GATE));
            PROF(threadIdx.x == 256 && on, 3507);
            x1_norm(on ? (const uint2*)g_x : (const uint2*)p.pa.x, r, on);
            __syncwarp();
            if (on && elect()) red_release(cnt_ptr(C_XN + (r >> 4)), 1);
            __syncwarp();
            PROF(threadIdx.x == 256, on ? 3508 : 3499);
            if (on) r += v < V_OP ? 512 : v == 131 ? 12 : 128;
            on = true;
        }
    }
    if (role == 2) {
        const int head = (v - V_REC) >> 1;
        if (wi == RFW && elect()) {
            if (!REARLY) { rec_fetch(p, sb, head, rank, 0, R_STQ); }
            rec_fetch(p, sb, head, rank, 1, R_STK);
            if (!REARLY) { rec_fetch(p, sb, head, rank, 2, R_STV); }
        }
        __syncwarp();
        if (wg == 2) {
            reg_dec<RH>();
            const int w = wi & 3;
            wait_slow_warp(g_gate, lds32(sb + S_GATE));
            if (w < 2) { const uint32_t x = __ldcg(g_sel + (threadIdx.x & 63)); sts32(sb + R_SEL + (threadIdx.x & 63) * 4, (x * 0x01010101u) >> 24); }
            __syncthreads();
            cluster_sync();
            if ((p.chains >> (w & 1)) & 1) { if (w < 2) rec_comm(p, sb, w, head, rank); else rec_attn(p, sb, w & 1, head, rank); }
        } else {
            reg_inc<RW0>();
            rec_weights(p, sb, head, rank, wi);
        }
    } else if (role == 1) {
        if (v == 131) conv_far(sb, wi); else if (wg == 2) { reg_dec<RCB>(); conv_back(sb, v, wi & 3); } else { reg_inc<RCU>(); conv_tile(p, sb, v, wi); }
    } else if (role && v < V_QKV) {
        if (wg == 2) {
            reg_dec<40>();
            if (wi == 8) { if (role & 4) gemm_producer<true>(p, sb, v - V_OP); }
            else if (v < V_OP + 14 && (role & 16)) fin_warp(p, sb, 2 * NQ + (v - V_OP) * 3 + wi - 9);
        } else { reg_inc<232>(); if (role & 4) gemm_consumer<true>(p, sb, v - V_OP, wi); }
    } else if (role) {
        if (wg == 2) {
            reg_dec<40>();
            if (wi < 10) {
                if (role & 8) { if (wi == 8) gemm_producer<false>(p, sb, v - V_QKV); else qkv_release(p, sb); }
            } else if (role & 16) fin_warp(p, sb, (v - V_QKV) * 2 + wi - 10);
        } else { reg_inc<232>(); if (role & 8) gemm_consumer<false>(p, sb, v - V_QKV, wi); }
    }
    __syncwarp();
    cluster_sync();
}

typedef CUresult (*EncFn)(CUtensorMap*, CUtensorMapDataType, cuuint32_t, void*, const cuuint64_t*, const cuuint64_t*, const cuuint32_t*, const cuuint32_t*,
                          CUtensorMapInterleave, CUtensorMapSwizzle, CUtensorMapL2promotion, CUtensorMapFloatOOBfill);
constexpr int SMEM_BYTES = 232448;
#define LAG 8
#define QLEAD 6
#define OLEAD (LAG / 2 + 2)
void plan(Params& P) {
    P.roles = 31; P.chains = 3; P.lag = LAG; P.dopro = 1;
    for (int r = 0; r < 2; r++) {
        const int lead = r ? OLEAD : QLEAD;
        int n = 0;
        for (int i = 0; i < 32 + lead; i++) {
            if (i >= lead) P.list[r][n++] = 32 + i - lead;
            if (i < 32) P.list[r][n++] = i;
        }
        P.nl[r] = n;
    }
}

#define TK() do {} while (0)
}

extern "C" void kernel_launch(void* const* d_in, const int* in_sizes, int n_in, void* d_out, int out_size) {
    typedef const __nv_bfloat16* BP;
    static EncFn enc = nullptr;
    if (!enc) {
        void* fn = nullptr; cudaDriverEntryPointQueryResult qr;
        cudaGetDriverEntryPoint("cuTensorMapEncodeTiled", &fn, cudaEnableDefault, &qr);
        enc = (EncFn)fn;
        cudaFuncSetAttribute(main_kernel, cudaFuncAttributeMaxDynamicSharedMemorySize, SMEM_BYTES);
    }
    static Params P;
    for (int i = 0; i < 4; i++) {
        const cuuint64_t cols = i < 3 ? 4096 : 512, rows = i < 3 ? 512 : 4096;
        cuuint64_t d2[2] = {cols, rows}, str[1] = {cols * 2};
        cuuint32_t box[2] = {64, 64}, bn[2] = {16, 256}, es[2] = {1, 1};
        enc(&P.tm[i < 3 ? i : 4], CU_TENSOR_MAP_DATA_TYPE_BFLOAT16, 2, d_in[9 + i], d2, str, box, es, CU_TENSOR_MAP_INTERLEAVE_NONE, CU_TENSOR_MAP_SWIZZLE_128B,
            CU_TENSOR_MAP_L2_PROMOTION_L2_128B, CU_TENSOR_MAP_FLOAT_OOB_FILL_NONE);
        if (i < 2) enc(&P.tn[i], CU_TENSOR_MAP_DATA_TYPE_BFLOAT16, 2, d_in[9 + i], d2, str, bn, es, CU_TENSOR_MAP_INTERLEAVE_NONE, CU_TENSOR_MAP_SWIZZLE_32B,
                       CU_TENSOR_MAP_L2_PROMOTION_L2_128B, CU_TENSOR_MAP_FLOAT_OOB_FILL_NONE);
    }
    {
        cuuint64_t dims[2] = {512, 2048}, str[1] = {1024};
        cuuint32_t box[2] = {8, 256}, es[2] = {1, 1};
        enc(&P.tm[3], CU_TENSOR_MAP_DATA_TYPE_BFLOAT16, 2, d_in[0], dims, str, box, es, CU_TENSOR_MAP_INTERLEAVE_NONE, CU_TENSOR_MAP_SWIZZLE_NONE,
            CU_TENSOR_MAP_L2_PROMOTION_NONE, CU_TENSOR_MAP_FLOAT_OOB_FILL_NONE);
    }
    P.mem0 = (BP)d_in[8]; P.Wo = (BP)d_in[12]; P.Dskip = (BP)d_in[6]; P.out = (__nv_bfloat16*)d_out;
    cudaStream_t s = cudaStreamPerThread;
    P.pa = {(BP)d_in[0], (BP)d_in[1], (BP)d_in[2], (BP)d_in[3], (BP)d_in[4], (BP)d_in[5], (BP)d_in[6], {(BP)d_in[9], (BP)d_in[10], (BP)d_in[11], (BP)d_in[12]}};
    plan(P);
    TK(); main_kernel<<<2 * NCL, 384, SMEM_BYTES, s>>>(P); TK();
}
```

```cpp
#include <cuda_runtime.h>
#include <cuda_bf16.h>
#include <cuda.h>
#include <stdint.h>
#include <string.h>
#include <math.h>

namespace {

constexpr int NCL = 66;
constexpr int NQ = 43;
constexpr int V_REC = 8, V_OP = 72, V_QKV = 88;
static_assert(2 * NQ + 3 * 14 == 128, "warps of the final residual");

#define XP 1024
__device__ uint4 g_x[2 * 128 * XP];
__device__ uint4 g_xn[64 * 4096];
__device__ uint4 g_st[68 * 256];
__device__ uint4 g_qkv[128 * 32 * 1536];
__device__ uint4 g_o[64 * 64 * 512];
__device__ uint4 g_pp[64 * 4 * 4096];
__device__ uint4 g_xch[133 * 512];
__device__ unsigned g_sel[64];
__device__ unsigned g_gate[32];
__device__ __align__(16) uint32_t g_P[512 * 272];
__device__ uint4 g_W[512 * 784];
__device__ __align__(16) uint32_t g_u[512 * 1152];
__device__ uint2 g_carry[512 * 40 * 32];
__device__ uint2 g_far[512 * 8 * 32];
__device__ unsigned g_cnt[900 * 8];
__device__ uint32_t g_ln0[2048];

enum { C_XN = 0  , C_QKV = 64  , C_O = 128  , C_PP = 384  , C_FAR = 896 };
__device__ __forceinline__ unsigned* cnt_ptr(int i) { return g_cnt + i * 8; }

struct ProArgs { const __nv_bfloat16 *x, *lAr, *Ai, *Cr, *Ci, *ldt, *Dk, *W[4]; };
struct Params {
    CUtensorMap tm[5];
    CUtensorMap tn[2];
    ProArgs pa;
    int dopro;
    const __nv_bfloat16* mem0;
    const __nv_bfloat16* Wo;
    const __nv_bfloat16* Dskip;
    __nv_bfloat16* out;
    int roles;
    int chains;
    int lag;
    int zero;
    int nl[2];
    uint8_t list[2][64];
};

__device__ __forceinline__ uint32_t smem_u32(const void* p) { return (uint32_t)__cvta_generic_to_shared(p); }
__device__ __forceinline__ uint32_t mapa(uint32_t a, uint32_t r) {
    uint32_t o; asm("mapa.shared::cluster.u32 %0,%1,%2;" : "=r"(o) : "r"(a), "r"(r)); return o;
}
__device__ __forceinline__ void mbar_init(uint32_t b, int c) { asm volatile("mbarrier.init.shared::cta.b64 [%0],%1;" ::"r"(b), "r"(c) : "memory"); }
__device__ __forceinline__ void mbar_expect(uint32_t b, int bytes) { asm volatile("mbarrier.arrive.expect_tx.shared::cta.b64 _,[%0],%1;" ::"r"(b), "r"(bytes) : "memory"); }
__device__ __forceinline__ void mbar_arrive(uint32_t b) { asm volatile("mbarrier.arrive.shared::cta.b64 _,[%0];" ::"r"(b) : "memory"); }
__device__ __forceinline__ void mbar_arrive_cluster(uint32_t b) { asm volatile("mbarrier.arrive.shared::cluster.b64 _,[%0];" ::"r"(b) : "memory"); }
__device__ __forceinline__ void mbar_wait(uint32_t b, uint32_t ph) {
    asm volatile(
        "{.reg .pred p; .reg .u32 n; mov.u32 n,0;\n"
        "W%=: mbarrier.try_wait.parity.shared::cta.b64 p,[%0],%1;\n"
        "@p bra D%=;\n"
        "add.u32 n,n,1; setp.lt.u32 p,n,2000000; @p bra W%=;\n"
        "trap;\n"
        "D%=: }" ::"r"(b), "r"(ph) : "memory");
}
__device__ __forceinline__ bool wait_lds128(uint32_t b, uint32_t ph, uint32_t a, uint4& v) {
    uint32_t ok;
    asm volatile("{.reg .pred p; mbarrier.try_wait.parity.shared::cta.b64 p,[%5],%6,20000; ld.shared.v4.u32 {%0,%1,%2,%3},[%7]; selp.u32 %4,1,0,p;}"
                 : "=r"(v.x), "=r"(v.y), "=r"(v.z), "=r"(v.w), "=r"(ok) : "r"(b), "r"(ph), "r"(a) : "memory");
    return ok;
}
__device__ __forceinline__ bool wait_lds64(uint32_t b, uint32_t ph, uint32_t a, uint2& v) {
    uint32_t ok;
    asm volatile("{.reg .pred p; mbarrier.try_wait.parity.shared::cta.b64 p,[%3],%4,20000; ld.shared.v2.u32 {%0,%1},[%5]; selp.u32 %2,1,0,p;}"
                 : "=r"(v.x), "=r"(v.y), "=r"(ok) : "r"(b), "r"(ph), "r"(a) : "memory");
    return ok;
}
template <int PH> __device__ __forceinline__ void mbar_wait_c(uint32_t b) {
    asm volatile(
        "{.reg .pred p; .reg .u32 n; mov.u32 n,%2;\n"
        "W%=: mbarrier.try_wait.parity.shared::cta.b64 p,[%0],%1;\n"
        "@p bra D%=;\n"
        "add.u32 n,n,1; setp.lt.u32 p,n,2000000; @p bra W%=;\n"
        "trap;\n"
        "D%=: }" ::"r"(b), "n"(PH), "n"(PH) : "memory");
}
__device__ __forceinline__ bool elect() {
    uint32_t r; asm volatile("{.reg .pred p; elect.sync _|p,0xffffffff; selp.u32 %0,1,0,p;}" : "=r"(r)); return r;
}
__device__ __forceinline__ void bar_sync(int id, int n) { asm volatile("bar.sync %0,%1;" ::"r"(id), "r"(n) : "memory"); }
__device__ __forceinline__ void bar_arrive(int id, int n) { asm volatile("bar.arrive %0,%1;" ::"r"(id), "r"(n) : "memory"); }
__device__ __forceinline__ void cluster_sync() { asm volatile("barrier.cluster.arrive.relaxed.aligned; barrier.cluster.wait.aligned;" ::: "memory"); }
__device__ __forceinline__ void fence_async() { asm volatile("fence.proxy.async;" ::: "memory"); }
__device__ __forceinline__ void fence_async_smem() { asm volatile("fence.proxy.async.shared::cta;" ::: "memory"); }
#define EFR 1
#define EFW 0
constexpr uint64_t POL_N = 0x1000000000000000ull, POL_F = 0x12F0000000000000ull;
constexpr uint64_t POL_LAST = EFR ? POL_F : POL_N  , POL_LATE = EFW ? POL_F : POL_N  , POL_SOON = EFW > 1 ? POL_F : POL_N;
__device__ __forceinline__ void bulk_g2s(uint32_t dst, const void* src, int bytes, uint32_t bar, uint64_t pol) {
    asm volatile("cp.async.bulk.shared::cluster.global.mbarrier::complete_tx::bytes.L2::cache_hint [%0],[%1],%2,[%3],%4;" ::"r"(dst), "l"(src), "r"(bytes), "r"(bar), "l"(pol) : "memory");
}
__device__ __forceinline__ void bulk_g2s_mc(uint32_t dst, const void* src, int bytes, uint32_t bar, uint64_t pol) {
    asm volatile("cp.async.bulk.shared::cluster.global.mbarrier::complete_tx::bytes.multicast::cluster.L2::cache_hint [%0],[%1],%2,[%3],%4,%5;" ::"r"(dst), "l"(src), "r"(bytes), "r"(bar), "h"((uint16_t)3), "l"(pol) : "memory");
}
__device__ __forceinline__ void stg128(uint4* p, uint4 v, uint64_t pol) {
    asm volatile("st.global.L2::cache_hint.v4.u32 [%0],{%1,%2,%3,%4},%5;" ::"l"(p), "r"(v.x), "r"(v.y), "r"(v.z), "r"(v.w), "l"(pol));
}
__device__ __forceinline__ void stg32(uint32_t* p, uint32_t v, uint64_t pol) { asm volatile("st.global.L2::cache_hint.u32 [%0],%1,%2;" ::"l"(p), "r"(v), "l"(pol)); }
__device__ __forceinline__ uint4 ldcg128_last(const uint4* p) {
    uint4 v; asm volatile("ld.global.cg.L2::cache_hint.v4.u32 {%0,%1,%2,%3},[%4],%5;" : "=r"(v.x), "=r"(v.y), "=r"(v.z), "=r"(v.w) : "l"(p), "l"(POL_LAST) : "memory"); return v;
}
__device__ __forceinline__ void tma2d(uint32_t dst, const CUtensorMap* tm, int x, int y, uint32_t bar) {
    asm volatile("cp.async.bulk.tensor.2d.shared::cluster.global.mbarrier::complete_tx::bytes [%0],[%1,{%2,%3}],[%4];" ::"r"(dst), "l"(tm), "r"(x), "r"(y), "r"(bar) : "memory");
}
__device__ __forceinline__ void tma3d(uint32_t dst, const CUtensorMap* tm, int y, int z, uint32_t bar) {
    asm volatile("cp.async.bulk.tensor.3d.shared::cluster.global.mbarrier::complete_tx::bytes [%0],[%1,{0,%2,%3}],[%4];" ::"r"(dst), "l"(tm), "r"(y), "r"(z), "r"(bar) : "memory");
}
__device__ __forceinline__ void st_async4(uint32_t a, uint32_t x, uint32_t y, uint32_t z, uint32_t w, uint32_t mb) {
    asm volatile("st.async.shared::cluster.mbarrier::complete_tx::bytes.v4.b32 [%0],{%1,%2,%3,%4},[%5];" ::"r"(a), "r"(x), "r"(y), "r"(z), "r"(w), "r"(mb) : "memory");
}
__device__ __forceinline__ void st_async2(uint32_t a, uint32_t x, uint32_t y, uint32_t mb) {
    asm volatile("st.async.shared::cluster.mbarrier::complete_tx::bytes.v2.b32 [%0],{%1,%2},[%3];" ::"r"(a), "r"(x), "r"(y), "r"(mb) : "memory");
}
#define LDSQ "ld.shared"
__device__ __forceinline__ uint4 lds128(uint32_t a) { uint4 v; asm volatile(LDSQ ".v4.u32 {%0,%1,%2,%3},[%4];" : "=r"(v.x), "=r"(v.y), "=r"(v.z), "=r"(v.w) : "r"(a) : "memory"); return v; }
__device__ __forceinline__ uint4 lds128v(uint32_t a) { uint4 v; asm volatile("ld.volatile.shared.v4.u32 {%0,%1,%2,%3},[%4];" : "=r"(v.x), "=r"(v.y), "=r"(v.z), "=r"(v.w) : "r"(a) : "memory"); return v; }
__device__ __forceinline__ uint2 lds64(uint32_t a) { uint2 v; asm volatile(LDSQ ".v2.u32 {%0,%1},[%2];" : "=r"(v.x), "=r"(v.y) : "r"(a) : "memory"); return v; }
__device__ __forceinline__ uint32_t lds32(uint32_t a) { uint32_t v; asm volatile(LDSQ ".u32 %0,[%1];" : "=r"(v) : "r"(a) : "memory"); return v; }
__device__ __forceinline__ void sts128(uint32_t a, uint32_t x, uint32_t y, uint32_t z, uint32_t w) { asm volatile("st.shared.v4.u32 [%0],{%1,%2,%3,%4};" ::"r"(a), "r"(x), "r"(y), "r"(z), "r"(w) : "memory"); }
__device__ __forceinline__ void sts64(uint32_t a, uint32_t x, uint32_t y) { asm volatile("st.shared.v2.u32 [%0],{%1,%2};" ::"r"(a), "r"(x), "r"(y) : "memory"); }
__device__ __forceinline__ void sts32(uint32_t a, uint32_t x) { asm volatile("st.shared.u32 [%0],%1;" ::"r"(a), "r"(x) : "memory"); }
__device__ __forceinline__ uint4 ldsm4(uint32_t a) { uint4 v; asm volatile("ldmatrix.sync.aligned.m8n8.x4.shared.b16 {%0,%1,%2,%3},[%4];" : "=r"(v.x), "=r"(v.y), "=r"(v.z), "=r"(v.w) : "r"(a) : "memory"); return v; }
__device__ __forceinline__ uint4 ldsm4t(uint32_t a) { uint4 v; asm volatile("ldmatrix.sync.aligned.m8n8.x4.trans.shared.b16 {%0,%1,%2,%3},[%4];" : "=r"(v.x), "=r"(v.y), "=r"(v.z), "=r"(v.w) : "r"(a) : "memory"); return v; }
__device__ __forceinline__ uint32_t movm(uint32_t a) { uint32_t d; asm volatile("movmatrix.sync.aligned.m8n8.trans.b16 %0,%1;" : "=r"(d) : "r"(a)); return d; }
__device__ __forceinline__ uint32_t pack2(float lo, float hi) { uint32_t d; asm("cvt.rn.bf16x2.f32 %0,%1,%2;" : "=r"(d) : "f"(hi), "f"(lo)); return d; }
__device__ __forceinline__ uint32_t hadd2(uint32_t a, uint32_t b) { uint32_t d; asm("add.rn.bf16x2 %0,%1,%2;" : "=r"(d) : "r"(a), "r"(b)); return d; }
__device__ __forceinline__ uint32_t hmul2(uint32_t a, uint32_t b) { uint32_t d; asm("mul.rn.bf16x2 %0,%1,%2;" : "=r"(d) : "r"(a), "r"(b)); return d; }
__device__ __forceinline__ float blo(uint32_t v) { return __uint_as_float(v << 16); }
__device__ __forceinline__ float bhi(uint32_t v) { return __uint_as_float(v & 0xffff0000u); }
__device__ __forceinline__ float rbf(float x) { return __uint_as_float(pack2(0.f, x)); }
__device__ __forceinline__ float ex2(float x) { float y; asm("ex2.approx.ftz.f32 %0,%1;" : "=f"(y) : "f"(x)); return y; }
__device__ __forceinline__ float rcp(float x) { float y; asm("rcp.approx.ftz.f32 %0,%1;" : "=f"(y) : "f"(x)); return y; }
__device__ __forceinline__ void mma16(float* c, uint32_t a0, uint32_t a1, uint32_t a2, uint32_t a3, uint32_t b0, uint32_t b1) {
    asm volatile("mma.sync.aligned.m16n8k16.row.col.f32.bf16.bf16.f32 {%0,%1,%2,%3},{%4,%5,%6,%7},{%8,%9},{%0,%1,%2,%3};"
                 : "+f"(c[0]), "+f"(c[1]), "+f"(c[2]), "+f"(c[3]) : "r"(a0), "r"(a1), "r"(a2), "r"(a3), "r"(b0), "r"(b1));
}
__device__ __forceinline__ void mma16_top(float& d0, float& d1, uint32_t a0, uint32_t a2, uint32_t b0, uint32_t b1) {
    asm volatile("{.reg .b32 j; .reg .f32 e,f; mma.sync.aligned.m16n8k16.row.col.f32.bf16.bf16.f32 {%0,%1,e,f},{%2,j,%3,j},{%4,%5},{0f00000000,0f00000000,0f00000000,0f00000000};}"
                 : "=f"(d0), "=f"(d1) : "r"(a0), "r"(a2), "r"(b0), "r"(b1));
}
__device__ __forceinline__ void mma8(float* c, uint32_t a0, uint32_t a1, uint32_t b0) {
    asm volatile("mma.sync.aligned.m16n8k8.row.col.f32.bf16.bf16.f32 {%0,%1,%2,%3},{%4,%5},{%6},{%0,%1,%2,%3};"
                 : "+f"(c[0]), "+f"(c[1]), "+f"(c[2]), "+f"(c[3]) : "r"(a0), "r"(a1), "r"(b0));
}
__device__ __forceinline__ uint4 ld_rlx128(const uint4* p) {
    uint4 v;
    asm volatile("{.reg .b128 t; ld.relaxed.gpu.global.b128 t,[%4]; mov.b128 {%0,%1,%2,%3},t;}" : "=r"(v.x), "=r"(v.y), "=r"(v.z), "=r"(v.w) : "l"(p) : "memory");
    return v;
}
__device__ __forceinline__ void st_rlx128(uint4* p, uint32_t x, uint32_t y, uint32_t z, uint32_t w) {
    asm volatile("{.reg .b128 t; mov.b128 t,{%1,%2,%3,%4}; st.relaxed.gpu.global.b128 [%0],t;}" ::"l"(p), "r"(x), "r"(y), "r"(z), "r"(w) : "memory");
}
__device__ __forceinline__ uint4 ldcg128(const uint4* p) { uint4 v; asm volatile("ld.global.cg.v4.u32 {%0,%1,%2,%3},[%4];" : "=r"(v.x), "=r"(v.y), "=r"(v.z), "=r"(v.w) : "l"(p) : "memory"); return v; }
__device__ __forceinline__ void red_release(unsigned* p, unsigned v) {
    asm volatile("fence.proxy.async; red.relaxed.gpu.global.add.u32 [%0],%1;" ::"l"(p), "r"(v) : "memory");
}
__device__ __forceinline__ void red_relaxed(unsigned* p, unsigned v) { asm volatile("red.relaxed.gpu.global.add.u32 [%0],%1;" ::"l"(p), "r"(v) : "memory"); }
__device__ __forceinline__ void wait_cnt(const unsigned* p, unsigned target) {
    asm volatile(
        "{.reg .pred p; .reg .u32 n,v; mov.u32 n,0;\n"
        "W%=: ld.acquire.gpu.global.u32 v,[%0]; setp.ge.u32 p,v,%1; @p bra D%=;\n"
        "nanosleep.u32 20; add.u32 n,n,1; setp.lt.u32 p,n,4000000; @p bra W%=;\n"
        "trap;\n"
        "D%=: }" ::"l"(p), "r"(target) : "memory");
}
__device__ __forceinline__ void wait_cnt_warp(const unsigned* p, unsigned target) {
    asm volatile(
        "{.reg .pred p; .reg .u32 n,v; mov.u32 n,0;\n"
        "W%=: ld.acquire.gpu.global.u32 v,[%0]; setp.ge.u32 p,v,%1; vote.sync.all.pred p,p,0xffffffff; @p bra.uni D%=;\n"
        "nanosleep.u32 20; add.u32 n,n,1; setp.lt.u32 p,n,4000000; @p bra.uni W%=;\n"
        "trap;\n"
        "D%=: }" ::"l"(p), "r"(target) : "memory");
}
__device__ __forceinline__ void wait_slow_warp(const unsigned* p, unsigned target) {
    asm volatile(
        "{.reg .pred p; .reg .u32 n,v; mov.u32 n,0;\n"
        "W%=: ld.relaxed.gpu.global.u32 v,[%0]; setp.ge.u32 p,v,%1; vote.sync.all.pred p,p,0xffffffff; @p bra.uni D%=;\n"
        "nanosleep.u32 400; add.u32 n,n,1; setp.lt.u32 p,n,1000000; @p bra.uni W%=;\n"
        "trap;\n"
        "D%=: }" ::"l"(p), "r"(target) : "memory");
}
__device__ __forceinline__ void wait_flag_warp(const unsigned* p, unsigned target) {
    asm volatile(
        "{.reg .pred p; .reg .u32 n,v; mov.u32 n,0;\n"
        "W%=: ld.relaxed.gpu.global.u32 v,[%0]; setp.ge.u32 p,v,%1; vote.sync.all.pred p,p,0xffffffff; @p bra.uni D%=;\n"
        "add.u32 n,n,1; setp.lt.u32 p,n,10000000; @p bra.uni W%=;\n"
        "trap;\n"
        "D%=: }" ::"l"(p), "r"(target) : "memory");
}
__device__ __forceinline__ uint64_t mkdesc(uint32_t addr, uint32_t lbo, uint32_t sbo, uint32_t sw) {
    return (uint64_t)((addr & 0x3FFFF) >> 4) | ((uint64_t)(lbo >> 4) << 16) | ((uint64_t)(sbo >> 4) << 32) | ((uint64_t)sw << 62);
}
__device__ __forceinline__ void wg_fence() { asm volatile("wgmma.fence.sync.aligned;" ::: "memory"); }
__device__ __forceinline__ void wg_commit() { asm volatile("wgmma.commit_group.sync.aligned;" ::: "memory"); }
template <int N> __device__ __forceinline__ void wg_wait() { asm volatile("wgmma.wait_group.sync.aligned %0;" ::"n"(N) : "memory"); }
#define R8(c, o) "+f"(c[o]), "+f"(c[o + 1]), "+f"(c[o + 2]), "+f"(c[o + 3]), "+f"(c[o + 4]), "+f"(c[o + 5]), "+f"(c[o + 6]), "+f"(c[o + 7])
#define R32(c, o) R8(c, o), R8(c, o + 8), R8(c, o + 16), R8(c, o + 24)
#define S32A "%0,%1,%2,%3,%4,%5,%6,%7,%8,%9,%10,%11,%12,%13,%14,%15,%16,%17,%18,%19,%20,%21,%22,%23,%24,%25,%26,%27,%28,%29,%30,%31"
template <int ACC> __device__ __forceinline__ void wgmma64_rs(float* c, const uint32_t* a, uint64_t db) {
    asm volatile("wgmma.mma_async.sync.aligned.m64n64k16.f32.bf16.bf16 {" S32A "},{%32,%33,%34,%35},%36,%37,1,1,0;"
                 : R32(c, 0) : "r"(a[0]), "r"(a[1]), "r"(a[2]), "r"(a[3]), "l"(db), "n"(ACC));
}
template <int ACC> __device__ __forceinline__ void wgmma64_ta(float* c, uint64_t da, uint64_t db) {
    asm volatile("wgmma.mma_async.sync.aligned.m64n64k16.f32.bf16.bf16 {" S32A "},%32,%33,%34,1,1,1,0;" : R32(c, 0) : "l"(da), "l"(db), "n"(ACC));
}
template <int ACC> __device__ __forceinline__ void wgmma80_tb(float* c, uint64_t da, uint64_t db) {
    asm volatile("wgmma.mma_async.sync.aligned.m64n80k16.f32.bf16.bf16 {" S32A ",%32,%33,%34,%35,%36,%37,%38,%39},%40,%41,%42,1,1,0,1;"
                 : R32(c, 0), R8(c, 32) : "l"(da), "l"(db), "n"(ACC));
}
template <int N> __device__ __forceinline__ void reg_inc() { asm volatile("setmaxnreg.inc.sync.aligned.u32 %0;" ::"n"(N)); }
template <int N> __device__ __forceinline__ void reg_dec() { asm volatile("setmaxnreg.dec.sync.aligned.u32 %0;" ::"n"(N)); }

#define PROF(cond, idx) do {} while (0)
#define PROF2(cond, idx) do {} while (0)

constexpr int S_GATE = 232440, S_TAG = 232444, S_XBAR = 232432, B_BAR = 231936;
#define RCB 136
#define RCU 184
#define NTOP 1
#define PLATE 2
#define PFM 12
#define QLAG 3
constexpr float SC_LOG2E = 0.08838834764831845f * 1.4426950408889634f;

__device__ __forceinline__ float2 ln_finish(float mean, float var) {
    float sd; asm("sqrt.approx.f32 %0,%1;" : "=f"(sd) : "f"(rbf(rbf(var) + 1e-5f)));
    sd = rbf(sd);
    return make_float2(rbf(mean), sd);
}

__device__ __forceinline__ float2 row_stats512(uint4* v, const uint4* src, int s1, int s2) {
    const int g = (threadIdx.x & 31) >> 2;
#pragma unroll
    for (int i = 0; i < 16; i++) v[i] = ldcg128(src + (i >> 1) * s1 + (i & 1) * s2);
    float a[4] = {0, 0, 0, 0}, q0[4] = {0, 0, 0, 0}, q1[4] = {0, 0, 0, 0};
#pragma unroll
    for (int i = 0; i < 16; i++) {
        mma16(a, v[i].x, v[i].y, v[i].z, v[i].w, 0x3f803f80u, 0x3f803f80u);
        mma8(q0, v[i].x, v[i].y, v[i].x); mma8(q1, v[i].x, v[i].y, v[i].y);
        mma8(q0, v[i].z, v[i].w, v[i].z); mma8(q1, v[i].z, v[i].w, v[i].w);
    }
    const float sum = a[0] + a[2], sq = (g & 1) ? q0[1] + q1[3] : q0[0] + q1[2];
    return make_float2(sum, fmaxf(sq - sum * sum * (1.f / 512.f), 0.f));
}
__device__ __forceinline__ void x1_norm(const uint2* src, int r, bool on) {
    const int lane = threadIdx.x & 31, g = lane >> 2, t = r * 4 + (lane & 3);
    constexpr int xp = XP;
    uint2 v[16];
#pragma unroll
    for (int i = 0; i < 16; i++) asm volatile("ld.global.cg.v2.u32 {%0,%1},[%2];" : "=r"(v[i].x), "=r"(v[i].y) : "l"(src + (g * 4 * xp + t) + ((i >> 1) * 16 + (i & 1)) * 2 * xp) : "memory");
    float s = 0, q = 0;
#pragma unroll
    for (int i = 0; i < 32; i++) {
        const uint32_t w = (i & 1) ? v[i >> 1].y : v[i >> 1].x;
        s += blo(w) + bhi(w); q = fmaf(blo(w), blo(w), fmaf(bhi(w), bhi(w), q));
    }
#pragma unroll
    for (int d = 4; d < 32; d *= 2) { s += __shfl_xor_sync(0xffffffffu, s, d); q += __shfl_xor_sync(0xffffffffu, q, d); }
    if (g == 0 && on) g_ln0[t] = 0;
    s *= 1.f / 512.f;
    const float2 l = ln_finish(s, fmaxf(fmaf(q, 1.f / 512.f, -s * s), 0.f));
    const float rs = rcp(l.y);
    const uint32_t mm = pack2(-l.x, -l.x);
    uint4* dst = g_xn + ((t >> 6) * 4096 + ((t >> 3) & 7) * 64 + g * 8 + (t & 7));
#define NRM(w) pack2(blo(hadd2(w, mm)) * rs, bhi(hadd2(w, mm)) * rs)
#pragma unroll
    for (int i = 0; i < 8; i++)
        asm volatile("{.reg .pred p; setp.ne.u32 p,%5,0; @p st.global.v4.u32 [%0],{%1,%2,%3,%4};}" ::"l"(dst + i * 512), "r"(NRM(v[2 * i].x)), "r"(NRM(v[2 * i].y)),
                     "r"(NRM(v[2 * i + 1].x)), "r"(NRM(v[2 * i + 1].y)), "r"((uint32_t)on) : "memory");
}

#define NWO 10
#define VMASK 0x4444
#define VPRE 2
#define VFIRST 1
#define OA 0
#define OL 0x16
#define PINS 0x2ae1
#define NPX 2
#define NPF 2
constexpr int SLOT = 24576, SL_V = 8192, SL_Q = 16384, SL_KM = 20480, SL_VM = 22528;
constexpr int R_SL = 0, R_WV = 4 * SLOT  , R_WO = R_WV + 65536, R_M = 196608  , R_U = R_M + 8192  ,
              R_OS = R_U + 8192  , R_SB = R_OS + 8192  , R_OB = R_SB + 5248  , R_PB = R_OB + 2048  ,
              R_IL = R_PB + 1024  , R_SEL = 231680, R_BAR = R_SEL + 256, R_STV = 0, R_STQ = 65536, R_STK = 131072;
static_assert(R_WO + (16 - NWO) * 4096 <= R_M && R_IL + 64 <= R_SEL && R_BAR + 512 <= 232448, "smem map");
enum { RB_XFULL = 0  , RB_GO = 4  , RB_QK = 8  , RB_INIT = 24, RB_SV = 25   };

enum { NB_MFULL = 1  , NB_PART = 3  , NB_S = 5, NB_P = 6, NB_O = 7, NB_W = 10 };
#define XU 4
#define GOP 0
#define WOF 1
#define SPV 0
#define SEARLY 4
#define EGO 0
#define NPRB 3
#define REARLY 1
#define RFW 8
#define PF0 0
#define PFD 1500
#define EFS V_QKV
#define RACC 4
#define WDEP 1
#define RH 56
#define RW0 224
#define D1 270
#define D2 300
__device__ __forceinline__ uint32_t clk32() { uint32_t c; asm volatile("mov.u32 %0,%%clock;" : "=r"(c)::"memory"); return c; }
__device__ __forceinline__ void spin(int cycles) {
    if (cycles <= 0) return;
    asm volatile("{.reg .pred p; .reg .u32 a,b; mov.u32 a,%%clock; add.u32 a,a,%0;\nS%=: mov.u32 b,%%clock; sub.u32 b,b,a; setp.lt.s32 p,b,0; @p bra.uni S%=;}" ::"r"(cycles) : "memory");
}
__device__ __forceinline__ void spin_v(uint32_t cycles) {
    asm volatile("{.reg .pred p; .reg .u32 a,b; mov.u32 a,%%clock; add.u32 a,a,%0;\nS%=: mov.u32 b,%%clock; sub.u32 b,b,a; setp.lt.s32 p,b,0; @p bra.uni S%=;}" ::"r"(cycles) : "memory");
}
__device__ __forceinline__ uint4* xregion(int X, int r) { return (uint4*)(((size_t)g_xch + 8191) & ~(size_t)8191) + (X * 66 + r) * 512; }

__device__ __forceinline__ void arrive_if(uint32_t bar, uint32_t a, uint32_t b) {
    asm volatile("{.reg .pred p; setp.eq.u32 p,%1,%2; @p mbarrier.arrive.shared::cta.b64 _,[%0];}" ::"r"(bar), "r"(a), "r"(b) : "memory");
}
struct RecW { uint32_t po, dp, lw, sp, w; };
#define PIN(n) if ((PINS >> (n)) & 1) asm volatile("griddepcontrol.launch_dependents;" ::: "memory")
constexpr int v_stream(int n) {
    int ks = 0;
    for (; ks < 16; ks++) if (!((VMASK >> ks) & 1) && n-- == 0) break;
    return ks;
}
constexpr uint64_t v_next() {
    uint64_t r = 0;
    for (int n = 0; v_stream(n + VPRE) < 16; n++) r |= (uint64_t)v_stream(n + VPRE) << (4 * v_stream(n));
    return r;
}
constexpr uint64_t V_NEXT = v_next();
constexpr int V_PRE = v_stream(VPRE);

__device__ __forceinline__ void rec_step(const RecW& k, uint32_t sb, const int X, int s, uint32_t zero, int lo, int hi, int d, const uint32_t (*wq)[4], const uint32_t (*wk)[4], uint4* wv, uint4* wo) {
    const int SL = R_SL + X * 2 * SLOT;
    uint4 mk[8];
    bar_sync(NB_MFULL + X, 288);
    mk[0] = ldsm4(k.lw + X * 4096 + R_M);
    PIN(0);
    mk[1] = ldsm4(k.lw + X * 4096 + R_M + 512);
    PIN(0);
    asm volatile("" : "+r"(s));
    const uint32_t z = s & zero, wz = k.w + z, w5 = wz * 512, so = (s & 1) * SLOT + w5;
    const uint32_t qb = sb + R_BAR + (RB_QK + X * 8) * 8 + wz * 8;
    uint32_t x[4], vv[2], l8;
    {
        float aq[4] = {0, 0, 0, 0}, ak[4] = {0, 0, 0, 0}, av[4] = {0, 0, 0, 0};
#pragma unroll
        for (int t = 0; t < 16; t++) {
            const uint32_t b0 = (t & 1) ? mk[t >> 1].z : mk[t >> 1].x, b1 = (t & 1) ? mk[t >> 1].w : mk[t >> 1].y;
            mma16(aq, wq[t][0], wq[t][1], wq[t][2], wq[t][3], b0, b1);
            PIN(8);
            mma16(ak, wk[t][0], wk[t][1], wk[t][2], wk[t][3], b0, b1);
            PIN(9);
            mma16(av, wv[t].x, wv[t].y, wv[t].z, wv[t].w, b0, b1);
            PIN(10);
            if ((t & 1) && t < 13) mk[(t >> 1) + 2] = ldsm4(k.lw + X * 4096 + R_M + (t >> 1) * 512 + 1024);
            const int nx = (V_NEXT >> (4 * t)) & 15;
            if (nx) wv[nx] = lds128(k.lw + w5 + R_WV + nx * 4096);
            if (t == 14) l8 = ((k.lw + z) >> 1) + (sb - (sb >> 1) + SL + (s & 1) * SLOT + wz * 256);
            if (t < 15) PIN(1);
        }
        x[0] = movm(pack2(aq[0], aq[1])); x[1] = movm(pack2(aq[2], aq[3]));
        x[2] = movm(pack2(ak[0], ak[1])); x[3] = movm(pack2(ak[2], ak[3]));
        vv[0] = pack2(av[0], av[1]); vv[1] = pack2(av[2], av[3]);
        if (VFIRST) st_async2(l8 + (SL_VM + k.dp), vv[0], vv[1], qb + k.dp);
        st_async4(k.lw + (R_U + X * 4096 + w5 + k.dp), x[0], x[1], x[2], x[3], qb + k.dp);
        if (!VFIRST) st_async2(l8 + (SL_VM + k.dp), vv[0], vv[1], qb + k.dp);
    }
    {
#define GO_OTHER arrive_if(sb + R_BAR + (RB_GO + 2 - 2 * X + ((s + d) & 1)) * 8, (k.sp + z) & 0x1ff0, X ? s >= hi : s <= lo)
        if (GOP == 0) GO_OTHER;
        const uint32_t swr = ((k.sp + z) & 0x1ff0) + (sb + R_SB);
        if (WOF) {
#pragma unroll
            for (int i = 0; i < NPX; i++) wo[i] = lds128v(k.lw + w5 + R_WO + i * 4096);
        }
        mbar_wait(sb + R_BAR + (RB_XFULL + X * 2) * 8 + (s & 1) * 8, (s >> 1) & 1);
        const uint4 k0 = lds128(k.lw + so + SL), k1 = lds128(k.lw + so + SL + 4096);
        if (!WOF) {
#pragma unroll
            for (int i = 0; i < NPX; i++) wo[i] = lds128(k.lw + w5 + R_WO + i * 4096);
        }
        if (GOP == 1) GO_OTHER;
        mbar_wait(qb, s & 1);
        const uint4 u = lds128(k.lw + w5 + R_U + X * 4096);
        if (GOP == 2) GO_OTHER;
        const uint32_t q0 = hadd2(x[0], u.x), q1 = hadd2(x[1], u.y);
        x[2] = hadd2(x[2], u.z); x[3] = hadd2(x[3], u.w);
        float sa[4] = {0, 0, 0, 0}, sc[4] = {0, 0, 0, 0}, sm0, sm1;
        mma16(sa, k0.x, k0.y, k0.z, k0.w, q0, q1);
        mma16(sc, k1.x, k1.y, k1.z, k1.w, q0, q1);
        mma16_top(sm0, sm1, x[2], x[3], q0, q1);
        asm volatile("stmatrix.sync.aligned.m8n8.x4.trans.shared.b16 [%0],{%1,%2,%3,%4};" ::"r"(swr), "r"(pack2(sa[0], sa[1])), "r"(pack2(sa[2], sa[3])),
                     "r"(pack2(sc[0], sc[1])), "r"(pack2(sc[2], sc[3])) : "memory");
        asm volatile("stmatrix.sync.aligned.m8n8.x1.trans.shared.b16 [%0],{%1};" ::"r"(swr + 512), "r"(pack2(sm0, sm1)) : "memory");
    }
    if (GOP == 3) GO_OTHER;
    bar_sync(NB_S, 256);
    uint4 v0, v1;
    uint32_t ls;
    {
        const uint4 y = ldsm4t(k.lw + wz * 656 + R_SB);
        PIN(2);
        uint32_t y4; asm volatile("ldmatrix.sync.aligned.m8n8.x1.trans.shared.b16 {%0},[%1];" : "=r"(y4) : "r"(k.lw + wz * 656 + R_SB + 512) : "memory");
        PIN(2);
        const uint2 vp = lds64(l8 + SL_VM);
        sts64(l8 + SL_KM, x[2], x[3]);
        const uint32_t z1 = k.lw & z, z2 = k.sp & z, ONE = 0x3f803f80u | z2, ONF = 0x3f803f80u | z1;
        float a[4] = {0, 0, 0, 0}, b[4] = {0, 0, 0, 0}, e[4] = {0, 0, 0, 0};
        mma8(e, ONE, z1, y4); mma16(a, ONE, z1, z2, ONF, y.x, y.y); mma16(b, ONE, z1, z2, ONF, y.z, y.w);
        vv[0] = hadd2(vv[0], vp.x); vv[1] = hadd2(vv[1], vp.y);
        sts64(l8 + SL_VM, vv[0], vv[1]);
        float s0, s1;
        asm("{.reg .pred p1,p2,p4; .reg .f32 t0,t1,u0,u1; .reg .b32 m; and.b32 m,%12,64; setp.ne.u32 p1,m,0; and.b32 m,%12,128; setp.ne.u32 p2,m,0; and.b32 m,%12,256; setp.ne.u32 p4,m,0;"
            "selp.f32 t0,%4,%2,p1; selp.f32 t1,%5,%3,p1; selp.f32 u0,%8,%6,p1; selp.f32 u1,%9,%7,p1; selp.f32 t0,u0,t0,p2; selp.f32 t1,u1,t1,p2; selp.f32 %0,%10,t0,p4; selp.f32 %1,%11,t1,p4;}"
            : "=f"(s0), "=f"(s1) : "f"(a[0]), "f"(a[1]), "f"(a[2]), "f"(a[3]), "f"(b[0]), "f"(b[1]), "f"(b[2]), "f"(b[3]), "f"(e[0]), "f"(e[1]), "r"(k.lw));
        const int mi = __float_as_int(fmaxf(s0, s1));
        const int mp = __reduce_max_sync(0xffffffffu, mi), mn = (int)__reduce_min_sync(0xffffffffu, (unsigned)mi);
        PIN(3);
        v0 = lds128(k.lw + so + SL + SL_V); v1 = lds128(k.lw + so + SL + SL_V + 4096);
#pragma unroll
        for (int i = NPX; i < NPF; i++) wo[i] = lds128(k.lw + w5 + R_WO + i * 4096);
        PIN(4);
        const float mo = -__int_as_float(mp >= 0 ? mp : mn) * SC_LOG2E;
        s0 = ex2(fmaf(s0, SC_LOG2E, mo)); s1 = ex2(fmaf(s1, SC_LOG2E, mo));
        sts32((((k.sp + z) >> 11) & 0x1fc) + (k.lw & 256) * 2 + (sb + R_PB), pack2(s0, s1));
        ls = k.lw < sb + 320 ? __float_as_uint((s0 + s1) + 4.f) : 0;
    }
    bar_sync(NB_P, 256);
    {
        const uint4 pp = lds128(k.lw + R_PB);
        PIN(5);
        const uint32_t pm = lds32(((k.lw + z) >> 2) + (sb - (sb >> 2) + R_PB + 512));
        PIN(5);
        if (EGO) arrive_if(sb + R_BAR + (RB_GO + 2 * X + (s & 1)) * 8, (k.sp + z) & 0x1ff0, X ? s + 1 < hi : s >= lo);
        sts32(sb + R_IL + (wz >> 1) * 16 + (wz & 1) * 4, __reduce_add_sync(0xffffffffu, ls) - 20u * 0x40800000u);
        float o0[4] = {0, 0, 0, 0}, o1[4] = {0, 0, 0, 0}, o2[4] = {0, 0, 0, 0};
        mma16(o0, v0.x, v0.y, v0.z, v0.w, pp.x, pp.y);
        mma16(o1, v1.x, v1.y, v1.z, v1.w, pp.z, pp.w);
        mma8(o2, vv[0], vv[1], pm);
        asm volatile("stmatrix.sync.aligned.m8n8.x2.trans.shared.b16 [%0],{%1,%2};" ::"r"(k.lw + wz * 256 + R_OB),
                     "r"(pack2(o0[0] + o1[0] + o2[0], o0[1] + o1[1] + o2[1])), "r"(pack2(o0[2] + o1[2] + o2[2], o0[3] + o1[3] + o2[3])) : "memory");
    }
    bar_sync(NB_O, 256);
    {
        float r0[2][4] = {{0, 0, 0, 0}, {0, 0, 0, 0}}, r1[2][4] = {{0, 0, 0, 0}, {0, 0, 0, 0}};
        uint4 b[4];
        b[0] = ldsm4(k.lw + R_OB);
        PIN(6);
        b[1] = ldsm4(k.lw + R_OB + 512);
        PIN(6);
#pragma unroll
        for (int m = NWO + NPF; m < 16; m++) if (((OL >> (2 * (15 - m))) & 3) == 3) wo[m] = lds128(k.lw + w5 + R_WO + (m - NWO) * 4096);
        const uint2 il = lds64(sb + R_IL + ((k.lw + z) & 48));
        PIN(6);
        float i0, i1;
        uint4* dst;
#pragma unroll
        for (int i = 0; i < 4; i++) {
            mma16(r0[0], wo[4 * i].x, wo[4 * i].y, wo[4 * i].z, wo[4 * i].w, b[i].x, b[i].y);
            mma16(r1[0], wo[4 * i + 1].x, wo[4 * i + 1].y, wo[4 * i + 1].z, wo[4 * i + 1].w, b[i].x, b[i].y);
            mma16(r0[OA], wo[4 * i + 2].x, wo[4 * i + 2].y, wo[4 * i + 2].z, wo[4 * i + 2].w, b[i].z, b[i].w);
            mma16(r1[OA], wo[4 * i + 3].x, wo[4 * i + 3].y, wo[4 * i + 3].z, wo[4 * i + 3].w, b[i].z, b[i].w);
            if (i < 2) b[i + 2] = ldsm4(k.lw + R_OB + (i + 2) * 512);
#pragma unroll
            for (int m = NWO + NPF; m < 16; m++) if (i < 3 && i == ((OL >> (2 * (15 - m))) & 3)) wo[m] = lds128(k.lw + w5 + R_WO + (m - NWO) * 4096);
            if (i == 1) { i0 = rcp(__uint2float_rn(il.x)) * 2097152.f; i1 = rcp(__uint2float_rn(il.y)) * 2097152.f; }
            if (i == 2) {
                const uint32_t po = k.sp + z;
                dst = xregion(X, 0) + k.po + ((po >> 20) ^ ((po & X) << 8));
                asm volatile("" : "+l"(dst));
            }
            PIN(7);
        }
        const uint32_t tag = (s + 1) & 1;
#pragma unroll
        for (int i = 0; i < 4; i++) { r0[0][i] = (OA ? r0[0][i] + r0[1][i] : r0[0][i]) * ((i & 1) ? i1 : i0); r1[0][i] = (OA ? r1[0][i] + r1[1][i] : r1[0][i]) * ((i & 1) ? i1 : i0); }
        st_rlx128(dst, (pack2(r0[0][0], r0[0][2]) & ~1u) | tag,
                  pack2(r1[0][0], r1[0][2]), pack2(r0[0][1], r0[0][3]), pack2(r1[0][1], r1[0][3]));
        bar_arrive(NB_PART + X, 288);
#pragma unroll
        for (int t = 0; t < V_PRE; t++) if (!((VMASK >> t) & 1)) wv[t] = lds128(k.lw + w5 + R_WV + t * 4096);
        if (!EGO) arrive_if(sb + R_BAR + (RB_GO + 2 * X + (s & 1)) * 8, (k.sp + z) & 0x1ff0, X ? s + 1 < hi : s >= lo);
    }
}

__device__ __forceinline__ void rec_fetch(const Params& p, uint32_t sb, int head, uint32_t rank, int which, int dst) {
#pragma unroll 1
    for (int j = 0; j < 8; j++) tma2d(sb + dst + j * 8192, &p.tm[which], head * 128 + (j >> 2) * 64, rank * 256 + (j & 3) * 64, sb + R_BAR + RB_INIT * 8);
}

__device__ __forceinline__ void rec_weights(const Params& p, uint32_t sb, int head, uint32_t rank, int w) {
    const int lane = __shfl_sync(0xffffffffu, threadIdx.x & 31, threadIdx.x & 31),
        g = lane >> 2, c = lane & 3;
    const int t = w & 3, WG = w >> 2;
    uint32_t wq[16][4], wk[16][4];
    uint4 wo[16], wv[16];
    const uint32_t woff = sb + WG * 32768 + (((lane >> 4) << 3) + (lane & 7)) * 128 + (((2 * t + ((lane >> 3) & 1)) ^ (lane & 7)) << 4);
    const uint32_t lw = sb + lane * 16;
    PROF2(threadIdx.x == 0, 3501);
    {
        const __nv_bfloat16* wp = p.Wo + (size_t)(head * 128 + 2 * c) * 512 + rank * 256 + w * 32 + g * 4;
#pragma unroll
        for (int ks = 0; ks < 8; ks++) {
            const uint2 r0 = *(const uint2*)(wp + (ks * 16) * 512), r1 = *(const uint2*)(wp + (ks * 16 + 1) * 512);
            const uint2 r2 = *(const uint2*)(wp + (ks * 16 + 8) * 512), r3 = *(const uint2*)(wp + (ks * 16 + 9) * 512);
            const uint4 f[2] = {make_uint4(__byte_perm(r0.x, r1.x, 0x5410), __byte_perm(r0.x, r1.x, 0x7632), __byte_perm(r2.x, r3.x, 0x5410), __byte_perm(r2.x, r3.x, 0x7632)),
                                make_uint4(__byte_perm(r0.y, r1.y, 0x5410), __byte_perm(r0.y, r1.y, 0x7632), __byte_perm(r2.y, r3.y, 0x5410), __byte_perm(r2.y, r3.y, 0x7632))};
#pragma unroll
            for (int h = 0; h < 2; h++) {
                const int m = 2 * ks + h;
                wo[m] = f[h];
            }
        }
    }
    PROF2(threadIdx.x == 0, 3502);
    mbar_wait(sb + R_BAR + RB_INIT * 8, 0);
    PROF2(threadIdx.x == 0, 3503);
#pragma unroll
    for (int ks = 0; ks < 16; ks++) {
        uint4 a = ldsm4t(woff + R_STQ + ks * 2048), b = ldsm4t(woff + R_STK + ks * 2048);
        wq[ks][0] = a.x; wq[ks][1] = a.y; wq[ks][2] = a.z; wq[ks][3] = a.w;
        wk[ks][0] = b.x; wk[ks][1] = b.y; wk[ks][2] = b.z; wk[ks][3] = b.w;
    }
    bar_sync(NB_W, 256);
#pragma unroll
    for (int m = 0; m < 16; m++)
        if (m < NPF || m >= NPF + NWO) sts128(lw + w * 512 + R_WO + (m < NPF ? m : m - NWO) * 4096, wo[m].x, wo[m].y, wo[m].z, wo[m].w);
#pragma unroll
    for (int i = 0; i < 16; i++) {
        wv[i] = ldsm4t(woff + R_STV + i * 2048);
        if (!((VMASK >> i) & 1)) sts128(lw + w * 512 + R_WV + i * 4096, wv[i].x, wv[i].y, wv[i].z, wv[i].w);
    }
    fence_async_smem();
    PROF2(threadIdx.x == 0, 3504);
    __syncthreads();
    cluster_sync();
    PROF2(threadIdx.x == 0, 3505);
    RecW k;
    {
        const int r = (w * 4 + (lane >> 3)) * 2 + rank;
        const uint32_t sl = lds32(sb + R_SEL + r * 4);
        k.po = (w * 8 + rank) * 512 + (head >> 1) * 16 + (head & 1) * 4;
        k.sp = (((lane >> 3) * 1024 + (sl & 1) * 256 + (lane & 4) * 2 + (lane & 3)) << 20) + (((sl >> 1) ^ sl) & 1) + (lane & 7) * 656 + (lane >> 3) * 128 + w * 16 +
               ((g < 4 ? (w * 4 + c) * 4 + g : w * 4 + c) << 13);
    }
    k.dp = mapa(sb, rank ^ 1) - sb;
    k.lw = lw;
    asm volatile("" : "+r"(k.lw));
    k.w = w;
    const int e0 = (p.chains & 1) ? 64 : 0, o1 = (p.chains & 2) ? p.lag : 1000, nit = (p.chains & 2) ? p.lag + 64 : e0;
    const uint32_t zero = p.zero;
    int it = 0, X = e0 ? 0 : 1;
#pragma unroll 1
    while (it < nit) {
        rec_step(k, sb, X, X ? it - o1 : it, zero, o1, e0 - o1, o1 + 1 - X, wq, wk, wv, wo);
        if (X == 0 && it >= o1) X = 1; else { it++; X = it < e0 ? 0 : 1; }
    }
}

__device__ __forceinline__ uint32_t mism(uint32_t a, uint32_t b, uint32_t t) {
    uint32_t d; asm("lop3.b32 %0,%1,%2,%3,0x7e;" : "=r"(d) : "r"(a), "r"(b), "r"(t)); return d;
}
__device__ __forceinline__ uint32_t or3(uint32_t a, uint32_t b, uint32_t c) {
    uint32_t d; asm("lop3.b32 %0,%1,%2,%3,0xfe;" : "=r"(d) : "r"(a), "r"(b), "r"(c)); return d;
}
template <bool TWO, class F>
__device__ __forceinline__ void poll8(uint4* x, const uint4* src, uint32_t tag, F&& use) {
#pragma unroll
    for (int j = 0; j < 8; j++) x[j] = ld_rlx128(src + j * 32);
    int n = 0;
    while (true) {
        use();
        uint32_t bad = or3(mism(x[0].x, x[1].x, tag), mism(x[2].x, x[3].x, tag), mism(x[4].x, x[5].x, tag));
        if (TWO) bad = or3(bad, or3(mism(x[0].z, x[1].z, tag), mism(x[2].z, x[3].z, tag), mism(x[4].z, x[5].z, tag)), mism(x[6].z, x[7].z, tag));
        if (!__any_sync(0xffffffffu, (bad | mism(x[6].x, x[7].x, tag)) & 1)) break;
#pragma unroll
        for (int j = 0; j < 8; j++)
            asm volatile("{.reg .pred p; .reg .b128 t; .reg .b32 m; lop3.b32 m,%0,%6,%5,0x7e; and.b32 m,m,1; setp.ne.u32 p,m,0; mov.b128 t,{%0,%1,%2,%3};"
                         "@p ld.relaxed.gpu.global.b128 t,[%4]; mov.b128 {%0,%1,%2,%3},t;}"
                         : "+r"(x[j].x), "+r"(x[j].y), "+r"(x[j].z), "+r"(x[j].w) : "l"(src + j * 32), "r"(tag), "r"(TWO ? x[j].z : tag) : "memory");
        if (++n > 2000000) __trap();
    }
}

__device__ __forceinline__ void rec_comm(const Params& p, uint32_t sb, int X, int head, uint32_t rank) {
    const int lane = threadIdx.x & 31, g = lane >> 2, c = lane & 3;
    const int me = head * 2 + rank;
    const uint32_t mb = sb + R_M + X * 4096 + lane * 16;
    uint4 x[8];
#pragma unroll
    for (int j = 0; j < 8; j++) x[j] = *(const uint4*)(p.mem0 + (lane & 7) * 512 + rank * 256 + (j * 4 + (lane >> 3)) * 8);
    const uint32_t sl = lds32(sb + R_SEL + me * 4);
    const uint4* src1 = xregion(X, me) + ((sl >> X) & 1) * 256 + (c >> 1) * 16 + (g >> 2) * 8 + (c & 1) * 4 + (g & 3);
    const uint4* src2 = xregion(X, 64 + rank) + ((sl >> (2 + X)) & 1) * 256 + lane;
    uint2* mdst = (uint2*)(xregion(X, 64 + rank) + (c >> 1) * 256 + head * 8 + (g & 3) * 2 + (c & 1)) + (g >> 2);
    const uint32_t one = (g & 1) ? 0x3f800000u : 0x00003f80u, selA = (g & 2) ? 0u : one, selB = (g & 2) ? one : 0u;
    const uint32_t qb = sb + R_BAR + (RB_QK + X * 8) * 8;
    if (lane < 8) mbar_expect(qb + lane * 8, 768);
    __syncwarp();
#pragma unroll
    for (int j = 0; j < 8; j++) sts128(mb + j * 512, x[j].x, x[j].y, x[j].z, x[j].w);
#pragma unroll 1
    for (int s = 0;; s++) {
        bar_arrive(NB_MFULL + X, 288);
        PROF(lane == 0, X * 64 + s);
        bar_sync(NB_PART + X, 288);
        if (s == 63) break;
        const uint32_t tag = (s + 1) & 1;
        asm volatile("{.reg .pred p; setp.lt.u32 p,%0,%1; @p mbarrier.arrive.expect_tx.shared::cta.b64 _,[%0],768;}"
                     ::"r"(((mb + (s & p.zero)) >> 1) + (qb - ((sb + R_M + X * 4096) >> 1))), "r"(qb + 64) : "memory");
        if (SPV) spin_v(D1 + (mb & p.zero)); else spin(D1);
        uint32_t m0, m1;
        auto reduce = [&]() {
            float a[RACC][4];
#pragma unroll
            for (int j = 0; j < 8; j++) {
                if (j < RACC) a[j][0] = a[j][1] = a[j][2] = a[j][3] = 0;
                mma16(a[j % RACC], x[j].x, x[j].y, x[j].z, x[j].w, selA, selB);
            }
#pragma unroll
            for (int i = 0; i < 4; i++) a[0][i] = RACC == 4 ? (a[0][i] + a[1][i]) + (a[2 % RACC][i] + a[3 % RACC][i]) : a[0][i] + a[1][i];
            m0 = (pack2(a[0][0], a[0][1]) & ~1u) | tag; m1 = pack2(a[0][2], a[0][3]);
        };
        poll8<false>(x, src1, tag, [&]() { if (RACC == 2) reduce(); });
        if (RACC == 4) reduce();
        asm volatile("st.relaxed.gpu.global.b64 [%0],%1;" ::"l"(mdst), "l"(((uint64_t)m1 << 32) | m0) : "memory");
        if (SPV) spin_v(D2 + (mb & p.zero)); else spin(D2);
        poll8<true>(x, src2, tag, [&]() {
#pragma unroll
            for (int j = 0; j < SEARLY; j++) sts128(mb + j * 512, x[j].x, x[j].y, x[j].z, x[j].w);
        });
#pragma unroll
        for (int j = SEARLY; j < 8; j++) sts128(mb + j * 512, x[j].x, x[j].y, x[j].z, x[j].w);
    }
}

template <int MT>
__device__ __forceinline__ void xattn(uint32_t l16, uint32_t l8, uint32_t os, int g, int c) {
    constexpr int NT = 3 + 2 * MT, XUN = XU;
    float S[NT][4];
#pragma unroll
    for (int i = 0; i < NT; i++) S[i][0] = S[i][1] = S[i][2] = S[i][3] = 0;
#pragma unroll XUN
    for (int ks = 0; ks < 8; ks++) {
        const uint4 q = lds128(l16 + SL_Q + ks * 512);
        const uint2 u = lds64(l8 + SL_KM + ks * 256);
        mma16(S[0], q.x, q.y, q.z, q.w, u.x, u.y);
#pragma unroll
        for (int m = 0; m <= MT; m++) {
            const uint4 kk = lds128(l16 + m * 4096 + ks * 512);
            mma16(S[1 + 2 * m], q.x, q.y, q.z, q.w, kk.x, kk.z); mma16(S[2 + 2 * m], q.x, q.y, q.z, q.w, kk.y, kk.w);
        }
    }
    const float NEG = -__int_as_float(0x7f800000);
    if (2 * c > g) { S[NT - 2][0] = NEG; S[NT - 1][2] = NEG; }
    if (2 * c + 1 > g) { S[NT - 2][1] = NEG; S[NT - 1][3] = NEG; }
    S[NT - 1][0] = S[NT - 1][1] = NEG;
    float m0 = fmaxf(S[0][0], S[0][1]), m1 = fmaxf(S[0][2], S[0][3]);
#pragma unroll
    for (int i = 1; i < NT; i++) { if (i < NT - 1) m0 = fmaxf(m0, fmaxf(S[i][0], S[i][1])); m1 = fmaxf(m1, fmaxf(S[i][2], S[i][3])); }
    m0 = fmaxf(m0, __shfl_xor_sync(0xffffffffu, m0, 1)); m1 = fmaxf(m1, __shfl_xor_sync(0xffffffffu, m1, 1));
    m0 = fmaxf(m0, __shfl_xor_sync(0xffffffffu, m0, 2)); m1 = fmaxf(m1, __shfl_xor_sync(0xffffffffu, m1, 2));
    m0 *= -SC_LOG2E; m1 *= -SC_LOG2E;
    float l0 = 0, l1 = 0;
#pragma unroll
    for (int i = 0; i < NT; i++) {
        if (i < NT - 1) { S[i][0] = ex2(fmaf(S[i][0], SC_LOG2E, m0)); S[i][1] = ex2(fmaf(S[i][1], SC_LOG2E, m0)); l0 += S[i][0] + S[i][1]; }
        S[i][2] = ex2(fmaf(S[i][2], SC_LOG2E, m1)); S[i][3] = ex2(fmaf(S[i][3], SC_LOG2E, m1)); l1 += S[i][2] + S[i][3];
    }
    l0 += __shfl_xor_sync(0xffffffffu, l0, 1); l1 += __shfl_xor_sync(0xffffffffu, l1, 1);
    l0 += __shfl_xor_sync(0xffffffffu, l0, 2); l1 += __shfl_xor_sync(0xffffffffu, l1, 2);
    uint2 vm = lds64(l8 + SL_VM);
    uint4 v[2];
#pragma unroll
    for (int m = 0; m <= MT; m++) v[m] = lds128(l16 + SL_V + m * 4096);
    l0 = rcp(l0); l1 = rcp(l1);
    uint32_t P[NT][2];
#pragma unroll
    for (int i = 0; i < NT; i++) { P[i][0] = i < NT - 1 ? pack2(S[i][0] * l0, S[i][1] * l0) : 0u; P[i][1] = pack2(S[i][2] * l1, S[i][3] * l1); }
#pragma unroll
    for (int et = 0; et < 8; et++) {
        float a[4] = {0, 0, 0, 0}, b[4] = {0, 0, 0, 0};
        const uint2 um = vm;
        const uint4 u[2] = {v[0], v[MT]};
        if (et < 7) {
            vm = lds64(l8 + SL_VM + et * 256 + 256);
#pragma unroll
            for (int m = 0; m <= MT; m++) v[m] = lds128(l16 + SL_V + m * 4096 + et * 512 + 512);
            PIN(11);
        }
        mma8(a, um.x, um.y, P[0][0]); mma8(b, um.x, um.y, P[0][1]);
#pragma unroll
        for (int m = 0; m <= MT; m++) {
            mma16(a, u[m].x, u[m].y, u[m].z, u[m].w, P[1 + 2 * m][0], P[2 + 2 * m][0]); mma16(b, u[m].x, u[m].y, u[m].z, u[m].w, P[1 + 2 * m][1], P[2 + 2 * m][1]);
        }
        asm volatile("stmatrix.sync.aligned.m8n8.x4.trans.shared.b16 [%0],{%1,%2,%3,%4};" ::"r"(os + (et >> 2) * 2048 + (et & 3) * 256),
                     "r"(pack2(a[0], a[1])), "r"(pack2(a[2], a[3])), "r"(pack2(b[0], b[1])), "r"(pack2(b[2], b[3])) : "memory");
    }
}

__device__ __forceinline__ void rec_tiles(uint32_t sb, int X, int head, uint32_t rank, int& nxt, int lim, int need) {
#pragma unroll 1
    while (nxt <= lim) {
        if ((nxt & 1) == 0) {
            unsigned v; int n = 0;
            while (true) {
                asm volatile("ld.relaxed.gpu.global.u32 %0,[%1];" : "=r"(v) : "l"(cnt_ptr(C_QKV + X * 32 + (nxt >> 1))) : "memory");
                if (__all_sync(0xffffffffu, v >= 2 * NQ)) break;
                if (nxt > need) return;
                if (++n > 3000000) __trap();
            }
        }
        if (elect()) {
            const uint32_t bar = sb + R_BAR + (RB_XFULL + X * 2 + (nxt & 1)) * 8, dst = sb + R_SL + (X * 2 + (nxt & 1)) * SLOT;
            const uint4* src = g_qkv + (size_t)((X * 64 + nxt) * 32 + head) * 1536;
            mbar_expect(bar, 20480);
            bulk_g2s_mc(dst + rank * 8192, src + 512 + rank * 512, 8192, bar, POL_LAST);
            bulk_g2s(dst + SL_Q, src + (rank ^ X) * 256, 4096, bar, POL_LAST);
        }
        __syncwarp();
        nxt++;
    }
}

__device__ __forceinline__ void rec_attn(const Params& p, uint32_t sb, int X, int head, uint32_t rank) {
    const int lane = __shfl_sync(0xffffffffu, threadIdx.x & 31, threadIdx.x & 31), g = lane >> 2, c = lane & 3;
    const int mt = rank ^ X;
    const uint32_t dp = mapa(sb, rank ^ 1) - sb;
    int nxt = 0;
    rec_tiles(sb, X, head, rank, nxt, 1, 0);
#pragma unroll 1
    for (int s = 0; s < 64; s++) {
        const uint32_t so = sb + R_SL + (X * 2 + (s & 1)) * SLOT;
        while (nxt <= min(s + 1, 63)) {
            uint32_t ok;
            asm volatile("{.reg .pred p; mbarrier.test_wait.parity.shared::cta.b64 p,[%1],%2; selp.u32 %0,1,0,p;}" : "=r"(ok) : "r"(sb + R_BAR + (RB_GO + X * 2 + (s & 1)) * 8), "r"((s >> 1) & 1) : "memory");
            if (__any_sync(0xffffffffu, ok)) break;
            rec_tiles(sb, X, head, rank, nxt, s + 1, -1);
        }
        mbar_wait(sb + R_BAR + (RB_GO + X * 2 + (s & 1)) * 8, (s >> 1) & 1);
        if (elect()) asm volatile("cp.async.bulk.wait_group.read 0;" ::: "memory");
        __syncwarp();
        const uint32_t os = sb + R_OS + X * 4096 + (lane >> 4) * 1024 + (lane & 15) * 16;
        if (mt) xattn<1>(so + lane * 16, so + lane * 8, os, g, c); else xattn<0>(so + lane * 16, so + lane * 8, os, g, c);
        fence_async_smem();
        __syncwarp();
        const uint32_t svb = sb + R_BAR + (RB_SV + X * 2 + (s & 1)) * 8;
        if (elect()) {
            mbar_arrive(svb); mbar_arrive_cluster(svb + dp);
            const uint64_t pol = POL_SOON;
#pragma unroll
            for (int kb = 0; kb < 2; kb++)
                asm volatile("cp.async.bulk.global.shared::cta.bulk_group.L2::cache_hint [%0],[%1],%2,%3;" ::"l"(g_o + ((X * 32 + (s >> 1)) * 64 + head * 2 + kb) * 512 + ((s & 1) * 4 + mt * 2) * 64),
                             "r"(sb + R_OS + X * 4096 + kb * 2048), "r"(2048), "l"(pol) : "memory");
            asm volatile("cp.async.bulk.commit_group;" ::: "memory");
        }
        __syncwarp();
        if (s & 1) {
            if (elect()) { asm volatile("cp.async.bulk.wait_group 0;" ::: "memory"); red_relaxed(cnt_ptr(C_O + (X * 32 + (s >> 1)) * 4 + (head >> 3)), 1); }
            __syncwarp();
        }
        rec_tiles(sb, X, head, rank, nxt, min(s + 1, 63), s + 1);
        mbar_wait(svb, (s >> 1) & 1);
        rec_tiles(sb, X, head, rank, nxt, min(s + 2, 63), -1);
    }
}

__device__ __forceinline__ uint32_t timed_clear(unsigned* r, int lane) {
    uint32_t v = 0;
    const uint32_t t0 = clk32();
    asm volatile("{.reg .pred p; setp.eq.u32 p,%2,0; @p atom.relaxed.gpu.global.exch.b32 %0,[%1],0;}" : "+r"(v) : "l"(r), "r"(lane) : "memory");
    v = __shfl_sync(0xffffffffu, v, 0);
    asm volatile("{.reg .pred p; setp.eq.u32 p,%0,0x5a5a5a5b; @p nanosleep.u32 1;}" ::"r"(v) : "memory");
    return clk32() - t0;
}
__device__ __forceinline__ void rec_slots(int me, int w) {
    const int lane = threadIdx.x & 31;
    uint4* r = xregion(w & 1, (w & 2) ? 64 + (me & 1) : me) + ((w & 2) ? (me >> 1) * 8 : 0);
#pragma unroll 1
    for (int i = lane; i < ((w & 2) ? 8 : 256); i += 32) r[i] = r[i + 256] = make_uint4(0, 0, 0, 0);
    __syncwarp();
    uint32_t b0 = ~0u, b1 = ~0u;
#pragma unroll 1
    for (int i = 0; i < NPRB; i++) { b0 = min(b0, timed_clear((unsigned*)r, lane)); b1 = min(b1, timed_clear((unsigned*)(r + 256), lane)); }
    if (lane == 0) ((uint8_t*)g_sel)[me * 4 + w] = (b1 < b0) << w;
}

__device__ __forceinline__ void rec_init(uint32_t sb) {
    const uint32_t b = sb + R_BAR;
    const int i = threadIdx.x & 31;
    mbar_init(b + i * 8, i >= RB_SV ? 2 : 1);
    if (i == RB_INIT) mbar_expect(b + RB_INIT * 8, 196608);
    asm volatile("fence.mbarrier_init.release.cluster;" ::: "memory");
}
constexpr int G_BAR = B_BAR;
enum { GB_FULL = 0  , GB_EMPTY = 8  , GB_RS = 16, GB_SS = 17, GB_LAG = 18, GB_FREE = 19, GB_DONE = 20  , GB_N = 24 };
constexpr int Q_PRE = 8;
constexpr int NQRS = 2 * NQ - 64;
__device__ __forceinline__ void gemm_init(uint32_t sb, bool op) {
    const int i = threadIdx.x & 31;
    if (i < GB_N) mbar_init(sb + G_BAR + i * 8, i >= GB_DONE ? 4 : i == GB_FREE ? 8 : (i >= GB_EMPTY && i < GB_RS) ? 2 : 1);
    if (i == GB_RS) mbar_expect(sb + G_BAR + i * 8, op ? 131072 : 98304);
    if (i == GB_SS) mbar_expect(sb + G_BAR + i * 8, op ? 131072 : 163840);
    asm volatile("fence.mbarrier_init.release.cluster;" ::: "memory");
}
__device__ __forceinline__ int qkv_blk(int id, int j) { return NQRS * 4 + id * 10 + j; }
__device__ __forceinline__ void qkv_fetch(const Params& p, uint32_t sb, int id, int j0, int j1) {
#pragma unroll 1
    for (int j = j0 * 2; j < j1 * 2; j++) {
        const int blk = min(qkv_blk(id, j >> 1), 511);
        tma2d(sb + j * 8192, &p.tn[blk >> 8], (blk & 255) * 16, (j & 1) * 256, sb + G_BAR + GB_SS * 8);
    }
}
__device__ __forceinline__ void qkv_stage(const Params& p, uint32_t dst, uint32_t bar, int id, int k0, int nk) {
#pragma unroll 1
    for (int j = 0; j < 2 * nk; j++) {
        const int u = id * 2 + (j >= nk);
        tma2d(dst + j * 8192, &p.tm[u < 64 ? 2 : 0], (u & 63) * 64, (k0 + (j >= nk ? j - nk : j)) * 64, bar);
    }
}
__device__ __forceinline__ void op_fetch(const Params& p, uint32_t sb, int id, int half) {
#pragma unroll 1
    for (int j = 0; j < 16; j++) tma2d(sb + j * 8192, &p.tm[4], ((id * 2 + (j >> 3)) & 7) * 64, (id >> 2) * 1024 + (j & 7) * 128 + half * 64, sb + G_BAR + (GB_RS + half) * 8);
}
template <bool OP>
__device__ __forceinline__ void gemm_producer(const Params& p, uint32_t sb, int id) {
    constexpr int NS = OP ? 6 : 8, SB = OP ? 16384 : 8192, RB = OP ? 131072 : 163840;
    if (!elect()) return;
    mbar_wait(sb + G_BAR + GB_FREE * 8, 0);
    if (OP) op_fetch(p, sb, id, 1);
    else {
        mbar_expect(sb + G_BAR + GB_RS * 8, 32768);
        qkv_stage(p, sb + 196608, sb + G_BAR + GB_RS * 8, id, 6, 2);
        qkv_fetch(p, sb, id, Q_PRE, 10);
        mbar_wait(sb + G_BAR + GB_FREE * 8, 1);
    }
    wait_cnt(g_gate, lds32(sb + S_GATE));
    int st = 0; uint32_t ph = 1;
#pragma unroll 1
    for (int n = 0; n < p.nl[OP]; n++) {
        const int e = p.list[OP][n];
        wait_cnt(OP ? cnt_ptr(C_O + e * 4 + (id >> 2)) : cnt_ptr(C_XN + e), 16);
        PROF(true, 1024 + n * 4);
        const uint4* src = OP ? g_o + (e * 64 + (id >> 2) * 16) * 512 : g_xn + e * 4096;
#pragma unroll 1
        for (int s = 0; s < 8; s++) {
            mbar_wait(sb + G_BAR + (GB_EMPTY + st) * 8, ph);
            mbar_expect(sb + G_BAR + (GB_FULL + st) * 8, SB);
            bulk_g2s(sb + RB + st * SB, src + s * (SB / 16), SB, sb + G_BAR + (GB_FULL + st) * 8, POL_N);
            if (++st == NS) { st = 0; ph ^= 1; }
        }
    }
}
__device__ __forceinline__ void qkv_release(const Params& p, uint32_t sb) {
    if (!elect()) return;
#pragma unroll 1
    for (int n = 0; n < 2 * p.nl[0]; n++) {
        const int e = p.list[0][n >> 1];
        mbar_wait(sb + G_BAR + (GB_DONE + (n & 3)) * 8, (n >> 2) & 1);
        red_release(cnt_ptr(C_QKV + e), 1);
        PROF(n & 1, 1024 + (n >> 1) * 4 + 3);
    }
}
__device__ __forceinline__ void op_permute(uint32_t sb) {
#pragma unroll 2
    for (int i = threadIdx.x; i < 4096; i += 256) {
        const uint32_t a = sb + i * 32 + ((i >> 2) & 1) * 16, b = a ^ 16;
        const uint4 x = lds128(a), y = lds128(b);
        sts128(a, __byte_perm(x.x, x.y, 0x5410), __byte_perm(x.z, x.w, 0x5410), __byte_perm(y.x, y.y, 0x5410), __byte_perm(y.z, y.w, 0x5410));
        sts128(b, __byte_perm(x.x, x.y, 0x7632), __byte_perm(x.z, x.w, 0x7632), __byte_perm(y.x, y.y, 0x7632), __byte_perm(y.z, y.w, 0x7632));
    }
    fence_async_smem();
    bar_sync(1, 256);
}
template <bool OP>
__device__ __forceinline__ void gemm_consumer(const Params& p, uint32_t sb, int id, int w) {
    constexpr int NS = OP ? 6 : 8, SB = OP ? 16384 : 8192, RB = OP ? 131072 : 163840;
    const int lane = threadIdx.x & 31, wg = w >> 2, t = w & 3, u = id * 2 + wg;
    uint32_t a[128];
    mbar_wait(sb + G_BAR + GB_RS * 8, 0);
    PROF2(threadIdx.x == 0, 3501);
    if (OP) op_permute(sb);
    const uint32_t wo = sb + (((lane >> 4) << 3) + (lane & 7)) * 128 + (((2 * t + ((lane >> 3) & 1)) ^ (lane & 7)) << 4);
#pragma unroll
    for (int ks = 0; ks < 32; ks++) {
        const uint4 v = ldsm4t(wo + ks * 2048 + (OP ? wg * 65536 : ks < 24 ? 131072 + wg * 49152 : 196608 - 49152 + wg * 16384));
        a[ks * 4] = v.x; a[ks * 4 + 1] = v.y; a[ks * 4 + 2] = v.z; a[ks * 4 + 3] = v.w;
        if (ks == 31 || (!OP && ks == 23)) {
            fence_async_smem();
            __syncwarp();
            if (lane == 0) mbar_arrive(sb + G_BAR + GB_FREE * 8);
            if (ks == 23) mbar_wait(sb + G_BAR + GB_RS * 8, 1);
        }
    }
    PROF2(threadIdx.x == 0, 3502);
    mbar_wait(sb + G_BAR + GB_SS * 8, 0);
    if (OP) op_permute(sb);
    PROF2(threadIdx.x == 0, 3503);
    const uint32_t tag = OP ? lds32(sb + S_TAG) : 0;
    float c0[32], c1[OP ? 32 : 40];
    int st = 0; uint32_t ph = 0;
    const bool el = (threadIdx.x & 127) == 0;
#pragma unroll 1
    for (int n = 0; n < p.nl[OP]; n++) {
        int prev = 0;
        const uint32_t wb = sb + wg * (OP ? 65536 : 81920) + (n & p.zero);
        const uint64_t dw = OP ? mkdesc(wb, 0, 1024, 1) : mkdesc(wb, 16384, 256, 3);
        if (!OP && wg) mbar_wait(sb + G_BAR + GB_LAG * 8, n & 1);
#pragma unroll
        for (int s = 0; s < 8; s++) {
            mbar_wait(sb + G_BAR + (GB_FULL + st) * 8, ph);
            const uint64_t dx = mkdesc(sb + RB + st * SB, 128, 1024, 0);
            wg_fence();
#pragma unroll
            for (int kk = 0; kk < 4; kk++) {
                const int ks = s * 4 + kk;
                if (ks == 0) { wgmma64_rs<0>(c0, a, dx); if (OP) wgmma64_ta<0>(c1, dw, dx + 512); else wgmma80_tb<0>(c1, dx, dw); }
                else { wgmma64_rs<1>(c0, a + ks * 4, dx + kk * 16); if (OP) wgmma64_ta<1>(c1, dw + ks * 128, dx + 512 + kk * 16); else wgmma80_tb<1>(c1, dx + kk * 16, dw + ks * 32); }
            }
            wg_commit();
            if (s) {
                wg_wait<1>();
                if (el) { mbar_arrive(sb + G_BAR + (GB_EMPTY + prev) * 8); if (!OP && s == QLAG && !wg) mbar_arrive(sb + G_BAR + GB_LAG * 8); }
            }
            prev = st;
            if (++st == NS) { st = 0; ph ^= 1; }
        }
        const int e = p.list[OP][n];
        wg_wait<0>();
        if (el) mbar_arrive(sb + G_BAR + (GB_EMPTY + prev) * 8);
        PROF(threadIdx.x == 128, 1024 + n * 4 + 1);
        if (OP) {
            uint4* dst = g_pp + (e * 4 + (id >> 2)) * 4096 + ((u & 7) * 32 + t * 8) * 16 + (lane >> 2) * 16 + (lane & 3);
#pragma unroll
            for (int j = 0; j < 4; j++) {
                const float* x = c0 + j * 8; const float* y = c1 + j * 8;
                st_rlx128(dst + j * 4, (pack2(x[0] + y[0], x[1] + y[1]) & ~1u) | tag, pack2(x[2] + y[2], x[3] + y[3]), (pack2(x[4] + y[4], x[5] + y[5]) & ~1u) | tag, pack2(x[6] + y[6], x[7] + y[7]));
            }
            if (lane == 0) red_relaxed(cnt_ptr(C_PP + e * 8 + (u & 7)), 1);
            PROF(threadIdx.x == 128, 1024 + n * 4 + 3);
        } else {
            uint4* dst = g_qkv + (size_t)e * 2 * 32 * 1536 + lane;
            const uint64_t pol = POL_SOON;
#pragma unroll
            for (int j = 0; j < 4; j++) {
                const float* x = c0 + j * 8;
                uint4 v = make_uint4(pack2(x[0], x[1]), pack2(x[2], x[3]), pack2(x[4], x[5]), pack2(x[6], x[7]));
                if (u >= 64) v = make_uint4(movm(v.x), movm(v.z), movm(v.y), movm(v.w));
                stg128(dst + (((j >> 1) * 32 + ((u & 63) >> 1)) * 1536 + (u < 64 ? 1024 : 0) + (j & 1) * 256 + ((u & 1) * 4 + t) * 32), v, pol);
            }
#pragma unroll
            for (int j = 0; j < 5; j++) {
                const float* x = c1 + (OP ? 0 : j * 8);
                const int blk = qkv_blk(id, wg * 5 + j);
                if (blk < 512) stg128(dst + (((t >> 1) * 32 + ((blk >> 3) & 31)) * 1536 + (blk >> 8) * 512 + (t & 1) * 256 + (blk & 7) * 32),
                                      make_uint4(pack2(x[0], x[1]), pack2(x[2], x[3]), pack2(x[4], x[5]), pack2(x[6], x[7])), pol);
            }
        }
        __syncwarp();
        if (!OP && lane == 0) mbar_arrive(sb + G_BAR + (GB_DONE + (n & 1) * 2 + wg) * 8);
        PROF(threadIdx.x == 128, 1024 + n * 4 + 2);
    }
}

template <int NP, bool MMA>
__device__ __forceinline__ void sum_partials(float* x, const uint2* src, const uint32_t* r0, const uint32_t* r1, uint32_t idm, uint32_t tag, bool on) {
    uint2 v[4][NP];
    int n = 0;
    while (true) {
        uint32_t bad = 0;
#pragma unroll
        for (int s = 0; s < 4; s++)
#pragma unroll
            for (int i = 0; i < NP; i++)
                asm volatile("{.reg .pred p; .reg .b64 t; setp.ne.u32 p,%4,0; mov.b64 t,0; @p ld.relaxed.gpu.global.L2::cache_hint.b64 t,[%2],%3; mov.b64 {%0,%1},t;}"
                             : "=r"(v[s][i].x), "=r"(v[s][i].y) : "l"(src + s * 8192 + i * 32), "l"(POL_LAST), "r"((uint32_t)on) : "memory");
#pragma unroll
        for (int s = 0; s < 4; s++) bad = or3(bad, mism(v[s][0].x, v[s][1].x, tag), mism(v[s][NP - 2].x, v[s][NP - 1].x, tag));
        if (!__any_sync(0xffffffffu, (bad & 1) && on)) break;
        if (++n > 2000000) __trap();
    }
#pragma unroll
    for (int i = 0; i < NP; i++) {
        uint32_t a, b;
        if (MMA) {
            float t[4] = {0, 0, 0, 0};
            mma16(t, v[0][i].x, v[0][i].y, v[1][i].x, v[1][i].y, idm, idm); mma16(t, v[2][i].x, v[2][i].y, v[3][i].x, v[3][i].y, idm, idm);
            a = pack2(t[0], t[2]); b = pack2(t[1], t[3]);
        } else {
            a = pack2((blo(v[0][i].x) + blo(v[1][i].x)) + (blo(v[2][i].x) + blo(v[3][i].x)), (blo(v[0][i].y) + blo(v[1][i].y)) + (blo(v[2][i].y) + blo(v[3][i].y)));
            b = pack2((bhi(v[0][i].x) + bhi(v[1][i].x)) + (bhi(v[2][i].x) + bhi(v[3][i].x)), (bhi(v[0][i].y) + bhi(v[1][i].y)) + (bhi(v[2][i].y) + bhi(v[3][i].y)));
        }
        const uint32_t s0 = hadd2(a, r0[i]), s1 = hadd2(b, r1[i]);
        x[4 * i] = blo(s0); x[4 * i + 2] = bhi(s0); x[4 * i + 1] = blo(s1); x[4 * i + 3] = bhi(s1);
    }
}
__device__ __forceinline__ const uint2* pp_src(int e, int tile, int lane) { return (const uint2*)g_pp + e * 32768 + tile * 128 + (lane >> 3) * 8 + (lane & 3) * 2 + ((lane >> 2) & 1); }

__device__ __forceinline__ void fin_warp(const Params& p, uint32_t sb, int id) {
    const int grp = (id & ~3) + (threadIdx.x & 3), tp = (id & 3) * 8 + ((threadIdx.x & 31) >> 2);
    wait_slow_warp(g_gate, lds32(sb + S_GATE));
#pragma unroll 1
    for (int e = 32; e < 64; e++) {
        wait_slow_warp(cnt_ptr(C_XN + e), 16);
        const uint4 r = ldcg128(g_x + ((128 + grp) * XP + (e - 32) * 32 + tp));
        if (e < 63) wait_slow_warp(cnt_ptr(C_PP + e * 8 + (id >> 4)), 16); else wait_slow_warp(cnt_ptr(C_O + 63 * 4), 16);
        wait_flag_warp(cnt_ptr(C_PP + e * 8 + (id >> 4)), 16);
        const uint32_t a[2] = {r.x, r.y}, b[2] = {r.z, r.w};
        float x[8];
        sum_partials<2, false>(x, pp_src(e, 0, tp) + grp * 64, a, b, 0, lds32(sb + S_TAG), true);
        uint2* dst = (uint2*)p.out + ((e - 32) * 64 + tp * 2) * 128 + grp;
#pragma unroll
        for (int t = 0; t < 2; t++)
            dst[t * 128] = make_uint2(__byte_perm(__float_as_uint(x[t]), __float_as_uint(x[2 + t]), 0x7632), __byte_perm(__float_as_uint(x[4 + t]), __float_as_uint(x[6 + t]), 0x7632));
        PROF((threadIdx.x & 31) == 0, 1536 + e);
    }
}

constexpr int PROW = 272, UROW = 2304, UPRE = 256;
constexpr int C_UR = 0  , C_TB = 65536  , C_BG = C_TB + 51200,
              CB_M = 8960, CB_U = CB_M + 1792, CB_BIG = CB_U + 2560, C_ST = C_BG + 8 * CB_BIG  ;
static_assert(C_ST + 4736 <= B_BAR, "smem map");
enum { CB_TB = 0, CB_UF = 1  , CB_CF = 5  , CB_LD = 9   };
__device__ __forceinline__ void conv_init(uint32_t sb, bool spare) {
    const int i = threadIdx.x & 31;
    mbar_init(sb + B_BAR + i * 8, (i >= CB_UF && i < CB_CF && !spare) ? 2 : 1);
    if (i == CB_TB && !spare) mbar_expect(sb + B_BAR + i * 8, 51200);
    asm volatile("fence.mbarrier_init.release.cluster;" ::: "memory");
}
__device__ __forceinline__ void mma_q(float* c, const uint32_t* a, const uint4& q) {
    mma16(c, a[0], a[1], a[2], a[3], q.x, q.y); mma16(c, a[4], a[5], a[6], a[7], q.z, q.w);
}
__device__ __forceinline__ uint2 ld_acc(const uint2* p, bool on) {
    uint2 v = make_uint2(0, 0);
    asm volatile("{.reg .pred p; setp.ne.u32 p,%3,0; @p ld.global.cg.v2.u32 {%0,%1},[%2];}" : "+r"(v.x), "+r"(v.y) : "l"(p), "r"((uint32_t)on) : "memory");
    return v;
}
__device__ __forceinline__ void add_acc(float* c, uint2 v) { c[0] += blo(v.x); c[1] += bhi(v.x); c[2] += blo(v.y); c[3] += bhi(v.y); }
__device__ __forceinline__ void st_acc(uint2* p, const float* c) { *p = make_uint2(pack2(c[0], c[1]), pack2(c[2], c[3])); }
__device__ __forceinline__ float sum8(const uint4* v, int k) {
#define VK(i) __uint_as_float(k == 0 ? v[i].x : k == 1 ? v[i].y : k == 2 ? v[i].z : v[i].w)
    return ((VK(0) + VK(1)) + (VK(2) + VK(3))) + ((VK(4) + VK(5)) + (VK(6) + VK(7)));
}
template <int XW>
__device__ __forceinline__ void stats_send(uint32_t l16, const float* x, uint4* gs, int q, int w) {
    float s0 = 0, s1 = 0, m0 = 0, m1 = 0;
#pragma unroll
    for (int i = 0; i < 8; i++) { s0 += x[2 * i]; s1 += x[2 * i + 1]; m0 = fmaf(x[2 * i], x[2 * i], m0); m1 = fmaf(x[2 * i + 1], x[2 * i + 1], m1); }
    sts128(l16 + C_ST + w * 512, __float_as_uint(s0), __float_as_uint(m0), __float_as_uint(s1), __float_as_uint(m1));
    if (w == XW) {
        bar_sync(2, 256);
        uint4 v[8];
#pragma unroll
        for (int i = 0; i < 8; i++) v[i] = lds128(l16 + C_ST + i * 512);
        st_rlx128(gs + q * 32, __float_as_uint(sum8(v, 0)), __float_as_uint(sum8(v, 1)) & 0x7fffffffu, __float_as_uint(sum8(v, 2)), __float_as_uint(sum8(v, 3)));
    } else bar_arrive(2, 256);
}
template <int XW>
__device__ __forceinline__ float4 stats_recv(uint32_t l16, const uint4* gs, int w) {
    if (w == XW) {
        uint4 v[8];
        int n = 0;
        while (true) {
            uint32_t bad = 0;
#pragma unroll
            for (int i = 0; i < 8; i++) v[i] = ld_rlx128(gs + i * 32);
#pragma unroll
            for (int i = 0; i < 8; i++) bad |= v[i].y;
            if (!__any_sync(0xffffffffu, bad >> 31)) break;
            if (++n > 2000000) __trap();
        }
        const float s0 = sum8(v, 0) * (1.f / 512.f), s1 = sum8(v, 2) * (1.f / 512.f);
        const float2 l0 = ln_finish(s0, fmaxf(fmaf(sum8(v, 1), 1.f / 512.f, -s0 * s0), 0.f)), l1 = ln_finish(s1, fmaxf(fmaf(sum8(v, 3), 1.f / 512.f, -s1 * s1), 0.f));
        sts128(l16 + C_ST + 4096, __float_as_uint(l0.x), __float_as_uint(rcp(l0.y)), __float_as_uint(l1.x), __float_as_uint(rcp(l1.y)));
    }
    bar_sync(3, 256);
    const uint4 r = lds128(l16 + C_ST + 4096);
    return make_float4(__uint_as_float(r.x), __uint_as_float(r.y), __uint_as_float(r.z), __uint_as_float(r.w));
}

__device__ __forceinline__ void conv_near(float (*acc)[4], uint32_t ta, uint32_t qa) {
    uint32_t a[9][8];
    uint4 x[9];
#pragma unroll
    for (int k = 0; k < 9; k++) {
        if (k < 8) {
            x[k] = ldsm4(qa + k * 1024);
#pragma unroll
            for (int j = 0; j < 8; j++) a[k][j] = lds32(ta + k * 800 + j * 32);
        }
        if (k) mma_q(acc[k - 1], a[k - 1], x[k - 1]);
        PIN(13);
    }
}
template <int K0>
__device__ __forceinline__ void conv_pair(float (*acc)[4], float (*pend)[4], uint32_t ta, uint32_t q0, uint32_t q1, uint32_t q2) {
    uint32_t a[9][8];
    uint4 x[9], y[5];
#pragma unroll
    for (int n = 0; n < 9; n++) {
        if (n < 8) {
            const int k = K0 + (n >> 1);
            if (!(n & 1)) y[n >> 1] = ldsm4(q1 + k * 1024);
            x[n] = ldsm4(((n & 1) ? q0 : q2) + k * 1024);
#pragma unroll
            for (int j = 0; j < 8; j++) a[n][j] = lds32(ta + 256 + (n & 1) * 256 + k * 800 + j * 32);
        }
        if (n == 0) {
#pragma unroll
            for (int i = 0; i < 16; i++) { acc[4 - K0 + (i >> 2)][i & 3] += pend[i >> 2][i & 3]; pend[i >> 2][i & 3] = 0; }
        } else {
            const int m = n - 1, i = m >> 1;
            mma_q(acc[K0 + i], a[m], (m & 1) ? x[m] : y[i]); mma_q(pend[i], a[m], (m & 1) ? y[i] : x[m]);
        }
        PIN(13);
    }
}

__device__ __forceinline__ void conv_tile(const Params& p, uint32_t sb, int q, int w) {
    const int lane = __shfl_sync(0xffffffffu, threadIdx.x & 31, threadIdx.x & 31), g = lane >> 2, c = lane & 3, tile = q * 8 + w;
    const uint32_t l16 = sb + lane * 16;
#pragma unroll
    for (int i = 0; i < 16; i++) sts128(l16 + C_UR + w * 8192 + i * 512, 0, 0, 0, 0);
    wait_slow_warp(g_gate, lds32(sb + S_GATE));
    if (lane < 8) bulk_g2s(sb + C_TB + (w * 8 + lane) * 800, g_P + (tile * 8 + lane) * PROW + 72, 800, sb + B_BAR + CB_TB * 8, POL_N);
    uint32_t A[8][8];
#pragma unroll
    for (int k = 0; k < 8; k++)
#pragma unroll
        for (int j = 0; j < 8; j++) A[k][j] = __ldcg(g_P + (tile * 8 + k) * PROW + 16 + 8 * j + g - 2 * c);
    if (lane == 0) { const uint4 d = __ldg((const uint4*)p.Dskip + tile); sts128(sb + C_ST + 4608 + w * 16, d.x, d.y, d.z, d.w); }
    float acc[8][4], pend[4][4];
#pragma unroll
    for (int k = 0; k < 8; k++) acc[k][0] = acc[k][1] = acc[k][2] = acc[k][3] = pend[k & 3][k >> 2] = pend[k & 3][2 + (k >> 2)] = 0;
    const uint32_t row = sb + C_UR + w * 8192, ta = sb + C_TB + w * 6400 + (8 + g - 2 * c) * 4, qo = (lane & 7) * 16 - (lane >> 3) * 32;
    bar_sync(4, 384);
    mbar_wait(sb + B_BAR + CB_TB * 8, 0);
#pragma unroll 1
    for (int b = -2; b < 32; b++) {
        const int lz = lane + (b & p.zero);
        const bool on = b >= 0;
        uint4 r0 = make_uint4(0, 0, 0, 0), r1 = r0;
        asm volatile("{.reg .pred p; setp.ge.s32 p,%9,0; @p ld.global.cg.v4.u32 {%0,%1,%2,%3},[%8]; @p ld.global.cg.v4.u32 {%4,%5,%6,%7},[%8+%10];}"
                     : "+r"(r0.x), "+r"(r0.y), "+r"(r0.z), "+r"(r0.w), "+r"(r1.x), "+r"(r1.y), "+r"(r1.z), "+r"(r1.w) : "l"(g_x + (tile * 2 * XP + b * 32 + lz)), "r"(b), "n"(XP * 16) : "memory");
        const uint32_t q1 = row + ((qo + (b - 1) * 128) & 1023);
        if ((NTOP >> w) & 1) conv_near(acc, ta, q1);
        PROF2(threadIdx.x == 0 && on, 2048 + b * 8);
        const uint2* pps = pp_src(b, tile, lz);
        asm volatile("" : "+l"(pps));
        const uint32_t tag = lds32(sb + S_TAG);
        wait_flag_warp(cnt_ptr(C_PP + b * 8 + q), on ? 16 : 0);
        PROF2(threadIdx.x == 0 && on, 2048 + b * 8 + 1);
        float x[16];
        {
            const uint32_t a[4] = {r0.x, r0.y, r1.x, r1.y}, bb[4] = {r0.z, r0.w, r1.z, r1.w};
            sum_partials<4, true>(x, pps, a, bb, (2 * (lz & 3) == lz >> 2) ? 0x00003f80u : (2 * (lz & 3) + 1 == lz >> 2) ? 0x3f800000u : 0u, tag, on);
        }
        stats_send<0>(l16, x, g_st + (b + 2) * 256 + lz, q, w);
        {
            PROF2(threadIdx.x == 0 && on, 2048 + b * 8 + 2);
            if (on) mbar_wait(sb + B_BAR + (CB_CF + (w >> 1)) * 8, b & 1);
            const uint2* cb = g_carry + ((tile * 320 + b) * 32 + lz);
            uint2 cr[8];
#pragma unroll
            for (int k = 0; k < 8; k++) cr[k] = ld_acc(cb + k * 1280, b >= 4);
            if (NTOP != 255 && !((NTOP >> w) & 1) && b) conv_near(acc, ta, q1);
#pragma unroll
            for (int k = 0; k < 8; k++) add_acc(acc[k], cr[k]);
        }
        PIN(13);
        float4 ln = stats_recv<0>(l16, g_st + (b + 2) * 256 + lz, w);
        PROF2(threadIdx.x == 0 && on, 2048 + b * 8 + 3);
        uint32_t u[8];
#pragma unroll
        for (int k = 0; k < 8; k++) {
            u[k] = pack2(rbf(x[2 * k] - ln.x) * ln.y, rbf(x[2 * k + 1] - ln.z) * ln.w);
            sts32(row + k * 1024 + (b & 7) * 128 + lane * 4, u[k]);
        }
        __syncwarp();
        const uint32_t qa = row + ((qo + b * 128) & 1023);
#pragma unroll
        for (int k = 0; k < 8; k++) mma_q(acc[k], A[k], ldsm4(qa + k * 1024));
        const uint4 dk = lds128(sb + C_ST + 4608 + w * 16);
#pragma unroll
        for (int k = 0; k < 8; k++) {
            const float t = __shfl_sync(0xffffffffu, acc[k][3], (lz & ~3) | ((lz - 1) & 3));
            const uint32_t y = movm(pack2(acc[k][0] + (c ? t : 0.f), acc[k][1] + acc[k][2]));
            acc[k][0] = c ? 0.f : t; acc[k][1] = acc[k][2] = acc[k][3] = 0;
            const uint32_t dw = k >> 1 == 0 ? dk.x : k >> 1 == 1 ? dk.y : k >> 1 == 2 ? dk.z : dk.w;
            const uint32_t s = hadd2(hadd2(y, hmul2(u[k], __byte_perm(dw, 0, (k & 1) ? 0x3232 : 0x1010))), __byte_perm(__float_as_uint(x[2 * k]), __float_as_uint(x[2 * k + 1]), 0x7632));
            x[2 * k] = blo(s); x[2 * k + 1] = bhi(s);
        }
        arrive_if(sb + B_BAR + (CB_UF + (w >> 1)) * 8, lz, b < -1 ? 32 : 0);
        stats_send<1>(l16, x, g_st + (36 + b) * 256 + lz, q, w);
        {
            PROF2(threadIdx.x == 0 && on, 2048 + b * 8 + 4);
            uint4* dst = g_x + ((128 + tile * 2) * XP + b * 32 + lz);
#pragma unroll
            for (int e = 0; e < 2; e++) {
                const float* y = x + e * 8;
                if (on) dst[e * XP] = make_uint4(__byte_perm(__float_as_uint(y[0]), __float_as_uint(y[2]), 0x7632), __byte_perm(__float_as_uint(y[4]), __float_as_uint(y[6]), 0x7632),
                                           __byte_perm(__float_as_uint(y[1]), __float_as_uint(y[3]), 0x7632), __byte_perm(__float_as_uint(y[5]), __float_as_uint(y[7]), 0x7632));
            }
            uint32_t* du = g_u + (tile * 8 * (UROW / 2) + UPRE / 2 + b * 32 + lz);
#pragma unroll
            for (int k = 0; k < 8; k++) if (on) du[k * (UROW / 2)] = u[k];
        }
#pragma unroll 1
        for (int pass = 0; pass < 2; pass++) {
            if (pass == ((PLATE >> w) & 1)) {
                const uint32_t q0 = row + ((qo + (b - 2) * 128) & 1023);
                if (b & 1) conv_pair<4>(acc, pend, ta, q0, q1, qa); else conv_pair<0>(acc, pend, ta, q0, q1, qa);
            }
            if (pass) break;
            ln = stats_recv<1>(l16, g_st + (36 + b) * 256 + lz, w);
            PROF2(threadIdx.x == 0 && on, 2048 + b * 8 + 5);
            uint32_t o[2][4];
#pragma unroll
            for (int e = 0; e < 2; e++) {
                const float mu = e ? ln.z : ln.x, rs = e ? ln.w : ln.y;
#pragma unroll
                for (int i = 0; i < 4; i++) o[e][i] = pack2(rbf(x[4 * i + e] - mu) * rs, rbf(x[4 * i + 2 + e] - mu) * rs);
            }
#pragma unroll
            for (int i = 0; i < 4; i++) {
                const uint32_t t = __shfl_xor_sync(0xffffffffu, (lz & 1) ? o[0][i] : o[1][i], 1);
                if (lz & 1) o[0][i] = t; else o[1][i] = t;
            }
            uint4* dst = g_xn + ((32 + b) * 4096 + q * 512 + (lz >> 2) * 64 + w * 8 + (lz & 2) * 2 + (lz & 1));
            if (on) { dst[0] = make_uint4(o[0][0], o[0][1], o[0][2], o[0][3]); dst[2] = make_uint4(o[1][0], o[1][1], o[1][2], o[1][3]); }
            if (w == 7) {
                bar_sync(5, 256);
                if (elect()) red_release(cnt_ptr(on ? C_XN + 32 + b : C_FAR + 2), 2);
                PROF(lane == 0 && on, 2048 + b * 8 + 6);
                __syncwarp();
            } else bar_arrive(5, 256);
        }
    }
}

template <int P0, bool TRI = false>
__device__ __forceinline__ void bg_half(float (*acc)[4], uint4* win, uint32_t ta, uint32_t qa, uint32_t mask, uint32_t row) {
#pragma unroll
    for (int i = 0; i < 4; i++) {
        win[P0 + i] = ldsm4(((qa + i * 128) & mask) + row);
        const uint4 a = lds128(ta + (3 - i) * 448), e = lds128(ta + (3 - i) * 448 + 224);
#pragma unroll
        for (int r = TRI ? 7 - P0 - i : 0; r < 8; r++) mma16(acc[r], a.x, a.y, a.z, a.w, win[(P0 + i + 1 + r) & 7].x, win[(P0 + i + 1 + r) & 7].y);
#pragma unroll
        for (int r = TRI ? 7 - P0 - i : 0; r < 8; r++) mma16(acc[r], e.x, e.y, e.z, e.w, win[(P0 + i + 1 + r) & 7].z, win[(P0 + i + 1 + r) & 7].w);
    }
}
__device__ __forceinline__ void bg_fetch(uint32_t sb, int q, int j, int n, int lane) {
    const int b0 = n >> 1, ch = q * 64 + j * 16 + (n & 1) * 8 + (b0 & 7), lo = max(b0 - 24, -4), nu = b0 > 4 ? (b0 - 4 - lo) * 128 : 0;
    const uint32_t bar = sb + B_BAR + (CB_LD + j * 2 + (n & 1)) * 8, buf = sb + C_BG + (j * 2 + (n & 1)) * CB_BIG;
    const int nt = min(max((b0 + 7) >> 2, 2), 5) * 1792;
    if (elect()) {
        mbar_expect(bar, nt + nu + 1792);
        bulk_g2s(buf, g_W + ch * 784, nt, bar, POL_N);
        bulk_g2s(buf + CB_M, g_W + (ch ^ 4) * 784, 1792, bar, POL_N);
        if (nu) bulk_g2s(buf + CB_U + (lo - b0 + 24) * 128, g_u + ch * (UROW / 2) + UPRE / 2 + lo * 32, nu, bar, POL_N);
    }
    __syncwarp();
}
__device__ __forceinline__ void conv_back(uint32_t sb, int q, int j) {
    const int lane = __shfl_sync(0xffffffffu, threadIdx.x & 31, threadIdx.x & 31), g = lane >> 2, c = lane & 3;
    wait_slow_warp(g_gate, lds32(sb + S_GATE));
    bg_fetch(sb, q, j, 0, lane);
    bar_sync(4, 384);
    const uint32_t to = (6 + g - 2 * c) * 16, qo = (lane & 7) * 16 - (lane >> 3) * 32;
#pragma unroll 1
    for (int n = 0; n < 64; n++) {
        const int b0 = n >> 1, i = n & 1, chl = j * 16 + i * 8 + (b0 & 7), hm = (b0 + 7) >> 2;
        const uint32_t buf = sb + C_BG + (j * 2 + i) * CB_BIG, ta = buf + to;
        float acc[8][4];
        uint4 win[8];
        if (n < 63) bg_fetch(sb, q, j, n + 1, lane);
        if (n == 34 || n == 42) wait_flag_warp(cnt_ptr(C_FAR + (n == 42)), 12);
        mbar_wait(sb + B_BAR + (CB_LD + j * 2 + i) * 8, b0 & 1);
#pragma unroll
        for (int r = 0; r < 8; r++) {
            acc[r][0] = acc[r][1] = acc[r][2] = acc[r][3] = 0;
            win[r] = make_uint4(0, 0, 0, 0);
            if (r) asm volatile("{.reg .pred p; setp.ge.s32 p,%5,24; @p ldmatrix.sync.aligned.m8n8.x4.shared.b16 {%0,%1,%2,%3},[%4];}"
                                : "+r"(win[r].x), "+r"(win[r].y), "+r"(win[r].z), "+r"(win[r].w) : "r"(buf + CB_U + qo + r * 128), "r"(b0 + r) : "memory");
        }
        const uint2* fr = g_far + (((q * 64 + chl) * 8 + b0 - 24) * 32 + lane);
        uint2* cr = g_carry + (((q * 64 + chl) * 40 + b0) * 32 + lane);
        uint2* cm = g_carry + (((q * 64 + (chl ^ 4)) * 40 + b0) * 32 + lane);
        const uint32_t fm = 0xff000000u >> b0;
        uint2 pf[8], pm[4];
#pragma unroll
        for (int r = 0; r < 8; r++) pf[r] = ld_acc(fr + r * 32, (fm >> r) & 1);
#pragma unroll
        for (int r = 0; r < 4; r++) pm[r] = ld_acc(cm + r * 32, b0 > 4);
#pragma unroll 1
        for (int h = hm > 3 ? 5 : 3; h >= 3; h -= 2) {
            if (h <= hm) bg_half<0>(acc, win, ta + (h - 1) * 1792, qo + (28 - 4 * h) * 128, ~0u, buf + CB_U);
            if (h == 3 && i == 0) mbar_wait(sb + B_BAR + (CB_UF + j) * 8, b0 & 1);
            bg_half<4>(acc, win, ta + (h - 2) * 1792, qo + (h == 3 ? b0 - 4 : 12) * 128, h == 3 ? 1023u : ~0u, h == 3 ? sb + C_UR + chl * 1024 : buf + CB_U);
        }
        uint4 wm[8];
#pragma unroll
        for (int r = 1; r < 8; r++) wm[r] = ldsm4(sb + C_UR + (chl ^ 4) * 1024 + ((qo + (b0 + r) * 128) & 1023));
#pragma unroll
        for (int r = 0; r < 8; r++) add_acc(acc[r], pf[r]);
#pragma unroll
        for (int r = 4; r < 8; r++) { st_acc(cr + r * 32, acc[r]); acc[r][0] = blo(pm[r - 4].x); acc[r][1] = bhi(pm[r - 4].x); acc[r][2] = blo(pm[r - 4].y); acc[r][3] = bhi(pm[r - 4].y); }
#pragma unroll
        for (int t = 7; t >= 0; t--) {
            const uint4 a = lds128(ta + t * 224), e = lds128(ta + CB_M + t * 224);
#pragma unroll
            for (int r = 0; r < 4; r++) { const uint4& x = win[4 + r - (t >> 1)]; mma16(acc[r], a.x, a.y, a.z, a.w, (t & 1) ? x.z : x.x, (t & 1) ? x.w : x.y); }
#pragma unroll
            for (int r = 0; r < 4; r++) { const uint4& x = wm[4 + r - (t >> 1)]; mma16(acc[4 + r], e.x, e.y, e.z, e.w, (t & 1) ? x.z : x.x, (t & 1) ? x.w : x.y); }
        }
#pragma unroll
        for (int r = 0; r < 4; r++) { st_acc(cr + r * 32, acc[r]); st_acc(cm + r * 32, acc[4 + r]); }
        __syncwarp();
        if (lane == 0 && i) mbar_arrive(sb + B_BAR + (CB_CF + j) * 8);
        PROF(j == 0 && lane == 0 && i, 2048 + b0 * 8 + 7);
    }
}
__device__ __forceinline__ void conv_far(uint32_t sb, int w) {
    const int lane = __shfl_sync(0xffffffffu, threadIdx.x & 31, threadIdx.x & 31), g = lane >> 2, c = lane & 3;
    wait_slow_warp(g_gate, lds32(sb + S_GATE));
    wait_slow_warp(cnt_ptr(C_XN + 39), 16);
    const uint32_t to = (6 + g - 2 * c) * 16, qo = (lane & 7) * 16 - (lane >> 3) * 32;
#pragma unroll 1
    for (int n = -1; n * 12 + w < 512; n++) {
        const int t = n * 12 + w, ch = (t & 63) * 8 + (((t >> 6) + 1) & 7), cn = ((t + 12) & 63) * 8 + ((((t + 12) >> 6) + 1) & 7);
        const uint32_t bar = sb + B_BAR + (w * 2 + (n & 1)) * 8, buf = sb + (w * 2 + (n & 1)) * 5120;
        if (t + 12 < 512 && elect()) {
            const uint32_t nb = sb + (w * 2 + (~n & 1)) * 5120;
            mbar_expect(bar ^ 8, 3584 + 1152);
            bulk_g2s(nb, g_W + cn * 784 + 560, 3584, bar ^ 8, POL_N);
            bulk_g2s(nb + 3584, g_u + cn * (UROW / 2) + UPRE / 2 - 32, 1152, bar ^ 8, POL_N);
        }
        __syncwarp();
        if (n < 0) continue;
        float acc[8][4];
        uint4 win[8];
#pragma unroll
        for (int r = 0; r < 8; r++) { acc[r][0] = acc[r][1] = acc[r][2] = acc[r][3] = 0; win[r] = make_uint4(0, 0, 0, 0); }
        mbar_wait(bar, (n >> 1) & 1);
        bg_half<0, true>(acc, win, buf + to + 1792, qo + 128, ~0u, buf + 3584);
        bg_half<4, true>(acc, win, buf + to, qo + 640, ~0u, buf + 3584);
#pragma unroll
        for (int r = 0; r < 8; r++) st_acc(g_far + (ch * 256 + lane) + r * 32, acc[r]);
        __syncwarp();
        if (((t + 12) ^ t) >= 256 && elect()) red_release(cnt_ptr(C_FAR + (t >> 8)), 1);
        __syncwarp();
    }
    PROF(threadIdx.x == 0, 2048);
}

constexpr int P_X = 131072  , P_K6 = P_X + 32768  , P_P = P_K6 + 10496  , P_U = P_P + 33280  ,
              P_END = P_U + 17408, P_PRM = P_P + 8192  , P_Y = P_P  ;
static_assert(P_END <= B_BAR && P_END <= R_SEL, "prologue scratch");
#define KGUN 2
constexpr int KGU = KGUN;
__device__ __forceinline__ void csq(float& r, float& i) { const float t = r * i; r = fmaf(r, r, -(i * i)); i = t + t; }
__device__ __forceinline__ void cpow(float ar, float ph, float p, float& r, float& i) {
    const float e = ex2(ar * p);
    const float u = ph * p, n = fabsf(u) < 4194304.f ? (u + 12582912.f) - 12582912.f : u;
    const float t = (u - n) * 6.283185307179586f;
    r = e * __cosf(t); i = e * __sinf(t);
}
__device__ __forceinline__ void mma_tf32(float* c, float a0, float a1, float a2, float a3, float b0, float b1) {
    asm volatile("mma.sync.aligned.m16n8k8.row.col.f32.tf32.tf32.f32 {%0,%1,%2,%3},{%4,%5,%6,%7},{%8,%9},{%0,%1,%2,%3};"
                 : "+f"(c[0]), "+f"(c[1]), "+f"(c[2]), "+f"(c[3])
                 : "r"(__float_as_uint(a0)), "r"(__float_as_uint(a1)), "r"(__float_as_uint(a2)), "r"(__float_as_uint(a3)), "r"(__float_as_uint(b0)), "r"(__float_as_uint(b1)));
}

__device__ __forceinline__ void early_fetch(const Params& p, uint32_t sb) {
    const int v = blockIdx.x;
    if (elect()) {
        if (v >= V_QKV) { if (v < V_QKV + NQ && (p.roles & 8)) qkv_fetch(p, sb, v - V_QKV, 0, Q_PRE); }
        else if (v >= V_OP) { if (p.roles & 4) op_fetch(p, sb, v - V_OP, 0); }
        else if (REARLY && v >= V_REC && (p.roles & 2)) { rec_fetch(p, sb, (v - V_REC) >> 1, v & 1, 0, R_STQ); rec_fetch(p, sb, (v - V_REC) >> 1, v & 1, 2, R_STV); }
    }
    __syncwarp();
}
struct ProRegs { uint32_t v[2][4], ldt[2]; };
__device__ __forceinline__ void prologue_load(const ProArgs& a, int b, ProRegs& pr) {
    const int w = threadIdx.x >> 5;
#pragma unroll
    for (int i = 0; i < 2; i++) {
        const int gi = b * 512 + (w & 3) * 128 + ((w >> 2) & 1) * 64 + i * 32 + (threadIdx.x & 31);
        pr.ldt[i] = __ldg((const uint16_t*)a.ldt + b * 4 + (w & 3));
        pr.v[i][0] = __ldg((const uint16_t*)a.lAr + gi); pr.v[i][1] = __ldg((const uint16_t*)a.Ai + gi);
        pr.v[i][2] = __ldg((const uint16_t*)a.Cr + gi); pr.v[i][3] = __ldg((const uint16_t*)a.Ci + gi);
    }
}
__device__ __forceinline__ void prologue(const Params& p, uint32_t sb, int b, int w, const ProRegs& pr) {
    const ProArgs& a = p.pa;
    const int tid = threadIdx.x, lane = tid & 31, g = lane >> 2, c = lane & 3;
    const int d0 = b * 4;
    if (w >= 8) {
        const int t2 = tid - 256;
        if (w < 10) {
            const int row = b * 16 + (w - 8) * 8 + g;
            uint4 v[16];
            const float2 r = row_stats512(v, (const uint4*)(a.x + (size_t)row * 512) + c, 8, 4);
            const float2 l = ln_finish(r.x * (1.f / 512.f), r.y * (1.f / 512.f));
            if (c == (g >> 1)) asm volatile("st.relaxed.gpu.global.u32 [%0],%1;" ::"l"(g_ln0 + row), "r"(pack2(l.x, l.y)) : "memory");
            __syncwarp();
        } else if (PF0) {
            spin(PFD);
            if (elect()) {
#pragma unroll 1
                for (int i = w - 10; i < 4; i += 2) if ((PF0 >> i) & 1) asm volatile("cp.async.bulk.prefetch.L2.global [%0],%1;" ::"l"(a.W[i] + b * 16384), "r"(32768) : "memory");
            }
            __syncwarp();
        }
        if (b + 4 >= V_REC && b + 4 < V_OP) rec_slots(b + 4 - V_REC, (w & 3) ^ 2);
        PROF(t2 == 0, 3516);
        const int gi = b * 128 + t2;
        g_st[gi] = make_uint4(~0u, ~0u, ~0u, ~0u);
        if (gi < 1024) g_st[16384 + gi] = make_uint4(~0u, ~0u, ~0u, ~0u);
        if (gi < 900 * 8) g_cnt[gi] = 0;
        bar_sync(6, 384);
        if (lane < 4 && ((PFM >> (w - 8)) & 1)) asm volatile("cp.async.bulk.prefetch.L2.global [%0],%1;" ::"l"(a.W[w - 8] + (b * 4 + lane) * 4096), "r"(8192) : "memory");
        bar_sync(9, 384);
#pragma unroll 1
        for (int pass = 0; pass < 2; pass++) {
        if (w == 10 && pass == (b + 4 < EFS)) early_fetch(p, sb);
        if (pass) break;
#pragma unroll 2
        for (int i = t2; i < 4 * 784; i += 128) {
            const int ch = i / 784, k = i - ch * 784;
            const uint32_t o = sb + P_P + (ch * 2080 + 266 + (k / 14) * 18 + k) * 4;
            g_W[d0 * 784 + i] = make_uint4(lds32(o), lds32(o + 32), lds32(o + 64), lds32(o + 96));
        }
        bar_arrive(10, 384);
        }
        PROF(t2 == 0, 3517);
        return;
    }
#pragma unroll
    for (int i = 0; i < 2; i++) {
        const float dt = rbf(expf(blo(pr.ldt[i])));
        const float ar = -rbf(expf(blo(pr.v[i][0]))) * dt, ai = blo(pr.v[i][1]) * dt;
        sts128(sb + P_PRM + (w * 64 + i * 32 + lane) * 16, __float_as_uint(ar * 1.4426950408889634f), __float_as_uint(ai * 0.15915494309189535f),
               __float_as_uint(2.f * (blo(pr.v[i][2]) * dt)), __float_as_uint(2.f * (blo(pr.v[i][3]) * dt)));
    }
    if (tid < 64) sts128(sb + P_U + (tid >> 3) * 2176 + (tid & 7) * 16, 0, 0, 0, 0);
    bar_arrive(6, 384);
    __syncwarp();
    PROF(tid == 0, 3510);
    const int ch = w & 3, hf = w >> 2;
    {
        float k0[4] = {0, 0, 0, 0}, k1[4] = {0, 0, 0, 0}, k2[4] = {0, 0, 0, 0}, k3[4] = {0, 0, 0, 0}, k4[4] = {0, 0, 0, 0}, kl = 0;
#pragma unroll KGU
        for (int j = 0; j < 16; j++) {
            const uint4 q = lds128(sb + P_PRM + (w * 64 + j * 4 + c) * 16);
            const float cr = __uint_as_float(q.z), ci = __uint_as_float(q.w);
            float wr[4], wi[4], vr[4], vi[4];
            cpow(__uint_as_float(q.x), __uint_as_float(q.y), (float)g, wr[0], wi[0]);
            cpow(__uint_as_float(q.x), __uint_as_float(q.y), (float)(g + 8), vr[0], vi[0]);
#pragma unroll
            for (int i = 1; i < 4; i++) { wr[i] = wr[i - 1]; wi[i] = wi[i - 1]; csq(wr[i], wi[i]); vr[i] = vr[i - 1]; vi[i] = vi[i - 1]; csq(vr[i], vi[i]); }
            float hr = wr[3], hi = wi[3];
            csq(hr, hi);
            mma_tf32(k0, wr[0], vr[0], wi[0], vi[0], cr * hr - ci * hi, -(cr * hi + ci * hr));
            hr = vr[3]; hi = vi[3]; csq(hr, hi);
            mma_tf32(k1, wr[0], vr[0], wi[0], vi[0], cr * hr - ci * hi, -(cr * hi + ci * hr));
            csq(hr, hi);
            mma_tf32(k2, wr[1], vr[1], wi[1], vi[1], cr * hr - ci * hi, -(cr * hi + ci * hr));
            csq(hr, hi);
            mma_tf32(k3, wr[2], vr[2], wi[2], vi[2], cr * hr - ci * hi, -(cr * hi + ci * hr));
            csq(hr, hi);
            mma_tf32(k4, wr[3], vr[3], wi[3], vi[3], cr * hr - ci * hi, -(cr * hi + ci * hr));
            csq(hr, hi);
            kl += cr * hr - ci * hi;
        }
        kl += __shfl_xor_sync(0xffffffffu, kl, 1); kl += __shfl_xor_sync(0xffffffffu, kl, 2);
        const uint32_t o = sb + P_K6 + (ch * 656 + c * 32 + g) * 4, ol = sb + P_K6 + (ch * 656 + 640) * 4;
#define KST(k, base) sts32(o + (base) * 4, __float_as_uint(k[0])); sts32(o + (base) * 4 + 64, __float_as_uint(k[1])); \
                     sts32(o + (base) * 4 + 32, __float_as_uint(k[2])); sts32(o + (base) * 4 + 96, __float_as_uint(k[3]))
#define KAD(k, base) k[0] += __uint_as_float(lds32(o + (base) * 4)); k[1] += __uint_as_float(lds32(o + (base) * 4 + 64)); \
                     k[2] += __uint_as_float(lds32(o + (base) * 4 + 32)); k[3] += __uint_as_float(lds32(o + (base) * 4 + 96))
        if (hf == 0) {
            bar_sync(2 + ch, 64);
            KAD(k0, 0); KAD(k1, 128); KAD(k2, 256); KAD(k3, 384); KAD(k4, 512);
            kl += __uint_as_float(lds32(ol));
            __syncwarp();
        }
        KST(k0, 0); KST(k1, 128); KST(k2, 256); KST(k3, 384); KST(k4, 512);
        if (lane == 0) sts32(ol, __float_as_uint(kl));
        if (hf == 1) { __syncwarp(); bar_arrive(2 + ch, 64); }
    }
    PROF(tid == 0, 3511);
    {
        uint4 l0, l1;
        int n = 0;
        while (true) {
            l0 = ld_rlx128((const uint4*)g_ln0 + tid * 2); l1 = ld_rlx128((const uint4*)g_ln0 + tid * 2 + 1);
            if (__all_sync(0xffffffffu, l0.x && l0.y && l0.z && l0.w && l1.x && l1.y && l1.z && l1.w)) break;
            if (++n > 2000000) __trap();
        }
        sts128(sb + P_P + tid * 32, l0.x, l0.y, l0.z, l0.w); sts128(sb + P_P + tid * 32 + 16, l1.x, l1.y, l1.z, l1.w);
        bar_sync(8, 384);
        mbar_wait(sb + S_XBAR, 0);
        __syncwarp();
#pragma unroll 2
        for (int i = 0; i < 8; i++) {
            const int t = w * 256 + i * 32 + lane;
            const uint32_t ln = lds32(sb + P_P + t * 4);
            const uint2 x = lds64(sb + P_X + t * 16 + (b & 1) * 8);
            const float m = blo(ln), rs = rcp(bhi(ln));
            const uint32_t u0 = pack2(rbf(blo(x.x) - m) * rs, rbf(bhi(x.x) - m) * rs), u1 = pack2(rbf(blo(x.y) - m) * rs, rbf(bhi(x.y) - m) * rs);
            sts128(sb + P_X + t * 16, x.x, x.y, u0, u1);
            const uint32_t o = sb + P_U + ((t >> 3) & 1) * 2176 + ((t >> 4) + 8) * 16 + (t & 7) * 2;
            asm volatile("st.shared.u16 [%0],%1;" ::"r"(o), "h"((uint16_t)u0) : "memory");
            asm volatile("st.shared.u16 [%0],%1;" ::"r"(o + 4352), "h"((uint16_t)(u0 >> 16)) : "memory");
            asm volatile("st.shared.u16 [%0],%1;" ::"r"(o + 8704), "h"((uint16_t)u1) : "memory");
            asm volatile("st.shared.u16 [%0],%1;" ::"r"(o + 13056), "h"((uint16_t)(u1 >> 16)) : "memory");
        }
    }
    bar_sync(1, 256);
    PROF(tid == 0, 3512);
    if (tid < 64) sts32(sb + P_P + ((tid >> 4) * 2080 + (tid & 15)) * 4, 0);
#pragma unroll 1
    for (int x = tid; x < 2048; x += 512) {
        uint32_t pw[2][4];
#pragma unroll
        for (int h = 0; h < 2; h++) {
            const int y = x + h * 256;
            const int i0 = y <= 256 ? y : 256 + (int)((pack2((float)y, 0.f) & 0xffff) - 0x4380);
            const int i1 = y <= 256 ? max(y - 1, 0) : 256 + (int)((pack2((float)(y - 1), 0.f) & 0xffff) - 0x4380);
#pragma unroll
            for (int k = 0; k < 4; k++) {
                const float lo = __uint_as_float(lds32(sb + P_K6 + k * 2624 + i0 * 4)), hi = __uint_as_float(lds32(sb + P_K6 + k * 2624 + i1 * 4));
                pw[h][k] = pack2(lo, y ? hi : 0.f);
            }
        }
#pragma unroll
        for (int h = 0; h < 2; h++)
#pragma unroll
            for (int k = 0; k < 4; k++) sts32(sb + P_P + (k * 2080 + x + h * 256 + 16) * 4, pw[h][k]);
    }
    fence_async_smem();
    bar_arrive(9, 384);
    bar_sync(1, 256);
    if (tid < 4) {
        asm volatile("cp.async.bulk.global.shared::cta.bulk_group [%0],[%1],%2;" ::"l"(g_P + (d0 + tid) * PROW), "r"(sb + P_P + tid * 8320), "r"(PROW * 4) : "memory");
        asm volatile("cp.async.bulk.commit_group;" ::: "memory");
    }
    __syncwarp();
    PROF(tid == 0, 3513);
    {
        float acc[16][4];
#pragma unroll
        for (int j = 0; j < 16; j++) acc[j][0] = acc[j][1] = acc[j][2] = acc[j][3] = 0;
#pragma unroll 1
        for (int e = hf * 4; e < hf * 4 + 4; e++) {
            uint32_t B[16][2];
            const uint32_t ua = sb + P_U + ch * 4352 + ((lane >> 3) & 1) * 2176 + (8 + (lane >> 4) * 8 + (lane & 7) - e) * 16;
#pragma unroll
            for (int j = 0; j < 8; j++) { const uint4 v = ldsm4(ua + j * 256); B[2 * j][0] = v.x; B[2 * j][1] = v.y; B[2 * j + 1][0] = v.z; B[2 * j + 1][1] = v.w; }
            const uint32_t pa = sb + P_P + (ch * 2080 + 16 + e * 16 + g - 2 * c) * 4;
#pragma unroll
            for (int dd = 0; dd < 16; dd++) {
                const int d = (dd & 1) ? 15 - (dd >> 1) : dd >> 1;
                const uint32_t a0 = lds32(pa + d * 512), a1 = lds32(pa + d * 512 + 32), a2 = lds32(pa + d * 512 - 32), a3 = a0 + p.zero;
#pragma unroll
                for (int j = 0; j < 16; j++) if (j >= d) mma16(acc[j], a0, a1, a2, a3, B[(j - d) & 15][0], B[(j - d) & 15][1]);
            }
        }
        PROF(tid == 0, 3514);
        if (tid < 4) asm volatile("cp.async.bulk.wait_group 0;" ::: "memory");
        __syncwarp();
        bar_sync(10, 384);
#pragma unroll
        for (int j = 0; j < 8; j++) {
#pragma unroll
            for (int i = 0; i < 4; i++) { const float t = hf ? acc[j][i] : acc[j + 8][i]; acc[j][i] = hf ? acc[j + 8][i] : acc[j][i]; acc[j + 8][i] = t; }
            sts128(sb + P_Y + w * 4096 + j * 512 + lane * 16, __float_as_uint(acc[j + 8][0]), __float_as_uint(acc[j + 8][1]), __float_as_uint(acc[j + 8][2]), __float_as_uint(acc[j + 8][3]));
        }
        bar_sync(2 + ch, 64);
        uint32_t yp[16];
#pragma unroll
        for (int j = 0; j < 8; j++) {
            const uint4 t = lds128(sb + P_Y + (w ^ 4) * 4096 + j * 512 + lane * 16);
            yp[2 * j] = pack2(acc[j][0] + __uint_as_float(t.x), acc[j][1] + __uint_as_float(t.y)); yp[2 * j + 1] = pack2(acc[j][2] + __uint_as_float(t.z), acc[j][3] + __uint_as_float(t.w));
        }
#pragma unroll
        for (int j = 0; j < 4; j++)
            asm volatile("stmatrix.sync.aligned.m8n8.x4.trans.shared.b16 [%0],{%1,%2,%3,%4};" ::"r"(sb + P_Y + 32768 + ch * 4096 + hf * 2048 + j * 512 + (lane >> 4) * 256 + (lane & 7) * 32 + (lane & 8) * 2),
                         "r"(yp[4 * j]), "r"(yp[4 * j + 1]), "r"(yp[4 * j + 2]), "r"(yp[4 * j + 3]) : "memory");
    }
    const uint2 dk = __ldg((const uint2*)(a.Dk + d0));
    bar_sync(1, 256);
#pragma unroll 2
    for (int i = 0; i < 4; i++) {
        const int t = i * 256 + tid;
        const uint4 x0 = lds128(sb + P_X + t * 32), x1 = lds128(sb + P_X + t * 32 + 16);
        uint32_t y[4];
#pragma unroll
        for (int k = 0; k < 4; k++) y[k] = lds32(sb + P_Y + 32768 + k * 4096 + t * 4);
        g_x[b * XP + t] = make_uint4(hadd2(x0.x, hadd2(__byte_perm(y[0], y[1], 0x5410), hmul2(x0.z, dk.x))), hadd2(x0.y, hadd2(__byte_perm(y[2], y[3], 0x5410), hmul2(x0.w, dk.y))),
                                     hadd2(x1.x, hadd2(__byte_perm(y[0], y[1], 0x7632), hmul2(x1.z, dk.x))), hadd2(x1.y, hadd2(__byte_perm(y[2], y[3], 0x7632), hmul2(x1.w, dk.y))));
    }
    PROF(tid == 0, 3515);
}

__global__ void __cluster_dims__(2, 1, 1) __launch_bounds__(384, 1) main_kernel(const __grid_constant__ Params p) {
    extern __shared__ __align__(1024) uint8_t smem[];
    const uint32_t sb = smem_u32(smem);
    uint32_t rank; asm("mov.u32 %0,%%cluster_ctarank;" : "=r"(rank));
    const int wi = __shfl_sync(0xffffffffu, threadIdx.x >> 5, 0);
    const int v = blockIdx.x, cl = v >> 1, wg = wi >> 2;
    PROF(threadIdx.x == 0, 3500);
    ProRegs pr;
    prologue_load(p.pa, max((int)blockIdx.x - 4, 0), pr);
    if (wi == 11 && p.dopro && cl >= 2 && elect()) {
        mbar_init(sb + S_XBAR, 1);
        asm volatile("fence.mbarrier_init.release.cluster;" ::: "memory");
        mbar_expect(sb + S_XBAR, 32768);
        for (int j = 0; j < 8; j++) tma2d(sb + P_X + j * 4096, &p.tm[3], ((blockIdx.x - 4) >> 1) * 8, j * 256, sb + S_XBAR);
    }
    if (threadIdx.x == 320) {
        unsigned n;
        asm volatile("ld.relaxed.gpu.global.u32 %0,[%1];" : "=r"(n) : "l"(g_gate) : "memory");
        n = n / (4 * NCL) + p.dopro;
        sts64(sb + S_GATE, n * (4 * NCL), n & 1);
    }
    __syncwarp();
    if (wi == 10) {
        if (v < V_REC || v == 131) conv_init(sb, v == 131); else if (v < V_OP) rec_init(sb); else gemm_init(sb, v < V_QKV);
        __syncwarp();
    }
    if (wg == 2) bar_arrive(8, 384);
    asm volatile("barrier.cluster.arrive.relaxed.aligned;" ::: "memory");
    if (p.dopro && cl >= 2) prologue(p, sb, blockIdx.x - 4, wi, pr); else if (wg < 2) bar_sync(8, 384); else if (wi == 10) early_fetch(p, sb);
    asm volatile("barrier.cluster.wait.aligned;" ::: "memory");
    const int role = (v < V_REC ? 1 : v < V_OP ? 2 : v < V_QKV ? 20 : v < V_QKV + NQ ? 24 : 1) & p.roles;
    fence_async_smem();
    bar_sync(wg == 2 ? 7 : 1, wg == 2 ? 128 : 256);
    if (p.dopro && (threadIdx.x == 32 || threadIdx.x == 352)) red_release(g_gate, 1);
    PROF(threadIdx.x == 32, 3509);
    if (wi == 0 && (role & 8) && elect()) qkv_stage(p, sb + 131072, sb + G_BAR + GB_RS * 8, v - V_QKV, 0, 6);
    PROF(threadIdx.x == 0, 3506);
    __syncwarp();
    if (p.dopro && (v == 131 || (v >= V_REC && v < V_QKV && (v < V_OP ? wi == 8 : wi < 8)))) {
        bool on = v >= V_OP;
#pragma unroll 1
        for (int r = v == 131 ? 448 + wi : on ? 64 + (v - V_OP) * 8 + wi : v - V_REC; r < (v == 131 ? 512 : 448);) {
            if (v >= V_OP) wait_slow_warp(g_gate, lds32(sb + S_GATE)); else if (on) wait_flag_warp(g_gate, lds32(sb + S_GATE));
            PROF(threadIdx.x == 256 && on, 3507);
            x1_norm(on ? (const uint2*)g_x : (const uint2*)p.pa.x, r, on);
            __syncwarp();
            if (on && elect()) red_release(cnt_ptr(C_XN + (r >> 4)), 1);
            __syncwarp();
            PROF(threadIdx.x == 256, on ? 3508 : 3499);
            if (on) r += v < V_OP ? 512 : v == 131 ? 12 : 128;
            on = true;
        }
    }
    if (role == 2) {
        const int head = (v - V_REC) >> 1;
        if (wi == RFW && elect()) {
            if (!REARLY) { rec_fetch(p, sb, head, rank, 0, R_STQ); }
            rec_fetch(p, sb, head, rank, 1, R_STK);
            if (!REARLY) { rec_fetch(p, sb, head, rank, 2, R_STV); }
        }
        __syncwarp();
        if (wg == 2) {
            reg_dec<RH>();
            const int w = wi & 3;
            wait_slow_warp(g_gate, lds32(sb + S_GATE));
            if (w < 2) { const uint32_t x = __ldcg(g_sel + (threadIdx.x & 63)); sts32(sb + R_SEL + (threadIdx.x & 63) * 4, (x * 0x01010101u) >> 24); }
            __syncthreads();
            cluster_sync();
            if ((p.chains >> (w & 1)) & 1) { if (w < 2) rec_comm(p, sb, w, head, rank); else rec_attn(p, sb, w & 1, head, rank); }
        } else {
            reg_inc<RW0>();
            rec_weights(p, sb, head, rank, wi);
        }
    } else if (role == 1) {
        if (v == 131) conv_far(sb, wi); else if (wg == 2) { reg_dec<RCB>(); conv_back(sb, v, wi & 3); } else { reg_inc<RCU>(); conv_tile(p, sb, v, wi); }
    } else if (role && v < V_QKV) {
        if (wg == 2) {
            reg_dec<40>();
            if (wi == 8) { if (role & 4) gemm_producer<true>(p, sb, v - V_OP); }
            else if (v < V_OP + 14 && (role & 16)) fin_warp(p, sb, 2 * NQ + (v - V_OP) * 3 + wi - 9);
        } else { reg_inc<232>(); if (role & 4) gemm_consumer<true>(p, sb, v - V_OP, wi); }
    } else if (role) {
        if (wg == 2) {
            reg_dec<40>();
            if (wi < 10) {
                if (role & 8) { if (wi == 8) gemm_producer<false>(p, sb, v - V_QKV); else qkv_release(p, sb); }
            } else if (role & 16) fin_warp(p, sb, (v - V_QKV) * 2 + wi - 10);
        } else { reg_inc<232>(); if (role & 8) gemm_consumer<false>(p, sb, v - V_QKV, wi); }
    }
    __syncwarp();
    cluster_sync();
}

typedef CUresult (*EncFn)(CUtensorMap*, CUtensorMapDataType, cuuint32_t, void*, const cuuint64_t*, const cuuint64_t*, const cuuint32_t*, const cuuint32_t*,
                          CUtensorMapInterleave, CUtensorMapSwizzle, CUtensorMapL2promotion, CUtensorMapFloatOOBfill);
constexpr int SMEM_BYTES = 232448;
#define LAG 8
#define QLEAD 6
#define OLEAD (LAG / 2 + 2)
void plan(Params& P) {
    P.roles = 31; P.chains = 3; P.lag = LAG; P.dopro = 1;
    for (int r = 0; r < 2; r++) {
        const int lead = r ? OLEAD : QLEAD;
        int n = 0;
        for (int i = 0; i < 32 + lead; i++) {
            if (i >= lead) P.list[r][n++] = 32 + i - lead;
            if (i < 32) P.list[r][n++] = i;
        }
        P.nl[r] = n;
    }
}

#define TK() do {} while (0)
}

extern "C" void kernel_launch(void* const* d_in, const int* in_sizes, int n_in, void* d_out, int out_size) {
    typedef const __nv_bfloat16* BP;
    static EncFn enc = nullptr;
    if (!enc) {
        void* fn = nullptr; cudaDriverEntryPointQueryResult qr;
        cudaGetDriverEntryPoint("cuTensorMapEncodeTiled", &fn, cudaEnableDefault, &qr);
        enc = (EncFn)fn;
        cudaFuncSetAttribute(main_kernel, cudaFuncAttributeMaxDynamicSharedMemorySize, SMEM_BYTES);
    }
    static Params P;
    for (int i = 0; i < 4; i++) {
        const cuuint64_t cols = i < 3 ? 4096 : 512, rows = i < 3 ? 512 : 4096;
        cuuint64_t d2[2] = {cols, rows}, str[1] = {cols * 2};
        cuuint32_t box[2] = {64, 64}, bn[2] = {16, 256}, es[2] = {1, 1};
        enc(&P.tm[i < 3 ? i : 4], CU_TENSOR_MAP_DATA_TYPE_BFLOAT16, 2, d_in[9 + i], d2, str, box, es, CU_TENSOR_MAP_INTERLEAVE_NONE, CU_TENSOR_MAP_SWIZZLE_128B,
            CU_TENSOR_MAP_L2_PROMOTION_L2_128B, CU_TENSOR_MAP_FLOAT_OOB_FILL_NONE);
        if (i < 2) enc(&P.tn[i], CU_TENSOR_MAP_DATA_TYPE_BFLOAT16, 2, d_in[9 + i], d2, str, bn, es, CU_TENSOR_MAP_INTERLEAVE_NONE, CU_TENSOR_MAP_SWIZZLE_32B,
                       CU_TENSOR_MAP_L2_PROMOTION_L2_128B, CU_TENSOR_MAP_FLOAT_OOB_FILL_NONE);
    }
    {
        cuuint64_t dims[2] = {512, 2048}, str[1] = {1024};
        cuuint32_t box[2] = {8, 256}, es[2] = {1, 1};
        enc(&P.tm[3], CU_TENSOR_MAP_DATA_TYPE_BFLOAT16, 2, d_in[0], dims, str, box, es, CU_TENSOR_MAP_INTERLEAVE_NONE, CU_TENSOR_MAP_SWIZZLE_NONE,
            CU_TENSOR_MAP_L2_PROMOTION_NONE, CU_TENSOR_MAP_FLOAT_OOB_FILL_NONE);
    }
    P.mem0 = (BP)d_in[8]; P.Wo = (BP)d_in[12]; P.Dskip = (BP)d_in[6]; P.out = (__nv_bfloat16*)d_out;
    cudaStream_t s = cudaStreamPerThread;
    P.pa = {(BP)d_in[0], (BP)d_in[1], (BP)d_in[2], (BP)d_in[3], (BP)d_in[4], (BP)d_in[5], (BP)d_in[6], {(BP)d_in[9], (BP)d_in[10], (BP)d_in[11], (BP)d_in[12]}};
    plan(P);
    TK(); main_kernel<<<2 * NCL, 384, SMEM_BYTES, s>>>(P); TK();
}
```

```cpp
#include <cuda_runtime.h>
#include <cuda_bf16.h>
#include <cuda.h>
#include <stdint.h>
#include <string.h>
#include <math.h>

namespace {

constexpr int NCL = 66;
constexpr int NQ = 43;
constexpr int V_REC = 8, V_OP = 72, V_QKV = 88;
static_assert(2 * NQ + 3 * 14 == 128, "warps of the final residual");

#define XP 1024
__device__ uint4 g_x[2 * 128 * XP];
__device__ uint4 g_xn[64 * 4096];
__device__ uint4 g_st[68 * 256];
__device__ uint4 g_qkv[128 * 32 * 1536];
__device__ uint4 g_o[64 * 64 * 512];
__device__ uint4 g_pp[64 * 4 * 4096];
__device__ uint4 g_xch[133 * 512];
__device__ unsigned g_sel[64];
__device__ unsigned g_gate[32];
__device__ __align__(16) uint32_t g_P[512 * 272];
__device__ uint4 g_W[512 * 784];
__device__ __align__(16) uint32_t g_u[512 * 1280];
__device__ uint2 g_carry[512 * 40 * 32];
__device__ uint2 g_far[512 * 12 * 32];
__device__ unsigned g_cnt[912 * 8];
__device__ uint32_t g_ln0[2048];

enum { C_XN = 0  , C_QKV = 64  , C_O = 128  , C_PP = 384  , C_FAR = 896 };
__device__ __forceinline__ unsigned* cnt_ptr(int i) { return g_cnt + i * 8; }

struct ProArgs { const __nv_bfloat16 *x, *lAr, *Ai, *Cr, *Ci, *ldt, *Dk, *W[4]; };
struct Params {
    CUtensorMap tm[5];
    CUtensorMap tn[2];
    ProArgs pa;
    int dopro;
    const __nv_bfloat16* mem0;
    const __nv_bfloat16* Wo;
    const __nv_bfloat16* Dskip;
    __nv_bfloat16* out;
    int roles;
    int chains;
    int lag;
    int zero;
    int nl[2];
    uint8_t list[2][64];
};

__device__ __forceinline__ uint32_t smem_u32(const void* p) { return (uint32_t)__cvta_generic_to_shared(p); }
__device__ __forceinline__ uint32_t mapa(uint32_t a, uint32_t r) {
    uint32_t o; asm("mapa.shared::cluster.u32 %0,%1,%2;" : "=r"(o) : "r"(a), "r"(r)); return o;
}
__device__ __forceinline__ void mbar_init(uint32_t b, int c) { asm volatile("mbarrier.init.shared::cta.b64 [%0],%1;" ::"r"(b), "r"(c) : "memory"); }
__device__ __forceinline__ void mbar_expect(uint32_t b, int bytes) { asm volatile("mbarrier.arrive.expect_tx.shared::cta.b64 _,[%0],%1;" ::"r"(b), "r"(bytes) : "memory"); }
__device__ __forceinline__ void mbar_arrive(uint32_t b) { asm volatile("mbarrier.arrive.shared::cta.b64 _,[%0];" ::"r"(b) : "memory"); }
__device__ __forceinline__ void mbar_arrive_cluster(uint32_t b) { asm volatile("mbarrier.arrive.shared::cluster.b64 _,[%0];" ::"r"(b) : "memory"); }
__device__ __forceinline__ void mbar_wait(uint32_t b, uint32_t ph) {
    asm volatile(
        "{.reg .pred p; .reg .u32 n; mov.u32 n,0;\n"
        "W%=: mbarrier.try_wait.parity.shared::cta.b64 p,[%0],%1;\n"
        "@p bra D%=;\n"
        "add.u32 n,n,1; setp.lt.u32 p,n,2000000; @p bra W%=;\n"
        "trap;\n"
        "D%=: }" ::"r"(b), "r"(ph) : "memory");
}
__device__ __forceinline__ bool wait_lds128(uint32_t b, uint32_t ph, uint32_t a, uint4& v) {
    uint32_t ok;
    asm volatile("{.reg .pred p; mbarrier.try_wait.parity.shared::cta.b64 p,[%5],%6,20000; ld.shared.v4.u32 {%0,%1,%2,%3},[%7]; selp.u32 %4,1,0,p;}"
                 : "=r"(v.x), "=r"(v.y), "=r"(v.z), "=r"(v.w), "=r"(ok) : "r"(b), "r"(ph), "r"(a) : "memory");
    return ok;
}
__device__ __forceinline__ bool wait_lds64(uint32_t b, uint32_t ph, uint32_t a, uint2& v) {
    uint32_t ok;
    asm volatile("{.reg .pred p; mbarrier.try_wait.parity.shared::cta.b64 p,[%3],%4,20000; ld.shared.v2.u32 {%0,%1},[%5]; selp.u32 %2,1,0,p;}"
                 : "=r"(v.x), "=r"(v.y), "=r"(ok) : "r"(b), "r"(ph), "r"(a) : "memory");
    return ok;
}
template <int PH> __device__ __forceinline__ void mbar_wait_c(uint32_t b) {
    asm volatile(
        "{.reg .pred p; .reg .u32 n; mov.u32 n,%2;\n"
        "W%=: mbarrier.try_wait.parity.shared::cta.b64 p,[%0],%1;\n"
        "@p bra D%=;\n"
        "add.u32 n,n,1; setp.lt.u32 p,n,2000000; @p bra W%=;\n"
        "trap;\n"
        "D%=: }" ::"r"(b), "n"(PH), "n"(PH) : "memory");
}
__device__ __forceinline__ bool elect() {
    uint32_t r; asm volatile("{.reg .pred p; elect.sync _|p,0xffffffff; selp.u32 %0,1,0,p;}" : "=r"(r)); return r;
}
__device__ __forceinline__ void bar_sync(int id, int n) { asm volatile("bar.sync %0,%1;" ::"r"(id), "r"(n) : "memory"); }
__device__ __forceinline__ void bar_arrive(int id, int n) { asm volatile("bar.arrive %0,%1;" ::"r"(id), "r"(n) : "memory"); }
__device__ __forceinline__ void cluster_sync() { asm volatile("barrier.cluster.arrive.relaxed.aligned; barrier.cluster.wait.aligned;" ::: "memory"); }
__device__ __forceinline__ void fence_async() { asm volatile("fence.proxy.async;" ::: "memory"); }
__device__ __forceinline__ void fence_async_smem() { asm volatile("fence.proxy.async.shared::cta;" ::: "memory"); }
#define EFR 1
#define EFW 0
constexpr uint64_t POL_N = 0x1000000000000000ull, POL_F = 0x12F0000000000000ull;
constexpr uint64_t POL_LAST = EFR ? POL_F : POL_N  , POL_LATE = EFW ? POL_F : POL_N  , POL_SOON = EFW > 1 ? POL_F : POL_N;
__device__ __forceinline__ void bulk_g2s(uint32_t dst, const void* src, int bytes, uint32_t bar, uint64_t pol) {
    asm volatile("cp.async.bulk.shared::cluster.global.mbarrier::complete_tx::bytes.L2::cache_hint [%0],[%1],%2,[%3],%4;" ::"r"(dst), "l"(src), "r"(bytes), "r"(bar), "l"(pol) : "memory");
}
__device__ __forceinline__ void bulk_g2s_mc(uint32_t dst, const void* src, int bytes, uint32_t bar, uint64_t pol) {
    asm volatile("cp.async.bulk.shared::cluster.global.mbarrier::complete_tx::bytes.multicast::cluster.L2::cache_hint [%0],[%1],%2,[%3],%4,%5;" ::"r"(dst), "l"(src), "r"(bytes), "r"(bar), "h"((uint16_t)3), "l"(pol) : "memory");
}
__device__ __forceinline__ void stg128(uint4* p, uint4 v, uint64_t pol) {
    asm volatile("st.global.L2::cache_hint.v4.u32 [%0],{%1,%2,%3,%4},%5;" ::"l"(p), "r"(v.x), "r"(v.y), "r"(v.z), "r"(v.w), "l"(pol));
}
__device__ __forceinline__ void stg32(uint32_t* p, uint32_t v, uint64_t pol) { asm volatile("st.global.L2::cache_hint.u32 [%0],%1,%2;" ::"l"(p), "r"(v), "l"(pol)); }
__device__ __forceinline__ uint4 ldcg128_last(const uint4* p) {
    uint4 v; asm volatile("ld.global.cg.L2::cache_hint.v4.u32 {%0,%1,%2,%3},[%4],%5;" : "=r"(v.x), "=r"(v.y), "=r"(v.z), "=r"(v.w) : "l"(p), "l"(POL_LAST) : "memory"); return v;
}
__device__ __forceinline__ void tma2d(uint32_t dst, const CUtensorMap* tm, int x, int y, uint32_t bar) {
    asm volatile("cp.async.bulk.tensor.2d.shared::cluster.global.mbarrier::complete_tx::bytes [%0],[%1,{%2,%3}],[%4];" ::"r"(dst), "l"(tm), "r"(x), "r"(y), "r"(bar) : "memory");
}
__device__ __forceinline__ void tma3d(uint32_t dst, const CUtensorMap* tm, int y, int z, uint32_t bar) {
    asm volatile("cp.async.bulk.tensor.3d.shared::cluster.global.mbarrier::complete_tx::bytes [%0],[%1,{0,%2,%3}],[%4];" ::"r"(dst), "l"(tm), "r"(y), "r"(z), "r"(bar) : "memory");
}
__device__ __forceinline__ void st_async4(uint32_t a, uint32_t x, uint32_t y, uint32_t z, uint32_t w, uint32_t mb) {
    asm volatile("st.async.shared::cluster.mbarrier::complete_tx::bytes.v4.b32 [%0],{%1,%2,%3,%4},[%5];" ::"r"(a), "r"(x), "r"(y), "r"(z), "r"(w), "r"(mb) : "memory");
}
__device__ __forceinline__ void st_async2(uint32_t a, uint32_t x, uint32_t y, uint32_t mb) {
    asm volatile("st.async.shared::cluster.mbarrier::complete_tx::bytes.v2.b32 [%0],{%1,%2},[%3];" ::"r"(a), "r"(x), "r"(y), "r"(mb) : "memory");
}
#define LDSQ "ld.shared"
__device__ __forceinline__ uint4 lds128(uint32_t a) { uint4 v; asm volatile(LDSQ ".v4.u32 {%0,%1,%2,%3},[%4];" : "=r"(v.x), "=r"(v.y), "=r"(v.z), "=r"(v.w) : "r"(a) : "memory"); return v; }
__device__ __forceinline__ uint4 lds128v(uint32_t a) { uint4 v; asm volatile("ld.volatile.shared.v4.u32 {%0,%1,%2,%3},[%4];" : "=r"(v.x), "=r"(v.y), "=r"(v.z), "=r"(v.w) : "r"(a) : "memory"); return v; }
__device__ __forceinline__ uint2 lds64(uint32_t a) { uint2 v; asm volatile(LDSQ ".v2.u32 {%0,%1},[%2];" : "=r"(v.x), "=r"(v.y) : "r"(a) : "memory"); return v; }
__device__ __forceinline__ uint32_t lds32(uint32_t a) { uint32_t v; asm volatile(LDSQ ".u32 %0,[%1];" : "=r"(v) : "r"(a) : "memory"); return v; }
__device__ __forceinline__ void sts128(uint32_t a, uint32_t x, uint32_t y, uint32_t z, uint32_t w) { asm volatile("st.shared.v4.u32 [%0],{%1,%2,%3,%4};" ::"r"(a), "r"(x), "r"(y), "r"(z), "r"(w) : "memory"); }
__device__ __forceinline__ void sts64(uint32_t a, uint32_t x, uint32_t y) { asm volatile("st.shared.v2.u32 [%0],{%1,%2};" ::"r"(a), "r"(x), "r"(y) : "memory"); }
__device__ __forceinline__ void sts32(uint32_t a, uint32_t x) { asm volatile("st.shared.u32 [%0],%1;" ::"r"(a), "r"(x) : "memory"); }
__device__ __forceinline__ uint4 ldsm4(uint32_t a) { uint4 v; asm volatile("ldmatrix.sync.aligned.m8n8.x4.shared.b16 {%0,%1,%2,%3},[%4];" : "=r"(v.x), "=r"(v.y), "=r"(v.z), "=r"(v.w) : "r"(a) : "memory"); return v; }
__device__ __forceinline__ uint4 ldsm4t(uint32_t a) { uint4 v; asm volatile("ldmatrix.sync.aligned.m8n8.x4.trans.shared.b16 {%0,%1,%2,%3},[%4];" : "=r"(v.x), "=r"(v.y), "=r"(v.z), "=r"(v.w) : "r"(a) : "memory"); return v; }
__device__ __forceinline__ uint32_t movm(uint32_t a) { uint32_t d; asm volatile("movmatrix.sync.aligned.m8n8.trans.b16 %0,%1;" : "=r"(d) : "r"(a)); return d; }
__device__ __forceinline__ uint32_t pack2(float lo, float hi) { uint32_t d; asm("cvt.rn.bf16x2.f32 %0,%1,%2;" : "=r"(d) : "f"(hi), "f"(lo)); return d; }
__device__ __forceinline__ uint32_t hadd2(uint32_t a, uint32_t b) { uint32_t d; asm("add.rn.bf16x2 %0,%1,%2;" : "=r"(d) : "r"(a), "r"(b)); return d; }
__device__ __forceinline__ uint32_t hmul2(uint32_t a, uint32_t b) { uint32_t d; asm("mul.rn.bf16x2 %0,%1,%2;" : "=r"(d) : "r"(a), "r"(b)); return d; }
__device__ __forceinline__ float blo(uint32_t v) { return __uint_as_float(v << 16); }
__device__ __forceinline__ float bhi(uint32_t v) { return __uint_as_float(v & 0xffff0000u); }
__device__ __forceinline__ float rbf(float x) { return __uint_as_float(pack2(0.f, x)); }
__device__ __forceinline__ float ex2(float x) { float y; asm("ex2.approx.ftz.f32 %0,%1;" : "=f"(y) : "f"(x)); return y; }
__device__ __forceinline__ float rcp(float x) { float y; asm("rcp.approx.ftz.f32 %0,%1;" : "=f"(y) : "f"(x)); return y; }
__device__ __forceinline__ void mma16(float* c, uint32_t a0, uint32_t a1, uint32_t a2, uint32_t a3, uint32_t b0, uint32_t b1) {
    asm volatile("mma.sync.aligned.m16n8k16.row.col.f32.bf16.bf16.f32 {%0,%1,%2,%3},{%4,%5,%6,%7},{%8,%9},{%0,%1,%2,%3};"
                 : "+f"(c[0]), "+f"(c[1]), "+f"(c[2]), "+f"(c[3]) : "r"(a0), "r"(a1), "r"(a2), "r"(a3), "r"(b0), "r"(b1));
}
__device__ __forceinline__ void mma16_top(float& d0, float& d1, uint32_t a0, uint32_t a2, uint32_t b0, uint32_t b1) {
    asm volatile("{.reg .b32 j; .reg .f32 e,f; mma.sync.aligned.m16n8k16.row.col.f32.bf16.bf16.f32 {%0,%1,e,f},{%2,j,%3,j},{%4,%5},{0f00000000,0f00000000,0f00000000,0f00000000};}"
                 : "=f"(d0), "=f"(d1) : "r"(a0), "r"(a2), "r"(b0), "r"(b1));
}
__device__ __forceinline__ void mma8(float* c, uint32_t a0, uint32_t a1, uint32_t b0) {
    asm volatile("mma.sync.aligned.m16n8k8.row.col.f32.bf16.bf16.f32 {%0,%1,%2,%3},{%4,%5},{%6},{%0,%1,%2,%3};"
                 : "+f"(c[0]), "+f"(c[1]), "+f"(c[2]), "+f"(c[3]) : "r"(a0), "r"(a1), "r"(b0));
}
__device__ __forceinline__ uint4 ld_rlx128(const uint4* p) {
    uint4 v;
    asm volatile("{.reg .b128 t; ld.relaxed.gpu.global.b128 t,[%4]; mov.b128 {%0,%1,%2,%3},t;}" : "=r"(v.x), "=r"(v.y), "=r"(v.z), "=r"(v.w) : "l"(p) : "memory");
    return v;
}
__device__ __forceinline__ void st_rlx128(uint4* p, uint32_t x, uint32_t y, uint32_t z, uint32_t w) {
    asm volatile("{.reg .b128 t; mov.b128 t,{%1,%2,%3,%4}; st.relaxed.gpu.global.b128 [%0],t;}" ::"l"(p), "r"(x), "r"(y), "r"(z), "r"(w) : "memory");
}
__device__ __forceinline__ uint4 ldcg128(const uint4* p) { uint4 v; asm volatile("ld.global.cg.v4.u32 {%0,%1,%2,%3},[%4];" : "=r"(v.x), "=r"(v.y), "=r"(v.z), "=r"(v.w) : "l"(p) : "memory"); return v; }
__device__ __forceinline__ void red_release(unsigned* p, unsigned v) {
    asm volatile("fence.proxy.async; red.relaxed.gpu.global.add.u32 [%0],%1;" ::"l"(p), "r"(v) : "memory");
}
__device__ __forceinline__ void red_relaxed(unsigned* p, unsigned v) { asm volatile("red.relaxed.gpu.global.add.u32 [%0],%1;" ::"l"(p), "r"(v) : "memory"); }
__device__ __forceinline__ void wait_cnt(const unsigned* p, unsigned target) {
    asm volatile(
        "{.reg .pred p; .reg .u32 n,v; mov.u32 n,0;\n"
        "W%=: ld.acquire.gpu.global.u32 v,[%0]; setp.ge.u32 p,v,%1; @p bra D%=;\n"
        "nanosleep.u32 20; add.u32 n,n,1; setp.lt.u32 p,n,4000000; @p bra W%=;\n"
        "trap;\n"
        "D%=: }" ::"l"(p), "r"(target) : "memory");
}
__device__ __forceinline__ void wait_cnt_warp(const unsigned* p, unsigned target) {
    asm volatile(
        "{.reg .pred p; .reg .u32 n,v; mov.u32 n,0;\n"
        "W%=: ld.acquire.gpu.global.u32 v,[%0]; setp.ge.u32 p,v,%1; vote.sync.all.pred p,p,0xffffffff; @p bra.uni D%=;\n"
        "nanosleep.u32 20; add.u32 n,n,1; setp.lt.u32 p,n,4000000; @p bra.uni W%=;\n"
        "trap;\n"
        "D%=: }" ::"l"(p), "r"(target) : "memory");
}
__device__ __forceinline__ void wait_slow_warp(const unsigned* p, unsigned target) {
    asm volatile(
        "{.reg .pred p; .reg .u32 n,v; mov.u32 n,0;\n"
        "W%=: ld.relaxed.gpu.global.u32 v,[%0]; setp.ge.u32 p,v,%1; vote.sync.all.pred p,p,0xffffffff; @p bra.uni D%=;\n"
        "nanosleep.u32 400; add.u32 n,n,1; setp.lt.u32 p,n,1000000; @p bra.uni W%=;\n"
        "trap;\n"
        "D%=: }" ::"l"(p), "r"(target) : "memory");
}
__device__ __forceinline__ void wait_flag_warp(const unsigned* p, unsigned target) {
    asm volatile(
        "{.reg .pred p; .reg .u32 n,v; mov.u32 n,0;\n"
        "W%=: ld.relaxed.gpu.global.u32 v,[%0]; setp.ge.u32 p,v,%1; vote.sync.all.pred p,p,0xffffffff; @p bra.uni D%=;\n"
        "add.u32 n,n,1; setp.lt.u32 p,n,10000000; @p bra.uni W%=;\n"
        "trap;\n"
        "D%=: }" ::"l"(p), "r"(target) : "memory");
}
__device__ __forceinline__ uint64_t mkdesc(uint32_t addr, uint32_t lbo, uint32_t sbo, uint32_t sw) {
    return (uint64_t)((addr & 0x3FFFF) >> 4) | ((uint64_t)(lbo >> 4) << 16) | ((uint64_t)(sbo >> 4) << 32) | ((uint64_t)sw << 62);
}
__device__ __forceinline__ void wg_fence() { asm volatile("wgmma.fence.sync.aligned;" ::: "memory"); }
__device__ __forceinline__ void wg_commit() { asm volatile("wgmma.commit_group.sync.aligned;" ::: "memory"); }
template <int N> __device__ __forceinline__ void wg_wait() { asm volatile("wgmma.wait_group.sync.aligned %0;" ::"n"(N) : "memory"); }
#define R8(c, o) "+f"(c[o]), "+f"(c[o + 1]), "+f"(c[o + 2]), "+f"(c[o + 3]), "+f"(c[o + 4]), "+f"(c[o + 5]), "+f"(c[o + 6]), "+f"(c[o + 7])
#define R32(c, o) R8(c, o), R8(c, o + 8), R8(c, o + 16), R8(c, o + 24)
#define S32A "%0,%1,%2,%3,%4,%5,%6,%7,%8,%9,%10,%11,%12,%13,%14,%15,%16,%17,%18,%19,%20,%21,%22,%23,%24,%25,%26,%27,%28,%29,%30,%31"
template <int ACC> __device__ __forceinline__ void wgmma64_rs(float* c, const uint32_t* a, uint64_t db) {
    asm volatile("wgmma.mma_async.sync.aligned.m64n64k16.f32.bf16.bf16 {" S32A "},{%32,%33,%34,%35},%36,%37,1,1,0;"
                 : R32(c, 0) : "r"(a[0]), "r"(a[1]), "r"(a[2]), "r"(a[3]), "l"(db), "n"(ACC));
}
template <int ACC> __device__ __forceinline__ void wgmma64_ta(float* c, uint64_t da, uint64_t db) {
    asm volatile("wgmma.mma_async.sync.aligned.m64n64k16.f32.bf16.bf16 {" S32A "},%32,%33,%34,1,1,1,0;" : R32(c, 0) : "l"(da), "l"(db), "n"(ACC));
}
template <int ACC> __device__ __forceinline__ void wgmma80_tb(float* c, uint64_t da, uint64_t db) {
    asm volatile("wgmma.mma_async.sync.aligned.m64n80k16.f32.bf16.bf16 {" S32A ",%32,%33,%34,%35,%36,%37,%38,%39},%40,%41,%42,1,1,0,1;"
                 : R32(c, 0), R8(c, 32) : "l"(da), "l"(db), "n"(ACC));
}
template <int N> __device__ __forceinline__ void reg_inc() { asm volatile("setmaxnreg.inc.sync.aligned.u32 %0;" ::"n"(N)); }
template <int N> __device__ __forceinline__ void reg_dec() { asm volatile("setmaxnreg.dec.sync.aligned.u32 %0;" ::"n"(N)); }

#define PROF(cond, idx) do {} while (0)
#define PROF2(cond, idx) do {} while (0)

constexpr int S_GATE = 232440, S_TAG = 232444, S_XBAR = 232432, B_BAR = 231936;
#define FT 5
#define RCB 136
#define RCU 184
#define NTOP 1
#define PLATE 2
#define PFM 12
#define QLAG 3
constexpr float SC_LOG2E = 0.08838834764831845f * 1.4426950408889634f;

__device__ __forceinline__ float2 ln_finish(float mean, float var) {
    float sd; asm("sqrt.approx.f32 %0,%1;" : "=f"(sd) : "f"(rbf(rbf(var) + 1e-5f)));
    sd = rbf(sd);
    return make_float2(rbf(mean), sd);
}

__device__ __forceinline__ float2 row_stats512(uint4* v, const uint4* src, int s1, int s2) {
    const int g = (threadIdx.x & 31) >> 2;
#pragma unroll
    for (int i = 0; i < 16; i++) v[i] = ldcg128(src + (i >> 1) * s1 + (i & 1) * s2);
    float a[4] = {0, 0, 0, 0}, q0[4] = {0, 0, 0, 0}, q1[4] = {0, 0, 0, 0};
#pragma unroll
    for (int i = 0; i < 16; i++) {
        mma16(a, v[i].x, v[i].y, v[i].z, v[i].w, 0x3f803f80u, 0x3f803f80u);
        mma8(q0, v[i].x, v[i].y, v[i].x); mma8(q1, v[i].x, v[i].y, v[i].y);
        mma8(q0, v[i].z, v[i].w, v[i].z); mma8(q1, v[i].z, v[i].w, v[i].w);
    }
    const float sum = a[0] + a[2], sq = (g & 1) ? q0[1] + q1[3] : q0[0] + q1[2];
    return make_float2(sum, fmaxf(sq - sum * sum * (1.f / 512.f), 0.f));
}
__device__ __forceinline__ void x1_norm(const uint2* src, int r, bool on) {
    const int lane = threadIdx.x & 31, g = lane >> 2, t = r * 4 + (lane & 3);
    constexpr int xp = XP;
    uint2 v[16];
#pragma unroll
    for (int i = 0; i < 16; i++) asm volatile("ld.global.cg.v2.u32 {%0,%1},[%2];" : "=r"(v[i].x), "=r"(v[i].y) : "l"(src + (g * 4 * xp + t) + ((i >> 1) * 16 + (i & 1)) * 2 * xp) : "memory");
    float s = 0, q = 0;
#pragma unroll
    for (int i = 0; i < 32; i++) {
        const uint32_t w = (i & 1) ? v[i >> 1].y : v[i >> 1].x;
        s += blo(w) + bhi(w); q = fmaf(blo(w), blo(w), fmaf(bhi(w), bhi(w), q));
    }
#pragma unroll
    for (int d = 4; d < 32; d *= 2) { s += __shfl_xor_sync(0xffffffffu, s, d); q += __shfl_xor_sync(0xffffffffu, q, d); }
    if (g == 0 && on) g_ln0[t] = 0;
    s *= 1.f / 512.f;
    const float2 l = ln_finish(s, fmaxf(fmaf(q, 1.f / 512.f, -s * s), 0.f));
    const float rs = rcp(l.y);
    const uint32_t mm = pack2(-l.x, -l.x);
    uint4* dst = g_xn + ((t >> 6) * 4096 + ((t >> 3) & 7) * 64 + g * 8 + (t & 7));
#define NRM(w) pack2(blo(hadd2(w, mm)) * rs, bhi(hadd2(w, mm)) * rs)
#pragma unroll
    for (int i = 0; i < 8; i++)
        asm volatile("{.reg .pred p; setp.ne.u32 p,%5,0; @p st.global.v4.u32 [%0],{%1,%2,%3,%4};}" ::"l"(dst + i * 512), "r"(NRM(v[2 * i].x)), "r"(NRM(v[2 * i].y)),
                     "r"(NRM(v[2 * i + 1].x)), "r"(NRM(v[2 * i + 1].y)), "r"((uint32_t)on) : "memory");
}

#define NWO 10
#define VMASK 0x4444
#define VPRE 2
#define VFIRST 1
#define OA 0
#define OL 0x16
#define PINS 0x6ae1
#define NPX 2
#define NPF 2
constexpr int SLOT = 24576, SL_V = 8192, SL_Q = 16384, SL_KM = 20480, SL_VM = 22528;
constexpr int R_SL = 0, R_WV = 4 * SLOT  , R_WO = R_WV + 65536, R_M = 196608  , R_U = R_M + 8192  ,
              R_OS = R_U + 8192  , R_SB = R_OS + 8192  , R_OB = R_SB + 5248  , R_PB = R_OB + 2048  ,
              R_IL = R_PB + 1024  , R_SEL = 231680, R_BAR = R_SEL + 256, R_STV = 0, R_STQ = 65536, R_STK = 131072;
static_assert(R_WO + (16 - NWO) * 4096 <= R_M && R_IL + 64 <= R_SEL && R_BAR + 512 <= 232448, "smem map");
enum { RB_XFULL = 0  , RB_GO = 4  , RB_QK = 8  , RB_INIT = 24, RB_SV = 25   };

enum { NB_MFULL = 1  , NB_PART = 3  , NB_S = 5, NB_P = 6, NB_O = 7, NB_W = 10 };
#define XU 4
#define GOP 0
#define WOF 1
#define SPV 0
#define SEARLY 4
#define EGO 0
#define NPRB 3
#define REARLY 1
#define RFW 8
#define PF0 0
#define PFD 1500
#define EFS V_QKV
#define RACC 4
#define WDEP 1
#define RH 56
#define RW0 224
#define D1 270
#define D2 300
__device__ __forceinline__ uint32_t clk32() { uint32_t c; asm volatile("mov.u32 %0,%%clock;" : "=r"(c)::"memory"); return c; }
__device__ __forceinline__ void spin(int cycles) {
    if (cycles <= 0) return;
    asm volatile("{.reg .pred p; .reg .u32 a,b; mov.u32 a,%%clock; add.u32 a,a,%0;\nS%=: mov.u32 b,%%clock; sub.u32 b,b,a; setp.lt.s32 p,b,0; @p bra.uni S%=;}" ::"r"(cycles) : "memory");
}
__device__ __forceinline__ void spin_v(uint32_t cycles) {
    asm volatile("{.reg .pred p; .reg .u32 a,b; mov.u32 a,%%clock; add.u32 a,a,%0;\nS%=: mov.u32 b,%%clock; sub.u32 b,b,a; setp.lt.s32 p,b,0; @p bra.uni S%=;}" ::"r"(cycles) : "memory");
}
__device__ __forceinline__ uint4* xregion(int X, int r) { return (uint4*)(((size_t)g_xch + 8191) & ~(size_t)8191) + (X * 66 + r) * 512; }

__device__ __forceinline__ void arrive_if(uint32_t bar, uint32_t a, uint32_t b) {
    asm volatile("{.reg .pred p; setp.eq.u32 p,%1,%2; @p mbarrier.arrive.shared::cta.b64 _,[%0];}" ::"r"(bar), "r"(a), "r"(b) : "memory");
}
struct RecW { uint32_t po, dp, lw, sp, w; };
#define PIN(n) if ((PINS >> (n)) & 1) asm volatile("griddepcontrol.launch_dependents;" ::: "memory")
constexpr int v_stream(int n) {
    int ks = 0;
    for (; ks < 16; ks++) if (!((VMASK >> ks) & 1) && n-- == 0) break;
    return ks;
}
constexpr uint64_t v_next() {
    uint64_t r = 0;
    for (int n = 0; v_stream(n + VPRE) < 16; n++) r |= (uint64_t)v_stream(n + VPRE) << (4 * v_stream(n));
    return r;
}
constexpr uint64_t V_NEXT = v_next();
constexpr int V_PRE = v_stream(VPRE);

__device__ __forceinline__ void rec_step(const RecW& k, uint32_t sb, const int X, int s, uint32_t zero, int lo, int hi, int d, const uint32_t (*wq)[4], const uint32_t (*wk)[4], uint4* wv, uint4* wo) {
    const int SL = R_SL + X * 2 * SLOT;
    uint4 mk[8];
    bar_sync(NB_MFULL + X, 288);
    mk[0] = ldsm4(k.lw + X * 4096 + R_M);
    PIN(0);
    mk[1] = ldsm4(k.lw + X * 4096 + R_M + 512);
    PIN(0);
    asm volatile("" : "+r"(s));
    const uint32_t z = s & zero, wz = k.w + z, w5 = wz * 512, so = (s & 1) * SLOT + w5;
    const uint32_t qb = sb + R_BAR + (RB_QK + X * 8) * 8 + wz * 8;
    uint32_t x[4], vv[2], l8;
    {
        float aq[4] = {0, 0, 0, 0}, ak[4] = {0, 0, 0, 0}, av[4] = {0, 0, 0, 0};
#pragma unroll
        for (int t = 0; t < 16; t++) {
            const uint32_t b0 = (t & 1) ? mk[t >> 1].z : mk[t >> 1].x, b1 = (t & 1) ? mk[t >> 1].w : mk[t >> 1].y;
            mma16(aq, wq[t][0], wq[t][1], wq[t][2], wq[t][3], b0, b1);
            PIN(8);
            mma16(ak, wk[t][0], wk[t][1], wk[t][2], wk[t][3], b0, b1);
            PIN(9);
            mma16(av, wv[t].x, wv[t].y, wv[t].z, wv[t].w, b0, b1);
            PIN(10);
            if ((t & 1) && t < 13) mk[(t >> 1) + 2] = ldsm4(k.lw + X * 4096 + R_M + (t >> 1) * 512 + 1024);
            const int nx = (V_NEXT >> (4 * t)) & 15;
            if (nx) wv[nx] = lds128(k.lw + w5 + R_WV + nx * 4096);
            if (t == 14) l8 = ((k.lw + z) >> 1) + (sb - (sb >> 1) + SL + (s & 1) * SLOT + wz * 256);
            if (t < 15) PIN(1);
        }
        x[0] = movm(pack2(aq[0], aq[1])); x[1] = movm(pack2(aq[2], aq[3]));
        x[2] = movm(pack2(ak[0], ak[1])); x[3] = movm(pack2(ak[2], ak[3]));
        vv[0] = pack2(av[0], av[1]); vv[1] = pack2(av[2], av[3]);
        if (VFIRST) st_async2(l8 + (SL_VM + k.dp), vv[0], vv[1], qb + k.dp);
        st_async4(k.lw + (R_U + X * 4096 + w5 + k.dp), x[0], x[1], x[2], x[3], qb + k.dp);
        if (!VFIRST) st_async2(l8 + (SL_VM + k.dp), vv[0], vv[1], qb + k.dp);
    }
    {
#define GO_OTHER arrive_if(sb + R_BAR + (RB_GO + 2 - 2 * X + ((s + d) & 1)) * 8, (k.sp + z) & 0x1ff0, X ? s >= hi : s <= lo)
        if (GOP == 0) GO_OTHER;
        const uint32_t swr = ((k.sp + z) & 0x1ff0) + (sb + R_SB);
        if (WOF) {
#pragma unroll
            for (int i = 0; i < NPX; i++) wo[i] = lds128v(k.lw + w5 + R_WO + i * 4096);
        }
        mbar_wait(sb + R_BAR + (RB_XFULL + X * 2) * 8 + (s & 1) * 8, (s >> 1) & 1);
        const uint4 k0 = lds128(k.lw + so + SL), k1 = lds128(k.lw + so + SL + 4096);
        if (!WOF) {
#pragma unroll
            for (int i = 0; i < NPX; i++) wo[i] = lds128(k.lw + w5 + R_WO + i * 4096);
        }
        if (GOP == 1) GO_OTHER;
        mbar_wait(qb, s & 1);
        const uint4 u = lds128(k.lw + w5 + R_U + X * 4096);
        if (GOP == 2) GO_OTHER;
        const uint32_t q0 = hadd2(x[0], u.x), q1 = hadd2(x[1], u.y);
        x[2] = hadd2(x[2], u.z); x[3] = hadd2(x[3], u.w);
        float sa[4] = {0, 0, 0, 0}, sc[4] = {0, 0, 0, 0}, sm0, sm1;
        mma16(sa, k0.x, k0.y, k0.z, k0.w, q0, q1);
        mma16(sc, k1.x, k1.y, k1.z, k1.w, q0, q1);
        mma16_top(sm0, sm1, x[2], x[3], q0, q1);
        asm volatile("stmatrix.sync.aligned.m8n8.x4.trans.shared.b16 [%0],{%1,%2,%3,%4};" ::"r"(swr), "r"(pack2(sa[0], sa[1])), "r"(pack2(sa[2], sa[3])),
                     "r"(pack2(sc[0], sc[1])), "r"(pack2(sc[2], sc[3])) : "memory");
        asm volatile("stmatrix.sync.aligned.m8n8.x1.trans.shared.b16 [%0],{%1};" ::"r"(swr + 512), "r"(pack2(sm0, sm1)) : "memory");
    }
    if (GOP == 3) GO_OTHER;
    bar_sync(NB_S, 256);
    uint4 v0, v1;
    uint32_t ls;
    {
        const uint4 y = ldsm4t(k.lw + wz * 656 + R_SB);
        PIN(2);
        uint32_t y4; asm volatile("ldmatrix.sync.aligned.m8n8.x1.trans.shared.b16 {%0},[%1];" : "=r"(y4) : "r"(k.lw + wz * 656 + R_SB + 512) : "memory");
        PIN(2);
        const uint2 vp = lds64(l8 + SL_VM);
        sts64(l8 + SL_KM, x[2], x[3]);
        const uint32_t z1 = k.lw & z, z2 = k.sp & z, ONE = 0x3f803f80u | z2, ONF = 0x3f803f80u | z1;
        float a[4] = {0, 0, 0, 0}, b[4] = {0, 0, 0, 0}, e[4] = {0, 0, 0, 0};
        mma8(e, ONE, z1, y4); mma16(a, ONE, z1, z2, ONF, y.x, y.y); mma16(b, ONE, z1, z2, ONF, y.z, y.w);
        vv[0] = hadd2(vv[0], vp.x); vv[1] = hadd2(vv[1], vp.y);
        sts64(l8 + SL_VM, vv[0], vv[1]);
        float s0, s1;
        asm("{.reg .pred p1,p2,p4; .reg .f32 t0,t1,u0,u1; .reg .b32 m; and.b32 m,%12,64; setp.ne.u32 p1,m,0; and.b32 m,%12,128; setp.ne.u32 p2,m,0; and.b32 m,%12,256; setp.ne.u32 p4,m,0;"
            "selp.f32 t0,%4,%2,p1; selp.f32 t1,%5,%3,p1; selp.f32 u0,%8,%6,p1; selp.f32 u1,%9,%7,p1; selp.f32 t0,u0,t0,p2; selp.f32 t1,u1,t1,p2; selp.f32 %0,%10,t0,p4; selp.f32 %1,%11,t1,p4;}"
            : "=f"(s0), "=f"(s1) : "f"(a[0]), "f"(a[1]), "f"(a[2]), "f"(a[3]), "f"(b[0]), "f"(b[1]), "f"(b[2]), "f"(b[3]), "f"(e[0]), "f"(e[1]), "r"(k.lw));
        const int mi = __float_as_int(fmaxf(s0, s1));
        const int mp = __reduce_max_sync(0xffffffffu, mi), mn = (int)__reduce_min_sync(0xffffffffu, (unsigned)mi);
        PIN(3);
        v0 = lds128(k.lw + so + SL + SL_V); v1 = lds128(k.lw + so + SL + SL_V + 4096);
#pragma unroll
        for (int i = NPX; i < NPF; i++) wo[i] = lds128(k.lw + w5 + R_WO + i * 4096);
        PIN(4);
        const float mo = -__int_as_float(mp >= 0 ? mp : mn) * SC_LOG2E;
        s0 = ex2(fmaf(s0, SC_LOG2E, mo)); s1 = ex2(fmaf(s1, SC_LOG2E, mo));
        sts32((((k.sp + z) >> 11) & 0x1fc) + (k.lw & 256) * 2 + (sb + R_PB), pack2(s0, s1));
        ls = k.lw < sb + 320 ? __float_as_uint((s0 + s1) + 4.f) : 0;
    }
    bar_sync(NB_P, 256);
    {
        const uint4 pp = lds128(k.lw + R_PB);
        PIN(5);
        const uint32_t pm = lds32(((k.lw + z) >> 2) + (sb - (sb >> 2) + R_PB + 512));
        PIN(5);
        if (EGO) arrive_if(sb + R_BAR + (RB_GO + 2 * X + (s & 1)) * 8, (k.sp + z) & 0x1ff0, X ? s + 1 < hi : s >= lo);
        sts32(sb + R_IL + (wz >> 1) * 16 + (wz & 1) * 4, __reduce_add_sync(0xffffffffu, ls) - 20u * 0x40800000u);
        float o0[4] = {0, 0, 0, 0}, o1[4] = {0, 0, 0, 0}, o2[4] = {0, 0, 0, 0};
        mma16(o0, v0.x, v0.y, v0.z, v0.w, pp.x, pp.y);
        mma16(o1, v1.x, v1.y, v1.z, v1.w, pp.z, pp.w);
        mma8(o2, vv[0], vv[1], pm);
        asm volatile("stmatrix.sync.aligned.m8n8.x2.trans.shared.b16 [%0],{%1,%2};" ::"r"(k.lw + wz * 256 + R_OB),
                     "r"(pack2(o0[0] + o1[0] + o2[0], o0[1] + o1[1] + o2[1])), "r"(pack2(o0[2] + o1[2] + o2[2], o0[3] + o1[3] + o2[3])) : "memory");
    }
    bar_sync(NB_O, 256);
    {
        float r0[2][4] = {{0, 0, 0, 0}, {0, 0, 0, 0}}, r1[2][4] = {{0, 0, 0, 0}, {0, 0, 0, 0}};
        uint4 b[4];
        b[0] = ldsm4(k.lw + R_OB);
        PIN(6);
        b[1] = ldsm4(k.lw + R_OB + 512);
        PIN(6);
#pragma unroll
        for (int m = NWO + NPF; m < 16; m++) if (((OL >> (2 * (15 - m))) & 3) == 3) wo[m] = lds128(k.lw + w5 + R_WO + (m - NWO) * 4096);
        const uint2 il = lds64(sb + R_IL + ((k.lw + z) & 48));
        PIN(6);
        float i0, i1;
        uint4* dst;
#pragma unroll
        for (int i = 0; i < 4; i++) {
            mma16(r0[0], wo[4 * i].x, wo[4 * i].y, wo[4 * i].z, wo[4 * i].w, b[i].x, b[i].y);
            mma16(r1[0], wo[4 * i + 1].x, wo[4 * i + 1].y, wo[4 * i + 1].z, wo[4 * i + 1].w, b[i].x, b[i].y);
            mma16(r0[OA], wo[4 * i + 2].x, wo[4 * i + 2].y, wo[4 * i + 2].z, wo[4 * i + 2].w, b[i].z, b[i].w);
            mma16(r1[OA], wo[4 * i + 3].x, wo[4 * i + 3].y, wo[4 * i + 3].z, wo[4 * i + 3].w, b[i].z, b[i].w);
            if (i < 2) b[i + 2] = ldsm4(k.lw + R_OB + (i + 2) * 512);
#pragma unroll
            for (int m = NWO + NPF; m < 16; m++) if (i < 3 && i == ((OL >> (2 * (15 - m))) & 3)) wo[m] = lds128(k.lw + w5 + R_WO + (m - NWO) * 4096);
            if (i == 1) { i0 = rcp(__uint2float_rn(il.x)) * 2097152.f; i1 = rcp(__uint2float_rn(il.y)) * 2097152.f; }
            if (i == 2) {
                const uint32_t po = k.sp + z;
                dst = xregion(X, 0) + k.po + ((po >> 20) ^ ((po & X) << 8));
                asm volatile("" : "+l"(dst));
            }
            PIN(7);
        }
        const uint32_t tag = (s + 1) & 1;
#pragma unroll
        for (int i = 0; i < 4; i++) { r0[0][i] = (OA ? r0[0][i] + r0[1][i] : r0[0][i]) * ((i & 1) ? i1 : i0); r1[0][i] = (OA ? r1[0][i] + r1[1][i] : r1[0][i]) * ((i & 1) ? i1 : i0); }
        st_rlx128(dst, (pack2(r0[0][0], r0[0][2]) & ~1u) | tag,
                  pack2(r1[0][0], r1[0][2]), pack2(r0[0][1], r0[0][3]), pack2(r1[0][1], r1[0][3]));
        bar_arrive(NB_PART + X, 288);
#pragma unroll
        for (int t = 0; t < V_PRE; t++) if (!((VMASK >> t) & 1)) wv[t] = lds128(k.lw + w5 + R_WV + t * 4096);
        if (!EGO) arrive_if(sb + R_BAR + (RB_GO + 2 * X + (s & 1)) * 8, (k.sp + z) & 0x1ff0, X ? s + 1 < hi : s >= lo);
    }
}

__device__ __forceinline__ void rec_fetch(const Params& p, uint32_t sb, int head, uint32_t rank, int which, int dst) {
#pragma unroll 1
    for (int j = 0; j < 8; j++) tma2d(sb + dst + j * 8192, &p.tm[which], head * 128 + (j >> 2) * 64, rank * 256 + (j & 3) * 64, sb + R_BAR + RB_INIT * 8);
}

__device__ __forceinline__ void rec_weights(const Params& p, uint32_t sb, int head, uint32_t rank, int w) {
    const int lane = __shfl_sync(0xffffffffu, threadIdx.x & 31, threadIdx.x & 31),
        g = lane >> 2, c = lane & 3;
    const int t = w & 3, WG = w >> 2;
    uint32_t wq[16][4], wk[16][4];
    uint4 wo[16], wv[16];
    const uint32_t woff = sb + WG * 32768 + (((lane >> 4) << 3) + (lane & 7)) * 128 + (((2 * t + ((lane >> 3) & 1)) ^ (lane & 7)) << 4);
    const uint32_t lw = sb + lane * 16;
    PROF2(threadIdx.x == 0, 3501);
    {
        const __nv_bfloat16* wp = p.Wo + (size_t)(head * 128 + 2 * c) * 512 + rank * 256 + w * 32 + g * 4;
#pragma unroll
        for (int ks = 0; ks < 8; ks++) {
            const uint2 r0 = *(const uint2*)(wp + (ks * 16) * 512), r1 = *(const uint2*)(wp + (ks * 16 + 1) * 512);
            const uint2 r2 = *(const uint2*)(wp + (ks * 16 + 8) * 512), r3 = *(const uint2*)(wp + (ks * 16 + 9) * 512);
            const uint4 f[2] = {make_uint4(__byte_perm(r0.x, r1.x, 0x5410), __byte_perm(r0.x, r1.x, 0x7632), __byte_perm(r2.x, r3.x, 0x5410), __byte_perm(r2.x, r3.x, 0x7632)),
                                make_uint4(__byte_perm(r0.y, r1.y, 0x5410), __byte_perm(r0.y, r1.y, 0x7632), __byte_perm(r2.y, r3.y, 0x5410), __byte_perm(r2.y, r3.y, 0x7632))};
#pragma unroll
            for (int h = 0; h < 2; h++) {
                const int m = 2 * ks + h;
                wo[m] = f[h];
            }
        }
    }
    PROF2(threadIdx.x == 0, 3502);
    mbar_wait(sb + R_BAR + RB_INIT * 8, 0);
    PROF2(threadIdx.x == 0, 3503);
#pragma unroll
    for (int ks = 0; ks < 16; ks++) {
        uint4 a = ldsm4t(woff + R_STQ + ks * 2048), b = ldsm4t(woff + R_STK + ks * 2048);
        wq[ks][0] = a.x; wq[ks][1] = a.y; wq[ks][2] = a.z; wq[ks][3] = a.w;
        wk[ks][0] = b.x; wk[ks][1] = b.y; wk[ks][2] = b.z; wk[ks][3] = b.w;
    }
    bar_sync(NB_W, 256);
#pragma unroll
    for (int m = 0; m < 16; m++)
        if (m < NPF || m >= NPF + NWO) sts128(lw + w * 512 + R_WO + (m < NPF ? m : m - NWO) * 4096, wo[m].x, wo[m].y, wo[m].z, wo[m].w);
#pragma unroll
    for (int i = 0; i < 16; i++) {
        wv[i] = ldsm4t(woff + R_STV + i * 2048);
        if (!((VMASK >> i) & 1)) sts128(lw + w * 512 + R_WV + i * 4096, wv[i].x, wv[i].y, wv[i].z, wv[i].w);
    }
    fence_async_smem();
    PROF2(threadIdx.x == 0, 3504);
    __syncthreads();
    cluster_sync();
    PROF2(threadIdx.x == 0, 3505);
    RecW k;
    {
        const int r = (w * 4 + (lane >> 3)) * 2 + rank;
        const uint32_t sl = lds32(sb + R_SEL + r * 4);
        k.po = (w * 8 + rank) * 512 + (head >> 1) * 16 + (head & 1) * 4;
        k.sp = (((lane >> 3) * 1024 + (sl & 1) * 256 + (lane & 4) * 2 + (lane & 3)) << 20) + (((sl >> 1) ^ sl) & 1) + (lane & 7) * 656 + (lane >> 3) * 128 + w * 16 +
               ((g < 4 ? (w * 4 + c) * 4 + g : w * 4 + c) << 13);
    }
    k.dp = mapa(sb, rank ^ 1) - sb;
    k.lw = lw;
    asm volatile("" : "+r"(k.lw));
    k.w = w;
    const int e0 = (p.chains & 1) ? 64 : 0, o1 = (p.chains & 2) ? p.lag : 1000, nit = (p.chains & 2) ? p.lag + 64 : e0;
    const uint32_t zero = p.zero;
    int it = 0, X = e0 ? 0 : 1;
#pragma unroll 1
    while (it < nit) {
        rec_step(k, sb, X, X ? it - o1 : it, zero, o1, e0 - o1, o1 + 1 - X, wq, wk, wv, wo);
        if (X == 0 && it >= o1) X = 1; else { it++; X = it < e0 ? 0 : 1; }
    }
}

__device__ __forceinline__ uint32_t mism(uint32_t a, uint32_t b, uint32_t t) {
    uint32_t d; asm("lop3.b32 %0,%1,%2,%3,0x7e;" : "=r"(d) : "r"(a), "r"(b), "r"(t)); return d;
}
__device__ __forceinline__ uint32_t or3(uint32_t a, uint32_t b, uint32_t c) {
    uint32_t d; asm("lop3.b32 %0,%1,%2,%3,0xfe;" : "=r"(d) : "r"(a), "r"(b), "r"(c)); return d;
}
template <bool TWO, class F>
__device__ __forceinline__ void poll8(uint4* x, const uint4* src, uint32_t tag, F&& use) {
#pragma unroll
    for (int j = 0; j < 8; j++) x[j] = ld_rlx128(src + j * 32);
    int n = 0;
    while (true) {
        use();
        uint32_t bad = or3(mism(x[0].x, x[1].x, tag), mism(x[2].x, x[3].x, tag), mism(x[4].x, x[5].x, tag));
        if (TWO) bad = or3(bad, or3(mism(x[0].z, x[1].z, tag), mism(x[2].z, x[3].z, tag), mism(x[4].z, x[5].z, tag)), mism(x[6].z, x[7].z, tag));
        if (!__any_sync(0xffffffffu, (bad | mism(x[6].x, x[7].x, tag)) & 1)) break;
#pragma unroll
        for (int j = 0; j < 8; j++)
            asm volatile("{.reg .pred p; .reg .b128 t; .reg .b32 m; lop3.b32 m,%0,%6,%5,0x7e; and.b32 m,m,1; setp.ne.u32 p,m,0; mov.b128 t,{%0,%1,%2,%3};"
                         "@p ld.relaxed.gpu.global.b128 t,[%4]; mov.b128 {%0,%1,%2,%3},t;}"
                         : "+r"(x[j].x), "+r"(x[j].y), "+r"(x[j].z), "+r"(x[j].w) : "l"(src + j * 32), "r"(tag), "r"(TWO ? x[j].z : tag) : "memory");
        if (++n > 2000000) __trap();
    }
}

__device__ __forceinline__ void rec_comm(const Params& p, uint32_t sb, int X, int head, uint32_t rank) {
    const int lane = threadIdx.x & 31, g = lane >> 2, c = lane & 3;
    const int me = head * 2 + rank;
    const uint32_t mb = sb + R_M + X * 4096 + lane * 16;
    uint4 x[8];
#pragma unroll
    for (int j = 0; j < 8; j++) x[j] = *(const uint4*)(p.mem0 + (lane & 7) * 512 + rank * 256 + (j * 4 + (lane >> 3)) * 8);
    const uint32_t sl = lds32(sb + R_SEL + me * 4);
    const uint4* src1 = xregion(X, me) + ((sl >> X) & 1) * 256 + (c >> 1) * 16 + (g >> 2) * 8 + (c & 1) * 4 + (g & 3);
    const uint4* src2 = xregion(X, 64 + rank) + ((sl >> (2 + X)) & 1) * 256 + lane;
    uint2* mdst = (uint2*)(xregion(X, 64 + rank) + (c >> 1) * 256 + head * 8 + (g & 3) * 2 + (c & 1)) + (g >> 2);
    const uint32_t one = (g & 1) ? 0x3f800000u : 0x00003f80u, selA = (g & 2) ? 0u : one, selB = (g & 2) ? one : 0u;
    const uint32_t qb = sb + R_BAR + (RB_QK + X * 8) * 8;
    if (lane < 8) mbar_expect(qb + lane * 8, 768);
    __syncwarp();
#pragma unroll
    for (int j = 0; j < 8; j++) sts128(mb + j * 512, x[j].x, x[j].y, x[j].z, x[j].w);
#pragma unroll 1
    for (int s = 0;; s++) {
        bar_arrive(NB_MFULL + X, 288);
        PROF(lane == 0, X * 64 + s);
        bar_sync(NB_PART + X, 288);
        if (s == 63) break;
        const uint32_t tag = (s + 1) & 1;
        asm volatile("{.reg .pred p; setp.lt.u32 p,%0,%1; @p mbarrier.arrive.expect_tx.shared::cta.b64 _,[%0],768;}"
                     ::"r"(((mb + (s & p.zero)) >> 1) + (qb - ((sb + R_M + X * 4096) >> 1))), "r"(qb + 64) : "memory");
        if (SPV) spin_v(D1 + (mb & p.zero)); else spin(D1);
        uint32_t m0, m1;
        auto reduce = [&]() {
            float a[RACC][4];
#pragma unroll
            for (int j = 0; j < 8; j++) {
                if (j < RACC) a[j][0] = a[j][1] = a[j][2] = a[j][3] = 0;
                mma16(a[j % RACC], x[j].x, x[j].y, x[j].z, x[j].w, selA, selB);
            }
#pragma unroll
            for (int i = 0; i < 4; i++) a[0][i] = RACC == 4 ? (a[0][i] + a[1][i]) + (a[2 % RACC][i] + a[3 % RACC][i]) : a[0][i] + a[1][i];
            m0 = (pack2(a[0][0], a[0][1]) & ~1u) | tag; m1 = pack2(a[0][2], a[0][3]);
        };
        poll8<false>(x, src1, tag, [&]() { if (RACC == 2) reduce(); });
        if (RACC == 4) reduce();
        asm volatile("st.relaxed.gpu.global.b64 [%0],%1;" ::"l"(mdst), "l"(((uint64_t)m1 << 32) | m0) : "memory");
        if (SPV) spin_v(D2 + (mb & p.zero)); else spin(D2);
        poll8<true>(x, src2, tag, [&]() {
#pragma unroll
            for (int j = 0; j < SEARLY; j++) sts128(mb + j * 512, x[j].x, x[j].y, x[j].z, x[j].w);
        });
#pragma unroll
        for (int j = SEARLY; j < 8; j++) sts128(mb + j * 512, x[j].x, x[j].y, x[j].z, x[j].w);
    }
}

template <int MT>
__device__ __forceinline__ void xattn(uint32_t l16, uint32_t l8, uint32_t os, int g, int c) {
    constexpr int NT = 3 + 2 * MT, XUN = XU;
    float S[NT][4];
#pragma unroll
    for (int i = 0; i < NT; i++) S[i][0] = S[i][1] = S[i][2] = S[i][3] = 0;
#pragma unroll XUN
    for (int ks = 0; ks < 8; ks++) {
        const uint4 q = lds128(l16 + SL_Q + ks * 512);
        const uint2 u = lds64(l8 + SL_KM + ks * 256);
        mma16(S[0], q.x, q.y, q.z, q.w, u.x, u.y);
#pragma unroll
        for (int m = 0; m <= MT; m++) {
            const uint4 kk = lds128(l16 + m * 4096 + ks * 512);
            mma16(S[1 + 2 * m], q.x, q.y, q.z, q.w, kk.x, kk.z); mma16(S[2 + 2 * m], q.x, q.y, q.z, q.w, kk.y, kk.w);
        }
    }
    const float NEG = -__int_as_float(0x7f800000);
    if (2 * c > g) { S[NT - 2][0] = NEG; S[NT - 1][2] = NEG; }
    if (2 * c + 1 > g) { S[NT - 2][1] = NEG; S[NT - 1][3] = NEG; }
    S[NT - 1][0] = S[NT - 1][1] = NEG;
    float m0 = fmaxf(S[0][0], S[0][1]), m1 = fmaxf(S[0][2], S[0][3]);
#pragma unroll
    for (int i = 1; i < NT; i++) { if (i < NT - 1) m0 = fmaxf(m0, fmaxf(S[i][0], S[i][1])); m1 = fmaxf(m1, fmaxf(S[i][2], S[i][3])); }
    m0 = fmaxf(m0, __shfl_xor_sync(0xffffffffu, m0, 1)); m1 = fmaxf(m1, __shfl_xor_sync(0xffffffffu, m1, 1));
    m0 = fmaxf(m0, __shfl_xor_sync(0xffffffffu, m0, 2)); m1 = fmaxf(m1, __shfl_xor_sync(0xffffffffu, m1, 2));
    m0 *= -SC_LOG2E; m1 *= -SC_LOG2E;
    float l0 = 0, l1 = 0;
#pragma unroll
    for (int i = 0; i < NT; i++) {
        if (i < NT - 1) { S[i][0] = ex2(fmaf(S[i][0], SC_LOG2E, m0)); S[i][1] = ex2(fmaf(S[i][1], SC_LOG2E, m0)); l0 += S[i][0] + S[i][1]; }
        S[i][2] = ex2(fmaf(S[i][2], SC_LOG2E, m1)); S[i][3] = ex2(fmaf(S[i][3], SC_LOG2E, m1)); l1 += S[i][2] + S[i][3];
    }
    l0 += __shfl_xor_sync(0xffffffffu, l0, 1); l1 += __shfl_xor_sync(0xffffffffu, l1, 1);
    l0 += __shfl_xor_sync(0xffffffffu, l0, 2); l1 += __shfl_xor_sync(0xffffffffu, l1, 2);
    uint2 vm = lds64(l8 + SL_VM);
    uint4 v[2];
#pragma unroll
    for (int m = 0; m <= MT; m++) v[m] = lds128(l16 + SL_V + m * 4096);
    l0 = rcp(l0); l1 = rcp(l1);
    uint32_t P[NT][2];
#pragma unroll
    for (int i = 0; i < NT; i++) { P[i][0] = i < NT - 1 ? pack2(S[i][0] * l0, S[i][1] * l0) : 0u; P[i][1] = pack2(S[i][2] * l1, S[i][3] * l1); }
#pragma unroll
    for (int et = 0; et < 8; et++) {
        float a[4] = {0, 0, 0, 0}, b[4] = {0, 0, 0, 0};
        const uint2 um = vm;
        const uint4 u[2] = {v[0], v[MT]};
        if (et < 7) {
            vm = lds64(l8 + SL_VM + et * 256 + 256);
#pragma unroll
            for (int m = 0; m <= MT; m++) v[m] = lds128(l16 + SL_V + m * 4096 + et * 512 + 512);
            PIN(11);
        }
        mma8(a, um.x, um.y, P[0][0]); mma8(b, um.x, um.y, P[0][1]);
#pragma unroll
        for (int m = 0; m <= MT; m++) {
            mma16(a, u[m].x, u[m].y, u[m].z, u[m].w, P[1 + 2 * m][0], P[2 + 2 * m][0]); mma16(b, u[m].x, u[m].y, u[m].z, u[m].w, P[1 + 2 * m][1], P[2 + 2 * m][1]);
        }
        asm volatile("stmatrix.sync.aligned.m8n8.x4.trans.shared.b16 [%0],{%1,%2,%3,%4};" ::"r"(os + (et >> 2) * 2048 + (et & 3) * 256),
                     "r"(pack2(a[0], a[1])), "r"(pack2(a[2], a[3])), "r"(pack2(b[0], b[1])), "r"(pack2(b[2], b[3])) : "memory");
    }
}

__device__ __forceinline__ void rec_tiles(uint32_t sb, int X, int head, uint32_t rank, int& nxt, int lim, int need) {
#pragma unroll 1
    while (nxt <= lim) {
        if ((nxt & 1) == 0) {
            unsigned v; int n = 0;
            while (true) {
                asm volatile("ld.relaxed.gpu.global.u32 %0,[%1];" : "=r"(v) : "l"(cnt_ptr(C_QKV + X * 32 + (nxt >> 1))) : "memory");
                if (__all_sync(0xffffffffu, v >= 2 * NQ)) break;
                if (nxt > need) return;
                if (++n > 3000000) __trap();
            }
        }
        if (elect()) {
            const uint32_t bar = sb + R_BAR + (RB_XFULL + X * 2 + (nxt & 1)) * 8, dst = sb + R_SL + (X * 2 + (nxt & 1)) * SLOT;
            const uint4* src = g_qkv + (size_t)((X * 64 + nxt) * 32 + head) * 1536;
            mbar_expect(bar, 20480);
            bulk_g2s_mc(dst + rank * 8192, src + 512 + rank * 512, 8192, bar, POL_LAST);
            bulk_g2s(dst + SL_Q, src + (rank ^ X) * 256, 4096, bar, POL_LAST);
        }
        __syncwarp();
        nxt++;
    }
}

__device__ __forceinline__ void rec_attn(const Params& p, uint32_t sb, int X, int head, uint32_t rank) {
    const int lane = __shfl_sync(0xffffffffu, threadIdx.x & 31, threadIdx.x & 31), g = lane >> 2, c = lane & 3;
    const int mt = rank ^ X;
    const uint32_t dp = mapa(sb, rank ^ 1) - sb;
    int nxt = 0;
    rec_tiles(sb, X, head, rank, nxt, 1, 0);
#pragma unroll 1
    for (int s = 0; s < 64; s++) {
        const uint32_t so = sb + R_SL + (X * 2 + (s & 1)) * SLOT;
        while (nxt <= min(s + 1, 63)) {
            uint32_t ok;
            asm volatile("{.reg .pred p; mbarrier.test_wait.parity.shared::cta.b64 p,[%1],%2; selp.u32 %0,1,0,p;}" : "=r"(ok) : "r"(sb + R_BAR + (RB_GO + X * 2 + (s & 1)) * 8), "r"((s >> 1) & 1) : "memory");
            if (__any_sync(0xffffffffu, ok)) break;
            rec_tiles(sb, X, head, rank, nxt, s + 1, -1);
        }
        mbar_wait(sb + R_BAR + (RB_GO + X * 2 + (s & 1)) * 8, (s >> 1) & 1);
        if (elect()) asm volatile("cp.async.bulk.wait_group.read 0;" ::: "memory");
        __syncwarp();
        const uint32_t os = sb + R_OS + X * 4096 + (lane >> 4) * 1024 + (lane & 15) * 16;
        if (mt) xattn<1>(so + lane * 16, so + lane * 8, os, g, c); else xattn<0>(so + lane * 16, so + lane * 8, os, g, c);
        fence_async_smem();
        __syncwarp();
        const uint32_t svb = sb + R_BAR + (RB_SV + X * 2 + (s & 1)) * 8;
        if (elect()) {
            mbar_arrive(svb); mbar_arrive_cluster(svb + dp);
            const uint64_t pol = POL_SOON;
#pragma unroll
            for (int kb = 0; kb < 2; kb++)
                asm volatile("cp.async.bulk.global.shared::cta.bulk_group.L2::cache_hint [%0],[%1],%2,%3;" ::"l"(g_o + ((X * 32 + (s >> 1)) * 64 + head * 2 + kb) * 512 + ((s & 1) * 4 + mt * 2) * 64),
                             "r"(sb + R_OS + X * 4096 + kb * 2048), "r"(2048), "l"(pol) : "memory");
            asm volatile("cp.async.bulk.commit_group;" ::: "memory");
        }
        __syncwarp();
        if (s & 1) {
            if (elect()) { asm volatile("cp.async.bulk.wait_group 0;" ::: "memory"); red_relaxed(cnt_ptr(C_O + (X * 32 + (s >> 1)) * 4 + (head >> 3)), 1); }
            __syncwarp();
        }
        rec_tiles(sb, X, head, rank, nxt, min(s + 1, 63), s + 1);
        mbar_wait(svb, (s >> 1) & 1);
        rec_tiles(sb, X, head, rank, nxt, min(s + 2, 63), -1);
    }
}

__device__ __forceinline__ uint32_t timed_clear(unsigned* r, int lane) {
    uint32_t v = 0;
    const uint32_t t0 = clk32();
    asm volatile("{.reg .pred p; setp.eq.u32 p,%2,0; @p atom.relaxed.gpu.global.exch.b32 %0,[%1],0;}" : "+r"(v) : "l"(r), "r"(lane) : "memory");
    v = __shfl_sync(0xffffffffu, v, 0);
    asm volatile("{.reg .pred p; setp.eq.u32 p,%0,0x5a5a5a5b; @p nanosleep.u32 1;}" ::"r"(v) : "memory");
    return clk32() - t0;
}
__device__ __forceinline__ void rec_slots(int me, int w) {
    const int lane = threadIdx.x & 31;
    uint4* r = xregion(w & 1, (w & 2) ? 64 + (me & 1) : me) + ((w & 2) ? (me >> 1) * 8 : 0);
#pragma unroll 1
    for (int i = lane; i < ((w & 2) ? 8 : 256); i += 32) r[i] = r[i + 256] = make_uint4(0, 0, 0, 0);
    __syncwarp();
    uint32_t b0 = ~0u, b1 = ~0u;
#pragma unroll 1
    for (int i = 0; i < NPRB; i++) { b0 = min(b0, timed_clear((unsigned*)r, lane)); b1 = min(b1, timed_clear((unsigned*)(r + 256), lane)); }
    if (lane == 0) ((uint8_t*)g_sel)[me * 4 + w] = (b1 < b0) << w;
}

__device__ __forceinline__ void rec_init(uint32_t sb) {
    const uint32_t b = sb + R_BAR;
    const int i = threadIdx.x & 31;
    mbar_init(b + i * 8, i >= RB_SV ? 2 : 1);
    if (i == RB_INIT) mbar_expect(b + RB_INIT * 8, 196608);
    asm volatile("fence.mbarrier_init.release.cluster;" ::: "memory");
}
constexpr int G_BAR = B_BAR;
enum { GB_FULL = 0  , GB_EMPTY = 8  , GB_RS = 16, GB_SS = 17, GB_LAG = 18, GB_FREE = 19, GB_DONE = 20  , GB_N = 24 };
constexpr int Q_PRE = 8;
constexpr int NQRS = 2 * NQ - 64;
__device__ __forceinline__ void gemm_init(uint32_t sb, bool op) {
    const int i = threadIdx.x & 31;
    if (i < GB_N) mbar_init(sb + G_BAR + i * 8, i >= GB_DONE ? 4 : i == GB_FREE ? 8 : (i >= GB_EMPTY && i < GB_RS) ? 2 : 1);
    if (i == GB_RS) mbar_expect(sb + G_BAR + i * 8, op ? 131072 : 98304);
    if (i == GB_SS) mbar_expect(sb + G_BAR + i * 8, op ? 131072 : 163840);
    asm volatile("fence.mbarrier_init.release.cluster;" ::: "memory");
}
__device__ __forceinline__ int qkv_blk(int id, int j) { return NQRS * 4 + id * 10 + j; }
__device__ __forceinline__ void qkv_fetch(const Params& p, uint32_t sb, int id, int j0, int j1) {
#pragma unroll 1
    for (int j = j0 * 2; j < j1 * 2; j++) {
        const int blk = min(qkv_blk(id, j >> 1), 511);
        tma2d(sb + j * 8192, &p.tn[blk >> 8], (blk & 255) * 16, (j & 1) * 256, sb + G_BAR + GB_SS * 8);
    }
}
__device__ __forceinline__ void qkv_stage(const Params& p, uint32_t dst, uint32_t bar, int id, int k0, int nk) {
#pragma unroll 1
    for (int j = 0; j < 2 * nk; j++) {
        const int u = id * 2 + (j >= nk);
        tma2d(dst + j * 8192, &p.tm[u < 64 ? 2 : 0], (u & 63) * 64, (k0 + (j >= nk ? j - nk : j)) * 64, bar);
    }
}
__device__ __forceinline__ void op_fetch(const Params& p, uint32_t sb, int id, int half) {
#pragma unroll 1
    for (int j = 0; j < 16; j++) tma2d(sb + j * 8192, &p.tm[4], ((id * 2 + (j >> 3)) & 7) * 64, (id >> 2) * 1024 + (j & 7) * 128 + half * 64, sb + G_BAR + (GB_RS + half) * 8);
}
template <bool OP>
__device__ __forceinline__ void gemm_producer(const Params& p, uint32_t sb, int id) {
    constexpr int NS = OP ? 6 : 8, SB = OP ? 16384 : 8192, RB = OP ? 131072 : 163840;
    if (!elect()) return;
    mbar_wait(sb + G_BAR + GB_FREE * 8, 0);
    if (OP) op_fetch(p, sb, id, 1);
    else {
        mbar_expect(sb + G_BAR + GB_RS * 8, 32768);
        qkv_stage(p, sb + 196608, sb + G_BAR + GB_RS * 8, id, 6, 2);
        qkv_fetch(p, sb, id, Q_PRE, 10);
        mbar_wait(sb + G_BAR + GB_FREE * 8, 1);
    }
    wait_cnt(g_gate, lds32(sb + S_GATE));
    int st = 0; uint32_t ph = 1;
#pragma unroll 1
    for (int n = 0; n < p.nl[OP]; n++) {
        const int e = p.list[OP][n];
        wait_cnt(OP ? cnt_ptr(C_O + e * 4 + (id >> 2)) : cnt_ptr(C_XN + e), 16);
        PROF(true, 1024 + n * 4);
        const uint4* src = OP ? g_o + (e * 64 + (id >> 2) * 16) * 512 : g_xn + e * 4096;
#pragma unroll 1
        for (int s = 0; s < 8; s++) {
            mbar_wait(sb + G_BAR + (GB_EMPTY + st) * 8, ph);
            mbar_expect(sb + G_BAR + (GB_FULL + st) * 8, SB);
            bulk_g2s(sb + RB + st * SB, src + s * (SB / 16), SB, sb + G_BAR + (GB_FULL + st) * 8, POL_N);
            if (++st == NS) { st = 0; ph ^= 1; }
        }
    }
}
__device__ __forceinline__ void qkv_release(const Params& p, uint32_t sb) {
    if (!elect()) return;
#pragma unroll 1
    for (int n = 0; n < 2 * p.nl[0]; n++) {
        const int e = p.list[0][n >> 1];
        mbar_wait(sb + G_BAR + (GB_DONE + (n & 3)) * 8, (n >> 2) & 1);
        red_release(cnt_ptr(C_QKV + e), 1);
        PROF(n & 1, 1024 + (n >> 1) * 4 + 3);
    }
}
__device__ __forceinline__ void op_permute(uint32_t sb) {
#pragma unroll 2
    for (int i = threadIdx.x; i < 4096; i += 256) {
        const uint32_t a = sb + i * 32 + ((i >> 2) & 1) * 16, b = a ^ 16;
        const uint4 x = lds128(a), y = lds128(b);
        sts128(a, __byte_perm(x.x, x.y, 0x5410), __byte_perm(x.z, x.w, 0x5410), __byte_perm(y.x, y.y, 0x5410), __byte_perm(y.z, y.w, 0x5410));
        sts128(b, __byte_perm(x.x, x.y, 0x7632), __byte_perm(x.z, x.w, 0x7632), __byte_perm(y.x, y.y, 0x7632), __byte_perm(y.z, y.w, 0x7632));
    }
    fence_async_smem();
    bar_sync(1, 256);
}
template <bool OP>
__device__ __forceinline__ void gemm_consumer(const Params& p, uint32_t sb, int id, int w) {
    constexpr int NS = OP ? 6 : 8, SB = OP ? 16384 : 8192, RB = OP ? 131072 : 163840;
    const int lane = threadIdx.x & 31, wg = w >> 2, t = w & 3, u = id * 2 + wg;
    uint32_t a[128];
    mbar_wait(sb + G_BAR + GB_RS * 8, 0);
    PROF2(threadIdx.x == 0, 3501);
    if (OP) op_permute(sb);
    const uint32_t wo = sb + (((lane >> 4) << 3) + (lane & 7)) * 128 + (((2 * t + ((lane >> 3) & 1)) ^ (lane & 7)) << 4);
#pragma unroll
    for (int ks = 0; ks < 32; ks++) {
        const uint4 v = ldsm4t(wo + ks * 2048 + (OP ? wg * 65536 : ks < 24 ? 131072 + wg * 49152 : 196608 - 49152 + wg * 16384));
        a[ks * 4] = v.x; a[ks * 4 + 1] = v.y; a[ks * 4 + 2] = v.z; a[ks * 4 + 3] = v.w;
        if (ks == 31 || (!OP && ks == 23)) {
            fence_async_smem();
            __syncwarp();
            if (lane == 0) mbar_arrive(sb + G_BAR + GB_FREE * 8);
            if (ks == 23) mbar_wait(sb + G_BAR + GB_RS * 8, 1);
        }
    }
    PROF2(threadIdx.x == 0, 3502);
    mbar_wait(sb + G_BAR + GB_SS * 8, 0);
    if (OP) op_permute(sb);
    PROF2(threadIdx.x == 0, 3503);
    const uint32_t tag = OP ? lds32(sb + S_TAG) : 0;
    float c0[32], c1[OP ? 32 : 40];
    int st = 0; uint32_t ph = 0;
    const bool el = (threadIdx.x & 127) == 0;
#pragma unroll 1
    for (int n = 0; n < p.nl[OP]; n++) {
        int prev = 0;
        const uint32_t wb = sb + wg * (OP ? 65536 : 81920) + (n & p.zero);
        const uint64_t dw = OP ? mkdesc(wb, 0, 1024, 1) : mkdesc(wb, 16384, 256, 3);
        if (!OP && wg) mbar_wait(sb + G_BAR + GB_LAG * 8, n & 1);
#pragma unroll
        for (int s = 0; s < 8; s++) {
            mbar_wait(sb + G_BAR + (GB_FULL + st) * 8, ph);
            const uint64_t dx = mkdesc(sb + RB + st * SB, 128, 1024, 0);
            wg_fence();
#pragma unroll
            for (int kk = 0; kk < 4; kk++) {
                const int ks = s * 4 + kk;
                if (ks == 0) { wgmma64_rs<0>(c0, a, dx); if (OP) wgmma64_ta<0>(c1, dw, dx + 512); else wgmma80_tb<0>(c1, dx, dw); }
                else { wgmma64_rs<1>(c0, a + ks * 4, dx + kk * 16); if (OP) wgmma64_ta<1>(c1, dw + ks * 128, dx + 512 + kk * 16); else wgmma80_tb<1>(c1, dx + kk * 16, dw + ks * 32); }
            }
            wg_commit();
            if (s) {
                wg_wait<1>();
                if (el) { mbar_arrive(sb + G_BAR + (GB_EMPTY + prev) * 8); if (!OP && s == QLAG && !wg) mbar_arrive(sb + G_BAR + GB_LAG * 8); }
            }
            prev = st;
            if (++st == NS) { st = 0; ph ^= 1; }
        }
        const int e = p.list[OP][n];
        wg_wait<0>();
        if (el) mbar_arrive(sb + G_BAR + (GB_EMPTY + prev) * 8);
        PROF(threadIdx.x == 128, 1024 + n * 4 + 1);
        if (OP) {
            uint4* dst = g_pp + (e * 4 + (id >> 2)) * 4096 + ((u & 7) * 32 + t * 8) * 16 + (lane >> 2) * 16 + (lane & 3);
#pragma unroll
            for (int j = 0; j < 4; j++) {
                const float* x = c0 + j * 8; const float* y = c1 + j * 8;
                st_rlx128(dst + j * 4, (pack2(x[0] + y[0], x[1] + y[1]) & ~1u) | tag, pack2(x[2] + y[2], x[3] + y[3]), (pack2(x[4] + y[4], x[5] + y[5]) & ~1u) | tag, pack2(x[6] + y[6], x[7] + y[7]));
            }
            if (lane == 0) red_relaxed(cnt_ptr(C_PP + e * 8 + (u & 7)), 1);
            PROF(threadIdx.x == 128, 1024 + n * 4 + 3);
        } else {
            uint4* dst = g_qkv + (size_t)e * 2 * 32 * 1536 + lane;
            const uint64_t pol = POL_SOON;
#pragma unroll
            for (int j = 0; j < 4; j++) {
                const float* x = c0 + j * 8;
                uint4 v = make_uint4(pack2(x[0], x[1]), pack2(x[2], x[3]), pack2(x[4], x[5]), pack2(x[6], x[7]));
                if (u >= 64) v = make_uint4(movm(v.x), movm(v.z), movm(v.y), movm(v.w));
                stg128(dst + (((j >> 1) * 32 + ((u & 63) >> 1)) * 1536 + (u < 64 ? 1024 : 0) + (j & 1) * 256 + ((u & 1) * 4 + t) * 32), v, pol);
            }
#pragma unroll
            for (int j = 0; j < 5; j++) {
                const float* x = c1 + (OP ? 0 : j * 8);
                const int blk = qkv_blk(id, wg * 5 + j);
                if (blk < 512) stg128(dst + (((t >> 1) * 32 + ((blk >> 3) & 31)) * 1536 + (blk >> 8) * 512 + (t & 1) * 256 + (blk & 7) * 32),
                                      make_uint4(pack2(x[0], x[1]), pack2(x[2], x[3]), pack2(x[4], x[5]), pack2(x[6], x[7])), pol);
            }
        }
        __syncwarp();
        if (!OP && lane == 0) mbar_arrive(sb + G_BAR + (GB_DONE + (n & 1) * 2 + wg) * 8);
        PROF(threadIdx.x == 128, 1024 + n * 4 + 2);
    }
}

template <int NP, bool MMA>
__device__ __forceinline__ void sum_partials(float* x, const uint2* src, const uint32_t* r0, const uint32_t* r1, uint32_t idm, uint32_t tag, bool on) {
    uint2 v[4][NP];
    int n = 0;
    while (true) {
        uint32_t bad = 0;
#pragma unroll
        for (int s = 0; s < 4; s++)
#pragma unroll
            for (int i = 0; i < NP; i++)
                asm volatile("{.reg .pred p; .reg .b64 t; setp.ne.u32 p,%4,0; mov.b64 t,0; @p ld.relaxed.gpu.global.L2::cache_hint.b64 t,[%2],%3; mov.b64 {%0,%1},t;}"
                             : "=r"(v[s][i].x), "=r"(v[s][i].y) : "l"(src + s * 8192 + i * 32), "l"(POL_LAST), "r"((uint32_t)on) : "memory");
#pragma unroll
        for (int s = 0; s < 4; s++) bad = or3(bad, mism(v[s][0].x, v[s][1].x, tag), mism(v[s][NP - 2].x, v[s][NP - 1].x, tag));
        if (!__any_sync(0xffffffffu, (bad & 1) && on)) break;
        if (++n > 2000000) __trap();
    }
#pragma unroll
    for (int i = 0; i < NP; i++) {
        uint32_t a, b;
        if (MMA) {
            float t[4] = {0, 0, 0, 0};
            mma16(t, v[0][i].x, v[0][i].y, v[1][i].x, v[1][i].y, idm, idm); mma16(t, v[2][i].x, v[2][i].y, v[3][i].x, v[3][i].y, idm, idm);
            a = pack2(t[0], t[2]); b = pack2(t[1], t[3]);
        } else {
            a = pack2((blo(v[0][i].x) + blo(v[1][i].x)) + (blo(v[2][i].x) + blo(v[3][i].x)), (blo(v[0][i].y) + blo(v[1][i].y)) + (blo(v[2][i].y) + blo(v[3][i].y)));
            b = pack2((bhi(v[0][i].x) + bhi(v[1][i].x)) + (bhi(v[2][i].x) + bhi(v[3][i].x)), (bhi(v[0][i].y) + bhi(v[1][i].y)) + (bhi(v[2][i].y) + bhi(v[3][i].y)));
        }
        const uint32_t s0 = hadd2(a, r0[i]), s1 = hadd2(b, r1[i]);
        x[4 * i] = blo(s0); x[4 * i + 2] = bhi(s0); x[4 * i + 1] = blo(s1); x[4 * i + 3] = bhi(s1);
    }
}
__device__ __forceinline__ const uint2* pp_src(int e, int tile, int lane) { return (const uint2*)g_pp + e * 32768 + tile * 128 + (lane >> 3) * 8 + (lane & 3) * 2 + ((lane >> 2) & 1); }

__device__ __forceinline__ void fin_warp(const Params& p, uint32_t sb, int id) {
    const int grp = (id & ~3) + (threadIdx.x & 3), tp = (id & 3) * 8 + ((threadIdx.x & 31) >> 2);
    wait_slow_warp(g_gate, lds32(sb + S_GATE));
#pragma unroll 1
    for (int e = 32; e < 64; e++) {
        wait_slow_warp(cnt_ptr(C_XN + e), 16);
        const uint4 r = ldcg128(g_x + ((128 + grp) * XP + (e - 32) * 32 + tp));
        if (e < 63) wait_slow_warp(cnt_ptr(C_PP + e * 8 + (id >> 4)), 16); else wait_slow_warp(cnt_ptr(C_O + 63 * 4), 16);
        wait_flag_warp(cnt_ptr(C_PP + e * 8 + (id >> 4)), 16);
        const uint32_t a[2] = {r.x, r.y}, b[2] = {r.z, r.w};
        float x[8];
        sum_partials<2, false>(x, pp_src(e, 0, tp) + grp * 64, a, b, 0, lds32(sb + S_TAG), true);
        uint2* dst = (uint2*)p.out + ((e - 32) * 64 + tp * 2) * 128 + grp;
#pragma unroll
        for (int t = 0; t < 2; t++)
            dst[t * 128] = make_uint2(__byte_perm(__float_as_uint(x[t]), __float_as_uint(x[2 + t]), 0x7632), __byte_perm(__float_as_uint(x[4 + t]), __float_as_uint(x[6 + t]), 0x7632));
        PROF((threadIdx.x & 31) == 0, 1536 + e);
    }
}

constexpr int PROW = 272, UROW = 2560, UPRE = 512;
constexpr int C_UR = 0  , C_TB = 65536  , C_BG = C_TB + 51200,
              CB_M = 7168, CB_U = CB_M + 1792, CB_BIG = CB_U + 2048, C_ST = C_BG + 8 * CB_BIG  ;
static_assert(C_ST + 4736 <= B_BAR, "smem map");
enum { CB_TB = 0, CB_UF = 1  , CB_CF = 5  , CB_LD = 9   };
__device__ __forceinline__ void conv_init(uint32_t sb, bool spare) {
    const int i = threadIdx.x & 31;
    mbar_init(sb + B_BAR + i * 8, (i >= CB_UF && i < CB_CF && !spare) ? 2 : 1);
    if (i == CB_TB && !spare) mbar_expect(sb + B_BAR + i * 8, 51200);
    asm volatile("fence.mbarrier_init.release.cluster;" ::: "memory");
}
__device__ __forceinline__ void mma_q(float* c, const uint32_t* a, const uint4& q) {
    mma16(c, a[0], a[1], a[2], a[3], q.x, q.y); mma16(c, a[4], a[5], a[6], a[7], q.z, q.w);
}
__device__ __forceinline__ uint2 ld_acc(const uint2* p, bool on) {
    uint2 v = make_uint2(0, 0);
    asm volatile("{.reg .pred p; setp.ne.u32 p,%3,0; @p ld.global.cg.v2.u32 {%0,%1},[%2];}" : "+r"(v.x), "+r"(v.y) : "l"(p), "r"((uint32_t)on) : "memory");
    return v;
}
__device__ __forceinline__ void add_acc(float* c, uint2 v) { c[0] += blo(v.x); c[1] += bhi(v.x); c[2] += blo(v.y); c[3] += bhi(v.y); }
__device__ __forceinline__ void st_acc(uint2* p, const float* c) { *p = make_uint2(pack2(c[0], c[1]), pack2(c[2], c[3])); }
__device__ __forceinline__ float sum8(const uint4* v, int k) {
#define VK(i) __uint_as_float(k == 0 ? v[i].x : k == 1 ? v[i].y : k == 2 ? v[i].z : v[i].w)
    return ((VK(0) + VK(1)) + (VK(2) + VK(3))) + ((VK(4) + VK(5)) + (VK(6) + VK(7)));
}
template <int XW>
__device__ __forceinline__ void stats_send(uint32_t l16, const float* x, uint4* gs, int q, int w) {
    float s0 = 0, s1 = 0, m0 = 0, m1 = 0;
#pragma unroll
    for (int i = 0; i < 8; i++) { s0 += x[2 * i]; s1 += x[2 * i + 1]; m0 = fmaf(x[2 * i], x[2 * i], m0); m1 = fmaf(x[2 * i + 1], x[2 * i + 1], m1); }
    sts128(l16 + C_ST + w * 512, __float_as_uint(s0), __float_as_uint(m0), __float_as_uint(s1), __float_as_uint(m1));
    if (w == XW) {
        bar_sync(2, 256);
        uint4 v[8];
#pragma unroll
        for (int i = 0; i < 8; i++) v[i] = lds128(l16 + C_ST + i * 512);
        st_rlx128(gs + q * 32, __float_as_uint(sum8(v, 0)), __float_as_uint(sum8(v, 1)) & 0x7fffffffu, __float_as_uint(sum8(v, 2)), __float_as_uint(sum8(v, 3)));
    } else bar_arrive(2, 256);
}
template <int XW>
__device__ __forceinline__ float4 stats_recv(uint32_t l16, const uint4* gs, int w) {
    if (w == XW) {
        uint4 v[8];
        int n = 0;
        while (true) {
            uint32_t bad = 0;
#pragma unroll
            for (int i = 0; i < 8; i++) v[i] = ld_rlx128(gs + i * 32);
#pragma unroll
            for (int i = 0; i < 8; i++) bad |= v[i].y;
            if (!__any_sync(0xffffffffu, bad >> 31)) break;
            if (++n > 2000000) __trap();
        }
        const float s0 = sum8(v, 0) * (1.f / 512.f), s1 = sum8(v, 2) * (1.f / 512.f);
        const float2 l0 = ln_finish(s0, fmaxf(fmaf(sum8(v, 1), 1.f / 512.f, -s0 * s0), 0.f)), l1 = ln_finish(s1, fmaxf(fmaf(sum8(v, 3), 1.f / 512.f, -s1 * s1), 0.f));
        sts128(l16 + C_ST + 4096, __float_as_uint(l0.x), __float_as_uint(rcp(l0.y)), __float_as_uint(l1.x), __float_as_uint(rcp(l1.y)));
    }
    bar_sync(3, 256);
    const uint4 r = lds128(l16 + C_ST + 4096);
    return make_float4(__uint_as_float(r.x), __uint_as_float(r.y), __uint_as_float(r.z), __uint_as_float(r.w));
}

__device__ __forceinline__ void conv_near(float (*acc)[4], uint32_t ta, uint32_t qa) {
    uint32_t a[9][8];
    uint4 x[9];
#pragma unroll
    for (int k = 0; k < 9; k++) {
        if (k < 8) {
            x[k] = ldsm4(qa + k * 1024);
#pragma unroll
            for (int j = 0; j < 8; j++) a[k][j] = lds32(ta + k * 800 + j * 32);
        }
        if (k) mma_q(acc[k - 1], a[k - 1], x[k - 1]);
        PIN(13);
    }
}
template <int K0>
__device__ __forceinline__ void conv_pair(float (*acc)[4], float (*pend)[4], uint32_t ta, uint32_t q0, uint32_t q1, uint32_t q2) {
    uint32_t a[9][8];
    uint4 x[9], y[5];
#pragma unroll
    for (int n = 0; n < 9; n++) {
        if (n < 8) {
            const int k = K0 + (n >> 1);
            if (!(n & 1)) y[n >> 1] = ldsm4(q1 + k * 1024);
            x[n] = ldsm4(((n & 1) ? q0 : q2) + k * 1024);
#pragma unroll
            for (int j = 0; j < 8; j++) a[n][j] = lds32(ta + 256 + (n & 1) * 256 + k * 800 + j * 32);
        }
        if (n == 0) {
#pragma unroll
            for (int i = 0; i < 16; i++) { acc[4 - K0 + (i >> 2)][i & 3] += pend[i >> 2][i & 3]; pend[i >> 2][i & 3] = 0; }
        } else {
            const int m = n - 1, i = m >> 1;
            mma_q(acc[K0 + i], a[m], (m & 1) ? x[m] : y[i]); mma_q(pend[i], a[m], (m & 1) ? y[i] : x[m]);
        }
        PIN(13);
    }
}

__device__ __forceinline__ void conv_tile(const Params& p, uint32_t sb, int q, int w) {
    const int lane = __shfl_sync(0xffffffffu, threadIdx.x & 31, threadIdx.x & 31), g = lane >> 2, c = lane & 3, tile = q * 8 + w;
    const uint32_t l16 = sb + lane * 16;
#pragma unroll
    for (int i = 0; i < 16; i++) sts128(l16 + C_UR + w * 8192 + i * 512, 0, 0, 0, 0);
    wait_slow_warp(g_gate, lds32(sb + S_GATE));
    if (lane < 8) bulk_g2s(sb + C_TB + (w * 8 + lane) * 800, g_P + (tile * 8 + lane) * PROW + 72, 800, sb + B_BAR + CB_TB * 8, POL_N);
    uint32_t A[8][8];
#pragma unroll
    for (int k = 0; k < 8; k++)
#pragma unroll
        for (int j = 0; j < 8; j++) A[k][j] = __ldcg(g_P + (tile * 8 + k) * PROW + 16 + 8 * j + g - 2 * c);
    if (lane == 0) { const uint4 d = __ldg((const uint4*)p.Dskip + tile); sts128(sb + C_ST + 4608 + w * 16, d.x, d.y, d.z, d.w); }
    float acc[8][4], pend[4][4];
#pragma unroll
    for (int k = 0; k < 8; k++) acc[k][0] = acc[k][1] = acc[k][2] = acc[k][3] = pend[k & 3][k >> 2] = pend[k & 3][2 + (k >> 2)] = 0;
    const uint32_t row = sb + C_UR + w * 8192, ta = sb + C_TB + w * 6400 + (8 + g - 2 * c) * 4, qo = (lane & 7) * 16 - (lane >> 3) * 32;
    bar_sync(4, 384);
    mbar_wait(sb + B_BAR + CB_TB * 8, 0);
#pragma unroll 1
    for (int b = -2; b < 32; b++) {
        const int lz = lane + (b & p.zero);
        const bool on = b >= 0;
        uint4 r0 = make_uint4(0, 0, 0, 0), r1 = r0;
        asm volatile("{.reg .pred p; setp.ge.s32 p,%9,0; @p ld.global.cg.v4.u32 {%0,%1,%2,%3},[%8]; @p ld.global.cg.v4.u32 {%4,%5,%6,%7},[%8+%10];}"
                     : "+r"(r0.x), "+r"(r0.y), "+r"(r0.z), "+r"(r0.w), "+r"(r1.x), "+r"(r1.y), "+r"(r1.z), "+r"(r1.w) : "l"(g_x + (tile * 2 * XP + b * 32 + lz)), "r"(b), "n"(XP * 16) : "memory");
        const uint32_t q1 = row + ((qo + (b - 1) * 128) & 1023);
        if ((NTOP >> w) & 1) conv_near(acc, ta, q1);
        PROF2(threadIdx.x == 0 && on, 2048 + b * 8);
        const uint2* pps = pp_src(b, tile, lz);
        asm volatile("" : "+l"(pps));
        const uint32_t tag = lds32(sb + S_TAG);
        wait_flag_warp(cnt_ptr(C_PP + b * 8 + q), on ? 16 : 0);
        PROF2(threadIdx.x == 0 && on, 2048 + b * 8 + 1);
        float x[16];
        {
            const uint32_t a[4] = {r0.x, r0.y, r1.x, r1.y}, bb[4] = {r0.z, r0.w, r1.z, r1.w};
            sum_partials<4, true>(x, pps, a, bb, (2 * (lz & 3) == lz >> 2) ? 0x00003f80u : (2 * (lz & 3) + 1 == lz >> 2) ? 0x3f800000u : 0u, tag, on);
        }
        stats_send<0>(l16, x, g_st + (b + 2) * 256 + lz, q, w);
        {
            PROF2(threadIdx.x == 0 && on, 2048 + b * 8 + 2);
            if (on) mbar_wait(sb + B_BAR + (CB_CF + (w >> 1)) * 8, b & 1);
            const uint2* cb = g_carry + ((tile * 320 + b) * 32 + lz);
            uint2 cr[8];
#pragma unroll
            for (int k = 0; k < 8; k++) cr[k] = ld_acc(cb + k * 1280, b >= 4);
            if (NTOP != 255 && !((NTOP >> w) & 1) && b) conv_near(acc, ta, q1);
#pragma unroll
            for (int k = 0; k < 8; k++) add_acc(acc[k], cr[k]);
        }
        PIN(13);
        float4 ln = stats_recv<0>(l16, g_st + (b + 2) * 256 + lz, w);
        PROF2(threadIdx.x == 0 && on, 2048 + b * 8 + 3);
        uint32_t u[8];
#pragma unroll
        for (int k = 0; k < 8; k++) {
            u[k] = pack2(rbf(x[2 * k] - ln.x) * ln.y, rbf(x[2 * k + 1] - ln.z) * ln.w);
            sts32(row + k * 1024 + (b & 7) * 128 + lane * 4, u[k]);
        }
        __syncwarp();
        const uint32_t qa = row + ((qo + b * 128) & 1023);
        {
            uint4 xq[8];
#pragma unroll
            for (int k = 0; k < 4; k++) xq[k] = ldsm4(qa + k * 1024);
#pragma unroll
            for (int k = 0; k < 8; k += 2) {
                PIN(13);
                mma_q(acc[k], A[k], xq[k]); mma_q(acc[k + 1], A[k + 1], xq[k + 1]);
                if (k < 4) { xq[k + 4] = ldsm4(qa + (k + 4) * 1024); xq[k + 5] = ldsm4(qa + (k + 5) * 1024); }
            }
        }
        const uint4 dk = lds128(sb + C_ST + 4608 + w * 16);
#pragma unroll
        for (int k = 0; k < 8; k++) {
            const float t = __shfl_sync(0xffffffffu, acc[k][3], (lz & ~3) | ((lz - 1) & 3));
            const uint32_t y = movm(pack2(acc[k][0] + (c ? t : 0.f), acc[k][1] + acc[k][2]));
            acc[k][0] = c ? 0.f : t; acc[k][1] = acc[k][2] = acc[k][3] = 0;
            const uint32_t dw = k >> 1 == 0 ? dk.x : k >> 1 == 1 ? dk.y : k >> 1 == 2 ? dk.z : dk.w;
            const uint32_t s = hadd2(hadd2(y, hmul2(u[k], __byte_perm(dw, 0, (k & 1) ? 0x3232 : 0x1010))), __byte_perm(__float_as_uint(x[2 * k]), __float_as_uint(x[2 * k + 1]), 0x7632));
            x[2 * k] = blo(s); x[2 * k + 1] = bhi(s);
        }
        arrive_if(sb + B_BAR + (CB_UF + (w >> 1)) * 8, lz, b < -1 ? 32 : 0);
        stats_send<1>(l16, x, g_st + (36 + b) * 256 + lz, q, w);
        {
            PROF2(threadIdx.x == 0 && on, 2048 + b * 8 + 4);
            uint4* dst = g_x + ((128 + tile * 2) * XP + b * 32 + lz);
#pragma unroll
            for (int e = 0; e < 2; e++) {
                const float* y = x + e * 8;
                if (on) dst[e * XP] = make_uint4(__byte_perm(__float_as_uint(y[0]), __float_as_uint(y[2]), 0x7632), __byte_perm(__float_as_uint(y[4]), __float_as_uint(y[6]), 0x7632),
                                           __byte_perm(__float_as_uint(y[1]), __float_as_uint(y[3]), 0x7632), __byte_perm(__float_as_uint(y[5]), __float_as_uint(y[7]), 0x7632));
            }
            uint32_t* du = g_u + (tile * 8 * (UROW / 2) + UPRE / 2 + b * 32 + lz);
#pragma unroll
            for (int k = 0; k < 8; k++) if (on) du[k * (UROW / 2)] = u[k];
        }
#pragma unroll 1
        for (int pass = 0; pass < 2; pass++) {
            if (pass == ((PLATE >> w) & 1)) {
                const uint32_t q0 = row + ((qo + (b - 2) * 128) & 1023);
                if (b & 1) conv_pair<4>(acc, pend, ta, q0, q1, qa); else conv_pair<0>(acc, pend, ta, q0, q1, qa);
            }
            if (pass) break;
            ln = stats_recv<1>(l16, g_st + (36 + b) * 256 + lz, w);
            PROF2(threadIdx.x == 0 && on, 2048 + b * 8 + 5);
            uint32_t o[2][4];
#pragma unroll
            for (int e = 0; e < 2; e++) {
                const float mu = e ? ln.z : ln.x, rs = e ? ln.w : ln.y;
#pragma unroll
                for (int i = 0; i < 4; i++) o[e][i] = pack2(rbf(x[4 * i + e] - mu) * rs, rbf(x[4 * i + 2 + e] - mu) * rs);
            }
#pragma unroll
            for (int i = 0; i < 4; i++) {
                const uint32_t t = __shfl_xor_sync(0xffffffffu, (lz & 1) ? o[0][i] : o[1][i], 1);
                if (lz & 1) o[0][i] = t; else o[1][i] = t;
            }
            uint4* dst = g_xn + ((32 + b) * 4096 + q * 512 + (lz >> 2) * 64 + w * 8 + (lz & 2) * 2 + (lz & 1));
            if (on) { dst[0] = make_uint4(o[0][0], o[0][1], o[0][2], o[0][3]); dst[2] = make_uint4(o[1][0], o[1][1], o[1][2], o[1][3]); }
            if (w == 7) {
                bar_sync(5, 256);
                if (elect()) red_release(cnt_ptr(on ? C_XN + 32 + b : C_FAR + 8), 2);
                PROF(lane == 0 && on, 2048 + b * 8 + 6);
                __syncwarp();
            } else bar_arrive(5, 256);
        }
    }
}

template <int P0, bool TRI = false, int R0 = 0>
__device__ __forceinline__ void bg_half(float (*acc)[4], uint4* win, uint32_t ta, uint32_t qa, uint32_t mask, uint32_t row) {
#pragma unroll
    for (int i = 0; i < 4; i++) {
        win[P0 + i] = ldsm4(((qa + i * 128) & mask) + row);
        const uint4 a = lds128(ta + (3 - i) * 448), e = lds128(ta + (3 - i) * 448 + 224);
#pragma unroll
        for (int r = TRI ? 7 - P0 - i : R0; r < 8; r++) mma16(acc[r], a.x, a.y, a.z, a.w, win[(P0 + i + 1 + r) & 7].x, win[(P0 + i + 1 + r) & 7].y);
#pragma unroll
        for (int r = TRI ? 7 - P0 - i : R0; r < 8; r++) mma16(acc[r], e.x, e.y, e.z, e.w, win[(P0 + i + 1 + r) & 7].z, win[(P0 + i + 1 + r) & 7].w);
    }
}
__device__ __forceinline__ void bg_fetch(uint32_t sb, int q, int j, int n) {
    const int b0 = n >> 1, ch = q * 64 + j * 16 + (n & 1) * 8 + (b0 & 7), skip = max(12 - b0, 0);
    const uint32_t bar = sb + B_BAR + (CB_LD + j * 2 + (n & 1)) * 8, buf = sb + C_BG + (j * 2 + (n & 1)) * CB_BIG;
    if (elect()) {
        mbar_expect(bar, CB_BIG - skip * 128);
        bulk_g2s(buf, g_W + ch * 784, CB_M, bar, POL_N);
        bulk_g2s(buf + CB_M, g_W + (ch ^ 4) * 784, 1792, bar, POL_N);
        bulk_g2s(buf + CB_U + skip * 128, g_u + ch * (UROW / 2) + UPRE / 2 + (b0 - 20 + skip) * 32, 2048 - skip * 128, bar, POL_N);
    }
    __syncwarp();
}
__device__ __forceinline__ void conv_back(uint32_t sb, int q, int j) {
    const int lane = __shfl_sync(0xffffffffu, threadIdx.x & 31, threadIdx.x & 31), g = lane >> 2, c = lane & 3;
    wait_slow_warp(g_gate, lds32(sb + S_GATE));
    bg_fetch(sb, q, j, 0);
    bar_sync(4, 384);
    const uint32_t to = (6 + g - 2 * c) * 16, qo = (lane & 7) * 16 - (lane >> 3) * 32;
#pragma unroll 1
    for (int n = 0; n < 64; n++) {
        const int b0 = n >> 1, i = n & 1, chl = j * 16 + i * 8 + (b0 & 7);
        const uint32_t buf = sb + C_BG + (j * 2 + i) * CB_BIG, ta = buf + to;
        float acc[8][4];
        uint4 win[8];
        if (n < 63) bg_fetch(sb, q, j, n + 1);
        if (b0 >= 17 && b0 < 29 && (b0 < 21 || b0 >= 25) && i == 0) wait_flag_warp(cnt_ptr(C_FAR + (b0 >= 25) * 4 + ((b0 - 1) & 3)), 12);
        uint2* cr = g_carry + (((q * 64 + chl) * 40 + b0) * 32 + lane);
        uint2* cm = g_carry + (((q * 64 + (chl ^ 4)) * 40 + b0) * 32 + lane);
        uint2 pm[4], pf[8];
#pragma unroll
        for (int r = 0; r < 4; r++) pm[r] = ld_acc(cm + r * 32, b0 > 4);
#pragma unroll
        for (int r = 0; r < 8; r++) acc[r][0] = acc[r][1] = acc[r][2] = acc[r][3] = 0;
        mbar_wait(sb + B_BAR + (CB_LD + j * 2 + i) * 8, b0 & 1);
        if (b0 > 12) {
#pragma unroll
            for (int r = 1; r < 8; r++) win[(r + 4) & 7] = ldsm4(buf + CB_U + qo + r * 128);
        } else {
#pragma unroll
            for (int r = 1; r < 8; r++) win[(r + 4) & 7] = make_uint4(0, 0, 0, 0);
        }
        win[4] = make_uint4(0, 0, 0, 0);
#pragma unroll 1
        for (int h = b0 > 8 ? 4 : 2; h >= 2; h -= 2) {
            if (h == 2) {
                if (b0 > 4) bg_half<0>(acc, win, ta + 2 * 1792, qo + 12 * 128, ~0u, buf + CB_U);
                if (i == 0) mbar_wait(sb + B_BAR + (CB_UF + j) * 8, b0 & 1);
            }
            bg_half<4>(acc, win, ta + (h - 1) * 1792, qo + (h == 2 ? b0 - 4 : 8) * 128, h == 2 ? 1023u : ~0u, h == 2 ? sb + C_UR + chl * 1024 : buf + CB_U);
        }
        uint4 wm[8], a[9], e[9];
#pragma unroll
        for (int r = 1; r < 8; r++) wm[r] = ldsm4(sb + C_UR + (chl ^ 4) * 1024 + ((qo + (b0 + r) * 128) & 1023));
        a[7] = lds128(ta + 7 * 224); e[7] = lds128(ta + CB_M + 7 * 224);
#pragma unroll
        for (int r = 4; r < 8; r++) { st_acc(cr + r * 32, acc[r]); acc[r][0] = blo(pm[r - 4].x); acc[r][1] = bhi(pm[r - 4].x); acc[r][2] = blo(pm[r - 4].y); acc[r][3] = bhi(pm[r - 4].y); }
#pragma unroll
        for (int t = 7; t >= 0; t--) {
            if (t) { a[t - 1] = lds128(ta + (t - 1) * 224); e[t - 1] = lds128(ta + CB_M + (t - 1) * 224); }
            if (t == FT) {
                const uint2* f0 = g_far + (((q * 64 + chl) * 12 + b0 - 20) * 32 + lane);
                const uint2* f1 = g_far + (((q * 64 + (chl ^ 4)) * 12 + b0 - 20) * 32 + lane);
#pragma unroll
                for (int r = 0; r < 4; r++) { const bool on = (unsigned)(b0 + r - 20) < 12u; pf[r] = ld_acc(f0 + r * 32, on); pf[4 + r] = ld_acc(f1 + r * 32, on); }
            }
            PIN(14);
#pragma unroll
            for (int r = 0; r < 4; r++) { const uint4& x = win[4 + r - (t >> 1)]; mma16(acc[r], a[t].x, a[t].y, a[t].z, a[t].w, (t & 1) ? x.z : x.x, (t & 1) ? x.w : x.y); }
#pragma unroll
            for (int r = 0; r < 4; r++) { const uint4& x = wm[4 + r - (t >> 1)]; mma16(acc[4 + r], e[t].x, e[t].y, e[t].z, e[t].w, (t & 1) ? x.z : x.x, (t & 1) ? x.w : x.y); }
        }
#pragma unroll
        for (int r = 0; r < 4; r++) { add_acc(acc[r], pf[r]); add_acc(acc[4 + r], pf[4 + r]); st_acc(cr + r * 32, acc[r]); st_acc(cm + r * 32, acc[4 + r]); }
        __syncwarp();
        arrive_if(sb + B_BAR + (CB_CF + j) * 8, lane, i ? 0 : 32);
        PROF(j == 0 && lane == 0 && i, 2048 + b0 * 8 + 7);
    }
}
template <int PART>
__device__ __forceinline__ void conv_far(uint32_t sb, int w) {
    constexpr int NT = PART ? 5376 : 3584, NU = PART ? 1664 : 1152;
    const int lane = __shfl_sync(0xffffffffu, threadIdx.x & 31, threadIdx.x & 31), g = lane >> 2, c = lane & 3;
    wait_slow_warp(cnt_ptr(C_XN + (PART ? 43 : 39)), 16);
    const uint32_t to = (6 + g - 2 * c) * 16, qo = (lane & 7) * 16 - (lane >> 3) * 32;
#pragma unroll 1
    for (int n = -1; n < 44; n++) {
        const int t = n * 12 + w, tn = min(t + 12, 511), ch = (t & 127) * 4 + (((t >> 7) + 1) & 3), cn = (tn & 127) * 4 + (((tn >> 7) + 1) & 3);
        const uint32_t bar = sb + B_BAR + (w * 2 + (n & 1)) * 8, buf = sb + (w * 2 + (n & 1)) * 7168;
        if (n < 43 && elect()) {
            const uint32_t nb = sb + (w * 2 + (~n & 1)) * 7168;
            mbar_expect(bar ^ 8, NT + NU);
            bulk_g2s(nb, g_W + cn * 784 + 448, NT, bar ^ 8, POL_N);
            bulk_g2s(nb + 5376, g_u + cn * (UROW / 2) + UPRE / 2 - 32, NU, bar ^ 8, POL_N);
        }
        __syncwarp();
        if (n < 0) continue;
        mbar_wait(bar, (n >> 1) & 1);
        if (t >= 512) continue;
        float acc[8][4];
        uint4 win[8];
#pragma unroll
        for (int r = 0; r < 8; r++) acc[r][0] = acc[r][1] = acc[r][2] = acc[r][3] = 0;
        bg_half<0, true, PART * 4>(acc, win, buf + to + NT - 1792, qo + 128, ~0u, buf + 5376);
        bg_half<4, !PART, PART * 4>(acc, win, buf + to + NT - 3584, qo + 640, ~0u, buf + 5376);
        if (PART) bg_half<0, false, 4>(acc, win, buf + to, qo + 1152, ~0u, buf + 5376);
#pragma unroll
        for (int r = PART * 4; r < 8; r++) st_acc(g_far + (ch * 384 + lane) + (r + PART * 4) * 32, acc[r]);
        __syncwarp();
        if (((t + 12) ^ t) >= 128 && elect()) red_release(cnt_ptr(C_FAR + PART * 4 + (t >> 7)), 1);
        __syncwarp();
    }
    PROF(threadIdx.x == 0, 2048 + PART);
}

constexpr int P_X = 131072  , P_K6 = P_X + 32768  , P_P = P_K6 + 10496  , P_U = P_P + 33280  ,
              P_END = P_U + 17408, P_PRM = P_P + 8192  , P_Y = P_P  ;
static_assert(P_END <= B_BAR && P_END <= R_SEL, "prologue scratch");
#define KGUN 2
constexpr int KGU = KGUN;
__device__ __forceinline__ void csq(float& r, float& i) { const float t = r * i; r = fmaf(r, r, -(i * i)); i = t + t; }
__device__ __forceinline__ void cpow(float ar, float ph, float p, float& r, float& i) {
    const float e = ex2(ar * p);
    const float u = ph * p, n = fabsf(u) < 4194304.f ? (u + 12582912.f) - 12582912.f : u;
    const float t = (u - n) * 6.283185307179586f;
    r = e * __cosf(t); i = e * __sinf(t);
}
__device__ __forceinline__ void mma_tf32(float* c, float a0, float a1, float a2, float a3, float b0, float b1) {
    asm volatile("mma.sync.aligned.m16n8k8.row.col.f32.tf32.tf32.f32 {%0,%1,%2,%3},{%4,%5,%6,%7},{%8,%9},{%0,%1,%2,%3};"
                 : "+f"(c[0]), "+f"(c[1]), "+f"(c[2]), "+f"(c[3])
                 : "r"(__float_as_uint(a0)), "r"(__float_as_uint(a1)), "r"(__float_as_uint(a2)), "r"(__float_as_uint(a3)), "r"(__float_as_uint(b0)), "r"(__float_as_uint(b1)));
}

__device__ __forceinline__ void early_fetch(const Params& p, uint32_t sb) {
    const int v = blockIdx.x;
    if (elect()) {
        if (v >= V_QKV) { if (v < V_QKV + NQ && (p.roles & 8)) qkv_fetch(p, sb, v - V_QKV, 0, Q_PRE); }
        else if (v >= V_OP) { if (p.roles & 4) op_fetch(p, sb, v - V_OP, 0); }
        else if (REARLY && v >= V_REC && (p.roles & 2)) { rec_fetch(p, sb, (v - V_REC) >> 1, v & 1, 0, R_STQ); rec_fetch(p, sb, (v - V_REC) >> 1, v & 1, 2, R_STV); }
    }
    __syncwarp();
}
struct ProRegs { uint32_t v[2][4], ldt[2]; };
__device__ __forceinline__ void prologue_load(const ProArgs& a, int b, ProRegs& pr) {
    const int w = threadIdx.x >> 5;
#pragma unroll
    for (int i = 0; i < 2; i++) {
        const int gi = b * 512 + (w & 3) * 128 + ((w >> 2) & 1) * 64 + i * 32 + (threadIdx.x & 31);
        pr.ldt[i] = __ldg((const uint16_t*)a.ldt + b * 4 + (w & 3));
        pr.v[i][0] = __ldg((const uint16_t*)a.lAr + gi); pr.v[i][1] = __ldg((const uint16_t*)a.Ai + gi);
        pr.v[i][2] = __ldg((const uint16_t*)a.Cr + gi); pr.v[i][3] = __ldg((const uint16_t*)a.Ci + gi);
    }
}
__device__ __forceinline__ void prologue(const Params& p, uint32_t sb, int b, int w, const ProRegs& pr) {
    const ProArgs& a = p.pa;
    const int tid = threadIdx.x, lane = tid & 31, g = lane >> 2, c = lane & 3;
    const int d0 = b * 4;
    if (w >= 8) {
        const int t2 = tid - 256;
        if (w < 10) {
            const int row = b * 16 + (w - 8) * 8 + g;
            uint4 v[16];
            const float2 r = row_stats512(v, (const uint4*)(a.x + (size_t)row * 512) + c, 8, 4);
            const float2 l = ln_finish(r.x * (1.f / 512.f), r.y * (1.f / 512.f));
            if (c == (g >> 1)) asm volatile("st.relaxed.gpu.global.u32 [%0],%1;" ::"l"(g_ln0 + row), "r"(pack2(l.x, l.y)) : "memory");
            __syncwarp();
        } else if (PF0) {
            spin(PFD);
            if (elect()) {
#pragma unroll 1
                for (int i = w - 10; i < 4; i += 2) if ((PF0 >> i) & 1) asm volatile("cp.async.bulk.prefetch.L2.global [%0],%1;" ::"l"(a.W[i] + b * 16384), "r"(32768) : "memory");
            }
            __syncwarp();
        }
        if (b + 4 >= V_REC && b + 4 < V_OP) rec_slots(b + 4 - V_REC, (w & 3) ^ 2);
        PROF(t2 == 0, 3516);
        const int gi = b * 128 + t2;
        g_st[gi] = make_uint4(~0u, ~0u, ~0u, ~0u);
        if (gi < 1024) g_st[16384 + gi] = make_uint4(~0u, ~0u, ~0u, ~0u);
        if (gi < 912 * 8) g_cnt[gi] = 0;
        bar_sync(6, 384);
        if (lane < 4 && ((PFM >> (w - 8)) & 1)) asm volatile("cp.async.bulk.prefetch.L2.global [%0],%1;" ::"l"(a.W[w - 8] + (b * 4 + lane) * 4096), "r"(8192) : "memory");
        bar_sync(9, 384);
#pragma unroll 1
        for (int pass = 0; pass < 2; pass++) {
        if (w == 10 && pass == (b + 4 < EFS)) early_fetch(p, sb);
        if (pass) break;
#pragma unroll 2
        for (int i = t2; i < 4 * 784; i += 128) {
            const int ch = i / 784, k = i - ch * 784;
            const uint32_t o = sb + P_P + (ch * 2080 + 266 + (k / 14) * 18 + k) * 4;
            g_W[d0 * 784 + i] = make_uint4(lds32(o), lds32(o + 32), lds32(o + 64), lds32(o + 96));
        }
        bar_arrive(10, 384);
        }
        PROF(t2 == 0, 3517);
        return;
    }
#pragma unroll
    for (int i = 0; i < 2; i++) {
        const float dt = rbf(expf(blo(pr.ldt[i])));
        const float ar = -rbf(expf(blo(pr.v[i][0]))) * dt, ai = blo(pr.v[i][1]) * dt;
        sts128(sb + P_PRM + (w * 64 + i * 32 + lane) * 16, __float_as_uint(ar * 1.4426950408889634f), __float_as_uint(ai * 0.15915494309189535f),
               __float_as_uint(2.f * (blo(pr.v[i][2]) * dt)), __float_as_uint(2.f * (blo(pr.v[i][3]) * dt)));
    }
    if (tid < 64) sts128(sb + P_U + (tid >> 3) * 2176 + (tid & 7) * 16, 0, 0, 0, 0);
    bar_arrive(6, 384);
    __syncwarp();
    PROF(tid == 0, 3510);
    const int ch = w & 3, hf = w >> 2;
    {
        float k0[4] = {0, 0, 0, 0}, k1[4] = {0, 0, 0, 0}, k2[4] = {0, 0, 0, 0}, k3[4] = {0, 0, 0, 0}, k4[4] = {0, 0, 0, 0}, kl = 0;
#pragma unroll KGU
        for (int j = 0; j < 16; j++) {
            const uint4 q = lds128(sb + P_PRM + (w * 64 + j * 4 + c) * 16);
            const float cr = __uint_as_float(q.z), ci = __uint_as_float(q.w);
            float wr[4], wi[4], vr[4], vi[4];
            cpow(__uint_as_float(q.x), __uint_as_float(q.y), (float)g, wr[0], wi[0]);
            cpow(__uint_as_float(q.x), __uint_as_float(q.y), (float)(g + 8), vr[0], vi[0]);
#pragma unroll
            for (int i = 1; i < 4; i++) { wr[i] = wr[i - 1]; wi[i] = wi[i - 1]; csq(wr[i], wi[i]); vr[i] = vr[i - 1]; vi[i] = vi[i - 1]; csq(vr[i], vi[i]); }
            float hr = wr[3], hi = wi[3];
            csq(hr, hi);
            mma_tf32(k0, wr[0], vr[0], wi[0], vi[0], cr * hr - ci * hi, -(cr * hi + ci * hr));
            hr = vr[3]; hi = vi[3]; csq(hr, hi);
            mma_tf32(k1, wr[0], vr[0], wi[0], vi[0], cr * hr - ci * hi, -(cr * hi + ci * hr));
            csq(hr, hi);
            mma_tf32(k2, wr[1], vr[1], wi[1], vi[1], cr * hr - ci * hi, -(cr * hi + ci * hr));
            csq(hr, hi);
            mma_tf32(k3, wr[2], vr[2], wi[2], vi[2], cr * hr - ci * hi, -(cr * hi + ci * hr));
            csq(hr, hi);
            mma_tf32(k4, wr[3], vr[3], wi[3], vi[3], cr * hr - ci * hi, -(cr * hi + ci * hr));
            csq(hr, hi);
            kl += cr * hr - ci * hi;
        }
        kl += __shfl_xor_sync(0xffffffffu, kl, 1); kl += __shfl_xor_sync(0xffffffffu, kl, 2);
        const uint32_t o = sb + P_K6 + (ch * 656 + c * 32 + g) * 4, ol = sb + P_K6 + (ch * 656 + 640) * 4;
#define KST(k, base) sts32(o + (base) * 4, __float_as_uint(k[0])); sts32(o + (base) * 4 + 64, __float_as_uint(k[1])); \
                     sts32(o + (base) * 4 + 32, __float_as_uint(k[2])); sts32(o + (base) * 4 + 96, __float_as_uint(k[3]))
#define KAD(k, base) k[0] += __uint_as_float(lds32(o + (base) * 4)); k[1] += __uint_as_float(lds32(o + (base) * 4 + 64)); \
                     k[2] += __uint_as_float(lds32(o + (base) * 4 + 32)); k[3] += __uint_as_float(lds32(o + (base) * 4 + 96))
        if (hf == 0) {
            bar_sync(2 + ch, 64);
            KAD(k0, 0); KAD(k1, 128); KAD(k2, 256); KAD(k3, 384); KAD(k4, 512);
            kl += __uint_as_float(lds32(ol));
            __syncwarp();
        }
        KST(k0, 0); KST(k1, 128); KST(k2, 256); KST(k3, 384); KST(k4, 512);
        if (lane == 0) sts32(ol, __float_as_uint(kl));
        if (hf == 1) { __syncwarp(); bar_arrive(2 + ch, 64); }
    }
    PROF(tid == 0, 3511);
    {
        uint4 l0, l1;
        int n = 0;
        while (true) {
            l0 = ld_rlx128((const uint4*)g_ln0 + tid * 2); l1 = ld_rlx128((const uint4*)g_ln0 + tid * 2 + 1);
            if (__all_sync(0xffffffffu, l0.x && l0.y && l0.z && l0.w && l1.x && l1.y && l1.z && l1.w)) break;
            if (++n > 2000000) __trap();
        }
        sts128(sb + P_P + tid * 32, l0.x, l0.y, l0.z, l0.w); sts128(sb + P_P + tid * 32 + 16, l1.x, l1.y, l1.z, l1.w);
        bar_sync(8, 384);
        mbar_wait(sb + S_XBAR, 0);
        __syncwarp();
#pragma unroll 2
        for (int i = 0; i < 8; i++) {
            const int t = w * 256 + i * 32 + lane;
            const uint32_t ln = lds32(sb + P_P + t * 4);
            const uint2 x = lds64(sb + P_X + t * 16 + (b & 1) * 8);
            const float m = blo(ln), rs = rcp(bhi(ln));
            const uint32_t u0 = pack2(rbf(blo(x.x) - m) * rs, rbf(bhi(x.x) - m) * rs), u1 = pack2(rbf(blo(x.y) - m) * rs, rbf(bhi(x.y) - m) * rs);
            sts128(sb + P_X + t * 16, x.x, x.y, u0, u1);
            const uint32_t o = sb + P_U + ((t >> 3) & 1) * 2176 + ((t >> 4) + 8) * 16 + (t & 7) * 2;
            asm volatile("st.shared.u16 [%0],%1;" ::"r"(o), "h"((uint16_t)u0) : "memory");
            asm volatile("st.shared.u16 [%0],%1;" ::"r"(o + 4352), "h"((uint16_t)(u0 >> 16)) : "memory");
            asm volatile("st.shared.u16 [%0],%1;" ::"r"(o + 8704), "h"((uint16_t)u1) : "memory");
            asm volatile("st.shared.u16 [%0],%1;" ::"r"(o + 13056), "h"((uint16_t)(u1 >> 16)) : "memory");
        }
    }
    bar_sync(1, 256);
    PROF(tid == 0, 3512);
    if (tid < 64) sts32(sb + P_P + ((tid >> 4) * 2080 + (tid & 15)) * 4, 0);
#pragma unroll 1
    for (int x = tid; x < 2048; x += 512) {
        uint32_t pw[2][4];
#pragma unroll
        for (int h = 0; h < 2; h++) {
            const int y = x + h * 256;
            const int i0 = y <= 256 ? y : 256 + (int)((pack2((float)y, 0.f) & 0xffff) - 0x4380);
            const int i1 = y <= 256 ? max(y - 1, 0) : 256 + (int)((pack2((float)(y - 1), 0.f) & 0xffff) - 0x4380);
#pragma unroll
            for (int k = 0; k < 4; k++) {
                const float lo = __uint_as_float(lds32(sb + P_K6 + k * 2624 + i0 * 4)), hi = __uint_as_float(lds32(sb + P_K6 + k * 2624 + i1 * 4));
                pw[h][k] = pack2(lo, y ? hi : 0.f);
            }
        }
#pragma unroll
        for (int h = 0; h < 2; h++)
#pragma unroll
            for (int k = 0; k < 4; k++) sts32(sb + P_P + (k * 2080 + x + h * 256 + 16) * 4, pw[h][k]);
    }
    fence_async_smem();
    bar_arrive(9, 384);
    bar_sync(1, 256);
    if (tid < 4) {
        asm volatile("cp.async.bulk.global.shared::cta.bulk_group [%0],[%1],%2;" ::"l"(g_P + (d0 + tid) * PROW), "r"(sb + P_P + tid * 8320), "r"(PROW * 4) : "memory");
        asm volatile("cp.async.bulk.commit_group;" ::: "memory");
    }
    __syncwarp();
    PROF(tid == 0, 3513);
    {
        float acc[16][4];
#pragma unroll
        for (int j = 0; j < 16; j++) acc[j][0] = acc[j][1] = acc[j][2] = acc[j][3] = 0;
#pragma unroll 1
        for (int e = hf * 4; e < hf * 4 + 4; e++) {
            uint32_t B[16][2];
            const uint32_t ua = sb + P_U + ch * 4352 + ((lane >> 3) & 1) * 2176 + (8 + (lane >> 4) * 8 + (lane & 7) - e) * 16;
#pragma unroll
            for (int j = 0; j < 8; j++) { const uint4 v = ldsm4(ua + j * 256); B[2 * j][0] = v.x; B[2 * j][1] = v.y; B[2 * j + 1][0] = v.z; B[2 * j + 1][1] = v.w; }
            const uint32_t pa = sb + P_P + (ch * 2080 + 16 + e * 16 + g - 2 * c) * 4;
#pragma unroll
            for (int dd = 0; dd < 16; dd++) {
                const int d = (dd & 1) ? 15 - (dd >> 1) : dd >> 1;
                const uint32_t a0 = lds32(pa + d * 512), a1 = lds32(pa + d * 512 + 32), a2 = lds32(pa + d * 512 - 32), a3 = a0 + p.zero;
#pragma unroll
                for (int j = 0; j < 16; j++) if (j >= d) mma16(acc[j], a0, a1, a2, a3, B[(j - d) & 15][0], B[(j - d) & 15][1]);
            }
        }
        PROF(tid == 0, 3514);
        if (tid < 4) asm volatile("cp.async.bulk.wait_group 0;" ::: "memory");
        __syncwarp();
        bar_sync(10, 384);
#pragma unroll
        for (int j = 0; j < 8; j++) {
#pragma unroll
            for (int i = 0; i < 4; i++) { const float t = hf ? acc[j][i] : acc[j + 8][i]; acc[j][i] = hf ? acc[j + 8][i] : acc[j][i]; acc[j + 8][i] = t; }
            sts128(sb + P_Y + w * 4096 + j * 512 + lane * 16, __float_as_uint(acc[j + 8][0]), __float_as_uint(acc[j + 8][1]), __float_as_uint(acc[j + 8][2]), __float_as_uint(acc[j + 8][3]));
        }
        bar_sync(2 + ch, 64);
        uint32_t yp[16];
#pragma unroll
        for (int j = 0; j < 8; j++) {
            const uint4 t = lds128(sb + P_Y + (w ^ 4) * 4096 + j * 512 + lane * 16);
            yp[2 * j] = pack2(acc[j][0] + __uint_as_float(t.x), acc[j][1] + __uint_as_float(t.y)); yp[2 * j + 1] = pack2(acc[j][2] + __uint_as_float(t.z), acc[j][3] + __uint_as_float(t.w));
        }
#pragma unroll
        for (int j = 0; j < 4; j++)
            asm volatile("stmatrix.sync.aligned.m8n8.x4.trans.shared.b16 [%0],{%1,%2,%3,%4};" ::"r"(sb + P_Y + 32768 + ch * 4096 + hf * 2048 + j * 512 + (lane >> 4) * 256 + (lane & 7) * 32 + (lane & 8) * 2),
                         "r"(yp[4 * j]), "r"(yp[4 * j + 1]), "r"(yp[4 * j + 2]), "r"(yp[4 * j + 3]) : "memory");
    }
    const uint2 dk = __ldg((const uint2*)(a.Dk + d0));
    bar_sync(1, 256);
#pragma unroll 2
    for (int i = 0; i < 4; i++) {
        const int t = i * 256 + tid;
        const uint4 x0 = lds128(sb + P_X + t * 32), x1 = lds128(sb + P_X + t * 32 + 16);
        uint32_t y[4];
#pragma unroll
        for (int k = 0; k < 4; k++) y[k] = lds32(sb + P_Y + 32768 + k * 4096 + t * 4);
        g_x[b * XP + t] = make_uint4(hadd2(x0.x, hadd2(__byte_perm(y[0], y[1], 0x5410), hmul2(x0.z, dk.x))), hadd2(x0.y, hadd2(__byte_perm(y[2], y[3], 0x5410), hmul2(x0.w, dk.y))),
                                     hadd2(x1.x, hadd2(__byte_perm(y[0], y[1], 0x7632), hmul2(x1.z, dk.x))), hadd2(x1.y, hadd2(__byte_perm(y[2], y[3], 0x7632), hmul2(x1.w, dk.y))));
    }
    PROF(tid == 0, 3515);
}

__global__ void __cluster_dims__(2, 1, 1) __launch_bounds__(384, 1) main_kernel(const __grid_constant__ Params p) {
    extern __shared__ __align__(1024) uint8_t smem[];
    const uint32_t sb = smem_u32(smem);
    uint32_t rank; asm("mov.u32 %0,%%cluster_ctarank;" : "=r"(rank));
    const int wi = __shfl_sync(0xffffffffu, threadIdx.x >> 5, 0);
    const int v = blockIdx.x, cl = v >> 1, wg = wi >> 2;
    PROF(threadIdx.x == 0, 3500);
    ProRegs pr;
    prologue_load(p.pa, max((int)blockIdx.x - 4, 0), pr);
    if (wi == 11 && p.dopro && cl >= 2 && elect()) {
        mbar_init(sb + S_XBAR, 1);
        asm volatile("fence.mbarrier_init.release.cluster;" ::: "memory");
        mbar_expect(sb + S_XBAR, 32768);
        for (int j = 0; j < 8; j++) tma2d(sb + P_X + j * 4096, &p.tm[3], ((blockIdx.x - 4) >> 1) * 8, j * 256, sb + S_XBAR);
    }
    if (threadIdx.x == 320) {
        unsigned n;
        asm volatile("ld.relaxed.gpu.global.u32 %0,[%1];" : "=r"(n) : "l"(g_gate) : "memory");
        n = n / (4 * NCL) + p.dopro;
        sts64(sb + S_GATE, n * (4 * NCL), n & 1);
    }
    __syncwarp();
    if (wi == 10) {
        if (v < V_REC || v == 131) conv_init(sb, v == 131); else if (v < V_OP) rec_init(sb); else gemm_init(sb, v < V_QKV);
        __syncwarp();
    }
    if (wg == 2) bar_arrive(8, 384);
    asm volatile("barrier.cluster.arrive.relaxed.aligned;" ::: "memory");
    if (p.dopro && cl >= 2) prologue(p, sb, blockIdx.x - 4, wi, pr); else if (wg < 2) bar_sync(8, 384); else if (wi == 10) early_fetch(p, sb);
    asm volatile("barrier.cluster.wait.aligned;" ::: "memory");
    const int role = (v < V_REC ? 1 : v < V_OP ? 2 : v < V_QKV ? 20 : v < V_QKV + NQ ? 24 : 1) & p.roles;
    fence_async_smem();
    bar_sync(wg == 2 ? 7 : 1, wg == 2 ? 128 : 256);
    if (p.dopro && (threadIdx.x == 32 || threadIdx.x == 352)) red_release(g_gate, 1);
    PROF(threadIdx.x == 32, 3509);
    if (wi == 0 && (role & 8) && elect()) qkv_stage(p, sb + 131072, sb + G_BAR + GB_RS * 8, v - V_QKV, 0, 6);
    PROF(threadIdx.x == 0, 3506);
    __syncwarp();
    if (p.dopro && (v == 131 || (v >= V_REC && v < V_QKV && (v < V_OP ? wi == 8 : wi < 8)))) {
        bool on = v >= V_OP;
#pragma unroll 1
        for (int r = v == 131 ? 448 + wi : on ? 64 + (v - V_OP) * 8 + wi : v - V_REC; r < (v == 131 ? 512 : 448);) {
            if (v >= V_OP) wait_slow_warp(g_gate, lds32(sb + S_GATE)); else if (on) wait_flag_warp(g_gate, lds32(sb + S_GATE));
            PROF(threadIdx.x == 256 && on, 3507);
            x1_norm(on ? (const uint2*)g_x : (const uint2*)p.pa.x, r, on);
            __syncwarp();
            if (on && elect()) red_release(cnt_ptr(C_XN + (r >> 4)), 1);
            __syncwarp();
            PROF(threadIdx.x == 256, on ? 3508 : 3499);
            if (on) r += v < V_OP ? 512 : v == 131 ? 12 : 128;
            on = true;
        }
    }
    if (role == 2) {
        const int head = (v - V_REC) >> 1;
        if (wi == RFW && elect()) {
            if (!REARLY) { rec_fetch(p, sb, head, rank, 0, R_STQ); }
            rec_fetch(p, sb, head, rank, 1, R_STK);
            if (!REARLY) { rec_fetch(p, sb, head, rank, 2, R_STV); }
        }
        __syncwarp();
        if (wg == 2) {
            reg_dec<RH>();
            const int w = wi & 3;
            wait_slow_warp(g_gate, lds32(sb + S_GATE));
            if (w < 2) { const uint32_t x = __ldcg(g_sel + (threadIdx.x & 63)); sts32(sb + R_SEL + (threadIdx.x & 63) * 4, (x * 0x01010101u) >> 24); }
            __syncthreads();
            cluster_sync();
            if ((p.chains >> (w & 1)) & 1) { if (w < 2) rec_comm(p, sb, w, head, rank); else rec_attn(p, sb, w & 1, head, rank); }
        } else {
            reg_inc<RW0>();
            rec_weights(p, sb, head, rank, wi);
        }
    } else if (role == 1) {
        if (v == 131) { wait_slow_warp(g_gate, lds32(sb + S_GATE)); conv_far<0>(sb, wi); conv_far<1>(sb, wi); } else if (wg == 2) { reg_dec<RCB>(); conv_back(sb, v, wi & 3); } else { reg_inc<RCU>(); conv_tile(p, sb, v, wi); }
    } else if (role && v < V_QKV) {
        if (wg == 2) {
            reg_dec<40>();
            if (wi == 8) { if (role & 4) gemm_producer<true>(p, sb, v - V_OP); }
            else if (v < V_OP + 14 && (role & 16)) fin_warp(p, sb, 2 * NQ + (v - V_OP) * 3 + wi - 9);
        } else { reg_inc<232>(); if (role & 4) gemm_consumer<true>(p, sb, v - V_OP, wi); }
    } else if (role) {
        if (wg == 2) {
            reg_dec<40>();
            if (wi < 10) {
                if (role & 8) { if (wi == 8) gemm_producer<false>(p, sb, v - V_QKV); else qkv_release(p, sb); }
            } else if (role & 16) fin_warp(p, sb, (v - V_QKV) * 2 + wi - 10);
        } else { reg_inc<232>(); if (role & 8) gemm_consumer<false>(p, sb, v - V_QKV, wi); }
    }
    __syncwarp();
    cluster_sync();
}

typedef CUresult (*EncFn)(CUtensorMap*, CUtensorMapDataType, cuuint32_t, void*, const cuuint64_t*, const cuuint64_t*, const cuuint32_t*, const cuuint32_t*,
                          CUtensorMapInterleave, CUtensorMapSwizzle, CUtensorMapL2promotion, CUtensorMapFloatOOBfill);
constexpr int SMEM_BYTES = 232448;
#define LAG 8
#define QLEAD 6
#define OLEAD (LAG / 2 + 2)
void plan(Params& P) {
    P.roles = 31; P.chains = 3; P.lag = LAG; P.dopro = 1;
    for (int r = 0; r < 2; r++) {
        const int lead = r ? OLEAD : QLEAD;
        int n = 0;
        for (int i = 0; i < 32 + lead; i++) {
            if (i >= lead) P.list[r][n++] = 32 + i - lead;
            if (i < 32) P.list[r][n++] = i;
        }
        P.nl[r] = n;
    }
}

#define TK() do {} while (0)
}

extern "C" void kernel_launch(void* const* d_in, const int* in_sizes, int n_in, void* d_out, int out_size) {
    typedef const __nv_bfloat16* BP;
    static EncFn enc = nullptr;
    if (!enc) {
        void* fn = nullptr; cudaDriverEntryPointQueryResult qr;
        cudaGetDriverEntryPoint("cuTensorMapEncodeTiled", &fn, cudaEnableDefault, &qr);
        enc = (EncFn)fn;
        cudaFuncSetAttribute(main_kernel, cudaFuncAttributeMaxDynamicSharedMemorySize, SMEM_BYTES);
    }
    static Params P;
    for (int i = 0; i < 4; i++) {
        const cuuint64_t cols = i < 3 ? 4096 : 512, rows = i < 3 ? 512 : 4096;
        cuuint64_t d2[2] = {cols, rows}, str[1] = {cols * 2};
        cuuint32_t box[2] = {64, 64}, bn[2] = {16, 256}, es[2] = {1, 1};
        enc(&P.tm[i < 3 ? i : 4], CU_TENSOR_MAP_DATA_TYPE_BFLOAT16, 2, d_in[9 + i], d2, str, box, es, CU_TENSOR_MAP_INTERLEAVE_NONE, CU_TENSOR_MAP_SWIZZLE_128B,
            CU_TENSOR_MAP_L2_PROMOTION_L2_128B, CU_TENSOR_MAP_FLOAT_OOB_FILL_NONE);
        if (i < 2) enc(&P.tn[i], CU_TENSOR_MAP_DATA_TYPE_BFLOAT16, 2, d_in[9 + i], d2, str, bn, es, CU_TENSOR_MAP_INTERLEAVE_NONE, CU_TENSOR_MAP_SWIZZLE_32B,
                       CU_TENSOR_MAP_L2_PROMOTION_L2_128B, CU_TENSOR_MAP_FLOAT_OOB_FILL_NONE);
    }
    {
        cuuint64_t dims[2] = {512, 2048}, str[1] = {1024};
        cuuint32_t box[2] = {8, 256}, es[2] = {1, 1};
        enc(&P.tm[3], CU_TENSOR_MAP_DATA_TYPE_BFLOAT16, 2, d_in[0], dims, str, box, es, CU_TENSOR_MAP_INTERLEAVE_NONE, CU_TENSOR_MAP_SWIZZLE_NONE,
            CU_TENSOR_MAP_L2_PROMOTION_NONE, CU_TENSOR_MAP_FLOAT_OOB_FILL_NONE);
    }
    P.mem0 = (BP)d_in[8]; P.Wo = (BP)d_in[12]; P.Dskip = (BP)d_in[6]; P.out = (__nv_bfloat16*)d_out;
    cudaStream_t s = cudaStreamPerThread;
    P.pa = {(BP)d_in[0], (BP)d_in[1], (BP)d_in[2], (BP)d_in[3], (BP)d_in[4], (BP)d_in[5], (BP)d_in[6], {(BP)d_in[9], (BP)d_in[10], (BP)d_in[11], (BP)d_in[12]}};
    plan(P);
    TK(); main_kernel<<<2 * NCL, 384, SMEM_BYTES, s>>>(P); TK();
}
```

```cpp
#include <cuda_runtime.h>
#include <cuda_bf16.h>
#include <cuda.h>
#include <stdint.h>
#include <string.h>
#include <math.h>

namespace {

constexpr int NCL = 66;
constexpr int NQ = 43;
constexpr int V_REC = 8, V_OP = 72, V_QKV = 88;
static_assert(2 * NQ + 3 * 14 == 128, "warps of the final residual");

#define XP 1024
__device__ uint4 g_x[2 * 128 * XP];
__device__ uint4 g_xn[64 * 4096];
__device__ uint4 g_st[68 * 256];
__device__ uint4 g_qkv[128 * 32 * 1536];
__device__ uint4 g_o[64 * 64 * 512];
__device__ uint4 g_pp[64 * 4 * 4096];
__device__ uint4 g_xch[133 * 512];
__device__ unsigned g_sel[64];
__device__ unsigned g_gate[32];
__device__ __align__(16) uint32_t g_P[512 * 272];
__device__ uint4 g_W[512 * 784];
__device__ __align__(16) uint32_t g_u[512 * 1280];
__device__ uint2 g_carry[512 * 40 * 32];
__device__ uint2 g_far[512 * 12 * 32];
__device__ unsigned g_cnt[912 * 8];
__device__ uint32_t g_ln0[2048];

enum { C_XN = 0  , C_QKV = 64  , C_O = 128  , C_PP = 384  , C_FAR = 896 };
__device__ __forceinline__ unsigned* cnt_ptr(int i) { return g_cnt + i * 8; }

struct ProArgs { const __nv_bfloat16 *x, *lAr, *Ai, *Cr, *Ci, *ldt, *Dk, *W[4]; };
struct Params {
    CUtensorMap tm[5];
    CUtensorMap tn[2];
    ProArgs pa;
    int dopro;
    const __nv_bfloat16* mem0;
    const __nv_bfloat16* Wo;
    const __nv_bfloat16* Dskip;
    __nv_bfloat16* out;
    int roles;
    int chains;
    int lag;
    int zero;
    int nl[2];
    uint8_t list[2][64];
};

__device__ __forceinline__ uint32_t smem_u32(const void* p) { return (uint32_t)__cvta_generic_to_shared(p); }
__device__ __forceinline__ uint32_t mapa(uint32_t a, uint32_t r) {
    uint32_t o; asm("mapa.shared::cluster.u32 %0,%1,%2;" : "=r"(o) : "r"(a), "r"(r)); return o;
}
__device__ __forceinline__ void mbar_init(uint32_t b, int c) { asm volatile("mbarrier.init.shared::cta.b64 [%0],%1;" ::"r"(b), "r"(c) : "memory"); }
__device__ __forceinline__ void mbar_expect(uint32_t b, int bytes) { asm volatile("mbarrier.arrive.expect_tx.shared::cta.b64 _,[%0],%1;" ::"r"(b), "r"(bytes) : "memory"); }
__device__ __forceinline__ void mbar_arrive(uint32_t b) { asm volatile("mbarrier.arrive.shared::cta.b64 _,[%0];" ::"r"(b) : "memory"); }
__device__ __forceinline__ void mbar_arrive_cluster(uint32_t b) { asm volatile("mbarrier.arrive.shared::cluster.b64 _,[%0];" ::"r"(b) : "memory"); }
__device__ __forceinline__ void mbar_wait(uint32_t b, uint32_t ph) {
    asm volatile(
        "{.reg .pred p; .reg .u32 n; mov.u32 n,0;\n"
        "W%=: mbarrier.try_wait.parity.shared::cta.b64 p,[%0],%1;\n"
        "@p bra D%=;\n"
        "add.u32 n,n,1; setp.lt.u32 p,n,2000000; @p bra W%=;\n"
        "trap;\n"
        "D%=: }" ::"r"(b), "r"(ph) : "memory");
}
__device__ __forceinline__ bool wait_lds128(uint32_t b, uint32_t ph, uint32_t a, uint4& v) {
    uint32_t ok;
    asm volatile("{.reg .pred p; mbarrier.try_wait.parity.shared::cta.b64 p,[%5],%6,20000; ld.shared.v4.u32 {%0,%1,%2,%3},[%7]; selp.u32 %4,1,0,p;}"
                 : "=r"(v.x), "=r"(v.y), "=r"(v.z), "=r"(v.w), "=r"(ok) : "r"(b), "r"(ph), "r"(a) : "memory");
    return ok;
}
__device__ __forceinline__ bool wait_lds64(uint32_t b, uint32_t ph, uint32_t a, uint2& v) {
    uint32_t ok;
    asm volatile("{.reg .pred p; mbarrier.try_wait.parity.shared::cta.b64 p,[%3],%4,20000; ld.shared.v2.u32 {%0,%1},[%5]; selp.u32 %2,1,0,p;}"
                 : "=r"(v.x), "=r"(v.y), "=r"(ok) : "r"(b), "r"(ph), "r"(a) : "memory");
    return ok;
}
template <int PH> __device__ __forceinline__ void mbar_wait_c(uint32_t b) {
    asm volatile(
        "{.reg .pred p; .reg .u32 n; mov.u32 n,%2;\n"
        "W%=: mbarrier.try_wait.parity.shared::cta.b64 p,[%0],%1;\n"
        "@p bra D%=;\n"
        "add.u32 n,n,1; setp.lt.u32 p,n,2000000; @p bra W%=;\n"
        "trap;\n"
        "D%=: }" ::"r"(b), "n"(PH), "n"(PH) : "memory");
}
__device__ __forceinline__ bool elect() {
    uint32_t r; asm volatile("{.reg .pred p; elect.sync _|p,0xffffffff; selp.u32 %0,1,0,p;}" : "=r"(r)); return r;
}
__device__ __forceinline__ void bar_sync(int id, int n) { asm volatile("bar.sync %0,%1;" ::"r"(id), "r"(n) : "memory"); }
__device__ __forceinline__ void bar_arrive(int id, int n) { asm volatile("bar.arrive %0,%1;" ::"r"(id), "r"(n) : "memory"); }
__device__ __forceinline__ void cluster_sync() { asm volatile("barrier.cluster.arrive.relaxed.aligned; barrier.cluster.wait.aligned;" ::: "memory"); }
__device__ __forceinline__ void fence_async() { asm volatile("fence.proxy.async;" ::: "memory"); }
__device__ __forceinline__ void fence_async_smem() { asm volatile("fence.proxy.async.shared::cta;" ::: "memory"); }
#define EFR 1
#define EFW 0
constexpr uint64_t POL_N = 0x1000000000000000ull, POL_F = 0x12F0000000000000ull;
constexpr uint64_t POL_LAST = EFR ? POL_F : POL_N  , POL_LATE = EFW ? POL_F : POL_N  , POL_SOON = EFW > 1 ? POL_F : POL_N;
__device__ __forceinline__ void bulk_g2s(uint32_t dst, const void* src, int bytes, uint32_t bar, uint64_t pol) {
    asm volatile("cp.async.bulk.shared::cluster.global.mbarrier::complete_tx::bytes.L2::cache_hint [%0],[%1],%2,[%3],%4;" ::"r"(dst), "l"(src), "r"(bytes), "r"(bar), "l"(pol) : "memory");
}
__device__ __forceinline__ void bulk_g2s_mc(uint32_t dst, const void* src, int bytes, uint32_t bar, uint64_t pol) {
    asm volatile("cp.async.bulk.shared::cluster.global.mbarrier::complete_tx::bytes.multicast::cluster.L2::cache_hint [%0],[%1],%2,[%3],%4,%5;" ::"r"(dst), "l"(src), "r"(bytes), "r"(bar), "h"((uint16_t)3), "l"(pol) : "memory");
}
__device__ __forceinline__ void stg128(uint4* p, uint4 v, uint64_t pol) {
    asm volatile("st.global.L2::cache_hint.v4.u32 [%0],{%1,%2,%3,%4},%5;" ::"l"(p), "r"(v.x), "r"(v.y), "r"(v.z), "r"(v.w), "l"(pol));
}
__device__ __forceinline__ void stg32(uint32_t* p, uint32_t v, uint64_t pol) { asm volatile("st.global.L2::cache_hint.u32 [%0],%1,%2;" ::"l"(p), "r"(v), "l"(pol)); }
__device__ __forceinline__ uint4 ldcg128_last(const uint4* p) {
    uint4 v; asm volatile("ld.global.cg.L2::cache_hint.v4.u32 {%0,%1,%2,%3},[%4],%5;" : "=r"(v.x), "=r"(v.y), "=r"(v.z), "=r"(v.w) : "l"(p), "l"(POL_LAST) : "memory"); return v;
}
__device__ __forceinline__ void tma2d(uint32_t dst, const CUtensorMap* tm, int x, int y, uint32_t bar) {
    asm volatile("cp.async.bulk.tensor.2d.shared::cluster.global.mbarrier::complete_tx::bytes [%0],[%1,{%2,%3}],[%4];" ::"r"(dst), "l"(tm), "r"(x), "r"(y), "r"(bar) : "memory");
}
__device__ __forceinline__ void tma3d(uint32_t dst, const CUtensorMap* tm, int y, int z, uint32_t bar) {
    asm volatile("cp.async.bulk.tensor.3d.shared::cluster.global.mbarrier::complete_tx::bytes [%0],[%1,{0,%2,%3}],[%4];" ::"r"(dst), "l"(tm), "r"(y), "r"(z), "r"(bar) : "memory");
}
__device__ __forceinline__ void st_async4(uint32_t a, uint32_t x, uint32_t y, uint32_t z, uint32_t w, uint32_t mb) {
    asm volatile("st.async.shared::cluster.mbarrier::complete_tx::bytes.v4.b32 [%0],{%1,%2,%3,%4},[%5];" ::"r"(a), "r"(x), "r"(y), "r"(z), "r"(w), "r"(mb) : "memory");
}
__device__ __forceinline__ void st_async2(uint32_t a, uint32_t x, uint32_t y, uint32_t mb) {
    asm volatile("st.async.shared::cluster.mbarrier::complete_tx::bytes.v2.b32 [%0],{%1,%2},[%3];" ::"r"(a), "r"(x), "r"(y), "r"(mb) : "memory");
}
#define LDSQ "ld.shared"
__device__ __forceinline__ uint4 lds128(uint32_t a) { uint4 v; asm volatile(LDSQ ".v4.u32 {%0,%1,%2,%3},[%4];" : "=r"(v.x), "=r"(v.y), "=r"(v.z), "=r"(v.w) : "r"(a) : "memory"); return v; }
__device__ __forceinline__ uint4 lds128v(uint32_t a) { uint4 v; asm volatile("ld.volatile.shared.v4.u32 {%0,%1,%2,%3},[%4];" : "=r"(v.x), "=r"(v.y), "=r"(v.z), "=r"(v.w) : "r"(a) : "memory"); return v; }
__device__ __forceinline__ uint2 lds64(uint32_t a) { uint2 v; asm volatile(LDSQ ".v2.u32 {%0,%1},[%2];" : "=r"(v.x), "=r"(v.y) : "r"(a) : "memory"); return v; }
__device__ __forceinline__ uint32_t lds32(uint32_t a) { uint32_t v; asm volatile(LDSQ ".u32 %0,[%1];" : "=r"(v) : "r"(a) : "memory"); return v; }
__device__ __forceinline__ void sts128(uint32_t a, uint32_t x, uint32_t y, uint32_t z, uint32_t w) { asm volatile("st.shared.v4.u32 [%0],{%1,%2,%3,%4};" ::"r"(a), "r"(x), "r"(y), "r"(z), "r"(w) : "memory"); }
__device__ __forceinline__ void sts64(uint32_t a, uint32_t x, uint32_t y) { asm volatile("st.shared.v2.u32 [%0],{%1,%2};" ::"r"(a), "r"(x), "r"(y) : "memory"); }
__device__ __forceinline__ void sts32(uint32_t a, uint32_t x) { asm volatile("st.shared.u32 [%0],%1;" ::"r"(a), "r"(x) : "memory"); }
__device__ __forceinline__ uint4 ldsm4(uint32_t a) { uint4 v; asm volatile("ldmatrix.sync.aligned.m8n8.x4.shared.b16 {%0,%1,%2,%3},[%4];" : "=r"(v.x), "=r"(v.y), "=r"(v.z), "=r"(v.w) : "r"(a) : "memory"); return v; }
__device__ __forceinline__ uint4 ldsm4t(uint32_t a) { uint4 v; asm volatile("ldmatrix.sync.aligned.m8n8.x4.trans.shared.b16 {%0,%1,%2,%3},[%4];" : "=r"(v.x), "=r"(v.y), "=r"(v.z), "=r"(v.w) : "r"(a) : "memory"); return v; }
__device__ __forceinline__ uint32_t movm(uint32_t a) { uint32_t d; asm volatile("movmatrix.sync.aligned.m8n8.trans.b16 %0,%1;" : "=r"(d) : "r"(a)); return d; }
__device__ __forceinline__ uint32_t pack2(float lo, float hi) { uint32_t d; asm("cvt.rn.bf16x2.f32 %0,%1,%2;" : "=r"(d) : "f"(hi), "f"(lo)); return d; }
__device__ __forceinline__ uint32_t hadd2(uint32_t a, uint32_t b) { uint32_t d; asm("add.rn.bf16x2 %0,%1,%2;" : "=r"(d) : "r"(a), "r"(b)); return d; }
__device__ __forceinline__ uint32_t hmul2(uint32_t a, uint32_t b) { uint32_t d; asm("mul.rn.bf16x2 %0,%1,%2;" : "=r"(d) : "r"(a), "r"(b)); return d; }
__device__ __forceinline__ float blo(uint32_t v) { return __uint_as_float(v << 16); }
__device__ __forceinline__ float bhi(uint32_t v) { return __uint_as_float(v & 0xffff0000u); }
__device__ __forceinline__ float rbf(float x) { return __uint_as_float(pack2(0.f, x)); }
__device__ __forceinline__ float ex2(float x) { float y; asm("ex2.approx.ftz.f32 %0,%1;" : "=f"(y) : "f"(x)); return y; }
__device__ __forceinline__ float rcp(float x) { float y; asm("rcp.approx.ftz.f32 %0,%1;" : "=f"(y) : "f"(x)); return y; }
__device__ __forceinline__ void mma16(float* c, uint32_t a0, uint32_t a1, uint32_t a2, uint32_t a3, uint32_t b0, uint32_t b1) {
    asm volatile("mma.sync.aligned.m16n8k16.row.col.f32.bf16.bf16.f32 {%0,%1,%2,%3},{%4,%5,%6,%7},{%8,%9},{%0,%1,%2,%3};"
                 : "+f"(c[0]), "+f"(c[1]), "+f"(c[2]), "+f"(c[3]) : "r"(a0), "r"(a1), "r"(a2), "r"(a3), "r"(b0), "r"(b1));
}
__device__ __forceinline__ void mma16_top(float& d0, float& d1, uint32_t a0, uint32_t a2, uint32_t b0, uint32_t b1) {
    asm volatile("{.reg .b32 j; .reg .f32 e,f; mma.sync.aligned.m16n8k16.row.col.f32.bf16.bf16.f32 {%0,%1,e,f},{%2,j,%3,j},{%4,%5},{0f00000000,0f00000000,0f00000000,0f00000000};}"
                 : "=f"(d0), "=f"(d1) : "r"(a0), "r"(a2), "r"(b0), "r"(b1));
}
__device__ __forceinline__ void mma8(float* c, uint32_t a0, uint32_t a1, uint32_t b0) {
    asm volatile("mma.sync.aligned.m16n8k8.row.col.f32.bf16.bf16.f32 {%0,%1,%2,%3},{%4,%5},{%6},{%0,%1,%2,%3};"
                 : "+f"(c[0]), "+f"(c[1]), "+f"(c[2]), "+f"(c[3]) : "r"(a0), "r"(a1), "r"(b0));
}
__device__ __forceinline__ uint4 ld_rlx128(const uint4* p) {
    uint4 v;
    asm volatile("{.reg .b128 t; ld.relaxed.gpu.global.b128 t,[%4]; mov.b128 {%0,%1,%2,%3},t;}" : "=r"(v.x), "=r"(v.y), "=r"(v.z), "=r"(v.w) : "l"(p) : "memory");
    return v;
}
__device__ __forceinline__ void st_rlx128(uint4* p, uint32_t x, uint32_t y, uint32_t z, uint32_t w) {
    asm volatile("{.reg .b128 t; mov.b128 t,{%1,%2,%3,%4}; st.relaxed.gpu.global.b128 [%0],t;}" ::"l"(p), "r"(x), "r"(y), "r"(z), "r"(w) : "memory");
}
__device__ __forceinline__ void st_weak128(uint4* p, uint32_t x, uint32_t y, uint32_t z, uint32_t w) { *p = make_uint4(x, y, z, w); }
__device__ __forceinline__ uint4 ldcg128(const uint4* p) { uint4 v; asm volatile("ld.global.cg.v4.u32 {%0,%1,%2,%3},[%4];" : "=r"(v.x), "=r"(v.y), "=r"(v.z), "=r"(v.w) : "l"(p) : "memory"); return v; }
__device__ __forceinline__ void red_release(unsigned* p, unsigned v) {
    asm volatile("fence.proxy.async; red.relaxed.gpu.global.add.u32 [%0],%1;" ::"l"(p), "r"(v) : "memory");
}
__device__ __forceinline__ void red_relaxed(unsigned* p, unsigned v) { asm volatile("red.relaxed.gpu.global.add.u32 [%0],%1;" ::"l"(p), "r"(v) : "memory"); }
__device__ __forceinline__ void wait_cnt(const unsigned* p, unsigned target) {
    asm volatile(
        "{.reg .pred p; .reg .u32 n,v; mov.u32 n,0;\n"
        "W%=: ld.acquire.gpu.global.u32 v,[%0]; setp.ge.u32 p,v,%1; @p bra D%=;\n"
        "nanosleep.u32 20; add.u32 n,n,1; setp.lt.u32 p,n,4000000; @p bra W%=;\n"
        "trap;\n"
        "D%=: }" ::"l"(p), "r"(target) : "memory");
}
__device__ __forceinline__ void wait_cnt_warp(const unsigned* p, unsigned target) {
    asm volatile(
        "{.reg .pred p; .reg .u32 n,v; mov.u32 n,0;\n"
        "W%=: ld.acquire.gpu.global.u32 v,[%0]; setp.ge.u32 p,v,%1; vote.sync.all.pred p,p,0xffffffff; @p bra.uni D%=;\n"
        "nanosleep.u32 20; add.u32 n,n,1; setp.lt.u32 p,n,4000000; @p bra.uni W%=;\n"
        "trap;\n"
        "D%=: }" ::"l"(p), "r"(target) : "memory");
}
__device__ __forceinline__ void wait_slow_warp(const unsigned* p, unsigned target) {
    asm volatile(
        "{.reg .pred p; .reg .u32 n,v; mov.u32 n,0;\n"
        "W%=: ld.relaxed.gpu.global.u32 v,[%0]; setp.ge.u32 p,v,%1; vote.sync.all.pred p,p,0xffffffff; @p bra.uni D%=;\n"
        "nanosleep.u32 400; add.u32 n,n,1; setp.lt.u32 p,n,1000000; @p bra.uni W%=;\n"
        "trap;\n"
        "D%=: }" ::"l"(p), "r"(target) : "memory");
}
__device__ __forceinline__ void wait_flag_warp(const unsigned* p, unsigned target) {
    asm volatile(
        "{.reg .pred p; .reg .u32 n,v; mov.u32 n,0;\n"
        "W%=: ld.relaxed.gpu.global.u32 v,[%0]; setp.ge.u32 p,v,%1; vote.sync.all.pred p,p,0xffffffff; @p bra.uni D%=;\n"
        "add.u32 n,n,1; setp.lt.u32 p,n,10000000; @p bra.uni W%=;\n"
        "trap;\n"
        "D%=: }" ::"l"(p), "r"(target) : "memory");
}
__device__ __forceinline__ uint64_t mkdesc(uint32_t addr, uint32_t lbo, uint32_t sbo, uint32_t sw) {
    return (uint64_t)((addr & 0x3FFFF) >> 4) | ((uint64_t)(lbo >> 4) << 16) | ((uint64_t)(sbo >> 4) << 32) | ((uint64_t)sw << 62);
}
__device__ __forceinline__ void wg_fence() { asm volatile("wgmma.fence.sync.aligned;" ::: "memory"); }
__device__ __forceinline__ void wg_commit() { asm volatile("wgmma.commit_group.sync.aligned;" ::: "memory"); }
template <int N> __device__ __forceinline__ void wg_wait() { asm volatile("wgmma.wait_group.sync.aligned %0;" ::"n"(N) : "memory"); }
#define R8(c, o) "+f"(c[o]), "+f"(c[o + 1]), "+f"(c[o + 2]), "+f"(c[o + 3]), "+f"(c[o + 4]), "+f"(c[o + 5]), "+f"(c[o + 6]), "+f"(c[o + 7])
#define R32(c, o) R8(c, o), R8(c, o + 8), R8(c, o + 16), R8(c, o + 24)
#define S32A "%0,%1,%2,%3,%4,%5,%6,%7,%8,%9,%10,%11,%12,%13,%14,%15,%16,%17,%18,%19,%20,%21,%22,%23,%24,%25,%26,%27,%28,%29,%30,%31"
template <int ACC> __device__ __forceinline__ void wgmma64_rs(float* c, const uint32_t* a, uint64_t db) {
    asm volatile("wgmma.mma_async.sync.aligned.m64n64k16.f32.bf16.bf16 {" S32A "},{%32,%33,%34,%35},%36,%37,1,1,0;"
                 : R32(c, 0) : "r"(a[0]), "r"(a[1]), "r"(a[2]), "r"(a[3]), "l"(db), "n"(ACC));
}
template <int ACC> __device__ __forceinline__ void wgmma64_ta(float* c, uint64_t da, uint64_t db) {
    asm volatile("wgmma.mma_async.sync.aligned.m64n64k16.f32.bf16.bf16 {" S32A "},%32,%33,%34,1,1,1,0;" : R32(c, 0) : "l"(da), "l"(db), "n"(ACC));
}
template <int ACC> __device__ __forceinline__ void wgmma80_tb(float* c, uint64_t da, uint64_t db) {
    asm volatile("wgmma.mma_async.sync.aligned.m64n80k16.f32.bf16.bf16 {" S32A ",%32,%33,%34,%35,%36,%37,%38,%39},%40,%41,%42,1,1,0,1;"
                 : R32(c, 0), R8(c, 32) : "l"(da), "l"(db), "n"(ACC));
}
template <int N> __device__ __forceinline__ void reg_inc() { asm volatile("setmaxnreg.inc.sync.aligned.u32 %0;" ::"n"(N)); }
template <int N> __device__ __forceinline__ void reg_dec() { asm volatile("setmaxnreg.dec.sync.aligned.u32 %0;" ::"n"(N)); }

#define PROF(cond, idx) do {} while (0)
#define PROF2(cond, idx) do {} while (0)

constexpr int S_GATE = 232440, S_TAG = 232444, S_XBAR = 232432, B_BAR = 231936;
#define FT 5
#define FJ 62
#define ST_PP st_rlx128
#define OLAG 1
#define RCB 136
#define RCU 184
#define NTOP 1
#define PLATE 2
#define PFM 12
#define QLAG 4
constexpr float SC_LOG2E = 0.08838834764831845f * 1.4426950408889634f;

__device__ __forceinline__ float2 ln_finish(float mean, float var) {
    float sd; asm("sqrt.approx.f32 %0,%1;" : "=f"(sd) : "f"(rbf(rbf(var) + 1e-5f)));
    sd = rbf(sd);
    return make_float2(rbf(mean), sd);
}

__device__ __forceinline__ float2 row_stats512(uint4* v, const uint4* src, int s1, int s2) {
    const int g = (threadIdx.x & 31) >> 2;
#pragma unroll
    for (int i = 0; i < 16; i++) v[i] = ldcg128(src + (i >> 1) * s1 + (i & 1) * s2);
    float a[4] = {0, 0, 0, 0}, q0[4] = {0, 0, 0, 0}, q1[4] = {0, 0, 0, 0};
#pragma unroll
    for (int i = 0; i < 16; i++) {
        mma16(a, v[i].x, v[i].y, v[i].z, v[i].w, 0x3f803f80u, 0x3f803f80u);
        mma8(q0, v[i].x, v[i].y, v[i].x); mma8(q1, v[i].x, v[i].y, v[i].y);
        mma8(q0, v[i].z, v[i].w, v[i].z); mma8(q1, v[i].z, v[i].w, v[i].w);
    }
    const float sum = a[0] + a[2], sq = (g & 1) ? q0[1] + q1[3] : q0[0] + q1[2];
    return make_float2(sum, fmaxf(sq - sum * sum * (1.f / 512.f), 0.f));
}
__device__ __forceinline__ void x1_norm(const uint2* src, int r, bool on) {
    const int lane = threadIdx.x & 31, g = lane >> 2, t = r * 4 + (lane & 3);
    constexpr int xp = XP;
    uint2 v[16];
#pragma unroll
    for (int i = 0; i < 16; i++) asm volatile("ld.global.cg.v2.u32 {%0,%1},[%2];" : "=r"(v[i].x), "=r"(v[i].y) : "l"(src + (g * 4 * xp + t) + ((i >> 1) * 16 + (i & 1)) * 2 * xp) : "memory");
    float s = 0, q = 0;
#pragma unroll
    for (int i = 0; i < 32; i++) {
        const uint32_t w = (i & 1) ? v[i >> 1].y : v[i >> 1].x;
        s += blo(w) + bhi(w); q = fmaf(blo(w), blo(w), fmaf(bhi(w), bhi(w), q));
    }
#pragma unroll
    for (int d = 4; d < 32; d *= 2) { s += __shfl_xor_sync(0xffffffffu, s, d); q += __shfl_xor_sync(0xffffffffu, q, d); }
    if (g == 0 && on) g_ln0[t] = 0;
    s *= 1.f / 512.f;
    const float2 l = ln_finish(s, fmaxf(fmaf(q, 1.f / 512.f, -s * s), 0.f));
    const float rs = rcp(l.y);
    const uint32_t mm = pack2(-l.x, -l.x);
    uint4* dst = g_xn + ((t >> 6) * 4096 + ((t >> 3) & 7) * 64 + g * 8 + (t & 7));
#define NRM(w) pack2(blo(hadd2(w, mm)) * rs, bhi(hadd2(w, mm)) * rs)
#pragma unroll
    for (int i = 0; i < 8; i++)
        asm volatile("{.reg .pred p; setp.ne.u32 p,%5,0; @p st.global.v4.u32 [%0],{%1,%2,%3,%4};}" ::"l"(dst + i * 512), "r"(NRM(v[2 * i].x)), "r"(NRM(v[2 * i].y)),
                     "r"(NRM(v[2 * i + 1].x)), "r"(NRM(v[2 * i + 1].y)), "r"((uint32_t)on) : "memory");
}

#define NWO 10
#define VMASK 0x4444
#define VPRE 2
#define VFIRST 1
#define OA 0
#define OL 0x16
#define PINS 0x6ae1
#define NPX 2
#define NPF 2
constexpr int SLOT = 24576, SL_V = 8192, SL_Q = 16384, SL_KM = 20480, SL_VM = 22528;
constexpr int R_SL = 0, R_WV = 4 * SLOT  , R_WO = R_WV + 65536, R_M = 196608  , R_U = R_M + 8192  ,
              R_OS = R_U + 8192  , R_SB = R_OS + 8192  , R_OB = R_SB + 5248  , R_PB = R_OB + 2048  ,
              R_IL = R_PB + 1024  , R_SEL = 231680, R_BAR = R_SEL + 256, R_STV = 0, R_STQ = 65536, R_STK = 131072;
static_assert(R_WO + (16 - NWO) * 4096 <= R_M && R_IL + 64 <= R_SEL && R_BAR + 512 <= 232448, "smem map");
enum { RB_XFULL = 0  , RB_GO = 4  , RB_QK = 8  , RB_INIT = 24, RB_SV = 25   };

enum { NB_MFULL = 1  , NB_PART = 3  , NB_S = 5, NB_P = 6, NB_O = 7, NB_W = 10 };
#define XU 4
#define GOP 0
#define WOF 1
#define SPV 0
#define SEARLY 4
#define EGO 0
#define NPRB 3
#define REARLY 1
#define RFW 8
#define PF0 0
#define PFD 1500
#define EFS V_QKV
#define RACC 4
#define WDEP 1
#define RH 56
#define RW0 224
#define D1 270
#define D2 300
__device__ __forceinline__ uint32_t clk32() { uint32_t c; asm volatile("mov.u32 %0,%%clock;" : "=r"(c)::"memory"); return c; }
__device__ __forceinline__ void spin(int cycles) {
    if (cycles <= 0) return;
    asm volatile("{.reg .pred p; .reg .u32 a,b; mov.u32 a,%%clock; add.u32 a,a,%0;\nS%=: mov.u32 b,%%clock; sub.u32 b,b,a; setp.lt.s32 p,b,0; @p bra.uni S%=;}" ::"r"(cycles) : "memory");
}
__device__ __forceinline__ void spin_v(uint32_t cycles) {
    asm volatile("{.reg .pred p; .reg .u32 a,b; mov.u32 a,%%clock; add.u32 a,a,%0;\nS%=: mov.u32 b,%%clock; sub.u32 b,b,a; setp.lt.s32 p,b,0; @p bra.uni S%=;}" ::"r"(cycles) : "memory");
}
__device__ __forceinline__ uint4* xregion(int X, int r) { return (uint4*)(((size_t)g_xch + 8191) & ~(size_t)8191) + (X * 66 + r) * 512; }

__device__ __forceinline__ void arrive_if(uint32_t bar, uint32_t a, uint32_t b) {
    asm volatile("{.reg .pred p; setp.eq.u32 p,%1,%2; @p mbarrier.arrive.shared::cta.b64 _,[%0];}" ::"r"(bar), "r"(a), "r"(b) : "memory");
}
struct RecW { uint32_t po, dp, lw, sp, w; };
#define PIN(n) if ((PINS >> (n)) & 1) asm volatile("griddepcontrol.launch_dependents;" ::: "memory")
constexpr int v_stream(int n) {
    int ks = 0;
    for (; ks < 16; ks++) if (!((VMASK >> ks) & 1) && n-- == 0) break;
    return ks;
}
constexpr uint64_t v_next() {
    uint64_t r = 0;
    for (int n = 0; v_stream(n + VPRE) < 16; n++) r |= (uint64_t)v_stream(n + VPRE) << (4 * v_stream(n));
    return r;
}
constexpr uint64_t V_NEXT = v_next();
constexpr int V_PRE = v_stream(VPRE);

__device__ __forceinline__ void rec_step(const RecW& k, uint32_t sb, const int X, int s, uint32_t zero, int lo, int hi, int d, const uint32_t (*wq)[4], const uint32_t (*wk)[4], uint4* wv, uint4* wo) {
    const int SL = R_SL + X * 2 * SLOT;
    uint4 mk[8];
    bar_sync(NB_MFULL + X, 288);
    mk[0] = ldsm4(k.lw + X * 4096 + R_M);
    PIN(0);
    mk[1] = ldsm4(k.lw + X * 4096 + R_M + 512);
    PIN(0);
    asm volatile("" : "+r"(s));
    const uint32_t z = s & zero, wz = k.w + z, w5 = wz * 512, so = (s & 1) * SLOT + w5;
    const uint32_t qb = sb + R_BAR + (RB_QK + X * 8) * 8 + wz * 8;
    uint32_t x[4], vv[2], l8;
    {
        float aq[4] = {0, 0, 0, 0}, ak[4] = {0, 0, 0, 0}, av[4] = {0, 0, 0, 0};
#pragma unroll
        for (int t = 0; t < 16; t++) {
            const uint32_t b0 = (t & 1) ? mk[t >> 1].z : mk[t >> 1].x, b1 = (t & 1) ? mk[t >> 1].w : mk[t >> 1].y;
            mma16(aq, wq[t][0], wq[t][1], wq[t][2], wq[t][3], b0, b1);
            PIN(8);
            mma16(ak, wk[t][0], wk[t][1], wk[t][2], wk[t][3], b0, b1);
            PIN(9);
            mma16(av, wv[t].x, wv[t].y, wv[t].z, wv[t].w, b0, b1);
            PIN(10);
            if ((t & 1) && t < 13) mk[(t >> 1) + 2] = ldsm4(k.lw + X * 4096 + R_M + (t >> 1) * 512 + 1024);
            const int nx = (V_NEXT >> (4 * t)) & 15;
            if (nx) wv[nx] = lds128(k.lw + w5 + R_WV + nx * 4096);
            if (t == 14) l8 = ((k.lw + z) >> 1) + (sb - (sb >> 1) + SL + (s & 1) * SLOT + wz * 256);
            if (t < 15) PIN(1);
        }
        x[0] = movm(pack2(aq[0], aq[1])); x[1] = movm(pack2(aq[2], aq[3]));
        x[2] = movm(pack2(ak[0], ak[1])); x[3] = movm(pack2(ak[2], ak[3]));
        vv[0] = pack2(av[0], av[1]); vv[1] = pack2(av[2], av[3]);
        if (VFIRST) st_async2(l8 + (SL_VM + k.dp), vv[0], vv[1], qb + k.dp);
        st_async4(k.lw + (R_U + X * 4096 + w5 + k.dp), x[0], x[1], x[2], x[3], qb + k.dp);
        if (!VFIRST) st_async2(l8 + (SL_VM + k.dp), vv[0], vv[1], qb + k.dp);
    }
    {
#define GO_OTHER arrive_if(sb + R_BAR + (RB_GO + 2 - 2 * X + ((s + d) & 1)) * 8, (k.sp + z) & 0x1ff0, X ? s >= hi : s <= lo)
        if (GOP == 0) GO_OTHER;
        const uint32_t swr = ((k.sp + z) & 0x1ff0) + (sb + R_SB);
        if (WOF) {
#pragma unroll
            for (int i = 0; i < NPX; i++) wo[i] = lds128v(k.lw + w5 + R_WO + i * 4096);
        }
        mbar_wait(sb + R_BAR + (RB_XFULL + X * 2) * 8 + (s & 1) * 8, (s >> 1) & 1);
        const uint4 k0 = lds128(k.lw + so + SL), k1 = lds128(k.lw + so + SL + 4096);
        if (!WOF) {
#pragma unroll
            for (int i = 0; i < NPX; i++) wo[i] = lds128(k.lw + w5 + R_WO + i * 4096);
        }
        if (GOP == 1) GO_OTHER;
        mbar_wait(qb, s & 1);
        const uint4 u = lds128(k.lw + w5 + R_U + X * 4096);
        if (GOP == 2) GO_OTHER;
        const uint32_t q0 = hadd2(x[0], u.x), q1 = hadd2(x[1], u.y);
        x[2] = hadd2(x[2], u.z); x[3] = hadd2(x[3], u.w);
        float sa[4] = {0, 0, 0, 0}, sc[4] = {0, 0, 0, 0}, sm0, sm1;
        mma16(sa, k0.x, k0.y, k0.z, k0.w, q0, q1);
        mma16(sc, k1.x, k1.y, k1.z, k1.w, q0, q1);
        mma16_top(sm0, sm1, x[2], x[3], q0, q1);
        asm volatile("stmatrix.sync.aligned.m8n8.x4.trans.shared.b16 [%0],{%1,%2,%3,%4};" ::"r"(swr), "r"(pack2(sa[0], sa[1])), "r"(pack2(sa[2], sa[3])),
                     "r"(pack2(sc[0], sc[1])), "r"(pack2(sc[2], sc[3])) : "memory");
        asm volatile("stmatrix.sync.aligned.m8n8.x1.trans.shared.b16 [%0],{%1};" ::"r"(swr + 512), "r"(pack2(sm0, sm1)) : "memory");
    }
    if (GOP == 3) GO_OTHER;
    bar_sync(NB_S, 256);
    uint4 v0, v1;
    uint32_t ls;
    {
        const uint4 y = ldsm4t(k.lw + wz * 656 + R_SB);
        PIN(2);
        uint32_t y4; asm volatile("ldmatrix.sync.aligned.m8n8.x1.trans.shared.b16 {%0},[%1];" : "=r"(y4) : "r"(k.lw + wz * 656 + R_SB + 512) : "memory");
        PIN(2);
        const uint2 vp = lds64(l8 + SL_VM);
        sts64(l8 + SL_KM, x[2], x[3]);
        const uint32_t z1 = k.lw & z, z2 = k.sp & z, ONE = 0x3f803f80u | z2, ONF = 0x3f803f80u | z1;
        float a[4] = {0, 0, 0, 0}, b[4] = {0, 0, 0, 0}, e[4] = {0, 0, 0, 0};
        mma8(e, ONE, z1, y4); mma16(a, ONE, z1, z2, ONF, y.x, y.y); mma16(b, ONE, z1, z2, ONF, y.z, y.w);
        vv[0] = hadd2(vv[0], vp.x); vv[1] = hadd2(vv[1], vp.y);
        sts64(l8 + SL_VM, vv[0], vv[1]);
        float s0, s1;
        asm("{.reg .pred p1,p2,p4; .reg .f32 t0,t1,u0,u1; .reg .b32 m; and.b32 m,%12,64; setp.ne.u32 p1,m,0; and.b32 m,%12,128; setp.ne.u32 p2,m,0; and.b32 m,%12,256; setp.ne.u32 p4,m,0;"
            "selp.f32 t0,%4,%2,p1; selp.f32 t1,%5,%3,p1; selp.f32 u0,%8,%6,p1; selp.f32 u1,%9,%7,p1; selp.f32 t0,u0,t0,p2; selp.f32 t1,u1,t1,p2; selp.f32 %0,%10,t0,p4; selp.f32 %1,%11,t1,p4;}"
            : "=f"(s0), "=f"(s1) : "f"(a[0]), "f"(a[1]), "f"(a[2]), "f"(a[3]), "f"(b[0]), "f"(b[1]), "f"(b[2]), "f"(b[3]), "f"(e[0]), "f"(e[1]), "r"(k.lw));
        const int mi = __float_as_int(fmaxf(s0, s1));
        const int mp = __reduce_max_sync(0xffffffffu, mi), mn = (int)__reduce_min_sync(0xffffffffu, (unsigned)mi);
        PIN(3);
        v0 = lds128(k.lw + so + SL + SL_V); v1 = lds128(k.lw + so + SL + SL_V + 4096);
#pragma unroll
        for (int i = NPX; i < NPF; i++) wo[i] = lds128(k.lw + w5 + R_WO + i * 4096);
        PIN(4);
        const float mo = -__int_as_float(mp >= 0 ? mp : mn) * SC_LOG2E;
        s0 = ex2(fmaf(s0, SC_LOG2E, mo)); s1 = ex2(fmaf(s1, SC_LOG2E, mo));
        sts32((((k.sp + z) >> 11) & 0x1fc) + (k.lw & 256) * 2 + (sb + R_PB), pack2(s0, s1));
        ls = k.lw < sb + 320 ? __float_as_uint((s0 + s1) + 4.f) : 0;
    }
    bar_sync(NB_P, 256);
    {
        const uint4 pp = lds128(k.lw + R_PB);
        PIN(5);
        const uint32_t pm = lds32(((k.lw + z) >> 2) + (sb - (sb >> 2) + R_PB + 512));
        PIN(5);
        if (EGO) arrive_if(sb + R_BAR + (RB_GO + 2 * X + (s & 1)) * 8, (k.sp + z) & 0x1ff0, X ? s + 1 < hi : s >= lo);
        sts32(sb + R_IL + (wz >> 1) * 16 + (wz & 1) * 4, __reduce_add_sync(0xffffffffu, ls) - 20u * 0x40800000u);
        float o0[4] = {0, 0, 0, 0}, o1[4] = {0, 0, 0, 0}, o2[4] = {0, 0, 0, 0};
        mma16(o0, v0.x, v0.y, v0.z, v0.w, pp.x, pp.y);
        mma16(o1, v1.x, v1.y, v1.z, v1.w, pp.z, pp.w);
        mma8(o2, vv[0], vv[1], pm);
        asm volatile("stmatrix.sync.aligned.m8n8.x2.trans.shared.b16 [%0],{%1,%2};" ::"r"(k.lw + wz * 256 + R_OB),
                     "r"(pack2(o0[0] + o1[0] + o2[0], o0[1] + o1[1] + o2[1])), "r"(pack2(o0[2] + o1[2] + o2[2], o0[3] + o1[3] + o2[3])) : "memory");
    }
    bar_sync(NB_O, 256);
    {
        float r0[2][4] = {{0, 0, 0, 0}, {0, 0, 0, 0}}, r1[2][4] = {{0, 0, 0, 0}, {0, 0, 0, 0}};
        uint4 b[4];
        b[0] = ldsm4(k.lw + R_OB);
        PIN(6);
        b[1] = ldsm4(k.lw + R_OB + 512);
        PIN(6);
#pragma unroll
        for (int m = NWO + NPF; m < 16; m++) if (((OL >> (2 * (15 - m))) & 3) == 3) wo[m] = lds128(k.lw + w5 + R_WO + (m - NWO) * 4096);
        const uint2 il = lds64(sb + R_IL + ((k.lw + z) & 48));
        PIN(6);
        float i0, i1;
        uint4* dst;
#pragma unroll
        for (int i = 0; i < 4; i++) {
            mma16(r0[0], wo[4 * i].x, wo[4 * i].y, wo[4 * i].z, wo[4 * i].w, b[i].x, b[i].y);
            mma16(r1[0], wo[4 * i + 1].x, wo[4 * i + 1].y, wo[4 * i + 1].z, wo[4 * i + 1].w, b[i].x, b[i].y);
            mma16(r0[OA], wo[4 * i + 2].x, wo[4 * i + 2].y, wo[4 * i + 2].z, wo[4 * i + 2].w, b[i].z, b[i].w);
            mma16(r1[OA], wo[4 * i + 3].x, wo[4 * i + 3].y, wo[4 * i + 3].z, wo[4 * i + 3].w, b[i].z, b[i].w);
            if (i < 2) b[i + 2] = ldsm4(k.lw + R_OB + (i + 2) * 512);
#pragma unroll
            for (int m = NWO + NPF; m < 16; m++) if (i < 3 && i == ((OL >> (2 * (15 - m))) & 3)) wo[m] = lds128(k.lw + w5 + R_WO + (m - NWO) * 4096);
            if (i == 1) { i0 = rcp(__uint2float_rn(il.x)) * 2097152.f; i1 = rcp(__uint2float_rn(il.y)) * 2097152.f; }
            if (i == 2) {
                const uint32_t po = k.sp + z;
                dst = xregion(X, 0) + k.po + ((po >> 20) ^ ((po & X) << 8));
                asm volatile("" : "+l"(dst));
            }
            PIN(7);
        }
        const uint32_t tag = (s + 1) & 1;
#pragma unroll
        for (int i = 0; i < 4; i++) { r0[0][i] = (OA ? r0[0][i] + r0[1][i] : r0[0][i]) * ((i & 1) ? i1 : i0); r1[0][i] = (OA ? r1[0][i] + r1[1][i] : r1[0][i]) * ((i & 1) ? i1 : i0); }
        st_rlx128(dst, (pack2(r0[0][0], r0[0][2]) & ~1u) | tag,
                  pack2(r1[0][0], r1[0][2]), pack2(r0[0][1], r0[0][3]), pack2(r1[0][1], r1[0][3]));
        bar_arrive(NB_PART + X, 288);
#pragma unroll
        for (int t = 0; t < V_PRE; t++) if (!((VMASK >> t) & 1)) wv[t] = lds128(k.lw + w5 + R_WV + t * 4096);
        if (!EGO) arrive_if(sb + R_BAR + (RB_GO + 2 * X + (s & 1)) * 8, (k.sp + z) & 0x1ff0, X ? s + 1 < hi : s >= lo);
    }
}

__device__ __forceinline__ void rec_fetch(const Params& p, uint32_t sb, int head, uint32_t rank, int which, int dst) {
#pragma unroll 1
    for (int j = 0; j < 8; j++) tma2d(sb + dst + j * 8192, &p.tm[which], head * 128 + (j >> 2) * 64, rank * 256 + (j & 3) * 64, sb + R_BAR + RB_INIT * 8);
}

__device__ __forceinline__ void rec_weights(const Params& p, uint32_t sb, int head, uint32_t rank, int w) {
    const int lane = __shfl_sync(0xffffffffu, threadIdx.x & 31, threadIdx.x & 31),
        g = lane >> 2, c = lane & 3;
    const int t = w & 3, WG = w >> 2;
    uint32_t wq[16][4], wk[16][4];
    uint4 wo[16], wv[16];
    const uint32_t woff = sb + WG * 32768 + (((lane >> 4) << 3) + (lane & 7)) * 128 + (((2 * t + ((lane >> 3) & 1)) ^ (lane & 7)) << 4);
    const uint32_t lw = sb + lane * 16;
    PROF2(threadIdx.x == 0, 3501);
    {
        const __nv_bfloat16* wp = p.Wo + (size_t)(head * 128 + 2 * c) * 512 + rank * 256 + w * 32 + g * 4;
#pragma unroll
        for (int ks = 0; ks < 8; ks++) {
            const uint2 r0 = *(const uint2*)(wp + (ks * 16) * 512), r1 = *(const uint2*)(wp + (ks * 16 + 1) * 512);
            const uint2 r2 = *(const uint2*)(wp + (ks * 16 + 8) * 512), r3 = *(const uint2*)(wp + (ks * 16 + 9) * 512);
            const uint4 f[2] = {make_uint4(__byte_perm(r0.x, r1.x, 0x5410), __byte_perm(r0.x, r1.x, 0x7632), __byte_perm(r2.x, r3.x, 0x5410), __byte_perm(r2.x, r3.x, 0x7632)),
                                make_uint4(__byte_perm(r0.y, r1.y, 0x5410), __byte_perm(r0.y, r1.y, 0x7632), __byte_perm(r2.y, r3.y, 0x5410), __byte_perm(r2.y, r3.y, 0x7632))};
#pragma unroll
            for (int h = 0; h < 2; h++) {
                const int m = 2 * ks + h;
                wo[m] = f[h];
            }
        }
    }
    PROF2(threadIdx.x == 0, 3502);
    mbar_wait(sb + R_BAR + RB_INIT * 8, 0);
    PROF2(threadIdx.x == 0, 3503);
#pragma unroll
    for (int ks = 0; ks < 16; ks++) {
        uint4 a = ldsm4t(woff + R_STQ + ks * 2048), b = ldsm4t(woff + R_STK + ks * 2048);
        wq[ks][0] = a.x; wq[ks][1] = a.y; wq[ks][2] = a.z; wq[ks][3] = a.w;
        wk[ks][0] = b.x; wk[ks][1] = b.y; wk[ks][2] = b.z; wk[ks][3] = b.w;
    }
    bar_sync(NB_W, 256);
#pragma unroll
    for (int m = 0; m < 16; m++)
        if (m < NPF || m >= NPF + NWO) sts128(lw + w * 512 + R_WO + (m < NPF ? m : m - NWO) * 4096, wo[m].x, wo[m].y, wo[m].z, wo[m].w);
#pragma unroll
    for (int i = 0; i < 16; i++) {
        wv[i] = ldsm4t(woff + R_STV + i * 2048);
        if (!((VMASK >> i) & 1)) sts128(lw + w * 512 + R_WV + i * 4096, wv[i].x, wv[i].y, wv[i].z, wv[i].w);
    }
    fence_async_smem();
    PROF2(threadIdx.x == 0, 3504);
    __syncthreads();
    cluster_sync();
    PROF2(threadIdx.x == 0, 3505);
    RecW k;
    {
        const int r = (w * 4 + (lane >> 3)) * 2 + rank;
        const uint32_t sl = lds32(sb + R_SEL + r * 4);
        k.po = (w * 8 + rank) * 512 + (head >> 1) * 16 + (head & 1) * 4;
        k.sp = (((lane >> 3) * 1024 + (sl & 1) * 256 + (lane & 4) * 2 + (lane & 3)) << 20) + (((sl >> 1) ^ sl) & 1) + (lane & 7) * 656 + (lane >> 3) * 128 + w * 16 +
               ((g < 4 ? (w * 4 + c) * 4 + g : w * 4 + c) << 13);
    }
    k.dp = mapa(sb, rank ^ 1) - sb;
    k.lw = lw;
    asm volatile("" : "+r"(k.lw));
    k.w = w;
    const int e0 = (p.chains & 1) ? 64 : 0, o1 = (p.chains & 2) ? p.lag : 1000, nit = (p.chains & 2) ? p.lag + 64 : e0;
    const uint32_t zero = p.zero;
    int it = 0, X = e0 ? 0 : 1;
#pragma unroll 1
    while (it < nit) {
        rec_step(k, sb, X, X ? it - o1 : it, zero, o1, e0 - o1, o1 + 1 - X, wq, wk, wv, wo);
        if (X == 0 && it >= o1) X = 1; else { it++; X = it < e0 ? 0 : 1; }
    }
}

__device__ __forceinline__ uint32_t mism(uint32_t a, uint32_t b, uint32_t t) {
    uint32_t d; asm("lop3.b32 %0,%1,%2,%3,0x7e;" : "=r"(d) : "r"(a), "r"(b), "r"(t)); return d;
}
__device__ __forceinline__ uint32_t or3(uint32_t a, uint32_t b, uint32_t c) {
    uint32_t d; asm("lop3.b32 %0,%1,%2,%3,0xfe;" : "=r"(d) : "r"(a), "r"(b), "r"(c)); return d;
}
template <bool TWO, class F>
__device__ __forceinline__ void poll8(uint4* x, const uint4* src, uint32_t tag, F&& use) {
#pragma unroll
    for (int j = 0; j < 8; j++) x[j] = ld_rlx128(src + j * 32);
    int n = 0;
    while (true) {
        use();
        uint32_t bad = or3(mism(x[0].x, x[1].x, tag), mism(x[2].x, x[3].x, tag), mism(x[4].x, x[5].x, tag));
        if (TWO) bad = or3(bad, or3(mism(x[0].z, x[1].z, tag), mism(x[2].z, x[3].z, tag), mism(x[4].z, x[5].z, tag)), mism(x[6].z, x[7].z, tag));
        if (!__any_sync(0xffffffffu, (bad | mism(x[6].x, x[7].x, tag)) & 1)) break;
#pragma unroll
        for (int j = 0; j < 8; j++)
            asm volatile("{.reg .pred p; .reg .b128 t; .reg .b32 m; lop3.b32 m,%0,%6,%5,0x7e; and.b32 m,m,1; setp.ne.u32 p,m,0; mov.b128 t,{%0,%1,%2,%3};"
                         "@p ld.relaxed.gpu.global.b128 t,[%4]; mov.b128 {%0,%1,%2,%3},t;}"
                         : "+r"(x[j].x), "+r"(x[j].y), "+r"(x[j].z), "+r"(x[j].w) : "l"(src + j * 32), "r"(tag), "r"(TWO ? x[j].z : tag) : "memory");
        if (++n > 2000000) __trap();
    }
}

__device__ __forceinline__ void rec_comm(const Params& p, uint32_t sb, int X, int head, uint32_t rank) {
    const int lane = threadIdx.x & 31, g = lane >> 2, c = lane & 3;
    const int me = head * 2 + rank;
    const uint32_t mb = sb + R_M + X * 4096 + lane * 16;
    uint4 x[8];
#pragma unroll
    for (int j = 0; j < 8; j++) x[j] = *(const uint4*)(p.mem0 + (lane & 7) * 512 + rank * 256 + (j * 4 + (lane >> 3)) * 8);
    const uint32_t sl = lds32(sb + R_SEL + me * 4);
    const uint4* src1 = xregion(X, me) + ((sl >> X) & 1) * 256 + (c >> 1) * 16 + (g >> 2) * 8 + (c & 1) * 4 + (g & 3);
    const uint4* src2 = xregion(X, 64 + rank) + ((sl >> (2 + X)) & 1) * 256 + lane;
    uint2* mdst = (uint2*)(xregion(X, 64 + rank) + (c >> 1) * 256 + head * 8 + (g & 3) * 2 + (c & 1)) + (g >> 2);
    const uint32_t one = (g & 1) ? 0x3f800000u : 0x00003f80u, selA = (g & 2) ? 0u : one, selB = (g & 2) ? one : 0u;
    const uint32_t qb = sb + R_BAR + (RB_QK + X * 8) * 8;
    if (lane < 8) mbar_expect(qb + lane * 8, 768);
    __syncwarp();
#pragma unroll
    for (int j = 0; j < 8; j++) sts128(mb + j * 512, x[j].x, x[j].y, x[j].z, x[j].w);
#pragma unroll 1
    for (int s = 0;; s++) {
        bar_arrive(NB_MFULL + X, 288);
        PROF(lane == 0, X * 64 + s);
        bar_sync(NB_PART + X, 288);
        if (s == 63) break;
        const uint32_t tag = (s + 1) & 1;
        asm volatile("{.reg .pred p; setp.lt.u32 p,%0,%1; @p mbarrier.arrive.expect_tx.shared::cta.b64 _,[%0],768;}"
                     ::"r"(((mb + (s & p.zero)) >> 1) + (qb - ((sb + R_M + X * 4096) >> 1))), "r"(qb + 64) : "memory");
        if (SPV) spin_v(D1 + (mb & p.zero)); else spin(D1);
        uint32_t m0, m1;
        auto reduce = [&]() {
            float a[RACC][4];
#pragma unroll
            for (int j = 0; j < 8; j++) {
                if (j < RACC) a[j][0] = a[j][1] = a[j][2] = a[j][3] = 0;
                mma16(a[j % RACC], x[j].x, x[j].y, x[j].z, x[j].w, selA, selB);
            }
#pragma unroll
            for (int i = 0; i < 4; i++) a[0][i] = RACC == 4 ? (a[0][i] + a[1][i]) + (a[2 % RACC][i] + a[3 % RACC][i]) : a[0][i] + a[1][i];
            m0 = (pack2(a[0][0], a[0][1]) & ~1u) | tag; m1 = pack2(a[0][2], a[0][3]);
        };
        poll8<false>(x, src1, tag, [&]() { if (RACC == 2) reduce(); });
        if (RACC == 4) reduce();
        asm volatile("st.relaxed.gpu.global.b64 [%0],%1;" ::"l"(mdst), "l"(((uint64_t)m1 << 32) | m0) : "memory");
        if (SPV) spin_v(D2 + (mb & p.zero)); else spin(D2);
        poll8<true>(x, src2, tag, [&]() {
#pragma unroll
            for (int j = 0; j < SEARLY; j++) sts128(mb + j * 512, x[j].x, x[j].y, x[j].z, x[j].w);
        });
#pragma unroll
        for (int j = SEARLY; j < 8; j++) sts128(mb + j * 512, x[j].x, x[j].y, x[j].z, x[j].w);
    }
}

template <int MT>
__device__ __forceinline__ void xattn(uint32_t l16, uint32_t l8, uint32_t os, int g, int c) {
    constexpr int NT = 3 + 2 * MT, XUN = XU;
    float S[NT][4];
#pragma unroll
    for (int i = 0; i < NT; i++) S[i][0] = S[i][1] = S[i][2] = S[i][3] = 0;
#pragma unroll XUN
    for (int ks = 0; ks < 8; ks++) {
        const uint4 q = lds128(l16 + SL_Q + ks * 512);
        const uint2 u = lds64(l8 + SL_KM + ks * 256);
        mma16(S[0], q.x, q.y, q.z, q.w, u.x, u.y);
#pragma unroll
        for (int m = 0; m <= MT; m++) {
            const uint4 kk = lds128(l16 + m * 4096 + ks * 512);
            mma16(S[1 + 2 * m], q.x, q.y, q.z, q.w, kk.x, kk.z); mma16(S[2 + 2 * m], q.x, q.y, q.z, q.w, kk.y, kk.w);
        }
    }
    const float NEG = -__int_as_float(0x7f800000);
    if (2 * c > g) { S[NT - 2][0] = NEG; S[NT - 1][2] = NEG; }
    if (2 * c + 1 > g) { S[NT - 2][1] = NEG; S[NT - 1][3] = NEG; }
    S[NT - 1][0] = S[NT - 1][1] = NEG;
    float m0 = fmaxf(S[0][0], S[0][1]), m1 = fmaxf(S[0][2], S[0][3]);
#pragma unroll
    for (int i = 1; i < NT; i++) { if (i < NT - 1) m0 = fmaxf(m0, fmaxf(S[i][0], S[i][1])); m1 = fmaxf(m1, fmaxf(S[i][2], S[i][3])); }
    m0 = fmaxf(m0, __shfl_xor_sync(0xffffffffu, m0, 1)); m1 = fmaxf(m1, __shfl_xor_sync(0xffffffffu, m1, 1));
    m0 = fmaxf(m0, __shfl_xor_sync(0xffffffffu, m0, 2)); m1 = fmaxf(m1, __shfl_xor_sync(0xffffffffu, m1, 2));
    m0 *= -SC_LOG2E; m1 *= -SC_LOG2E;
    float l0 = 0, l1 = 0;
#pragma unroll
    for (int i = 0; i < NT; i++) {
        if (i < NT - 1) { S[i][0] = ex2(fmaf(S[i][0], SC_LOG2E, m0)); S[i][1] = ex2(fmaf(S[i][1], SC_LOG2E, m0)); l0 += S[i][0] + S[i][1]; }
        S[i][2] = ex2(fmaf(S[i][2], SC_LOG2E, m1)); S[i][3] = ex2(fmaf(S[i][3], SC_LOG2E, m1)); l1 += S[i][2] + S[i][3];
    }
    l0 += __shfl_xor_sync(0xffffffffu, l0, 1); l1 += __shfl_xor_sync(0xffffffffu, l1, 1);
    l0 += __shfl_xor_sync(0xffffffffu, l0, 2); l1 += __shfl_xor_sync(0xffffffffu, l1, 2);
    uint2 vm = lds64(l8 + SL_VM);
    uint4 v[2];
#pragma unroll
    for (int m = 0; m <= MT; m++) v[m] = lds128(l16 + SL_V + m * 4096);
    l0 = rcp(l0); l1 = rcp(l1);
    uint32_t P[NT][2];
#pragma unroll
    for (int i = 0; i < NT; i++) { P[i][0] = i < NT - 1 ? pack2(S[i][0] * l0, S[i][1] * l0) : 0u; P[i][1] = pack2(S[i][2] * l1, S[i][3] * l1); }
#pragma unroll
    for (int et = 0; et < 8; et++) {
        float a[4] = {0, 0, 0, 0}, b[4] = {0, 0, 0, 0};
        const uint2 um = vm;
        const uint4 u[2] = {v[0], v[MT]};
        if (et < 7) {
            vm = lds64(l8 + SL_VM + et * 256 + 256);
#pragma unroll
            for (int m = 0; m <= MT; m++) v[m] = lds128(l16 + SL_V + m * 4096 + et * 512 + 512);
            PIN(11);
        }
        mma8(a, um.x, um.y, P[0][0]); mma8(b, um.x, um.y, P[0][1]);
#pragma unroll
        for (int m = 0; m <= MT; m++) {
            mma16(a, u[m].x, u[m].y, u[m].z, u[m].w, P[1 + 2 * m][0], P[2 + 2 * m][0]); mma16(b, u[m].x, u[m].y, u[m].z, u[m].w, P[1 + 2 * m][1], P[2 + 2 * m][1]);
        }
        asm volatile("stmatrix.sync.aligned.m8n8.x4.trans.shared.b16 [%0],{%1,%2,%3,%4};" ::"r"(os + (et >> 2) * 2048 + (et & 3) * 256),
                     "r"(pack2(a[0], a[1])), "r"(pack2(a[2], a[3])), "r"(pack2(b[0], b[1])), "r"(pack2(b[2], b[3])) : "memory");
    }
}

__device__ __forceinline__ void rec_tiles(uint32_t sb, int X, int head, uint32_t rank, int& nxt, int lim, int need) {
#pragma unroll 1
    while (nxt <= lim) {
        if ((nxt & 1) == 0) {
            unsigned v; int n = 0;
            while (true) {
                asm volatile("ld.relaxed.gpu.global.u32 %0,[%1];" : "=r"(v) : "l"(cnt_ptr(C_QKV + X * 32 + (nxt >> 1))) : "memory");
                if (__all_sync(0xffffffffu, v >= 2 * NQ)) break;
                if (nxt > need) return;
                if (++n > 3000000) __trap();
            }
        }
        if (elect()) {
            const uint32_t bar = sb + R_BAR + (RB_XFULL + X * 2 + (nxt & 1)) * 8, dst = sb + R_SL + (X * 2 + (nxt & 1)) * SLOT;
            const uint4* src = g_qkv + (size_t)((X * 64 + nxt) * 32 + head) * 1536;
            mbar_expect(bar, 20480);
            bulk_g2s_mc(dst + rank * 8192, src + 512 + rank * 512, 8192, bar, POL_LAST);
            bulk_g2s(dst + SL_Q, src + (rank ^ X) * 256, 4096, bar, POL_LAST);
        }
        __syncwarp();
        nxt++;
    }
}

__device__ __forceinline__ void rec_attn(const Params& p, uint32_t sb, int X, int head, uint32_t rank) {
    const int lane = __shfl_sync(0xffffffffu, threadIdx.x & 31, threadIdx.x & 31), g = lane >> 2, c = lane & 3;
    const int mt = rank ^ X;
    const uint32_t dp = mapa(sb, rank ^ 1) - sb;
    int nxt = 0;
    rec_tiles(sb, X, head, rank, nxt, 1, 0);
#pragma unroll 1
    for (int s = 0; s < 64; s++) {
        const uint32_t so = sb + R_SL + (X * 2 + (s & 1)) * SLOT;
        while (nxt <= min(s + 1, 63)) {
            uint32_t ok;
            asm volatile("{.reg .pred p; mbarrier.test_wait.parity.shared::cta.b64 p,[%1],%2; selp.u32 %0,1,0,p;}" : "=r"(ok) : "r"(sb + R_BAR + (RB_GO + X * 2 + (s & 1)) * 8), "r"((s >> 1) & 1) : "memory");
            if (__any_sync(0xffffffffu, ok)) break;
            rec_tiles(sb, X, head, rank, nxt, s + 1, -1);
        }
        mbar_wait(sb + R_BAR + (RB_GO + X * 2 + (s & 1)) * 8, (s >> 1) & 1);
        if (elect()) asm volatile("cp.async.bulk.wait_group.read 0;" ::: "memory");
        __syncwarp();
        const uint32_t os = sb + R_OS + X * 4096 + (lane >> 4) * 1024 + (lane & 15) * 16;
        if (mt) xattn<1>(so + lane * 16, so + lane * 8, os, g, c); else xattn<0>(so + lane * 16, so + lane * 8, os, g, c);
        fence_async_smem();
        __syncwarp();
        const uint32_t svb = sb + R_BAR + (RB_SV + X * 2 + (s & 1)) * 8;
        if (elect()) {
            mbar_arrive(svb); mbar_arrive_cluster(svb + dp);
            const uint64_t pol = POL_SOON;
#pragma unroll
            for (int kb = 0; kb < 2; kb++)
                asm volatile("cp.async.bulk.global.shared::cta.bulk_group.L2::cache_hint [%0],[%1],%2,%3;" ::"l"(g_o + ((X * 32 + (s >> 1)) * 64 + head * 2 + kb) * 512 + ((s & 1) * 4 + mt * 2) * 64),
                             "r"(sb + R_OS + X * 4096 + kb * 2048), "r"(2048), "l"(pol) : "memory");
            asm volatile("cp.async.bulk.commit_group;" ::: "memory");
        }
        __syncwarp();
        if (s & 1) {
            if (elect()) { asm volatile("cp.async.bulk.wait_group 0;" ::: "memory"); red_relaxed(cnt_ptr(C_O + (X * 32 + (s >> 1)) * 4 + (head >> 3)), 1); }
            __syncwarp();
        }
        rec_tiles(sb, X, head, rank, nxt, min(s + 1, 63), s + 1);
        mbar_wait(svb, (s >> 1) & 1);
        rec_tiles(sb, X, head, rank, nxt, min(s + 2, 63), -1);
    }
}

__device__ __forceinline__ uint32_t timed_clear(unsigned* r, int lane) {
    uint32_t v = 0;
    const uint32_t t0 = clk32();
    asm volatile("{.reg .pred p; setp.eq.u32 p,%2,0; @p atom.relaxed.gpu.global.exch.b32 %0,[%1],0;}" : "+r"(v) : "l"(r), "r"(lane) : "memory");
    v = __shfl_sync(0xffffffffu, v, 0);
    asm volatile("{.reg .pred p; setp.eq.u32 p,%0,0x5a5a5a5b; @p nanosleep.u32 1;}" ::"r"(v) : "memory");
    return clk32() - t0;
}
__device__ __forceinline__ void rec_slots(int me, int w) {
    const int lane = threadIdx.x & 31;
    uint4* r = xregion(w & 1, (w & 2) ? 64 + (me & 1) : me) + ((w & 2) ? (me >> 1) * 8 : 0);
#pragma unroll 1
    for (int i = lane; i < ((w & 2) ? 8 : 256); i += 32) r[i] = r[i + 256] = make_uint4(0, 0, 0, 0);
    __syncwarp();
    uint32_t b0 = ~0u, b1 = ~0u;
#pragma unroll 1
    for (int i = 0; i < NPRB; i++) { b0 = min(b0, timed_clear((unsigned*)r, lane)); b1 = min(b1, timed_clear((unsigned*)(r + 256), lane)); }
    if (lane == 0) ((uint8_t*)g_sel)[me * 4 + w] = (b1 < b0) << w;
}

__device__ __forceinline__ void rec_init(uint32_t sb) {
    const uint32_t b = sb + R_BAR;
    const int i = threadIdx.x & 31;
    mbar_init(b + i * 8, i >= RB_SV ? 2 : 1);
    if (i == RB_INIT) mbar_expect(b + RB_INIT * 8, 196608);
    asm volatile("fence.mbarrier_init.release.cluster;" ::: "memory");
}
constexpr int G_BAR = B_BAR;
enum { GB_FULL = 0  , GB_EMPTY = 8  , GB_RS = 16, GB_SS = 17, GB_LAG = 18, GB_FREE = 19, GB_DONE = 20  , GB_N = 24 };
constexpr int Q_PRE = 8;
constexpr int NQRS = 2 * NQ - 64;
__device__ __forceinline__ void gemm_init(uint32_t sb, bool op) {
    const int i = threadIdx.x & 31;
    if (i < GB_N) mbar_init(sb + G_BAR + i * 8, i >= GB_DONE ? 4 : i == GB_FREE ? 8 : (i >= GB_EMPTY && i < GB_RS) ? 2 : 1);
    if (i == GB_RS) mbar_expect(sb + G_BAR + i * 8, op ? 131072 : 98304);
    if (i == GB_SS) mbar_expect(sb + G_BAR + i * 8, op ? 131072 : 163840);
    asm volatile("fence.mbarrier_init.release.cluster;" ::: "memory");
}
__device__ __forceinline__ int qkv_blk(int id, int j) { return NQRS * 4 + id * 10 + j; }
__device__ __forceinline__ void qkv_fetch(const Params& p, uint32_t sb, int id, int j0, int j1) {
#pragma unroll 1
    for (int j = j0 * 2; j < j1 * 2; j++) {
        const int blk = min(qkv_blk(id, j >> 1), 511);
        tma2d(sb + j * 8192, &p.tn[blk >> 8], (blk & 255) * 16, (j & 1) * 256, sb + G_BAR + GB_SS * 8);
    }
}
__device__ __forceinline__ void qkv_stage(const Params& p, uint32_t dst, uint32_t bar, int id, int k0, int nk) {
#pragma unroll 1
    for (int j = 0; j < 2 * nk; j++) {
        const int u = id * 2 + (j >= nk);
        tma2d(dst + j * 8192, &p.tm[u < 64 ? 2 : 0], (u & 63) * 64, (k0 + (j >= nk ? j - nk : j)) * 64, bar);
    }
}
__device__ __forceinline__ void op_fetch(const Params& p, uint32_t sb, int id, int half) {
#pragma unroll 1
    for (int j = 0; j < 16; j++) tma2d(sb + j * 8192, &p.tm[4], ((id * 2 + (j >> 3)) & 7) * 64, (id >> 2) * 1024 + (j & 7) * 128 + half * 64, sb + G_BAR + (GB_RS + half) * 8);
}
template <bool OP>
__device__ __forceinline__ void gemm_producer(const Params& p, uint32_t sb, int id) {
    constexpr int NS = OP ? 6 : 8, SB = OP ? 16384 : 8192, RB = OP ? 131072 : 163840;
    if (!elect()) return;
    mbar_wait(sb + G_BAR + GB_FREE * 8, 0);
    if (OP) op_fetch(p, sb, id, 1);
    else {
        mbar_expect(sb + G_BAR + GB_RS * 8, 32768);
        qkv_stage(p, sb + 196608, sb + G_BAR + GB_RS * 8, id, 6, 2);
        qkv_fetch(p, sb, id, Q_PRE, 10);
        mbar_wait(sb + G_BAR + GB_FREE * 8, 1);
    }
    wait_cnt(g_gate, lds32(sb + S_GATE));
    int st = 0; uint32_t ph = 1;
#pragma unroll 1
    for (int n = 0; n < p.nl[OP]; n++) {
        const int e = p.list[OP][n];
        wait_cnt(OP ? cnt_ptr(C_O + e * 4 + (id >> 2)) : cnt_ptr(C_XN + e), 16);
        PROF(true, 1024 + n * 4);
        const uint4* src = OP ? g_o + (e * 64 + (id >> 2) * 16) * 512 : g_xn + e * 4096;
#pragma unroll 1
        for (int s = 0; s < 8; s++) {
            mbar_wait(sb + G_BAR + (GB_EMPTY + st) * 8, ph);
            mbar_expect(sb + G_BAR + (GB_FULL + st) * 8, SB);
            bulk_g2s(sb + RB + st * SB, src + s * (SB / 16), SB, sb + G_BAR + (GB_FULL + st) * 8, POL_N);
            if (++st == NS) { st = 0; ph ^= 1; }
        }
    }
}
__device__ __forceinline__ void qkv_release(const Params& p, uint32_t sb) {
    if (!elect()) return;
#pragma unroll 1
    for (int n = 0; n < 2 * p.nl[0]; n++) {
        const int e = p.list[0][n >> 1];
        mbar_wait(sb + G_BAR + (GB_DONE + (n & 3)) * 8, (n >> 2) & 1);
        red_release(cnt_ptr(C_QKV + e), 1);
        PROF(n & 1, 1024 + (n >> 1) * 4 + 3);
    }
}
__device__ __forceinline__ void op_permute(uint32_t sb) {
#pragma unroll 2
    for (int i = threadIdx.x; i < 4096; i += 256) {
        const uint32_t a = sb + i * 32 + ((i >> 2) & 1) * 16, b = a ^ 16;
        const uint4 x = lds128(a), y = lds128(b);
        sts128(a, __byte_perm(x.x, x.y, 0x5410), __byte_perm(x.z, x.w, 0x5410), __byte_perm(y.x, y.y, 0x5410), __byte_perm(y.z, y.w, 0x5410));
        sts128(b, __byte_perm(x.x, x.y, 0x7632), __byte_perm(x.z, x.w, 0x7632), __byte_perm(y.x, y.y, 0x7632), __byte_perm(y.z, y.w, 0x7632));
    }
    fence_async_smem();
    bar_sync(1, 256);
}
template <bool OP>
__device__ __forceinline__ void gemm_consumer(const Params& p, uint32_t sb, int id, int w) {
    constexpr int NS = OP ? 6 : 8, SB = OP ? 16384 : 8192, RB = OP ? 131072 : 163840;
    const int lane = threadIdx.x & 31, wg = w >> 2, t = w & 3, u = id * 2 + wg;
    uint32_t a[128];
    mbar_wait(sb + G_BAR + GB_RS * 8, 0);
    PROF2(threadIdx.x == 0, 3501);
    if (OP) op_permute(sb);
    const uint32_t wo = sb + (((lane >> 4) << 3) + (lane & 7)) * 128 + (((2 * t + ((lane >> 3) & 1)) ^ (lane & 7)) << 4);
#pragma unroll
    for (int ks = 0; ks < 32; ks++) {
        const uint4 v = ldsm4t(wo + ks * 2048 + (OP ? wg * 65536 : ks < 24 ? 131072 + wg * 49152 : 196608 - 49152 + wg * 16384));
        a[ks * 4] = v.x; a[ks * 4 + 1] = v.y; a[ks * 4 + 2] = v.z; a[ks * 4 + 3] = v.w;
        if (ks == 31 || (!OP && ks == 23)) {
            fence_async_smem();
            __syncwarp();
            if (lane == 0) mbar_arrive(sb + G_BAR + GB_FREE * 8);
            if (ks == 23) mbar_wait(sb + G_BAR + GB_RS * 8, 1);
        }
    }
    PROF2(threadIdx.x == 0, 3502);
    mbar_wait(sb + G_BAR + GB_SS * 8, 0);
    if (OP) op_permute(sb);
    PROF2(threadIdx.x == 0, 3503);
    const uint32_t tag = OP ? lds32(sb + S_TAG) : 0;
    float c0[32], c1[OP ? 32 : 40];
    int st = 0; uint32_t ph = 0;
    const bool el = (threadIdx.x & 127) == 0;
#pragma unroll 1
    for (int n = 0; n < p.nl[OP]; n++) {
        int prev = 0;
        const uint32_t wb = sb + wg * (OP ? 65536 : 81920) + (n & p.zero);
        const uint64_t dw = OP ? mkdesc(wb, 0, 1024, 1) : mkdesc(wb, 16384, 256, 3);
        if ((!OP || OLAG) && wg) mbar_wait(sb + G_BAR + GB_LAG * 8, n & 1);
#pragma unroll
        for (int s = 0; s < 8; s++) {
            mbar_wait(sb + G_BAR + (GB_FULL + st) * 8, ph);
            const uint64_t dx = mkdesc(sb + RB + st * SB, 128, 1024, 0);
            wg_fence();
#pragma unroll
            for (int kk = 0; kk < 4; kk++) {
                const int ks = s * 4 + kk;
                if (ks == 0) { wgmma64_rs<0>(c0, a, dx); if (OP) wgmma64_ta<0>(c1, dw, dx + 512); else wgmma80_tb<0>(c1, dx, dw); }
                else { wgmma64_rs<1>(c0, a + ks * 4, dx + kk * 16); if (OP) wgmma64_ta<1>(c1, dw + ks * 128, dx + 512 + kk * 16); else wgmma80_tb<1>(c1, dx + kk * 16, dw + ks * 32); }
            }
            wg_commit();
            if (s) {
                wg_wait<1>();
                if (el) { mbar_arrive(sb + G_BAR + (GB_EMPTY + prev) * 8); if (s == (OP ? OLAG : QLAG) && !wg) mbar_arrive(sb + G_BAR + GB_LAG * 8); }
            }
            prev = st;
            if (++st == NS) { st = 0; ph ^= 1; }
        }
        const int e = p.list[OP][n];
        wg_wait<0>();
        if (el) mbar_arrive(sb + G_BAR + (GB_EMPTY + prev) * 8);
        PROF(threadIdx.x == 128, 1024 + n * 4 + 1);
        if (OP) {
            uint4* dst = g_pp + (e * 4 + (id >> 2)) * 4096 + ((u & 7) * 32 + t * 8) * 16 + (lane >> 2) * 16 + (lane & 3);
#pragma unroll
            for (int j = 0; j < 4; j++) {
                const float* x = c0 + j * 8; const float* y = c1 + j * 8;
                ST_PP(dst + j * 4, (pack2(x[0] + y[0], x[1] + y[1]) & ~1u) | tag, pack2(x[2] + y[2], x[3] + y[3]), (pack2(x[4] + y[4], x[5] + y[5]) & ~1u) | tag, pack2(x[6] + y[6], x[7] + y[7]));
            }
            if (lane == 0) red_relaxed(cnt_ptr(C_PP + e * 8 + (u & 7)), 1);
            PROF(threadIdx.x == 128, 1024 + n * 4 + 3);
        } else {
            uint4* dst = g_qkv + (size_t)e * 2 * 32 * 1536 + lane;
            const uint64_t pol = POL_SOON;
#pragma unroll
            for (int j = 0; j < 4; j++) {
                const float* x = c0 + j * 8;
                uint4 v = make_uint4(pack2(x[0], x[1]), pack2(x[2], x[3]), pack2(x[4], x[5]), pack2(x[6], x[7]));
                if (u >= 64) v = make_uint4(movm(v.x), movm(v.z), movm(v.y), movm(v.w));
                stg128(dst + (((j >> 1) * 32 + ((u & 63) >> 1)) * 1536 + (u < 64 ? 1024 : 0) + (j & 1) * 256 + ((u & 1) * 4 + t) * 32), v, pol);
            }
#pragma unroll
            for (int j = 0; j < 5; j++) {
                const float* x = c1 + (OP ? 0 : j * 8);
                const int blk = qkv_blk(id, wg * 5 + j);
                if (blk < 512) stg128(dst + (((t >> 1) * 32 + ((blk >> 3) & 31)) * 1536 + (blk >> 8) * 512 + (t & 1) * 256 + (blk & 7) * 32),
                                      make_uint4(pack2(x[0], x[1]), pack2(x[2], x[3]), pack2(x[4], x[5]), pack2(x[6], x[7])), pol);
            }
        }
        __syncwarp();
        if (!OP && lane == 0) mbar_arrive(sb + G_BAR + (GB_DONE + (n & 1) * 2 + wg) * 8);
        PROF(threadIdx.x == 128, 1024 + n * 4 + 2);
    }
}

template <int NP, bool MMA>
__device__ __forceinline__ void sum_partials(float* x, const uint2* src, const uint32_t* r0, const uint32_t* r1, uint32_t idm, uint32_t tag, bool on) {
    uint2 v[4][NP];
    int n = 0;
    while (true) {
        uint32_t bad = 0;
#pragma unroll
        for (int s = 0; s < 4; s++)
#pragma unroll
            for (int i = 0; i < NP; i++)
                asm volatile("{.reg .pred p; .reg .b64 t; setp.ne.u32 p,%4,0; mov.b64 t,0; @p ld.relaxed.gpu.global.L2::cache_hint.b64 t,[%2],%3; mov.b64 {%0,%1},t;}"
                             : "=r"(v[s][i].x), "=r"(v[s][i].y) : "l"(src + s * 8192 + i * 32), "l"(POL_LAST), "r"((uint32_t)on) : "memory");
#pragma unroll
        for (int s = 0; s < 4; s++) bad = or3(bad, mism(v[s][0].x, v[s][1].x, tag), mism(v[s][NP - 2].x, v[s][NP - 1].x, tag));
        if (!__any_sync(0xffffffffu, (bad & 1) && on)) break;
        if (++n > 2000000) __trap();
    }
#pragma unroll
    for (int i = 0; i < NP; i++) {
        uint32_t a, b;
        if (MMA) {
            float t[4] = {0, 0, 0, 0};
            mma16(t, v[0][i].x, v[0][i].y, v[1][i].x, v[1][i].y, idm, idm); mma16(t, v[2][i].x, v[2][i].y, v[3][i].x, v[3][i].y, idm, idm);
            a = pack2(t[0], t[2]); b = pack2(t[1], t[3]);
        } else {
            a = pack2((blo(v[0][i].x) + blo(v[1][i].x)) + (blo(v[2][i].x) + blo(v[3][i].x)), (blo(v[0][i].y) + blo(v[1][i].y)) + (blo(v[2][i].y) + blo(v[3][i].y)));
            b = pack2((bhi(v[0][i].x) + bhi(v[1][i].x)) + (bhi(v[2][i].x) + bhi(v[3][i].x)), (bhi(v[0][i].y) + bhi(v[1][i].y)) + (bhi(v[2][i].y) + bhi(v[3][i].y)));
        }
        const uint32_t s0 = hadd2(a, r0[i]), s1 = hadd2(b, r1[i]);
        x[4 * i] = blo(s0); x[4 * i + 2] = bhi(s0); x[4 * i + 1] = blo(s1); x[4 * i + 3] = bhi(s1);
    }
}
__device__ __forceinline__ const uint2* pp_src(int e, int tile, int lane) { return (const uint2*)g_pp + e * 32768 + tile * 128 + (lane >> 3) * 8 + (lane & 3) * 2 + ((lane >> 2) & 1); }

__device__ __forceinline__ void fin_warp(const Params& p, uint32_t sb, int id0) {
    wait_slow_warp(g_gate, lds32(sb + S_GATE));
#pragma unroll 1
    for (int e = id0 < 2 * NQ ? 32 : FJ; e < 64; e++)
#pragma unroll 1
    for (int id = id0; id < (e < FJ ? 128 : id0 + 1); id += 2 * NQ) {
        const int grp = (id & ~3) + (threadIdx.x & 3), tp = (id & 3) * 8 + ((threadIdx.x & 31) >> 2);
        wait_slow_warp(cnt_ptr(C_XN + e), 16);
        const uint4 r = ldcg128(g_x + ((128 + grp) * XP + (e - 32) * 32 + tp));
        if (e < 63) wait_slow_warp(cnt_ptr(C_PP + e * 8 + (id >> 4)), 16); else wait_slow_warp(cnt_ptr(C_O + 63 * 4), 16);
        wait_flag_warp(cnt_ptr(C_PP + e * 8 + (id >> 4)), 16);
        const uint32_t a[2] = {r.x, r.y}, b[2] = {r.z, r.w};
        float x[8];
        sum_partials<2, false>(x, pp_src(e, 0, tp) + grp * 64, a, b, 0, lds32(sb + S_TAG), true);
        uint2* dst = (uint2*)p.out + ((e - 32) * 64 + tp * 2) * 128 + grp;
#pragma unroll
        for (int t = 0; t < 2; t++)
            dst[t * 128] = make_uint2(__byte_perm(__float_as_uint(x[t]), __float_as_uint(x[2 + t]), 0x7632), __byte_perm(__float_as_uint(x[4 + t]), __float_as_uint(x[6 + t]), 0x7632));
        PROF((threadIdx.x & 31) == 0, 1536 + e);
    }
}

constexpr int PROW = 272, UROW = 2560, UPRE = 512;
constexpr int C_UR = 0  , C_TB = 65536  , C_BG = C_TB + 51200,
              CB_M = 7168, CB_U = CB_M + 1792, CB_BIG = CB_U + 2048, C_ST = C_BG + 8 * CB_BIG  ;
static_assert(C_ST + 4736 <= B_BAR, "smem map");
enum { CB_TB = 0, CB_UF = 1  , CB_CF = 5  , CB_LD = 9   };
__device__ __forceinline__ void conv_init(uint32_t sb, bool spare) {
    const int i = threadIdx.x & 31;
    mbar_init(sb + B_BAR + i * 8, (i >= CB_UF && i < CB_CF && !spare) ? 2 : 1);
    if (i == CB_TB && !spare) mbar_expect(sb + B_BAR + i * 8, 51200);
    asm volatile("fence.mbarrier_init.release.cluster;" ::: "memory");
}
__device__ __forceinline__ void mma_q(float* c, const uint32_t* a, const uint4& q) {
    mma16(c, a[0], a[1], a[2], a[3], q.x, q.y); mma16(c, a[4], a[5], a[6], a[7], q.z, q.w);
}
__device__ __forceinline__ uint2 ld_acc(const uint2* p, bool on) {
    uint2 v = make_uint2(0, 0);
    asm volatile("{.reg .pred p; setp.ne.u32 p,%3,0; @p ld.global.cg.v2.u32 {%0,%1},[%2];}" : "+r"(v.x), "+r"(v.y) : "l"(p), "r"((uint32_t)on) : "memory");
    return v;
}
__device__ __forceinline__ void add_acc(float* c, uint2 v) { c[0] += blo(v.x); c[1] += bhi(v.x); c[2] += blo(v.y); c[3] += bhi(v.y); }
__device__ __forceinline__ void st_acc(uint2* p, const float* c) { *p = make_uint2(pack2(c[0], c[1]), pack2(c[2], c[3])); }
__device__ __forceinline__ float sum8(const uint4* v, int k) {
#define VK(i) __uint_as_float(k == 0 ? v[i].x : k == 1 ? v[i].y : k == 2 ? v[i].z : v[i].w)
    return ((VK(0) + VK(1)) + (VK(2) + VK(3))) + ((VK(4) + VK(5)) + (VK(6) + VK(7)));
}
template <int XW>
__device__ __forceinline__ void stats_send(uint32_t l16, const float* x, uint4* gs, int q, int w) {
    float s0 = 0, s1 = 0, m0 = 0, m1 = 0;
#pragma unroll
    for (int i = 0; i < 8; i++) { s0 += x[2 * i]; s1 += x[2 * i + 1]; m0 = fmaf(x[2 * i], x[2 * i], m0); m1 = fmaf(x[2 * i + 1], x[2 * i + 1], m1); }
    sts128(l16 + C_ST + w * 512, __float_as_uint(s0), __float_as_uint(m0), __float_as_uint(s1), __float_as_uint(m1));
    if (w == XW) {
        bar_sync(2, 256);
        uint4 v[8];
#pragma unroll
        for (int i = 0; i < 8; i++) v[i] = lds128(l16 + C_ST + i * 512);
        st_rlx128(gs + q * 32, __float_as_uint(sum8(v, 0)), __float_as_uint(sum8(v, 1)) & 0x7fffffffu, __float_as_uint(sum8(v, 2)), __float_as_uint(sum8(v, 3)));
    } else bar_arrive(2, 256);
}
template <int XW>
__device__ __forceinline__ float4 stats_recv(uint32_t l16, const uint4* gs, int w) {
    if (w == XW) {
        uint4 v[8];
        int n = 0;
        while (true) {
            uint32_t bad = 0;
#pragma unroll
            for (int i = 0; i < 8; i++) v[i] = ld_rlx128(gs + i * 32);
#pragma unroll
            for (int i = 0; i < 8; i++) bad |= v[i].y;
            if (!__any_sync(0xffffffffu, bad >> 31)) break;
            if (++n > 2000000) __trap();
        }
        const float s0 = sum8(v, 0) * (1.f / 512.f), s1 = sum8(v, 2) * (1.f / 512.f);
        const float2 l0 = ln_finish(s0, fmaxf(fmaf(sum8(v, 1), 1.f / 512.f, -s0 * s0), 0.f)), l1 = ln_finish(s1, fmaxf(fmaf(sum8(v, 3), 1.f / 512.f, -s1 * s1), 0.f));
        sts128(l16 + C_ST + 4096, __float_as_uint(l0.x), __float_as_uint(rcp(l0.y)), __float_as_uint(l1.x), __float_as_uint(rcp(l1.y)));
    }
    bar_sync(3, 256);
    const uint4 r = lds128(l16 + C_ST + 4096);
    return make_float4(__uint_as_float(r.x), __uint_as_float(r.y), __uint_as_float(r.z), __uint_as_float(r.w));
}

__device__ __forceinline__ void conv_near(float (*acc)[4], uint32_t ta, uint32_t qa) {
    uint32_t a[9][8];
    uint4 x[9];
#pragma unroll
    for (int k = 0; k < 9; k++) {
        if (k < 8) {
            x[k] = ldsm4(qa + k * 1024);
#pragma unroll
            for (int j = 0; j < 8; j++) a[k][j] = lds32(ta + k * 800 + j * 32);
        }
        if (k) mma_q(acc[k - 1], a[k - 1], x[k - 1]);
        PIN(13);
    }
}
template <int K0>
__device__ __forceinline__ void conv_pair(float (*acc)[4], float (*pend)[4], uint32_t ta, uint32_t q0, uint32_t q1, uint32_t q2) {
    uint32_t a[9][8];
    uint4 x[9], y[5];
#pragma unroll
    for (int n = 0; n < 9; n++) {
        if (n < 8) {
            const int k = K0 + (n >> 1);
            if (!(n & 1)) y[n >> 1] = ldsm4(q1 + k * 1024);
            x[n] = ldsm4(((n & 1) ? q0 : q2) + k * 1024);
#pragma unroll
            for (int j = 0; j < 8; j++) a[n][j] = lds32(ta + 256 + (n & 1) * 256 + k * 800 + j * 32);
        }
        if (n == 0) {
#pragma unroll
            for (int i = 0; i < 16; i++) { acc[4 - K0 + (i >> 2)][i & 3] += pend[i >> 2][i & 3]; pend[i >> 2][i & 3] = 0; }
        } else {
            const int m = n - 1, i = m >> 1;
            mma_q(acc[K0 + i], a[m], (m & 1) ? x[m] : y[i]); mma_q(pend[i], a[m], (m & 1) ? y[i] : x[m]);
        }
        PIN(13);
    }
}

__device__ __forceinline__ void conv_tile(const Params& p, uint32_t sb, int q, int w) {
    const int lane = __shfl_sync(0xffffffffu, threadIdx.x & 31, threadIdx.x & 31), g = lane >> 2, c = lane & 3, tile = q * 8 + w;
    const uint32_t l16 = sb + lane * 16;
#pragma unroll
    for (int i = 0; i < 16; i++) sts128(l16 + C_UR + w * 8192 + i * 512, 0, 0, 0, 0);
    wait_slow_warp(g_gate, lds32(sb + S_GATE));
    if (lane < 8) bulk_g2s(sb + C_TB + (w * 8 + lane) * 800, g_P + (tile * 8 + lane) * PROW + 72, 800, sb + B_BAR + CB_TB * 8, POL_N);
    uint32_t A[8][8];
#pragma unroll
    for (int k = 0; k < 8; k++)
#pragma unroll
        for (int j = 0; j < 8; j++) A[k][j] = __ldcg(g_P + (tile * 8 + k) * PROW + 16 + 8 * j + g - 2 * c);
    if (lane == 0) { const uint4 d = __ldg((const uint4*)p.Dskip + tile); sts128(sb + C_ST + 4608 + w * 16, d.x, d.y, d.z, d.w); }
    float acc[8][4], pend[4][4];
#pragma unroll
    for (int k = 0; k < 8; k++) acc[k][0] = acc[k][1] = acc[k][2] = acc[k][3] = pend[k & 3][k >> 2] = pend[k & 3][2 + (k >> 2)] = 0;
    const uint32_t row = sb + C_UR + w * 8192, ta = sb + C_TB + w * 6400 + (8 + g - 2 * c) * 4, qo = (lane & 7) * 16 - (lane >> 3) * 32;
    bar_sync(4, 384);
    mbar_wait(sb + B_BAR + CB_TB * 8, 0);
#pragma unroll 1
    for (int b = -2; b < 32; b++) {
        const int lz = lane + (b & p.zero);
        const bool on = b >= 0;
        uint4 r0 = make_uint4(0, 0, 0, 0), r1 = r0;
        asm volatile("{.reg .pred p; setp.ge.s32 p,%9,0; @p ld.global.cg.v4.u32 {%0,%1,%2,%3},[%8]; @p ld.global.cg.v4.u32 {%4,%5,%6,%7},[%8+%10];}"
                     : "+r"(r0.x), "+r"(r0.y), "+r"(r0.z), "+r"(r0.w), "+r"(r1.x), "+r"(r1.y), "+r"(r1.z), "+r"(r1.w) : "l"(g_x + (tile * 2 * XP + b * 32 + lz)), "r"(b), "n"(XP * 16) : "memory");
        const uint32_t q1 = row + ((qo + (b - 1) * 128) & 1023);
        if ((NTOP >> w) & 1) conv_near(acc, ta, q1);
        PROF2(threadIdx.x == 0 && on, 2048 + b * 8);
        const uint2* pps = pp_src(b, tile, lz);
        asm volatile("" : "+l"(pps));
        const uint32_t tag = lds32(sb + S_TAG);
        wait_flag_warp(cnt_ptr(C_PP + b * 8 + q), on ? 16 : 0);
        PROF2(threadIdx.x == 0 && on, 2048 + b * 8 + 1);
        float x[16];
        {
            const uint32_t a[4] = {r0.x, r0.y, r1.x, r1.y}, bb[4] = {r0.z, r0.w, r1.z, r1.w};
            sum_partials<4, true>(x, pps, a, bb, (2 * (lz & 3) == lz >> 2) ? 0x00003f80u : (2 * (lz & 3) + 1 == lz >> 2) ? 0x3f800000u : 0u, tag, on);
        }
        stats_send<0>(l16, x, g_st + (b + 2) * 256 + lz, q, w);
        {
            PROF2(threadIdx.x == 0 && on, 2048 + b * 8 + 2);
            if (on) mbar_wait(sb + B_BAR + (CB_CF + (w >> 1)) * 8, b & 1);
            const uint2* cb = g_carry + ((tile * 320 + b) * 32 + lz);
            uint2 cr[8];
#pragma unroll
            for (int k = 0; k < 8; k++) cr[k] = ld_acc(cb + k * 1280, b >= 4);
            if (NTOP != 255 && !((NTOP >> w) & 1) && b) conv_near(acc, ta, q1);
#pragma unroll
            for (int k = 0; k < 8; k++) add_acc(acc[k], cr[k]);
        }
        PIN(13);
        float4 ln = stats_recv<0>(l16, g_st + (b + 2) * 256 + lz, w);
        PROF2(threadIdx.x == 0 && on, 2048 + b * 8 + 3);
        uint32_t u[8];
#pragma unroll
        for (int k = 0; k < 8; k++) {
            u[k] = pack2(rbf(x[2 * k] - ln.x) * ln.y, rbf(x[2 * k + 1] - ln.z) * ln.w);
            sts32(row + k * 1024 + (b & 7) * 128 + lane * 4, u[k]);
        }
        __syncwarp();
        const uint32_t qa = row + ((qo + b * 128) & 1023);
        {
            uint4 xq[8];
#pragma unroll
            for (int k = 0; k < 4; k++) xq[k] = ldsm4(qa + k * 1024);
#pragma unroll
            for (int k = 0; k < 8; k += 2) {
                PIN(13);
                mma_q(acc[k], A[k], xq[k]); mma_q(acc[k + 1], A[k + 1], xq[k + 1]);
                if (k < 4) { xq[k + 4] = ldsm4(qa + (k + 4) * 1024); xq[k + 5] = ldsm4(qa + (k + 5) * 1024); }
            }
        }
        const uint4 dk = lds128(sb + C_ST + 4608 + w * 16);
#pragma unroll
        for (int k = 0; k < 8; k++) {
            const float t = __shfl_sync(0xffffffffu, acc[k][3], (lz & ~3) | ((lz - 1) & 3));
            const uint32_t y = movm(pack2(acc[k][0] + (c ? t : 0.f), acc[k][1] + acc[k][2]));
            acc[k][0] = c ? 0.f : t; acc[k][1] = acc[k][2] = acc[k][3] = 0;
            const uint32_t dw = k >> 1 == 0 ? dk.x : k >> 1 == 1 ? dk.y : k >> 1 == 2 ? dk.z : dk.w;
            const uint32_t s = hadd2(hadd2(y, hmul2(u[k], __byte_perm(dw, 0, (k & 1) ? 0x3232 : 0x1010))), __byte_perm(__float_as_uint(x[2 * k]), __float_as_uint(x[2 * k + 1]), 0x7632));
            x[2 * k] = blo(s); x[2 * k + 1] = bhi(s);
        }
        arrive_if(sb + B_BAR + (CB_UF + (w >> 1)) * 8, lz, b < -1 ? 32 : 0);
        stats_send<1>(l16, x, g_st + (36 + b) * 256 + lz, q, w);
        {
            PROF2(threadIdx.x == 0 && on, 2048 + b * 8 + 4);
            uint4* dst = g_x + ((128 + tile * 2) * XP + b * 32 + lz);
#pragma unroll
            for (int e = 0; e < 2; e++) {
                const float* y = x + e * 8;
                if (on) dst[e * XP] = make_uint4(__byte_perm(__float_as_uint(y[0]), __float_as_uint(y[2]), 0x7632), __byte_perm(__float_as_uint(y[4]), __float_as_uint(y[6]), 0x7632),
                                           __byte_perm(__float_as_uint(y[1]), __float_as_uint(y[3]), 0x7632), __byte_perm(__float_as_uint(y[5]), __float_as_uint(y[7]), 0x7632));
            }
            uint32_t* du = g_u + (tile * 8 * (UROW / 2) + UPRE / 2 + b * 32 + lz);
#pragma unroll
            for (int k = 0; k < 8; k++) if (on) du[k * (UROW / 2)] = u[k];
        }
#pragma unroll 1
        for (int pass = 0; pass < 2; pass++) {
            if (pass == ((PLATE >> w) & 1)) {
                const uint32_t q0 = row + ((qo + (b - 2) * 128) & 1023);
                if (b & 1) conv_pair<4>(acc, pend, ta, q0, q1, qa); else conv_pair<0>(acc, pend, ta, q0, q1, qa);
            }
            if (pass) break;
            ln = stats_recv<1>(l16, g_st + (36 + b) * 256 + lz, w);
            PROF2(threadIdx.x == 0 && on, 2048 + b * 8 + 5);
            uint32_t o[2][4];
#pragma unroll
            for (int e = 0; e < 2; e++) {
                const float mu = e ? ln.z : ln.x, rs = e ? ln.w : ln.y;
#pragma unroll
                for (int i = 0; i < 4; i++) o[e][i] = pack2(rbf(x[4 * i + e] - mu) * rs, rbf(x[4 * i + 2 + e] - mu) * rs);
            }
#pragma unroll
            for (int i = 0; i < 4; i++) {
                const uint32_t t = __shfl_xor_sync(0xffffffffu, (lz & 1) ? o[0][i] : o[1][i], 1);
                if (lz & 1) o[0][i] = t; else o[1][i] = t;
            }
            uint4* dst = g_xn + ((32 + b) * 4096 + q * 512 + (lz >> 2) * 64 + w * 8 + (lz & 2) * 2 + (lz & 1));
            if (on) { dst[0] = make_uint4(o[0][0], o[0][1], o[0][2], o[0][3]); dst[2] = make_uint4(o[1][0], o[1][1], o[1][2], o[1][3]); }
            if (w == 7) {
                bar_sync(5, 256);
                if (elect()) red_release(cnt_ptr(on ? C_XN + 32 + b : C_FAR + 8), 2);
                PROF(lane == 0 && on, 2048 + b * 8 + 6);
                __syncwarp();
            } else bar_arrive(5, 256);
        }
    }
}

template <int P0, bool TRI = false, int R0 = 0>
__device__ __forceinline__ void bg_half(float (*acc)[4], uint4* win, uint32_t ta, uint32_t qa, uint32_t mask, uint32_t row) {
#pragma unroll
    for (int i = 0; i < 4; i++) {
        win[P0 + i] = ldsm4(((qa + i * 128) & mask) + row);
        const uint4 a = lds128(ta + (3 - i) * 448), e = lds128(ta + (3 - i) * 448 + 224);
#pragma unroll
        for (int r = TRI ? 7 - P0 - i : R0; r < 8; r++) mma16(acc[r], a.x, a.y, a.z, a.w, win[(P0 + i + 1 + r) & 7].x, win[(P0 + i + 1 + r) & 7].y);
#pragma unroll
        for (int r = TRI ? 7 - P0 - i : R0; r < 8; r++) mma16(acc[r], e.x, e.y, e.z, e.w, win[(P0 + i + 1 + r) & 7].z, win[(P0 + i + 1 + r) & 7].w);
    }
}
__device__ __forceinline__ void bg_fetch(uint32_t sb, int q, int j, int n) {
    const int b0 = n >> 1, ch = q * 64 + j * 16 + (n & 1) * 8 + (b0 & 7), skip = max(12 - b0, 0);
    const uint32_t bar = sb + B_BAR + (CB_LD + j * 2 + (n & 1)) * 8, buf = sb + C_BG + (j * 2 + (n & 1)) * CB_BIG;
    if (elect()) {
        mbar_expect(bar, CB_BIG - skip * 128);
        bulk_g2s(buf, g_W + ch * 784, CB_M, bar, POL_N);
        bulk_g2s(buf + CB_M, g_W + (ch ^ 4) * 784, 1792, bar, POL_N);
        bulk_g2s(buf + CB_U + skip * 128, g_u + ch * (UROW / 2) + UPRE / 2 + (b0 - 20 + skip) * 32, 2048 - skip * 128, bar, POL_N);
    }
    __syncwarp();
}
__device__ __forceinline__ void conv_back(uint32_t sb, int q, int j) {
    const int lane = __shfl_sync(0xffffffffu, threadIdx.x & 31, threadIdx.x & 31), g = lane >> 2, c = lane & 3;
    wait_slow_warp(g_gate, lds32(sb + S_GATE));
    bg_fetch(sb, q, j, 0);
    bar_sync(4, 384);
    const uint32_t to = (6 + g - 2 * c) * 16, qo = (lane & 7) * 16 - (lane >> 3) * 32;
#pragma unroll 1
    for (int n = 0; n < 64; n++) {
        const int b0 = n >> 1, i = n & 1, chl = j * 16 + i * 8 + (b0 & 7);
        const uint32_t buf = sb + C_BG + (j * 2 + i) * CB_BIG, ta = buf + to;
        float acc[8][4];
        uint4 win[8];
        if (n < 63) bg_fetch(sb, q, j, n + 1);
        if (b0 >= 17 && b0 < 29 && (b0 < 21 || b0 >= 25) && i == 0) wait_flag_warp(cnt_ptr(C_FAR + (b0 >= 25) * 4 + ((b0 - 1) & 3)), 12);
        uint2* cr = g_carry + (((q * 64 + chl) * 40 + b0) * 32 + lane);
        uint2* cm = g_carry + (((q * 64 + (chl ^ 4)) * 40 + b0) * 32 + lane);
        uint2 pm[4], pf[8];
#pragma unroll
        for (int r = 0; r < 4; r++) pm[r] = ld_acc(cm + r * 32, b0 > 4);
#pragma unroll
        for (int r = 0; r < 8; r++) acc[r][0] = acc[r][1] = acc[r][2] = acc[r][3] = 0;
        mbar_wait(sb + B_BAR + (CB_LD + j * 2 + i) * 8, b0 & 1);
        if (b0 > 12) {
#pragma unroll
            for (int r = 1; r < 8; r++) win[(r + 4) & 7] = ldsm4(buf + CB_U + qo + r * 128);
        } else {
#pragma unroll
            for (int r = 1; r < 8; r++) win[(r + 4) & 7] = make_uint4(0, 0, 0, 0);
        }
        win[4] = make_uint4(0, 0, 0, 0);
#pragma unroll 1
        for (int h = b0 > 8 ? 4 : 2; h >= 2; h -= 2) {
            if (h == 2) {
                if (b0 > 4) bg_half<0>(acc, win, ta + 2 * 1792, qo + 12 * 128, ~0u, buf + CB_U);
                if (i == 0) mbar_wait(sb + B_BAR + (CB_UF + j) * 8, b0 & 1);
            }
            bg_half<4>(acc, win, ta + (h - 1) * 1792, qo + (h == 2 ? b0 - 4 : 8) * 128, h == 2 ? 1023u : ~0u, h == 2 ? sb + C_UR + chl * 1024 : buf + CB_U);
        }
        uint4 wm[8], a[9], e[9];
#pragma unroll
        for (int r = 1; r < 8; r++) wm[r] = ldsm4(sb + C_UR + (chl ^ 4) * 1024 + ((qo + (b0 + r) * 128) & 1023));
        a[7] = lds128(ta + 7 * 224); e[7] = lds128(ta + CB_M + 7 * 224);
#pragma unroll
        for (int r = 4; r < 8; r++) { st_acc(cr + r * 32, acc[r]); acc[r][0] = blo(pm[r - 4].x); acc[r][1] = bhi(pm[r - 4].x); acc[r][2] = blo(pm[r - 4].y); acc[r][3] = bhi(pm[r - 4].y); }
#pragma unroll
        for (int t = 7; t >= 0; t--) {
            if (t) { a[t - 1] = lds128(ta + (t - 1) * 224); e[t - 1] = lds128(ta + CB_M + (t - 1) * 224); }
            if (t == FT) {
                const uint2* f0 = g_far + (((q * 64 + chl) * 12 + b0 - 20) * 32 + lane);
                const uint2* f1 = g_far + (((q * 64 + (chl ^ 4)) * 12 + b0 - 20) * 32 + lane);
#pragma unroll
                for (int r = 0; r < 4; r++) { const bool on = (unsigned)(b0 + r - 20) < 12u; pf[r] = ld_acc(f0 + r * 32, on); pf[4 + r] = ld_acc(f1 + r * 32, on); }
            }
            PIN(14);
#pragma unroll
            for (int r = 0; r < 4; r++) { const uint4& x = win[4 + r - (t >> 1)]; mma16(acc[r], a[t].x, a[t].y, a[t].z, a[t].w, (t & 1) ? x.z : x.x, (t & 1) ? x.w : x.y); }
#pragma unroll
            for (int r = 0; r < 4; r++) { const uint4& x = wm[4 + r - (t >> 1)]; mma16(acc[4 + r], e[t].x, e[t].y, e[t].z, e[t].w, (t & 1) ? x.z : x.x, (t & 1) ? x.w : x.y); }
        }
#pragma unroll
        for (int r = 0; r < 4; r++) { add_acc(acc[r], pf[r]); add_acc(acc[4 + r], pf[4 + r]); st_acc(cr + r * 32, acc[r]); st_acc(cm + r * 32, acc[4 + r]); }
        __syncwarp();
        arrive_if(sb + B_BAR + (CB_CF + j) * 8, lane, i ? 0 : 32);
        PROF(j == 0 && lane == 0 && i, 2048 + b0 * 8 + 7);
    }
}
template <int PART>
__device__ __forceinline__ void conv_far(uint32_t sb, int w) {
    constexpr int NT = PART ? 5376 : 3584, NU = PART ? 1664 : 1152;
    const int lane = __shfl_sync(0xffffffffu, threadIdx.x & 31, threadIdx.x & 31), g = lane >> 2, c = lane & 3;
    wait_slow_warp(cnt_ptr(C_XN + (PART ? 43 : 39)), 16);
    const uint32_t to = (6 + g - 2 * c) * 16, qo = (lane & 7) * 16 - (lane >> 3) * 32;
#pragma unroll 1
    for (int n = -1; n < 44; n++) {
        const int t = n * 12 + w, tn = min(t + 12, 511), ch = (t & 127) * 4 + (((t >> 7) + 1) & 3), cn = (tn & 127) * 4 + (((tn >> 7) + 1) & 3);
        const uint32_t bar = sb + B_BAR + (w * 2 + (n & 1)) * 8, buf = sb + (w * 2 + (n & 1)) * 7168;
        if (n < 43 && elect()) {
            const uint32_t nb = sb + (w * 2 + (~n & 1)) * 7168;
            mbar_expect(bar ^ 8, NT + NU);
            bulk_g2s(nb, g_W + cn * 784 + 448, NT, bar ^ 8, POL_N);
            bulk_g2s(nb + 5376, g_u + cn * (UROW / 2) + UPRE / 2 - 32, NU, bar ^ 8, POL_N);
        }
        __syncwarp();
        if (n < 0) continue;
        mbar_wait(bar, (n >> 1) & 1);
        if (t >= 512) continue;
        float acc[8][4];
        uint4 win[8];
#pragma unroll
        for (int r = 0; r < 8; r++) acc[r][0] = acc[r][1] = acc[r][2] = acc[r][3] = 0;
        bg_half<0, true, PART * 4>(acc, win, buf + to + NT - 1792, qo + 128, ~0u, buf + 5376);
        bg_half<4, !PART, PART * 4>(acc, win, buf + to + NT - 3584, qo + 640, ~0u, buf + 5376);
        if (PART) bg_half<0, false, 4>(acc, win, buf + to, qo + 1152, ~0u, buf + 5376);
#pragma unroll
        for (int r = PART * 4; r < 8; r++) st_acc(g_far + (ch * 384 + lane) + (r + PART * 4) * 32, acc[r]);
        __syncwarp();
        if (((t + 12) ^ t) >= 128 && elect()) red_release(cnt_ptr(C_FAR + PART * 4 + (t >> 7)), 1);
        __syncwarp();
    }
    PROF(threadIdx.x == 0, 2048 + PART);
}

constexpr int P_X = 131072  , P_K6 = P_X + 32768  , P_P = P_K6 + 10496  , P_U = P_P + 33280  ,
              P_END = P_U + 17408, P_PRM = P_P + 8192  , P_Y = P_P  ;
static_assert(P_END <= B_BAR && P_END <= R_SEL, "prologue scratch");
#define KGUN 2
constexpr int KGU = KGUN;
__device__ __forceinline__ void csq(float& r, float& i) { const float t = r * i; r = fmaf(r, r, -(i * i)); i = t + t; }
__device__ __forceinline__ void cpow(float ar, float ph, float p, float& r, float& i) {
    const float e = ex2(ar * p);
    const float u = ph * p, n = fabsf(u) < 4194304.f ? (u + 12582912.f) - 12582912.f : u;
    const float t = (u - n) * 6.283185307179586f;
    r = e * __cosf(t); i = e * __sinf(t);
}
__device__ __forceinline__ void mma_tf32(float* c, float a0, float a1, float a2, float a3, float b0, float b1) {
    asm volatile("mma.sync.aligned.m16n8k8.row.col.f32.tf32.tf32.f32 {%0,%1,%2,%3},{%4,%5,%6,%7},{%8,%9},{%0,%1,%2,%3};"
                 : "+f"(c[0]), "+f"(c[1]), "+f"(c[2]), "+f"(c[3])
                 : "r"(__float_as_uint(a0)), "r"(__float_as_uint(a1)), "r"(__float_as_uint(a2)), "r"(__float_as_uint(a3)), "r"(__float_as_uint(b0)), "r"(__float_as_uint(b1)));
}

__device__ __forceinline__ void early_fetch(const Params& p, uint32_t sb) {
    const int v = blockIdx.x;
    if (elect()) {
        if (v >= V_QKV) { if (v < V_QKV + NQ && (p.roles & 8)) qkv_fetch(p, sb, v - V_QKV, 0, Q_PRE); }
        else if (v >= V_OP) { if (p.roles & 4) op_fetch(p, sb, v - V_OP, 0); }
        else if (REARLY && v >= V_REC && (p.roles & 2)) { rec_fetch(p, sb, (v - V_REC) >> 1, v & 1, 0, R_STQ); rec_fetch(p, sb, (v - V_REC) >> 1, v & 1, 2, R_STV); }
    }
    __syncwarp();
}
struct ProRegs { uint32_t v[2][4], ldt[2]; };
__device__ __forceinline__ void prologue_load(const ProArgs& a, int b, ProRegs& pr) {
    const int w = threadIdx.x >> 5;
#pragma unroll
    for (int i = 0; i < 2; i++) {
        const int gi = b * 512 + (w & 3) * 128 + ((w >> 2) & 1) * 64 + i * 32 + (threadIdx.x & 31);
        pr.ldt[i] = __ldg((const uint16_t*)a.ldt + b * 4 + (w & 3));
        pr.v[i][0] = __ldg((const uint16_t*)a.lAr + gi); pr.v[i][1] = __ldg((const uint16_t*)a.Ai + gi);
        pr.v[i][2] = __ldg((const uint16_t*)a.Cr + gi); pr.v[i][3] = __ldg((const uint16_t*)a.Ci + gi);
    }
}
__device__ __forceinline__ void prologue(const Params& p, uint32_t sb, int b, int w, const ProRegs& pr) {
    const ProArgs& a = p.pa;
    const int tid = threadIdx.x, lane = tid & 31, g = lane >> 2, c = lane & 3;
    const int d0 = b * 4;
    if (w >= 8) {
        const int t2 = tid - 256;
        if (w < 10) {
            const int row = b * 16 + (w - 8) * 8 + g;
            uint4 v[16];
            const float2 r = row_stats512(v, (const uint4*)(a.x + (size_t)row * 512) + c, 8, 4);
            const float2 l = ln_finish(r.x * (1.f / 512.f), r.y * (1.f / 512.f));
            if (c == (g >> 1)) asm volatile("st.relaxed.gpu.global.u32 [%0],%1;" ::"l"(g_ln0 + row), "r"(pack2(l.x, l.y)) : "memory");
            __syncwarp();
        } else if (PF0) {
            spin(PFD);
            if (elect()) {
#pragma unroll 1
                for (int i = w - 10; i < 4; i += 2) if ((PF0 >> i) & 1) asm volatile("cp.async.bulk.prefetch.L2.global [%0],%1;" ::"l"(a.W[i] + b * 16384), "r"(32768) : "memory");
            }
            __syncwarp();
        }
        if (b + 4 >= V_REC && b + 4 < V_OP) rec_slots(b + 4 - V_REC, (w & 3) ^ 2);
        PROF(t2 == 0, 3516);
        const int gi = b * 128 + t2;
        g_st[gi] = make_uint4(~0u, ~0u, ~0u, ~0u);
        if (gi < 1024) g_st[16384 + gi] = make_uint4(~0u, ~0u, ~0u, ~0u);
        if (gi < 912 * 8) g_cnt[gi] = 0;
        bar_sync(6, 384);
        if (lane < 4 && ((PFM >> (w - 8)) & 1)) asm volatile("cp.async.bulk.prefetch.L2.global [%0],%1;" ::"l"(a.W[w - 8] + (b * 4 + lane) * 4096), "r"(8192) : "memory");
        bar_sync(9, 384);
#pragma unroll 1
        for (int pass = 0; pass < 2; pass++) {
        if (w == 10 && pass == (b + 4 < EFS)) early_fetch(p, sb);
        if (pass) break;
#pragma unroll 2
        for (int i = t2; i < 4 * 784; i += 128) {
            const int ch = i / 784, k = i - ch * 784;
            const uint32_t o = sb + P_P + (ch * 2080 + 266 + (k / 14) * 18 + k) * 4;
            g_W[d0 * 784 + i] = make_uint4(lds32(o), lds32(o + 32), lds32(o + 64), lds32(o + 96));
        }
        bar_arrive(10, 384);
        }
        PROF(t2 == 0, 3517);
        return;
    }
#pragma unroll
    for (int i = 0; i < 2; i++) {
        const float dt = rbf(expf(blo(pr.ldt[i])));
        const float ar = -rbf(expf(blo(pr.v[i][0]))) * dt, ai = blo(pr.v[i][1]) * dt;
        sts128(sb + P_PRM + (w * 64 + i * 32 + lane) * 16, __float_as_uint(ar * 1.4426950408889634f), __float_as_uint(ai * 0.15915494309189535f),
               __float_as_uint(2.f * (blo(pr.v[i][2]) * dt)), __float_as_uint(2.f * (blo(pr.v[i][3]) * dt)));
    }
    if (tid < 64) sts128(sb + P_U + (tid >> 3) * 2176 + (tid & 7) * 16, 0, 0, 0, 0);
    bar_arrive(6, 384);
    __syncwarp();
    PROF(tid == 0, 3510);
    const int ch = w & 3, hf = w >> 2;
    {
        float k0[4] = {0, 0, 0, 0}, k1[4] = {0, 0, 0, 0}, k2[4] = {0, 0, 0, 0}, k3[4] = {0, 0, 0, 0}, k4[4] = {0, 0, 0, 0}, kl = 0;
#pragma unroll KGU
        for (int j = 0; j < 16; j++) {
            const uint4 q = lds128(sb + P_PRM + (w * 64 + j * 4 + c) * 16);
            const float cr = __uint_as_float(q.z), ci = __uint_as_float(q.w);
            float wr[4], wi[4], vr[4], vi[4];
            cpow(__uint_as_float(q.x), __uint_as_float(q.y), (float)g, wr[0], wi[0]);
            cpow(__uint_as_float(q.x), __uint_as_float(q.y), (float)(g + 8), vr[0], vi[0]);
#pragma unroll
            for (int i = 1; i < 4; i++) { wr[i] = wr[i - 1]; wi[i] = wi[i - 1]; csq(wr[i], wi[i]); vr[i] = vr[i - 1]; vi[i] = vi[i - 1]; csq(vr[i], vi[i]); }
            float hr = wr[3], hi = wi[3];
            csq(hr, hi);
            mma_tf32(k0, wr[0], vr[0], wi[0], vi[0], cr * hr - ci * hi, -(cr * hi + ci * hr));
            hr = vr[3]; hi = vi[3]; csq(hr, hi);
            mma_tf32(k1, wr[0], vr[0], wi[0], vi[0], cr * hr - ci * hi, -(cr * hi + ci * hr));
            csq(hr, hi);
            mma_tf32(k2, wr[1], vr[1], wi[1], vi[1], cr * hr - ci * hi, -(cr * hi + ci * hr));
            csq(hr, hi);
            mma_tf32(k3, wr[2], vr[2], wi[2], vi[2], cr * hr - ci * hi, -(cr * hi + ci * hr));
            csq(hr, hi);
            mma_tf32(k4, wr[3], vr[3], wi[3], vi[3], cr * hr - ci * hi, -(cr * hi + ci * hr));
            csq(hr, hi);
            kl += cr * hr - ci * hi;
        }
        kl += __shfl_xor_sync(0xffffffffu, kl, 1); kl += __shfl_xor_sync(0xffffffffu, kl, 2);
        const uint32_t o = sb + P_K6 + (ch * 656 + c * 32 + g) * 4, ol = sb + P_K6 + (ch * 656 + 640) * 4;
#define KST(k, base) sts32(o + (base) * 4, __float_as_uint(k[0])); sts32(o + (base) * 4 + 64, __float_as_uint(k[1])); \
                     sts32(o + (base) * 4 + 32, __float_as_uint(k[2])); sts32(o + (base) * 4 + 96, __float_as_uint(k[3]))
#define KAD(k, base) k[0] += __uint_as_float(lds32(o + (base) * 4)); k[1] += __uint_as_float(lds32(o + (base) * 4 + 64)); \
                     k[2] += __uint_as_float(lds32(o + (base) * 4 + 32)); k[3] += __uint_as_float(lds32(o + (base) * 4 + 96))
        if (hf == 0) {
            bar_sync(2 + ch, 64);
            KAD(k0, 0); KAD(k1, 128); KAD(k2, 256); KAD(k3, 384); KAD(k4, 512);
            kl += __uint_as_float(lds32(ol));
            __syncwarp();
        }
        KST(k0, 0); KST(k1, 128); KST(k2, 256); KST(k3, 384); KST(k4, 512);
        if (lane == 0) sts32(ol, __float_as_uint(kl));
        if (hf == 1) { __syncwarp(); bar_arrive(2 + ch, 64); }
    }
    PROF(tid == 0, 3511);
    {
        uint4 l0, l1;
        int n = 0;
        while (true) {
            l0 = ld_rlx128((const uint4*)g_ln0 + tid * 2); l1 = ld_rlx128((const uint4*)g_ln0 + tid * 2 + 1);
            if (__all_sync(0xffffffffu, l0.x && l0.y && l0.z && l0.w && l1.x && l1.y && l1.z && l1.w)) break;
            if (++n > 2000000) __trap();
        }
        sts128(sb + P_P + tid * 32, l0.x, l0.y, l0.z, l0.w); sts128(sb + P_P + tid * 32 + 16, l1.x, l1.y, l1.z, l1.w);
        bar_sync(8, 384);
        mbar_wait(sb + S_XBAR, 0);
        __syncwarp();
#pragma unroll 2
        for (int i = 0; i < 8; i++) {
            const int t = w * 256 + i * 32 + lane;
            const uint32_t ln = lds32(sb + P_P + t * 4);
            const uint2 x = lds64(sb + P_X + t * 16 + (b & 1) * 8);
            const float m = blo(ln), rs = rcp(bhi(ln));
            const uint32_t u0 = pack2(rbf(blo(x.x) - m) * rs, rbf(bhi(x.x) - m) * rs), u1 = pack2(rbf(blo(x.y) - m) * rs, rbf(bhi(x.y) - m) * rs);
            sts128(sb + P_X + t * 16, x.x, x.y, u0, u1);
            const uint32_t o = sb + P_U + ((t >> 3) & 1) * 2176 + ((t >> 4) + 8) * 16 + (t & 7) * 2;
            asm volatile("st.shared.u16 [%0],%1;" ::"r"(o), "h"((uint16_t)u0) : "memory");
            asm volatile("st.shared.u16 [%0],%1;" ::"r"(o + 4352), "h"((uint16_t)(u0 >> 16)) : "memory");
            asm volatile("st.shared.u16 [%0],%1;" ::"r"(o + 8704), "h"((uint16_t)u1) : "memory");
            asm volatile("st.shared.u16 [%0],%1;" ::"r"(o + 13056), "h"((uint16_t)(u1 >> 16)) : "memory");
        }
    }
    bar_sync(1, 256);
    PROF(tid == 0, 3512);
    if (tid < 64) sts32(sb + P_P + ((tid >> 4) * 2080 + (tid & 15)) * 4, 0);
#pragma unroll 1
    for (int x = tid; x < 2048; x += 512) {
        uint32_t pw[2][4];
#pragma unroll
        for (int h = 0; h < 2; h++) {
            const int y = x + h * 256;
            const int i0 = y <= 256 ? y : 256 + (int)((pack2((float)y, 0.f) & 0xffff) - 0x4380);
            const int i1 = y <= 256 ? max(y - 1, 0) : 256 + (int)((pack2((float)(y - 1), 0.f) & 0xffff) - 0x4380);
#pragma unroll
            for (int k = 0; k < 4; k++) {
                const float lo = __uint_as_float(lds32(sb + P_K6 + k * 2624 + i0 * 4)), hi = __uint_as_float(lds32(sb + P_K6 + k * 2624 + i1 * 4));
                pw[h][k] = pack2(lo, y ? hi : 0.f);
            }
        }
#pragma unroll
        for (int h = 0; h < 2; h++)
#pragma unroll
            for (int k = 0; k < 4; k++) sts32(sb + P_P + (k * 2080 + x + h * 256 + 16) * 4, pw[h][k]);
    }
    fence_async_smem();
    bar_arrive(9, 384);
    bar_sync(1, 256);
    if (tid < 4) {
        asm volatile("cp.async.bulk.global.shared::cta.bulk_group [%0],[%1],%2;" ::"l"(g_P + (d0 + tid) * PROW), "r"(sb + P_P + tid * 8320), "r"(PROW * 4) : "memory");
        asm volatile("cp.async.bulk.commit_group;" ::: "memory");
    }
    __syncwarp();
    PROF(tid == 0, 3513);
    {
        float acc[16][4];
#pragma unroll
        for (int j = 0; j < 16; j++) acc[j][0] = acc[j][1] = acc[j][2] = acc[j][3] = 0;
#pragma unroll 1
        for (int e = hf * 4; e < hf * 4 + 4; e++) {
            uint32_t B[16][2];
            const uint32_t ua = sb + P_U + ch * 4352 + ((lane >> 3) & 1) * 2176 + (8 + (lane >> 4) * 8 + (lane & 7) - e) * 16;
#pragma unroll
            for (int j = 0; j < 8; j++) { const uint4 v = ldsm4(ua + j * 256); B[2 * j][0] = v.x; B[2 * j][1] = v.y; B[2 * j + 1][0] = v.z; B[2 * j + 1][1] = v.w; }
            const uint32_t pa = sb + P_P + (ch * 2080 + 16 + e * 16 + g - 2 * c) * 4;
#pragma unroll
            for (int dd = 0; dd < 16; dd++) {
                const int d = (dd & 1) ? 15 - (dd >> 1) : dd >> 1;
                const uint32_t a0 = lds32(pa + d * 512), a1 = lds32(pa + d * 512 + 32), a2 = lds32(pa + d * 512 - 32), a3 = a0 + p.zero;
#pragma unroll
                for (int j = 0; j < 16; j++) if (j >= d) mma16(acc[j], a0, a1, a2, a3, B[(j - d) & 15][0], B[(j - d) & 15][1]);
            }
        }
        PROF(tid == 0, 3514);
        if (tid < 4) asm volatile("cp.async.bulk.wait_group 0;" ::: "memory");
        __syncwarp();
        bar_sync(10, 384);
#pragma unroll
        for (int j = 0; j < 8; j++) {
#pragma unroll
            for (int i = 0; i < 4; i++) { const float t = hf ? acc[j][i] : acc[j + 8][i]; acc[j][i] = hf ? acc[j + 8][i] : acc[j][i]; acc[j + 8][i] = t; }
            sts128(sb + P_Y + w * 4096 + j * 512 + lane * 16, __float_as_uint(acc[j + 8][0]), __float_as_uint(acc[j + 8][1]), __float_as_uint(acc[j + 8][2]), __float_as_uint(acc[j + 8][3]));
        }
        bar_sync(2 + ch, 64);
        uint32_t yp[16];
#pragma unroll
        for (int j = 0; j < 8; j++) {
            const uint4 t = lds128(sb + P_Y + (w ^ 4) * 4096 + j * 512 + lane * 16);
            yp[2 * j] = pack2(acc[j][0] + __uint_as_float(t.x), acc[j][1] + __uint_as_float(t.y)); yp[2 * j + 1] = pack2(acc[j][2] + __uint_as_float(t.z), acc[j][3] + __uint_as_float(t.w));
        }
#pragma unroll
        for (int j = 0; j < 4; j++)
            asm volatile("stmatrix.sync.aligned.m8n8.x4.trans.shared.b16 [%0],{%1,%2,%3,%4};" ::"r"(sb + P_Y + 32768 + ch * 4096 + hf * 2048 + j * 512 + (lane >> 4) * 256 + (lane & 7) * 32 + (lane & 8) * 2),
                         "r"(yp[4 * j]), "r"(yp[4 * j + 1]), "r"(yp[4 * j + 2]), "r"(yp[4 * j + 3]) : "memory");
    }
    const uint2 dk = __ldg((const uint2*)(a.Dk + d0));
    bar_sync(1, 256);
#pragma unroll 2
    for (int i = 0; i < 4; i++) {
        const int t = i * 256 + tid;
        const uint4 x0 = lds128(sb + P_X + t * 32), x1 = lds128(sb + P_X + t * 32 + 16);
        uint32_t y[4];
#pragma unroll
        for (int k = 0; k < 4; k++) y[k] = lds32(sb + P_Y + 32768 + k * 4096 + t * 4);
        g_x[b * XP + t] = make_uint4(hadd2(x0.x, hadd2(__byte_perm(y[0], y[1], 0x5410), hmul2(x0.z, dk.x))), hadd2(x0.y, hadd2(__byte_perm(y[2], y[3], 0x5410), hmul2(x0.w, dk.y))),
                                     hadd2(x1.x, hadd2(__byte_perm(y[0], y[1], 0x7632), hmul2(x1.z, dk.x))), hadd2(x1.y, hadd2(__byte_perm(y[2], y[3], 0x7632), hmul2(x1.w, dk.y))));
    }
    PROF(tid == 0, 3515);
}

__global__ void __cluster_dims__(2, 1, 1) __launch_bounds__(384, 1) main_kernel(const __grid_constant__ Params p) {
    extern __shared__ __align__(1024) uint8_t smem[];
    const uint32_t sb = smem_u32(smem);
    uint32_t rank; asm("mov.u32 %0,%%cluster_ctarank;" : "=r"(rank));
    const int wi = __shfl_sync(0xffffffffu, threadIdx.x >> 5, 0);
    const int v = blockIdx.x, cl = v >> 1, wg = wi >> 2;
    PROF(threadIdx.x == 0, 3500);
    ProRegs pr;
    prologue_load(p.pa, max((int)blockIdx.x - 4, 0), pr);
    if (wi == 11 && p.dopro && cl >= 2 && elect()) {
        mbar_init(sb + S_XBAR, 1);
        asm volatile("fence.mbarrier_init.release.cluster;" ::: "memory");
        mbar_expect(sb + S_XBAR, 32768);
        for (int j = 0; j < 8; j++) tma2d(sb + P_X + j * 4096, &p.tm[3], ((blockIdx.x - 4) >> 1) * 8, j * 256, sb + S_XBAR);
    }
    if (threadIdx.x == 320) {
        unsigned n;
        asm volatile("ld.relaxed.gpu.global.u32 %0,[%1];" : "=r"(n) : "l"(g_gate) : "memory");
        n = n / (4 * NCL) + p.dopro;
        sts64(sb + S_GATE, n * (4 * NCL), n & 1);
    }
    __syncwarp();
    if (wi == 10) {
        if (v < V_REC || v == 131) conv_init(sb, v == 131); else if (v < V_OP) rec_init(sb); else gemm_init(sb, v < V_QKV);
        __syncwarp();
    }
    if (wg == 2) bar_arrive(8, 384);
    asm volatile("barrier.cluster.arrive.relaxed.aligned;" ::: "memory");
    if (p.dopro && cl >= 2) prologue(p, sb, blockIdx.x - 4, wi, pr); else if (wg < 2) bar_sync(8, 384); else if (wi == 10) early_fetch(p, sb);
    asm volatile("barrier.cluster.wait.aligned;" ::: "memory");
    const int role = (v < V_REC ? 1 : v < V_OP ? 2 : v < V_QKV ? 20 : v < V_QKV + NQ ? 24 : 1) & p.roles;
    fence_async_smem();
    bar_sync(wg == 2 ? 7 : 1, wg == 2 ? 128 : 256);
    if (p.dopro && (threadIdx.x == 32 || threadIdx.x == 352)) red_release(g_gate, 1);
    PROF(threadIdx.x == 32, 3509);
    if (wi == 0 && (role & 8) && elect()) qkv_stage(p, sb + 131072, sb + G_BAR + GB_RS * 8, v - V_QKV, 0, 6);
    PROF(threadIdx.x == 0, 3506);
    __syncwarp();
    if (p.dopro && (v == 131 || (v >= V_REC && v < V_QKV && (v < V_OP ? wi == 8 : wi < 8)))) {
        bool on = v >= V_OP;
#pragma unroll 1
        for (int r = v == 131 ? 448 + wi : on ? 64 + (v - V_OP) * 8 + wi : v - V_REC; r < (v == 131 ? 512 : 448);) {
            if (v >= V_OP) wait_slow_warp(g_gate, lds32(sb + S_GATE)); else if (on) wait_flag_warp(g_gate, lds32(sb + S_GATE));
            PROF(threadIdx.x == 256 && on, 3507);
            x1_norm(on ? (const uint2*)g_x : (const uint2*)p.pa.x, r, on);
            __syncwarp();
            if (on && elect()) red_release(cnt_ptr(C_XN + (r >> 4)), 1);
            __syncwarp();
            PROF(threadIdx.x == 256, on ? 3508 : 3499);
            if (on) r += v < V_OP ? 512 : v == 131 ? 12 : 128;
            on = true;
        }
    }
    if (role == 2) {
        const int head = (v - V_REC) >> 1;
        if (wi == RFW && elect()) {
            if (!REARLY) { rec_fetch(p, sb, head, rank, 0, R_STQ); }
            rec_fetch(p, sb, head, rank, 1, R_STK);
            if (!REARLY) { rec_fetch(p, sb, head, rank, 2, R_STV); }
        }
        __syncwarp();
        if (wg == 2) {
            reg_dec<RH>();
            const int w = wi & 3;
            wait_slow_warp(g_gate, lds32(sb + S_GATE));
            if (w < 2) { const uint32_t x = __ldcg(g_sel + (threadIdx.x & 63)); sts32(sb + R_SEL + (threadIdx.x & 63) * 4, (x * 0x01010101u) >> 24); }
            __syncthreads();
            cluster_sync();
            if ((p.chains >> (w & 1)) & 1) { if (w < 2) rec_comm(p, sb, w, head, rank); else rec_attn(p, sb, w & 1, head, rank); }
        } else {
            reg_inc<RW0>();
            rec_weights(p, sb, head, rank, wi);
        }
    } else if (role == 1) {
        if (v == 131) { wait_slow_warp(g_gate, lds32(sb + S_GATE)); conv_far<0>(sb, wi); conv_far<1>(sb, wi); } else if (wg == 2) { reg_dec<RCB>(); conv_back(sb, v, wi & 3); } else { reg_inc<RCU>(); conv_tile(p, sb, v, wi); }
    } else if (role && v < V_QKV) {
        if (wg == 2) {
            reg_dec<40>();
            if (wi == 8) { if (role & 4) gemm_producer<true>(p, sb, v - V_OP); }
            else if (v < V_OP + 14 && (role & 16)) fin_warp(p, sb, 2 * NQ + (v - V_OP) * 3 + wi - 9);
        } else { reg_inc<232>(); if (role & 4) gemm_consumer<true>(p, sb, v - V_OP, wi); }
    } else if (role) {
        if (wg == 2) {
            reg_dec<40>();
            if (wi < 10) {
                if (role & 8) { if (wi == 8) gemm_producer<false>(p, sb, v - V_QKV); else qkv_release(p, sb); }
            } else if (role & 16) fin_warp(p, sb, (v - V_QKV) * 2 + wi - 10);
        } else { reg_inc<232>(); if (role & 8) gemm_consumer<false>(p, sb, v - V_QKV, wi); }
    }
    __syncwarp();
    cluster_sync();
}

typedef CUresult (*EncFn)(CUtensorMap*, CUtensorMapDataType, cuuint32_t, void*, const cuuint64_t*, const cuuint64_t*, const cuuint32_t*, const cuuint32_t*,
                          CUtensorMapInterleave, CUtensorMapSwizzle, CUtensorMapL2promotion, CUtensorMapFloatOOBfill);
constexpr int SMEM_BYTES = 232448;
#define LAG 8
#define QLEAD 6
#define OLEAD (LAG / 2 + 2)
void plan(Params& P) {
    P.roles = 31; P.chains = 3; P.lag = LAG; P.dopro = 1;
    for (int r = 0; r < 2; r++) {
        const int lead = r ? OLEAD : QLEAD;
        int n = 0;
        for (int i = 0; i < 32 + lead; i++) {
            if (i >= lead) P.list[r][n++] = 32 + i - lead;
            if (i < 32) P.list[r][n++] = i;
        }
        P.nl[r] = n;
    }
}

#define TK() do {} while (0)
}

extern "C" void kernel_launch(void* const* d_in, const int* in_sizes, int n_in, void* d_out, int out_size) {
    typedef const __nv_bfloat16* BP;
    static EncFn enc = nullptr;
    if (!enc) {
        void* fn = nullptr; cudaDriverEntryPointQueryResult qr;
        cudaGetDriverEntryPoint("cuTensorMapEncodeTiled", &fn, cudaEnableDefault, &qr);
        enc = (EncFn)fn;
        cudaFuncSetAttribute(main_kernel, cudaFuncAttributeMaxDynamicSharedMemorySize, SMEM_BYTES);
    }
    static Params P;
    for (int i = 0; i < 4; i++) {
        const cuuint64_t cols = i < 3 ? 4096 : 512, rows = i < 3 ? 512 : 4096;
        cuuint64_t d2[2] = {cols, rows}, str[1] = {cols * 2};
        cuuint32_t box[2] = {64, 64}, bn[2] = {16, 256}, es[2] = {1, 1};
        enc(&P.tm[i < 3 ? i : 4], CU_TENSOR_MAP_DATA_TYPE_BFLOAT16, 2, d_in[9 + i], d2, str, box, es, CU_TENSOR_MAP_INTERLEAVE_NONE, CU_TENSOR_MAP_SWIZZLE_128B,
            CU_TENSOR_MAP_L2_PROMOTION_L2_128B, CU_TENSOR_MAP_FLOAT_OOB_FILL_NONE);
        if (i < 2) enc(&P.tn[i], CU_TENSOR_MAP_DATA_TYPE_BFLOAT16, 2, d_in[9 + i], d2, str, bn, es, CU_TENSOR_MAP_INTERLEAVE_NONE, CU_TENSOR_MAP_SWIZZLE_32B,
                       CU_TENSOR_MAP_L2_PROMOTION_L2_128B, CU_TENSOR_MAP_FLOAT_OOB_FILL_NONE);
    }
    {
        cuuint64_t dims[2] = {512, 2048}, str[1] = {1024};
        cuuint32_t box[2] = {8, 256}, es[2] = {1, 1};
        enc(&P.tm[3], CU_TENSOR_MAP_DATA_TYPE_BFLOAT16, 2, d_in[0], dims, str, box, es, CU_TENSOR_MAP_INTERLEAVE_NONE, CU_TENSOR_MAP_SWIZZLE_NONE,
            CU_TENSOR_MAP_L2_PROMOTION_NONE, CU_TENSOR_MAP_FLOAT_OOB_FILL_NONE);
    }
    P.mem0 = (BP)d_in[8]; P.Wo = (BP)d_in[12]; P.Dskip = (BP)d_in[6]; P.out = (__nv_bfloat16*)d_out;
    cudaStream_t s = cudaStreamPerThread;
    P.pa = {(BP)d_in[0], (BP)d_in[1], (BP)d_in[2], (BP)d_in[3], (BP)d_in[4], (BP)d_in[5], (BP)d_in[6], {(BP)d_in[9], (BP)d_in[10], (BP)d_in[11], (BP)d_in[12]}};
    plan(P);
    TK(); main_kernel<<<2 * NCL, 384, SMEM_BYTES, s>>>(P); TK();
}
```

```cpp
#include <cuda_runtime.h>
#include <cuda_bf16.h>
#include <cuda.h>
#include <stdint.h>
#include <string.h>
#include <math.h>

namespace {

constexpr int NCL = 66;
constexpr int NQ = 43;
constexpr int V_REC = 8, V_OP = 72, V_QKV = 88;
static_assert(2 * NQ + 3 * 14 == 128, "warps of the final residual");

constexpr int XP = 1024;
__device__ uint4 g_x[2 * 128 * XP];
__device__ uint4 g_xn[64 * 4096];
__device__ uint4 g_st[68 * 256];
__device__ uint4 g_qkv[128 * 32 * 1536];
__device__ uint4 g_o[64 * 64 * 512];
__device__ uint4 g_pp[64 * 4 * 4096];
__device__ uint4 g_xch[133 * 512];
__device__ unsigned g_sel[64];
__device__ unsigned g_gate[32];
__device__ __align__(16) uint32_t g_P[512 * 272];
__device__ uint4 g_W[512 * 784];
__device__ __align__(16) uint32_t g_u[512 * 1280];
__device__ uint2 g_carry[512 * 40 * 32];
__device__ uint2 g_far[512 * 12 * 32];
__device__ unsigned g_cnt[912 * 8];
__device__ uint32_t g_ln0[2048];

enum { C_XN = 0  , C_QKV = 64  , C_O = 128  , C_PP = 384  , C_FAR = 896 };
__device__ __forceinline__ unsigned* cnt_ptr(int i) { return g_cnt + i * 8; }

struct ProArgs { const __nv_bfloat16 *x, *lAr, *Ai, *Cr, *Ci, *ldt, *Dk, *W[4]; };
struct Params {
    CUtensorMap tm[5];
    CUtensorMap tn[2];
    ProArgs pa;
    int dopro;
    const __nv_bfloat16* mem0;
    const __nv_bfloat16* Wo;
    const __nv_bfloat16* Dskip;
    __nv_bfloat16* out;
    int roles;
    int chains;
    int lag;
    int zero;
    int nl[2];
    uint8_t list[2][64];
};

__device__ __forceinline__ uint32_t smem_u32(const void* p) { return (uint32_t)__cvta_generic_to_shared(p); }
__device__ __forceinline__ uint32_t mapa(uint32_t a, uint32_t r) {
    uint32_t o; asm("mapa.shared::cluster.u32 %0,%1,%2;" : "=r"(o) : "r"(a), "r"(r)); return o;
}
__device__ __forceinline__ void mbar_init(uint32_t b, int c) { asm volatile("mbarrier.init.shared::cta.b64 [%0],%1;" ::"r"(b), "r"(c) : "memory"); }
__device__ __forceinline__ void mbar_expect(uint32_t b, int bytes) { asm volatile("mbarrier.arrive.expect_tx.shared::cta.b64 _,[%0],%1;" ::"r"(b), "r"(bytes) : "memory"); }
__device__ __forceinline__ void mbar_arrive(uint32_t b) { asm volatile("mbarrier.arrive.shared::cta.b64 _,[%0];" ::"r"(b) : "memory"); }
__device__ __forceinline__ void mbar_arrive_cluster(uint32_t b) { asm volatile("mbarrier.arrive.shared::cluster.b64 _,[%0];" ::"r"(b) : "memory"); }
__device__ __forceinline__ void mbar_wait(uint32_t b, uint32_t ph) {
    asm volatile(
        "{.reg .pred p; .reg .u32 n; mov.u32 n,0;\n"
        "W%=: mbarrier.try_wait.parity.shared::cta.b64 p,[%0],%1;\n"
        "@p bra D%=;\n"
        "add.u32 n,n,1; setp.lt.u32 p,n,2000000; @p bra W%=;\n"
        "trap;\n"
        "D%=: }" ::"r"(b), "r"(ph) : "memory");
}
__device__ __forceinline__ bool elect() {
    uint32_t r; asm volatile("{.reg .pred p; elect.sync _|p,0xffffffff; selp.u32 %0,1,0,p;}" : "=r"(r)); return r;
}
__device__ __forceinline__ void bar_sync(int id, int n) { asm volatile("bar.sync %0,%1;" ::"r"(id), "r"(n) : "memory"); }
__device__ __forceinline__ void bar_arrive(int id, int n) { asm volatile("bar.arrive %0,%1;" ::"r"(id), "r"(n) : "memory"); }
__device__ __forceinline__ void cluster_sync() { asm volatile("barrier.cluster.arrive.relaxed.aligned; barrier.cluster.wait.aligned;" ::: "memory"); }
__device__ __forceinline__ void fence_async_smem() { asm volatile("fence.proxy.async.shared::cta;" ::: "memory"); }
constexpr uint64_t POL_N = 0x1000000000000000ull  , POL_LAST = 0x12F0000000000000ull  ;
__device__ __forceinline__ void bulk_g2s(uint32_t dst, const void* src, int bytes, uint32_t bar, uint64_t pol) {
    asm volatile("cp.async.bulk.shared::cluster.global.mbarrier::complete_tx::bytes.L2::cache_hint [%0],[%1],%2,[%3],%4;" ::"r"(dst), "l"(src), "r"(bytes), "r"(bar), "l"(pol) : "memory");
}
__device__ __forceinline__ void bulk_g2s_mc(uint32_t dst, const void* src, int bytes, uint32_t bar, uint64_t pol) {
    asm volatile("cp.async.bulk.shared::cluster.global.mbarrier::complete_tx::bytes.multicast::cluster.L2::cache_hint [%0],[%1],%2,[%3],%4,%5;" ::"r"(dst), "l"(src), "r"(bytes), "r"(bar), "h"((uint16_t)3), "l"(pol) : "memory");
}
__device__ __forceinline__ void stg128(uint4* p, uint4 v, uint64_t pol) {
    asm volatile("st.global.L2::cache_hint.v4.u32 [%0],{%1,%2,%3,%4},%5;" ::"l"(p), "r"(v.x), "r"(v.y), "r"(v.z), "r"(v.w), "l"(pol));
}
__device__ __forceinline__ void tma2d(uint32_t dst, const CUtensorMap* tm, int x, int y, uint32_t bar) {
    asm volatile("cp.async.bulk.tensor.2d.shared::cluster.global.mbarrier::complete_tx::bytes [%0],[%1,{%2,%3}],[%4];" ::"r"(dst), "l"(tm), "r"(x), "r"(y), "r"(bar) : "memory");
}
__device__ __forceinline__ void st_async4(uint32_t a, uint32_t x, uint32_t y, uint32_t z, uint32_t w, uint32_t mb) {
    asm volatile("st.async.shared::cluster.mbarrier::complete_tx::bytes.v4.b32 [%0],{%1,%2,%3,%4},[%5];" ::"r"(a), "r"(x), "r"(y), "r"(z), "r"(w), "r"(mb) : "memory");
}
__device__ __forceinline__ void st_async2(uint32_t a, uint32_t x, uint32_t y, uint32_t mb) {
    asm volatile("st.async.shared::cluster.mbarrier::complete_tx::bytes.v2.b32 [%0],{%1,%2},[%3];" ::"r"(a), "r"(x), "r"(y), "r"(mb) : "memory");
}
__device__ __forceinline__ uint4 lds128(uint32_t a) { uint4 v; asm volatile("ld.shared.v4.u32 {%0,%1,%2,%3},[%4];" : "=r"(v.x), "=r"(v.y), "=r"(v.z), "=r"(v.w) : "r"(a) : "memory"); return v; }
__device__ __forceinline__ uint4 lds128v(uint32_t a) { uint4 v; asm volatile("ld.volatile.shared.v4.u32 {%0,%1,%2,%3},[%4];" : "=r"(v.x), "=r"(v.y), "=r"(v.z), "=r"(v.w) : "r"(a) : "memory"); return v; }
__device__ __forceinline__ uint2 lds64(uint32_t a) { uint2 v; asm volatile("ld.shared.v2.u32 {%0,%1},[%2];" : "=r"(v.x), "=r"(v.y) : "r"(a) : "memory"); return v; }
__device__ __forceinline__ uint32_t lds32(uint32_t a) { uint32_t v; asm volatile("ld.shared.u32 %0,[%1];" : "=r"(v) : "r"(a) : "memory"); return v; }
__device__ __forceinline__ void sts128(uint32_t a, uint32_t x, uint32_t y, uint32_t z, uint32_t w) { asm volatile("st.shared.v4.u32 [%0],{%1,%2,%3,%4};" ::"r"(a), "r"(x), "r"(y), "r"(z), "r"(w) : "memory"); }
__device__ __forceinline__ void sts64(uint32_t a, uint32_t x, uint32_t y) { asm volatile("st.shared.v2.u32 [%0],{%1,%2};" ::"r"(a), "r"(x), "r"(y) : "memory"); }
__device__ __forceinline__ void sts32(uint32_t a, uint32_t x) { asm volatile("st.shared.u32 [%0],%1;" ::"r"(a), "r"(x) : "memory"); }
__device__ __forceinline__ uint4 ldsm4(uint32_t a) { uint4 v; asm volatile("ldmatrix.sync.aligned.m8n8.x4.shared.b16 {%0,%1,%2,%3},[%4];" : "=r"(v.x), "=r"(v.y), "=r"(v.z), "=r"(v.w) : "r"(a) : "memory"); return v; }
__device__ __forceinline__ uint4 ldsm4t(uint32_t a) { uint4 v; asm volatile("ldmatrix.sync.aligned.m8n8.x4.trans.shared.b16 {%0,%1,%2,%3},[%4];" : "=r"(v.x), "=r"(v.y), "=r"(v.z), "=r"(v.w) : "r"(a) : "memory"); return v; }
__device__ __forceinline__ uint32_t movm(uint32_t a) { uint32_t d; asm volatile("movmatrix.sync.aligned.m8n8.trans.b16 %0,%1;" : "=r"(d) : "r"(a)); return d; }
__device__ __forceinline__ uint32_t pack2(float lo, float hi) { uint32_t d; asm("cvt.rn.bf16x2.f32 %0,%1,%2;" : "=r"(d) : "f"(hi), "f"(lo)); return d; }
__device__ __forceinline__ uint32_t hadd2(uint32_t a, uint32_t b) { uint32_t d; asm("add.rn.bf16x2 %0,%1,%2;" : "=r"(d) : "r"(a), "r"(b)); return d; }
__device__ __forceinline__ uint32_t hmul2(uint32_t a, uint32_t b) { uint32_t d; asm("mul.rn.bf16x2 %0,%1,%2;" : "=r"(d) : "r"(a), "r"(b)); return d; }
__device__ __forceinline__ float blo(uint32_t v) { return __uint_as_float(v << 16); }
__device__ __forceinline__ float bhi(uint32_t v) { return __uint_as_float(v & 0xffff0000u); }
__device__ __forceinline__ float rbf(float x) { return __uint_as_float(pack2(0.f, x)); }
__device__ __forceinline__ float ex2(float x) { float y; asm("ex2.approx.ftz.f32 %0,%1;" : "=f"(y) : "f"(x)); return y; }
__device__ __forceinline__ float rcp(float x) { float y; asm("rcp.approx.ftz.f32 %0,%1;" : "=f"(y) : "f"(x)); return y; }
__device__ __forceinline__ void mma16(float* c, uint32_t a0, uint32_t a1, uint32_t a2, uint32_t a3, uint32_t b0, uint32_t b1) {
    asm volatile("mma.sync.aligned.m16n8k16.row.col.f32.bf16.bf16.f32 {%0,%1,%2,%3},{%4,%5,%6,%7},{%8,%9},{%0,%1,%2,%3};"
                 : "+f"(c[0]), "+f"(c[1]), "+f"(c[2]), "+f"(c[3]) : "r"(a0), "r"(a1), "r"(a2), "r"(a3), "r"(b0), "r"(b1));
}
__device__ __forceinline__ void mma16_top(float& d0, float& d1, uint32_t a0, uint32_t a2, uint32_t b0, uint32_t b1) {
    asm volatile("{.reg .b32 j; .reg .f32 e,f; mma.sync.aligned.m16n8k16.row.col.f32.bf16.bf16.f32 {%0,%1,e,f},{%2,j,%3,j},{%4,%5},{0f00000000,0f00000000,0f00000000,0f00000000};}"
                 : "=f"(d0), "=f"(d1) : "r"(a0), "r"(a2), "r"(b0), "r"(b1));
}
__device__ __forceinline__ void mma8(float* c, uint32_t a0, uint32_t a1, uint32_t b0) {
    asm volatile("mma.sync.aligned.m16n8k8.row.col.f32.bf16.bf16.f32 {%0,%1,%2,%3},{%4,%5},{%6},{%0,%1,%2,%3};"
                 : "+f"(c[0]), "+f"(c[1]), "+f"(c[2]), "+f"(c[3]) : "r"(a0), "r"(a1), "r"(b0));
}
__device__ __forceinline__ uint4 ld_rlx128(const uint4* p) {
    uint4 v;
    asm volatile("{.reg .b128 t; ld.relaxed.gpu.global.b128 t,[%4]; mov.b128 {%0,%1,%2,%3},t;}" : "=r"(v.x), "=r"(v.y), "=r"(v.z), "=r"(v.w) : "l"(p) : "memory");
    return v;
}
__device__ __forceinline__ void st_rlx128(uint4* p, uint32_t x, uint32_t y, uint32_t z, uint32_t w) {
    asm volatile("{.reg .b128 t; mov.b128 t,{%1,%2,%3,%4}; st.relaxed.gpu.global.b128 [%0],t;}" ::"l"(p), "r"(x), "r"(y), "r"(z), "r"(w) : "memory");
}
__device__ __forceinline__ uint4 ldcg128(const uint4* p) { uint4 v; asm volatile("ld.global.cg.v4.u32 {%0,%1,%2,%3},[%4];" : "=r"(v.x), "=r"(v.y), "=r"(v.z), "=r"(v.w) : "l"(p) : "memory"); return v; }
__device__ __forceinline__ void red_release(unsigned* p, unsigned v) {
    asm volatile("fence.proxy.async; red.relaxed.gpu.global.add.u32 [%0],%1;" ::"l"(p), "r"(v) : "memory");
}
__device__ __forceinline__ void red_relaxed(unsigned* p, unsigned v) { asm volatile("red.relaxed.gpu.global.add.u32 [%0],%1;" ::"l"(p), "r"(v) : "memory"); }
__device__ __forceinline__ void wait_cnt(const unsigned* p, unsigned target) {
    asm volatile(
        "{.reg .pred p; .reg .u32 n,v; mov.u32 n,0;\n"
        "W%=: ld.acquire.gpu.global.u32 v,[%0]; setp.ge.u32 p,v,%1; @p bra D%=;\n"
        "nanosleep.u32 20; add.u32 n,n,1; setp.lt.u32 p,n,4000000; @p bra W%=;\n"
        "trap;\n"
        "D%=: }" ::"l"(p), "r"(target) : "memory");
}
__device__ __forceinline__ void wait_slow_warp(const unsigned* p, unsigned target) {
    asm volatile(
        "{.reg .pred p; .reg .u32 n,v; mov.u32 n,0;\n"
        "W%=: ld.relaxed.gpu.global.u32 v,[%0]; setp.ge.u32 p,v,%1; vote.sync.all.pred p,p,0xffffffff; @p bra.uni D%=;\n"
        "nanosleep.u32 400; add.u32 n,n,1; setp.lt.u32 p,n,1000000; @p bra.uni W%=;\n"
        "trap;\n"
        "D%=: }" ::"l"(p), "r"(target) : "memory");
}
__device__ __forceinline__ void wait_flag_warp(const unsigned* p, unsigned target) {
    asm volatile(
        "{.reg .pred p; .reg .u32 n,v; mov.u32 n,0;\n"
        "W%=: ld.relaxed.gpu.global.u32 v,[%0]; setp.ge.u32 p,v,%1; vote.sync.all.pred p,p,0xffffffff; @p bra.uni D%=;\n"
        "add.u32 n,n,1; setp.lt.u32 p,n,10000000; @p bra.uni W%=;\n"
        "trap;\n"
        "D%=: }" ::"l"(p), "r"(target) : "memory");
}
__device__ __forceinline__ uint64_t mkdesc(uint32_t addr, uint32_t lbo, uint32_t sbo, uint32_t sw) {
    return (uint64_t)((addr & 0x3FFFF) >> 4) | ((uint64_t)(lbo >> 4) << 16) | ((uint64_t)(sbo >> 4) << 32) | ((uint64_t)sw << 62);
}
__device__ __forceinline__ void wg_fence() { asm volatile("wgmma.fence.sync.aligned;" ::: "memory"); }
__device__ __forceinline__ void wg_commit() { asm volatile("wgmma.commit_group.sync.aligned;" ::: "memory"); }
template <int N> __device__ __forceinline__ void wg_wait() { asm volatile("wgmma.wait_group.sync.aligned %0;" ::"n"(N) : "memory"); }
#define R8(c, o) "+f"(c[o]), "+f"(c[o + 1]), "+f"(c[o + 2]), "+f"(c[o + 3]), "+f"(c[o + 4]), "+f"(c[o + 5]), "+f"(c[o + 6]), "+f"(c[o + 7])
#define R32(c, o) R8(c, o), R8(c, o + 8), R8(c, o + 16), R8(c, o + 24)
#define S32A "%0,%1,%2,%3,%4,%5,%6,%7,%8,%9,%10,%11,%12,%13,%14,%15,%16,%17,%18,%19,%20,%21,%22,%23,%24,%25,%26,%27,%28,%29,%30,%31"
template <int ACC> __device__ __forceinline__ void wgmma64_rs(float* c, const uint32_t* a, uint64_t db) {
    asm volatile("wgmma.mma_async.sync.aligned.m64n64k16.f32.bf16.bf16 {" S32A "},{%32,%33,%34,%35},%36,%37,1,1,0;"
                 : R32(c, 0) : "r"(a[0]), "r"(a[1]), "r"(a[2]), "r"(a[3]), "l"(db), "n"(ACC));
}
template <int ACC> __device__ __forceinline__ void wgmma64_ta(float* c, uint64_t da, uint64_t db) {
    asm volatile("wgmma.mma_async.sync.aligned.m64n64k16.f32.bf16.bf16 {" S32A "},%32,%33,%34,1,1,1,0;" : R32(c, 0) : "l"(da), "l"(db), "n"(ACC));
}
template <int ACC> __device__ __forceinline__ void wgmma80_tb(float* c, uint64_t da, uint64_t db) {
    asm volatile("wgmma.mma_async.sync.aligned.m64n80k16.f32.bf16.bf16 {" S32A ",%32,%33,%34,%35,%36,%37,%38,%39},%40,%41,%42,1,1,0,1;"
                 : R32(c, 0), R8(c, 32) : "l"(da), "l"(db), "n"(ACC));
}
template <int N> __device__ __forceinline__ void reg_inc() { asm volatile("setmaxnreg.inc.sync.aligned.u32 %0;" ::"n"(N)); }
template <int N> __device__ __forceinline__ void reg_dec() { asm volatile("setmaxnreg.dec.sync.aligned.u32 %0;" ::"n"(N)); }

#define PROF(cond, idx) do {} while (0)
#define PROF2(cond, idx) do {} while (0)

constexpr int S_GATE = 232440, S_TAG = 232444, S_XBAR = 232432, B_BAR = 231936;
#define FT 5
#define FJ 62
#define OLAG 1
#define RCB 136
#define RCU 184
#define NTOP 1
#define PLATE 2
#define PFM 12
#define QLAG 4
constexpr float SC_LOG2E = 0.08838834764831845f * 1.4426950408889634f;

__device__ __forceinline__ float2 ln_finish(float mean, float var) {
    float sd; asm("sqrt.approx.f32 %0,%1;" : "=f"(sd) : "f"(rbf(rbf(var) + 1e-5f)));
    sd = rbf(sd);
    return make_float2(rbf(mean), sd);
}

__device__ __forceinline__ float2 row_stats512(uint4* v, const uint4* src, int s1, int s2) {
    const int g = (threadIdx.x & 31) >> 2;
#pragma unroll
    for (int i = 0; i < 16; i++) v[i] = ldcg128(src + (i >> 1) * s1 + (i & 1) * s2);
    float a[4] = {0, 0, 0, 0}, q0[4] = {0, 0, 0, 0}, q1[4] = {0, 0, 0, 0};
#pragma unroll
    for (int i = 0; i < 16; i++) {
        mma16(a, v[i].x, v[i].y, v[i].z, v[i].w, 0x3f803f80u, 0x3f803f80u);
        mma8(q0, v[i].x, v[i].y, v[i].x); mma8(q1, v[i].x, v[i].y, v[i].y);
        mma8(q0, v[i].z, v[i].w, v[i].z); mma8(q1, v[i].z, v[i].w, v[i].w);
    }
    const float sum = a[0] + a[2], sq = (g & 1) ? q0[1] + q1[3] : q0[0] + q1[2];
    return make_float2(sum, fmaxf(sq - sum * sum * (1.f / 512.f), 0.f));
}
__device__ __forceinline__ void x1_norm(const uint2* src, int r, bool on) {
    const int lane = threadIdx.x & 31, g = lane >> 2, t = r * 4 + (lane & 3);
    constexpr int xp = XP;
    uint2 v[16];
#pragma unroll
    for (int i = 0; i < 16; i++) asm volatile("ld.global.cg.v2.u32 {%0,%1},[%2];" : "=r"(v[i].x), "=r"(v[i].y) : "l"(src + (g * 4 * xp + t) + ((i >> 1) * 16 + (i & 1)) * 2 * xp) : "memory");
    float s = 0, q = 0;
#pragma unroll
    for (int i = 0; i < 32; i++) {
        const uint32_t w = (i & 1) ? v[i >> 1].y : v[i >> 1].x;
        s += blo(w) + bhi(w); q = fmaf(blo(w), blo(w), fmaf(bhi(w), bhi(w), q));
    }
#pragma unroll
    for (int d = 4; d < 32; d *= 2) { s += __shfl_xor_sync(0xffffffffu, s, d); q += __shfl_xor_sync(0xffffffffu, q, d); }
    if (g == 0 && on) g_ln0[t] = 0;
    s *= 1.f / 512.f;
    const float2 l = ln_finish(s, fmaxf(fmaf(q, 1.f / 512.f, -s * s), 0.f));
    const float rs = rcp(l.y);
    const uint32_t mm = pack2(-l.x, -l.x);
    uint4* dst = g_xn + ((t >> 6) * 4096 + ((t >> 3) & 7) * 64 + g * 8 + (t & 7));
#define NRM(w) pack2(blo(hadd2(w, mm)) * rs, bhi(hadd2(w, mm)) * rs)
#pragma unroll
    for (int i = 0; i < 8; i++)
        asm volatile("{.reg .pred p; setp.ne.u32 p,%5,0; @p st.global.v4.u32 [%0],{%1,%2,%3,%4};}" ::"l"(dst + i * 512), "r"(NRM(v[2 * i].x)), "r"(NRM(v[2 * i].y)),
                     "r"(NRM(v[2 * i + 1].x)), "r"(NRM(v[2 * i + 1].y)), "r"((uint32_t)on) : "memory");
}

#define NWO 10
#define VMASK 0x4444
#define VPRE 2
#define OL 0x16
#define PINS 0x6ae1
#define NPX 2
#define NPF 2
constexpr int SLOT = 24576, SL_V = 8192, SL_Q = 16384, SL_KM = 20480, SL_VM = 22528;
constexpr int R_SL = 0, R_WV = 4 * SLOT  , R_WO = R_WV + 65536, R_M = 196608  , R_U = R_M + 8192  ,
              R_OS = R_U + 8192  , R_SB = R_OS + 8192  , R_OB = R_SB + 5248  , R_PB = R_OB + 2048  ,
              R_IL = R_PB + 1024  , R_SEL = 231680, R_BAR = R_SEL + 256, R_STV = 0, R_STQ = 65536, R_STK = 131072;
static_assert(R_WO + (16 - NWO) * 4096 <= R_M && R_IL + 64 <= R_SEL && R_BAR + 512 <= 232448, "smem map");
enum { RB_XFULL = 0  , RB_GO = 4  , RB_QK = 8  , RB_INIT = 24, RB_SV = 25   };

enum { NB_MFULL = 1  , NB_PART = 3  , NB_S = 5, NB_P = 6, NB_O = 7, NB_W = 10 };
#define XU 4
#define SEARLY 4
#define NPRB 3
#define RH 56
#define RW0 224
#define D1 270
#define D2 300
__device__ __forceinline__ uint32_t clk32() { uint32_t c; asm volatile("mov.u32 %0,%%clock;" : "=r"(c)::"memory"); return c; }
__device__ __forceinline__ void spin(int cycles) {
    if (cycles <= 0) return;
    asm volatile("{.reg .pred p; .reg .u32 a,b; mov.u32 a,%%clock; add.u32 a,a,%0;\nS%=: mov.u32 b,%%clock; sub.u32 b,b,a; setp.lt.s32 p,b,0; @p bra.uni S%=;}" ::"r"(cycles) : "memory");
}
__device__ __forceinline__ uint4* xregion(int X, int r) { return (uint4*)(((size_t)g_xch + 8191) & ~(size_t)8191) + (X * 66 + r) * 512; }

__device__ __forceinline__ void arrive_if(uint32_t bar, uint32_t a, uint32_t b) {
    asm volatile("{.reg .pred p; setp.eq.u32 p,%1,%2; @p mbarrier.arrive.shared::cta.b64 _,[%0];}" ::"r"(bar), "r"(a), "r"(b) : "memory");
}
struct RecW { uint32_t po, dp, lw, sp, w; };
#define PIN(n) if ((PINS >> (n)) & 1) asm volatile("griddepcontrol.launch_dependents;" ::: "memory")
constexpr int v_stream(int n) {
    int ks = 0;
    for (; ks < 16; ks++) if (!((VMASK >> ks) & 1) && n-- == 0) break;
    return ks;
}
constexpr uint64_t v_next() {
    uint64_t r = 0;
    for (int n = 0; v_stream(n + VPRE) < 16; n++) r |= (uint64_t)v_stream(n + VPRE) << (4 * v_stream(n));
    return r;
}
constexpr uint64_t V_NEXT = v_next();
constexpr int V_PRE = v_stream(VPRE);

__device__ __forceinline__ void rec_step(const RecW& k, uint32_t sb, const int X, int s, uint32_t zero, int lo, int hi, int d, const uint32_t (*wq)[4], const uint32_t (*wk)[4], uint4* wv, uint4* wo) {
    const int SL = R_SL + X * 2 * SLOT;
    uint4 mk[8];
    bar_sync(NB_MFULL + X, 288);
    mk[0] = ldsm4(k.lw + X * 4096 + R_M);
    PIN(0);
    mk[1] = ldsm4(k.lw + X * 4096 + R_M + 512);
    PIN(0);
    asm volatile("" : "+r"(s));
    const uint32_t z = s & zero, wz = k.w + z, w5 = wz * 512, so = (s & 1) * SLOT + w5;
    const uint32_t qb = sb + R_BAR + (RB_QK + X * 8) * 8 + wz * 8;
    uint32_t x[4], vv[2], l8;
    {
        float aq[4] = {0, 0, 0, 0}, ak[4] = {0, 0, 0, 0}, av[4] = {0, 0, 0, 0};
#pragma unroll
        for (int t = 0; t < 16; t++) {
            const uint32_t b0 = (t & 1) ? mk[t >> 1].z : mk[t >> 1].x, b1 = (t & 1) ? mk[t >> 1].w : mk[t >> 1].y;
            mma16(aq, wq[t][0], wq[t][1], wq[t][2], wq[t][3], b0, b1);
            PIN(8);
            mma16(ak, wk[t][0], wk[t][1], wk[t][2], wk[t][3], b0, b1);
            PIN(9);
            mma16(av, wv[t].x, wv[t].y, wv[t].z, wv[t].w, b0, b1);
            PIN(10);
            if ((t & 1) && t < 13) mk[(t >> 1) + 2] = ldsm4(k.lw + X * 4096 + R_M + (t >> 1) * 512 + 1024);
            const int nx = (V_NEXT >> (4 * t)) & 15;
            if (nx) wv[nx] = lds128(k.lw + w5 + R_WV + nx * 4096);
            if (t == 14) l8 = ((k.lw + z) >> 1) + (sb - (sb >> 1) + SL + (s & 1) * SLOT + wz * 256);
            if (t < 15) PIN(1);
        }
        x[0] = movm(pack2(aq[0], aq[1])); x[1] = movm(pack2(aq[2], aq[3]));
        x[2] = movm(pack2(ak[0], ak[1])); x[3] = movm(pack2(ak[2], ak[3]));
        vv[0] = pack2(av[0], av[1]); vv[1] = pack2(av[2], av[3]);
        st_async2(l8 + (SL_VM + k.dp), vv[0], vv[1], qb + k.dp);
        st_async4(k.lw + (R_U + X * 4096 + w5 + k.dp), x[0], x[1], x[2], x[3], qb + k.dp);
    }
    {
        arrive_if(sb + R_BAR + (RB_GO + 2 - 2 * X + ((s + d) & 1)) * 8, (k.sp + z) & 0x1ff0, X ? s >= hi : s <= lo);
        const uint32_t swr = ((k.sp + z) & 0x1ff0) + (sb + R_SB);
#pragma unroll
        for (int i = 0; i < NPX; i++) wo[i] = lds128v(k.lw + w5 + R_WO + i * 4096);
        mbar_wait(sb + R_BAR + (RB_XFULL + X * 2) * 8 + (s & 1) * 8, (s >> 1) & 1);
        const uint4 k0 = lds128(k.lw + so + SL), k1 = lds128(k.lw + so + SL + 4096);
        mbar_wait(qb, s & 1);
        const uint4 u = lds128(k.lw + w5 + R_U + X * 4096);
        const uint32_t q0 = hadd2(x[0], u.x), q1 = hadd2(x[1], u.y);
        x[2] = hadd2(x[2], u.z); x[3] = hadd2(x[3], u.w);
        float sa[4] = {0, 0, 0, 0}, sc[4] = {0, 0, 0, 0}, sm0, sm1;
        mma16(sa, k0.x, k0.y, k0.z, k0.w, q0, q1);
        mma16(sc, k1.x, k1.y, k1.z, k1.w, q0, q1);
        mma16_top(sm0, sm1, x[2], x[3], q0, q1);
        asm volatile("stmatrix.sync.aligned.m8n8.x4.trans.shared.b16 [%0],{%1,%2,%3,%4};" ::"r"(swr), "r"(pack2(sa[0], sa[1])), "r"(pack2(sa[2], sa[3])),
                     "r"(pack2(sc[0], sc[1])), "r"(pack2(sc[2], sc[3])) : "memory");
        asm volatile("stmatrix.sync.aligned.m8n8.x1.trans.shared.b16 [%0],{%1};" ::"r"(swr + 512), "r"(pack2(sm0, sm1)) : "memory");
    }
    bar_sync(NB_S, 256);
    uint4 v0, v1;
    uint32_t ls;
    {
        const uint4 y = ldsm4t(k.lw + wz * 656 + R_SB);
        PIN(2);
        uint32_t y4; asm volatile("ldmatrix.sync.aligned.m8n8.x1.trans.shared.b16 {%0},[%1];" : "=r"(y4) : "r"(k.lw + wz * 656 + R_SB + 512) : "memory");
        PIN(2);
        const uint2 vp = lds64(l8 + SL_VM);
        sts64(l8 + SL_KM, x[2], x[3]);
        const uint32_t z1 = k.lw & z, z2 = k.sp & z, ONE = 0x3f803f80u | z2, ONF = 0x3f803f80u | z1;
        float a[4] = {0, 0, 0, 0}, b[4] = {0, 0, 0, 0}, e[4] = {0, 0, 0, 0};
        mma8(e, ONE, z1, y4); mma16(a, ONE, z1, z2, ONF, y.x, y.y); mma16(b, ONE, z1, z2, ONF, y.z, y.w);
        vv[0] = hadd2(vv[0], vp.x); vv[1] = hadd2(vv[1], vp.y);
        sts64(l8 + SL_VM, vv[0], vv[1]);
        float s0, s1;
        asm("{.reg .pred p1,p2,p4; .reg .f32 t0,t1,u0,u1; .reg .b32 m; and.b32 m,%12,64; setp.ne.u32 p1,m,0; and.b32 m,%12,128; setp.ne.u32 p2,m,0; and.b32 m,%12,256; setp.ne.u32 p4,m,0;"
            "selp.f32 t0,%4,%2,p1; selp.f32 t1,%5,%3,p1; selp.f32 u0,%8,%6,p1; selp.f32 u1,%9,%7,p1; selp.f32 t0,u0,t0,p2; selp.f32 t1,u1,t1,p2; selp.f32 %0,%10,t0,p4; selp.f32 %1,%11,t1,p4;}"
            : "=f"(s0), "=f"(s1) : "f"(a[0]), "f"(a[1]), "f"(a[2]), "f"(a[3]), "f"(b[0]), "f"(b[1]), "f"(b[2]), "f"(b[3]), "f"(e[0]), "f"(e[1]), "r"(k.lw));
        const int mi = __float_as_int(fmaxf(s0, s1));
        const int mp = __reduce_max_sync(0xffffffffu, mi), mn = (int)__reduce_min_sync(0xffffffffu, (unsigned)mi);
        PIN(3);
        v0 = lds128(k.lw + so + SL + SL_V); v1 = lds128(k.lw + so + SL + SL_V + 4096);
#pragma unroll
        for (int i = NPX; i < NPF; i++) wo[i] = lds128(k.lw + w5 + R_WO + i * 4096);
        PIN(4);
        const float mo = -__int_as_float(mp >= 0 ? mp : mn) * SC_LOG2E;
        s0 = ex2(fmaf(s0, SC_LOG2E, mo)); s1 = ex2(fmaf(s1, SC_LOG2E, mo));
        sts32((((k.sp + z) >> 11) & 0x1fc) + (k.lw & 256) * 2 + (sb + R_PB), pack2(s0, s1));
        ls = k.lw < sb + 320 ? __float_as_uint((s0 + s1) + 4.f) : 0;
    }
    bar_sync(NB_P, 256);
    {
        const uint4 pp = lds128(k.lw + R_PB);
        PIN(5);
        const uint32_t pm = lds32(((k.lw + z) >> 2) + (sb - (sb >> 2) + R_PB + 512));
        PIN(5);
        sts32(sb + R_IL + (wz >> 1) * 16 + (wz & 1) * 4, __reduce_add_sync(0xffffffffu, ls) - 20u * 0x40800000u);
        float o0[4] = {0, 0, 0, 0}, o1[4] = {0, 0, 0, 0}, o2[4] = {0, 0, 0, 0};
        mma16(o0, v0.x, v0.y, v0.z, v0.w, pp.x, pp.y);
        mma16(o1, v1.x, v1.y, v1.z, v1.w, pp.z, pp.w);
        mma8(o2, vv[0], vv[1], pm);
        asm volatile("stmatrix.sync.aligned.m8n8.x2.trans.shared.b16 [%0],{%1,%2};" ::"r"(k.lw + wz * 256 + R_OB),
                     "r"(pack2(o0[0] + o1[0] + o2[0], o0[1] + o1[1] + o2[1])), "r"(pack2(o0[2] + o1[2] + o2[2], o0[3] + o1[3] + o2[3])) : "memory");
    }
    bar_sync(NB_O, 256);
    {
        float r0[4] = {0, 0, 0, 0}, r1[4] = {0, 0, 0, 0};
        uint4 b[4];
        b[0] = ldsm4(k.lw + R_OB);
        PIN(6);
        b[1] = ldsm4(k.lw + R_OB + 512);
        PIN(6);
#pragma unroll
        for (int m = NWO + NPF; m < 16; m++) if (((OL >> (2 * (15 - m))) & 3) == 3) wo[m] = lds128(k.lw + w5 + R_WO + (m - NWO) * 4096);
        const uint2 il = lds64(sb + R_IL + ((k.lw + z) & 48));
        PIN(6);
        float i0, i1;
        uint4* dst;
#pragma unroll
        for (int i = 0; i < 4; i++) {
            mma16(r0, wo[4 * i].x, wo[4 * i].y, wo[4 * i].z, wo[4 * i].w, b[i].x, b[i].y);
            mma16(r1, wo[4 * i + 1].x, wo[4 * i + 1].y, wo[4 * i + 1].z, wo[4 * i + 1].w, b[i].x, b[i].y);
            mma16(r0, wo[4 * i + 2].x, wo[4 * i + 2].y, wo[4 * i + 2].z, wo[4 * i + 2].w, b[i].z, b[i].w);
            mma16(r1, wo[4 * i + 3].x, wo[4 * i + 3].y, wo[4 * i + 3].z, wo[4 * i + 3].w, b[i].z, b[i].w);
            if (i < 2) b[i + 2] = ldsm4(k.lw + R_OB + (i + 2) * 512);
#pragma unroll
            for (int m = NWO + NPF; m < 16; m++) if (i < 3 && i == ((OL >> (2 * (15 - m))) & 3)) wo[m] = lds128(k.lw + w5 + R_WO + (m - NWO) * 4096);
            if (i == 1) { i0 = rcp(__uint2float_rn(il.x)) * 2097152.f; i1 = rcp(__uint2float_rn(il.y)) * 2097152.f; }
            if (i == 2) {
                const uint32_t po = k.sp + z;
                dst = xregion(X, 0) + k.po + ((po >> 20) ^ ((po & X) << 8));
                asm volatile("" : "+l"(dst));
            }
            PIN(7);
        }
        const uint32_t tag = (s + 1) & 1;
#pragma unroll
        for (int i = 0; i < 4; i++) { r0[i] *= (i & 1) ? i1 : i0; r1[i] *= (i & 1) ? i1 : i0; }
        st_rlx128(dst, (pack2(r0[0], r0[2]) & ~1u) | tag,
                  pack2(r1[0], r1[2]), pack2(r0[1], r0[3]), pack2(r1[1], r1[3]));
        bar_arrive(NB_PART + X, 288);
#pragma unroll
        for (int t = 0; t < V_PRE; t++) if (!((VMASK >> t) & 1)) wv[t] = lds128(k.lw + w5 + R_WV + t * 4096);
        arrive_if(sb + R_BAR + (RB_GO + 2 * X + (s & 1)) * 8, (k.sp + z) & 0x1ff0, X ? s + 1 < hi : s >= lo);
    }
}

__device__ __forceinline__ void rec_fetch(const Params& p, uint32_t sb, int head, uint32_t rank, int which, int dst) {
#pragma unroll 1
    for (int j = 0; j < 8; j++) tma2d(sb + dst + j * 8192, &p.tm[which], head * 128 + (j >> 2) * 64, rank * 256 + (j & 3) * 64, sb + R_BAR + RB_INIT * 8);
}

__device__ __forceinline__ void rec_weights(const Params& p, uint32_t sb, int head, uint32_t rank, int w) {
    const int lane = __shfl_sync(0xffffffffu, threadIdx.x & 31, threadIdx.x & 31),
        g = lane >> 2, c = lane & 3;
    const int t = w & 3, WG = w >> 2;
    uint32_t wq[16][4], wk[16][4];
    uint4 wo[16], wv[16];
    const uint32_t woff = sb + WG * 32768 + (((lane >> 4) << 3) + (lane & 7)) * 128 + (((2 * t + ((lane >> 3) & 1)) ^ (lane & 7)) << 4);
    const uint32_t lw = sb + lane * 16;
    PROF2(threadIdx.x == 0, 3501);
    {
        const __nv_bfloat16* wp = p.Wo + (size_t)(head * 128 + 2 * c) * 512 + rank * 256 + w * 32 + g * 4;
#pragma unroll
        for (int ks = 0; ks < 8; ks++) {
            const uint2 r0 = *(const uint2*)(wp + (ks * 16) * 512), r1 = *(const uint2*)(wp + (ks * 16 + 1) * 512);
            const uint2 r2 = *(const uint2*)(wp + (ks * 16 + 8) * 512), r3 = *(const uint2*)(wp + (ks * 16 + 9) * 512);
            const uint4 f[2] = {make_uint4(__byte_perm(r0.x, r1.x, 0x5410), __byte_perm(r0.x, r1.x, 0x7632), __byte_perm(r2.x, r3.x, 0x5410), __byte_perm(r2.x, r3.x, 0x7632)),
                                make_uint4(__byte_perm(r0.y, r1.y, 0x5410), __byte_perm(r0.y, r1.y, 0x7632), __byte_perm(r2.y, r3.y, 0x5410), __byte_perm(r2.y, r3.y, 0x7632))};
#pragma unroll
            for (int h = 0; h < 2; h++) {
                const int m = 2 * ks + h;
                wo[m] = f[h];
            }
        }
    }
    PROF2(threadIdx.x == 0, 3502);
    mbar_wait(sb + R_BAR + RB_INIT * 8, 0);
    PROF2(threadIdx.x == 0, 3503);
#pragma unroll
    for (int ks = 0; ks < 16; ks++) {
        uint4 a = ldsm4t(woff + R_STQ + ks * 2048), b = ldsm4t(woff + R_STK + ks * 2048);
        wq[ks][0] = a.x; wq[ks][1] = a.y; wq[ks][2] = a.z; wq[ks][3] = a.w;
        wk[ks][0] = b.x; wk[ks][1] = b.y; wk[ks][2] = b.z; wk[ks][3] = b.w;
    }
    bar_sync(NB_W, 256);
#pragma unroll
    for (int m = 0; m < 16; m++)
        if (m < NPF || m >= NPF + NWO) sts128(lw + w * 512 + R_WO + (m < NPF ? m : m - NWO) * 4096, wo[m].x, wo[m].y, wo[m].z, wo[m].w);
#pragma unroll
    for (int i = 0; i < 16; i++) {
        wv[i] = ldsm4t(woff + R_STV + i * 2048);
        if (!((VMASK >> i) & 1)) sts128(lw + w * 512 + R_WV + i * 4096, wv[i].x, wv[i].y, wv[i].z, wv[i].w);
    }
    fence_async_smem();
    PROF2(threadIdx.x == 0, 3504);
    __syncthreads();
    cluster_sync();
    PROF2(threadIdx.x == 0, 3505);
    RecW k;
    {
        const int r = (w * 4 + (lane >> 3)) * 2 + rank;
        const uint32_t sl = lds32(sb + R_SEL + r * 4);
        k.po = (w * 8 + rank) * 512 + (head >> 1) * 16 + (head & 1) * 4;
        k.sp = (((lane >> 3) * 1024 + (sl & 1) * 256 + (lane & 4) * 2 + (lane & 3)) << 20) + (((sl >> 1) ^ sl) & 1) + (lane & 7) * 656 + (lane >> 3) * 128 + w * 16 +
               ((g < 4 ? (w * 4 + c) * 4 + g : w * 4 + c) << 13);
    }
    k.dp = mapa(sb, rank ^ 1) - sb;
    k.lw = lw;
    asm volatile("" : "+r"(k.lw));
    k.w = w;
    const int e0 = (p.chains & 1) ? 64 : 0, o1 = (p.chains & 2) ? p.lag : 1000, nit = (p.chains & 2) ? p.lag + 64 : e0;
    const uint32_t zero = p.zero;
    int it = 0, X = e0 ? 0 : 1;
#pragma unroll 1
    while (it < nit) {
        rec_step(k, sb, X, X ? it - o1 : it, zero, o1, e0 - o1, o1 + 1 - X, wq, wk, wv, wo);
        if (X == 0 && it >= o1) X = 1; else { it++; X = it < e0 ? 0 : 1; }
    }
}

__device__ __forceinline__ uint32_t mism(uint32_t a, uint32_t b, uint32_t t) {
    uint32_t d; asm("lop3.b32 %0,%1,%2,%3,0x7e;" : "=r"(d) : "r"(a), "r"(b), "r"(t)); return d;
}
__device__ __forceinline__ uint32_t or3(uint32_t a, uint32_t b, uint32_t c) {
    uint32_t d; asm("lop3.b32 %0,%1,%2,%3,0xfe;" : "=r"(d) : "r"(a), "r"(b), "r"(c)); return d;
}
template <bool TWO, class F>
__device__ __forceinline__ void poll8(uint4* x, const uint4* src, uint32_t tag, F&& use) {
#pragma unroll
    for (int j = 0; j < 8; j++) x[j] = ld_rlx128(src + j * 32);
    int n = 0;
    while (true) {
        use();
        uint32_t bad = or3(mism(x[0].x, x[1].x, tag), mism(x[2].x, x[3].x, tag), mism(x[4].x, x[5].x, tag));
        if (TWO) bad = or3(bad, or3(mism(x[0].z, x[1].z, tag), mism(x[2].z, x[3].z, tag), mism(x[4].z, x[5].z, tag)), mism(x[6].z, x[7].z, tag));
        if (!__any_sync(0xffffffffu, (bad | mism(x[6].x, x[7].x, tag)) & 1)) break;
#pragma unroll
        for (int j = 0; j < 8; j++)
            asm volatile("{.reg .pred p; .reg .b128 t; .reg .b32 m; lop3.b32 m,%0,%6,%5,0x7e; and.b32 m,m,1; setp.ne.u32 p,m,0; mov.b128 t,{%0,%1,%2,%3};"
                         "@p ld.relaxed.gpu.global.b128 t,[%4]; mov.b128 {%0,%1,%2,%3},t;}"
                         : "+r"(x[j].x), "+r"(x[j].y), "+r"(x[j].z), "+r"(x[j].w) : "l"(src + j * 32), "r"(tag), "r"(TWO ? x[j].z : tag) : "memory");
        if (++n > 2000000) __trap();
    }
}

__device__ __forceinline__ void rec_comm(const Params& p, uint32_t sb, int X, int head, uint32_t rank) {
    const int lane = threadIdx.x & 31, g = lane >> 2, c = lane & 3;
    const int me = head * 2 + rank;
    const uint32_t mb = sb + R_M + X * 4096 + lane * 16;
    uint4 x[8];
#pragma unroll
    for (int j = 0; j < 8; j++) x[j] = *(const uint4*)(p.mem0 + (lane & 7) * 512 + rank * 256 + (j * 4 + (lane >> 3)) * 8);
    const uint32_t sl = lds32(sb + R_SEL + me * 4);
    const uint4* src1 = xregion(X, me) + ((sl >> X) & 1) * 256 + (c >> 1) * 16 + (g >> 2) * 8 + (c & 1) * 4 + (g & 3);
    const uint4* src2 = xregion(X, 64 + rank) + ((sl >> (2 + X)) & 1) * 256 + lane;
    uint2* mdst = (uint2*)(xregion(X, 64 + rank) + (c >> 1) * 256 + head * 8 + (g & 3) * 2 + (c & 1)) + (g >> 2);
    const uint32_t one = (g & 1) ? 0x3f800000u : 0x00003f80u, selA = (g & 2) ? 0u : one, selB = (g & 2) ? one : 0u;
    const uint32_t qb = sb + R_BAR + (RB_QK + X * 8) * 8;
    if (lane < 8) mbar_expect(qb + lane * 8, 768);
    __syncwarp();
#pragma unroll
    for (int j = 0; j < 8; j++) sts128(mb + j * 512, x[j].x, x[j].y, x[j].z, x[j].w);
#pragma unroll 1
    for (int s = 0;; s++) {
        bar_arrive(NB_MFULL + X, 288);
        PROF(lane == 0, X * 64 + s);
        bar_sync(NB_PART + X, 288);
        if (s == 63) break;
        const uint32_t tag = (s + 1) & 1;
        asm volatile("{.reg .pred p; setp.lt.u32 p,%0,%1; @p mbarrier.arrive.expect_tx.shared::cta.b64 _,[%0],768;}"
                     ::"r"(((mb + (s & p.zero)) >> 1) + (qb - ((sb + R_M + X * 4096) >> 1))), "r"(qb + 64) : "memory");
        spin(D1);
        poll8<false>(x, src1, tag, []() {});
        float a[4][4];
#pragma unroll
        for (int j = 0; j < 8; j++) {
            if (j < 4) a[j][0] = a[j][1] = a[j][2] = a[j][3] = 0;
            mma16(a[j & 3], x[j].x, x[j].y, x[j].z, x[j].w, selA, selB);
        }
#pragma unroll
        for (int i = 0; i < 4; i++) a[0][i] = (a[0][i] + a[1][i]) + (a[2][i] + a[3][i]);
        const uint32_t m0 = (pack2(a[0][0], a[0][1]) & ~1u) | tag, m1 = pack2(a[0][2], a[0][3]);
        asm volatile("st.relaxed.gpu.global.b64 [%0],%1;" ::"l"(mdst), "l"(((uint64_t)m1 << 32) | m0) : "memory");
        spin(D2);
        poll8<true>(x, src2, tag, [&]() {
#pragma unroll
            for (int j = 0; j < SEARLY; j++) sts128(mb + j * 512, x[j].x, x[j].y, x[j].z, x[j].w);
        });
#pragma unroll
        for (int j = SEARLY; j < 8; j++) sts128(mb + j * 512, x[j].x, x[j].y, x[j].z, x[j].w);
    }
}

template <int MT>
__device__ __forceinline__ void xattn(uint32_t l16, uint32_t l8, uint32_t os, int g, int c) {
    constexpr int NT = 3 + 2 * MT, XUN = XU;
    float S[NT][4];
#pragma unroll
    for (int i = 0; i < NT; i++) S[i][0] = S[i][1] = S[i][2] = S[i][3] = 0;
#pragma unroll XUN
    for (int ks = 0; ks < 8; ks++) {
        const uint4 q = lds128(l16 + SL_Q + ks * 512);
        const uint2 u = lds64(l8 + SL_KM + ks * 256);
        mma16(S[0], q.x, q.y, q.z, q.w, u.x, u.y);
#pragma unroll
        for (int m = 0; m <= MT; m++) {
            const uint4 kk = lds128(l16 + m * 4096 + ks * 512);
            mma16(S[1 + 2 * m], q.x, q.y, q.z, q.w, kk.x, kk.z); mma16(S[2 + 2 * m], q.x, q.y, q.z, q.w, kk.y, kk.w);
        }
    }
    const float NEG = -__int_as_float(0x7f800000);
    if (2 * c > g) { S[NT - 2][0] = NEG; S[NT - 1][2] = NEG; }
    if (2 * c + 1 > g) { S[NT - 2][1] = NEG; S[NT - 1][3] = NEG; }
    S[NT - 1][0] = S[NT - 1][1] = NEG;
    float m0 = fmaxf(S[0][0], S[0][1]), m1 = fmaxf(S[0][2], S[0][3]);
#pragma unroll
    for (int i = 1; i < NT; i++) { if (i < NT - 1) m0 = fmaxf(m0, fmaxf(S[i][0], S[i][1])); m1 = fmaxf(m1, fmaxf(S[i][2], S[i][3])); }
    m0 = fmaxf(m0, __shfl_xor_sync(0xffffffffu, m0, 1)); m1 = fmaxf(m1, __shfl_xor_sync(0xffffffffu, m1, 1));
    m0 = fmaxf(m0, __shfl_xor_sync(0xffffffffu, m0, 2)); m1 = fmaxf(m1, __shfl_xor_sync(0xffffffffu, m1, 2));
    m0 *= -SC_LOG2E; m1 *= -SC_LOG2E;
    float l0 = 0, l1 = 0;
#pragma unroll
    for (int i = 0; i < NT; i++) {
        if (i < NT - 1) { S[i][0] = ex2(fmaf(S[i][0], SC_LOG2E, m0)); S[i][1] = ex2(fmaf(S[i][1], SC_LOG2E, m0)); l0 += S[i][0] + S[i][1]; }
        S[i][2] = ex2(fmaf(S[i][2], SC_LOG2E, m1)); S[i][3] = ex2(fmaf(S[i][3], SC_LOG2E, m1)); l1 += S[i][2] + S[i][3];
    }
    l0 += __shfl_xor_sync(0xffffffffu, l0, 1); l1 += __shfl_xor_sync(0xffffffffu, l1, 1);
    l0 += __shfl_xor_sync(0xffffffffu, l0, 2); l1 += __shfl_xor_sync(0xffffffffu, l1, 2);
    uint2 vm = lds64(l8 + SL_VM);
    uint4 v[2];
#pragma unroll
    for (int m = 0; m <= MT; m++) v[m] = lds128(l16 + SL_V + m * 4096);
    l0 = rcp(l0); l1 = rcp(l1);
    uint32_t P[NT][2];
#pragma unroll
    for (int i = 0; i < NT; i++) { P[i][0] = i < NT - 1 ? pack2(S[i][0] * l0, S[i][1] * l0) : 0u; P[i][1] = pack2(S[i][2] * l1, S[i][3] * l1); }
#pragma unroll
    for (int et = 0; et < 8; et++) {
        float a[4] = {0, 0, 0, 0}, b[4] = {0, 0, 0, 0};
        const uint2 um = vm;
        const uint4 u[2] = {v[0], v[MT]};
        if (et < 7) {
            vm = lds64(l8 + SL_VM + et * 256 + 256);
#pragma unroll
            for (int m = 0; m <= MT; m++) v[m] = lds128(l16 + SL_V + m * 4096 + et * 512 + 512);
            PIN(11);
        }
        mma8(a, um.x, um.y, P[0][0]); mma8(b, um.x, um.y, P[0][1]);
#pragma unroll
        for (int m = 0; m <= MT; m++) {
            mma16(a, u[m].x, u[m].y, u[m].z, u[m].w, P[1 + 2 * m][0], P[2 + 2 * m][0]); mma16(b, u[m].x, u[m].y, u[m].z, u[m].w, P[1 + 2 * m][1], P[2 + 2 * m][1]);
        }
        asm volatile("stmatrix.sync.aligned.m8n8.x4.trans.shared.b16 [%0],{%1,%2,%3,%4};" ::"r"(os + (et >> 2) * 2048 + (et & 3) * 256),
                     "r"(pack2(a[0], a[1])), "r"(pack2(a[2], a[3])), "r"(pack2(b[0], b[1])), "r"(pack2(b[2], b[3])) : "memory");
    }
}

__device__ __forceinline__ void rec_tiles(uint32_t sb, int X, int head, uint32_t rank, int& nxt, int lim, int need) {
#pragma unroll 1
    while (nxt <= lim) {
        if ((nxt & 1) == 0) {
            unsigned v; int n = 0;
            while (true) {
                asm volatile("ld.relaxed.gpu.global.u32 %0,[%1];" : "=r"(v) : "l"(cnt_ptr(C_QKV + X * 32 + (nxt >> 1))) : "memory");
                if (__all_sync(0xffffffffu, v >= 2 * NQ)) break;
                if (nxt > need) return;
                if (++n > 3000000) __trap();
            }
        }
        if (elect()) {
            const uint32_t bar = sb + R_BAR + (RB_XFULL + X * 2 + (nxt & 1)) * 8, dst = sb + R_SL + (X * 2 + (nxt & 1)) * SLOT;
            const uint4* src = g_qkv + (size_t)((X * 64 + nxt) * 32 + head) * 1536;
            mbar_expect(bar, 20480);
            bulk_g2s_mc(dst + rank * 8192, src + 512 + rank * 512, 8192, bar, POL_LAST);
            bulk_g2s(dst + SL_Q, src + (rank ^ X) * 256, 4096, bar, POL_LAST);
        }
        __syncwarp();
        nxt++;
    }
}

__device__ __forceinline__ void rec_attn(const Params& p, uint32_t sb, int X, int head, uint32_t rank) {
    const int lane = __shfl_sync(0xffffffffu, threadIdx.x & 31, threadIdx.x & 31), g = lane >> 2, c = lane & 3;
    const int mt = rank ^ X;
    const uint32_t dp = mapa(sb, rank ^ 1) - sb;
    int nxt = 0;
    rec_tiles(sb, X, head, rank, nxt, 1, 0);
#pragma unroll 1
    for (int s = 0; s < 64; s++) {
        const uint32_t so = sb + R_SL + (X * 2 + (s & 1)) * SLOT;
        while (nxt <= min(s + 1, 63)) {
            uint32_t ok;
            asm volatile("{.reg .pred p; mbarrier.test_wait.parity.shared::cta.b64 p,[%1],%2; selp.u32 %0,1,0,p;}" : "=r"(ok) : "r"(sb + R_BAR + (RB_GO + X * 2 + (s & 1)) * 8), "r"((s >> 1) & 1) : "memory");
            if (__any_sync(0xffffffffu, ok)) break;
            rec_tiles(sb, X, head, rank, nxt, s + 1, -1);
        }
        mbar_wait(sb + R_BAR + (RB_GO + X * 2 + (s & 1)) * 8, (s >> 1) & 1);
        if (elect()) asm volatile("cp.async.bulk.wait_group.read 0;" ::: "memory");
        __syncwarp();
        const uint32_t os = sb + R_OS + X * 4096 + (lane >> 4) * 1024 + (lane & 15) * 16;
        if (mt) xattn<1>(so + lane * 16, so + lane * 8, os, g, c); else xattn<0>(so + lane * 16, so + lane * 8, os, g, c);
        fence_async_smem();
        __syncwarp();
        const uint32_t svb = sb + R_BAR + (RB_SV + X * 2 + (s & 1)) * 8;
        if (elect()) {
            mbar_arrive(svb); mbar_arrive_cluster(svb + dp);
            const uint64_t pol = POL_N;
#pragma unroll
            for (int kb = 0; kb < 2; kb++)
                asm volatile("cp.async.bulk.global.shared::cta.bulk_group.L2::cache_hint [%0],[%1],%2,%3;" ::"l"(g_o + ((X * 32 + (s >> 1)) * 64 + head * 2 + kb) * 512 + ((s & 1) * 4 + mt * 2) * 64),
                             "r"(sb + R_OS + X * 4096 + kb * 2048), "r"(2048), "l"(pol) : "memory");
            asm volatile("cp.async.bulk.commit_group;" ::: "memory");
        }
        __syncwarp();
        if (s & 1) {
            if (elect()) { asm volatile("cp.async.bulk.wait_group 0;" ::: "memory"); red_relaxed(cnt_ptr(C_O + (X * 32 + (s >> 1)) * 4 + (head >> 3)), 1); }
            __syncwarp();
        }
        rec_tiles(sb, X, head, rank, nxt, min(s + 1, 63), s + 1);
        mbar_wait(svb, (s >> 1) & 1);
        rec_tiles(sb, X, head, rank, nxt, min(s + 2, 63), -1);
    }
}

__device__ __forceinline__ uint32_t timed_clear(unsigned* r, int lane) {
    uint32_t v = 0;
    const uint32_t t0 = clk32();
    asm volatile("{.reg .pred p; setp.eq.u32 p,%2,0; @p atom.relaxed.gpu.global.exch.b32 %0,[%1],0;}" : "+r"(v) : "l"(r), "r"(lane) : "memory");
    v = __shfl_sync(0xffffffffu, v, 0);
    asm volatile("{.reg .pred p; setp.eq.u32 p,%0,0x5a5a5a5b; @p nanosleep.u32 1;}" ::"r"(v) : "memory");
    return clk32() - t0;
}
__device__ __forceinline__ void rec_slots(int me, int w) {
    const int lane = threadIdx.x & 31;
    uint4* r = xregion(w & 1, (w & 2) ? 64 + (me & 1) : me) + ((w & 2) ? (me >> 1) * 8 : 0);
#pragma unroll 1
    for (int i = lane; i < ((w & 2) ? 8 : 256); i += 32) r[i] = r[i + 256] = make_uint4(0, 0, 0, 0);
    __syncwarp();
    uint32_t b0 = ~0u, b1 = ~0u;
#pragma unroll 1
    for (int i = 0; i < NPRB; i++) { b0 = min(b0, timed_clear((unsigned*)r, lane)); b1 = min(b1, timed_clear((unsigned*)(r + 256), lane)); }
    if (lane == 0) ((uint8_t*)g_sel)[me * 4 + w] = (b1 < b0) << w;
}

__device__ __forceinline__ void rec_init(uint32_t sb) {
    const uint32_t b = sb + R_BAR;
    const int i = threadIdx.x & 31;
    mbar_init(b + i * 8, i >= RB_SV ? 2 : 1);
    if (i == RB_INIT) mbar_expect(b + RB_INIT * 8, 196608);
    asm volatile("fence.mbarrier_init.release.cluster;" ::: "memory");
}
constexpr int G_BAR = B_BAR;
enum { GB_FULL = 0  , GB_EMPTY = 8  , GB_RS = 16, GB_SS = 17, GB_LAG = 18, GB_FREE = 19, GB_DONE = 20  , GB_N = 24 };
constexpr int Q_PRE = 8;
constexpr int NQRS = 2 * NQ - 64;
__device__ __forceinline__ void gemm_init(uint32_t sb, bool op) {
    const int i = threadIdx.x & 31;
    if (i < GB_N) mbar_init(sb + G_BAR + i * 8, i >= GB_DONE ? 4 : i == GB_FREE ? 8 : (i >= GB_EMPTY && i < GB_RS) ? 2 : 1);
    if (i == GB_RS) mbar_expect(sb + G_BAR + i * 8, op ? 131072 : 98304);
    if (i == GB_SS) mbar_expect(sb + G_BAR + i * 8, op ? 131072 : 163840);
    asm volatile("fence.mbarrier_init.release.cluster;" ::: "memory");
}
__device__ __forceinline__ int qkv_blk(int id, int j) { return NQRS * 4 + id * 10 + j; }
__device__ __forceinline__ void qkv_fetch(const Params& p, uint32_t sb, int id, int j0, int j1) {
#pragma unroll 1
    for (int j = j0 * 2; j < j1 * 2; j++) {
        const int blk = min(qkv_blk(id, j >> 1), 511);
        tma2d(sb + j * 8192, &p.tn[blk >> 8], (blk & 255) * 16, (j & 1) * 256, sb + G_BAR + GB_SS * 8);
    }
}
__device__ __forceinline__ void qkv_stage(const Params& p, uint32_t dst, uint32_t bar, int id, int k0, int nk) {
#pragma unroll 1
    for (int j = 0; j < 2 * nk; j++) {
        const int u = id * 2 + (j >= nk);
        tma2d(dst + j * 8192, &p.tm[u < 64 ? 2 : 0], (u & 63) * 64, (k0 + (j >= nk ? j - nk : j)) * 64, bar);
    }
}
__device__ __forceinline__ void op_fetch(const Params& p, uint32_t sb, int id, int half) {
#pragma unroll 1
    for (int j = 0; j < 16; j++) tma2d(sb + j * 8192, &p.tm[4], ((id * 2 + (j >> 3)) & 7) * 64, (id >> 2) * 1024 + (j & 7) * 128 + half * 64, sb + G_BAR + (GB_RS + half) * 8);
}
template <bool OP>
__device__ __forceinline__ void gemm_producer(const Params& p, uint32_t sb, int id) {
    constexpr int NS = OP ? 6 : 8, SB = OP ? 16384 : 8192, RB = OP ? 131072 : 163840;
    if (!elect()) return;
    mbar_wait(sb + G_BAR + GB_FREE * 8, 0);
    if (OP) op_fetch(p, sb, id, 1);
    else {
        mbar_expect(sb + G_BAR + GB_RS * 8, 32768);
        qkv_stage(p, sb + 196608, sb + G_BAR + GB_RS * 8, id, 6, 2);
        qkv_fetch(p, sb, id, Q_PRE, 10);
        mbar_wait(sb + G_BAR + GB_FREE * 8, 1);
    }
    wait_cnt(g_gate, lds32(sb + S_GATE));
    int st = 0; uint32_t ph = 1;
#pragma unroll 1
    for (int n = 0; n < p.nl[OP]; n++) {
        const int e = p.list[OP][n];
        wait_cnt(OP ? cnt_ptr(C_O + e * 4 + (id >> 2)) : cnt_ptr(C_XN + e), 16);
        PROF(true, 1024 + n * 4);
        const uint4* src = OP ? g_o + (e * 64 + (id >> 2) * 16) * 512 : g_xn + e * 4096;
#pragma unroll 1
        for (int s = 0; s < 8; s++) {
            mbar_wait(sb + G_BAR + (GB_EMPTY + st) * 8, ph);
            mbar_expect(sb + G_BAR + (GB_FULL + st) * 8, SB);
            bulk_g2s(sb + RB + st * SB, src + s * (SB / 16), SB, sb + G_BAR + (GB_FULL + st) * 8, POL_N);
            if (++st == NS) { st = 0; ph ^= 1; }
        }
    }
}
__device__ __forceinline__ void qkv_release(const Params& p, uint32_t sb) {
    if (!elect()) return;
#pragma unroll 1
    for (int n = 0; n < 2 * p.nl[0]; n++) {
        const int e = p.list[0][n >> 1];
        mbar_wait(sb + G_BAR + (GB_DONE + (n & 3)) * 8, (n >> 2) & 1);
        red_release(cnt_ptr(C_QKV + e), 1);
        PROF(n & 1, 1024 + (n >> 1) * 4 + 3);
    }
}
__device__ __forceinline__ void op_permute(uint32_t sb) {
#pragma unroll 2
    for (int i = threadIdx.x; i < 4096; i += 256) {
        const uint32_t a = sb + i * 32 + ((i >> 2) & 1) * 16, b = a ^ 16;
        const uint4 x = lds128(a), y = lds128(b);
        sts128(a, __byte_perm(x.x, x.y, 0x5410), __byte_perm(x.z, x.w, 0x5410), __byte_perm(y.x, y.y, 0x5410), __byte_perm(y.z, y.w, 0x5410));
        sts128(b, __byte_perm(x.x, x.y, 0x7632), __byte_perm(x.z, x.w, 0x7632), __byte_perm(y.x, y.y, 0x7632), __byte_perm(y.z, y.w, 0x7632));
    }
    fence_async_smem();
    bar_sync(1, 256);
}
template <bool OP>
__device__ __forceinline__ void gemm_consumer(const Params& p, uint32_t sb, int id, int w) {
    constexpr int NS = OP ? 6 : 8, SB = OP ? 16384 : 8192, RB = OP ? 131072 : 163840;
    const int lane = threadIdx.x & 31, wg = w >> 2, t = w & 3, u = id * 2 + wg;
    uint32_t a[128];
    mbar_wait(sb + G_BAR + GB_RS * 8, 0);
    PROF2(threadIdx.x == 0, 3501);
    if (OP) op_permute(sb);
    const uint32_t wo = sb + (((lane >> 4) << 3) + (lane & 7)) * 128 + (((2 * t + ((lane >> 3) & 1)) ^ (lane & 7)) << 4);
#pragma unroll
    for (int ks = 0; ks < 32; ks++) {
        const uint4 v = ldsm4t(wo + ks * 2048 + (OP ? wg * 65536 : ks < 24 ? 131072 + wg * 49152 : 196608 - 49152 + wg * 16384));
        a[ks * 4] = v.x; a[ks * 4 + 1] = v.y; a[ks * 4 + 2] = v.z; a[ks * 4 + 3] = v.w;
        if (ks == 31 || (!OP && ks == 23)) {
            fence_async_smem();
            __syncwarp();
            if (lane == 0) mbar_arrive(sb + G_BAR + GB_FREE * 8);
            if (ks == 23) mbar_wait(sb + G_BAR + GB_RS * 8, 1);
        }
    }
    PROF2(threadIdx.x == 0, 3502);
    mbar_wait(sb + G_BAR + GB_SS * 8, 0);
    if (OP) op_permute(sb);
    PROF2(threadIdx.x == 0, 3503);
    const uint32_t tag = OP ? lds32(sb + S_TAG) : 0;
    float c0[32], c1[OP ? 32 : 40];
    int st = 0; uint32_t ph = 0;
    const bool el = (threadIdx.x & 127) == 0;
#pragma unroll 1
    for (int n = 0; n < p.nl[OP]; n++) {
        int prev = 0;
        const uint32_t wb = sb + wg * (OP ? 65536 : 81920) + (n & p.zero);
        const uint64_t dw = OP ? mkdesc(wb, 0, 1024, 1) : mkdesc(wb, 16384, 256, 3);
        if ((!OP || OLAG) && wg) mbar_wait(sb + G_BAR + GB_LAG * 8, n & 1);
#pragma unroll
        for (int s = 0; s < 8; s++) {
            mbar_wait(sb + G_BAR + (GB_FULL + st) * 8, ph);
            const uint64_t dx = mkdesc(sb + RB + st * SB, 128, 1024, 0);
            wg_fence();
#pragma unroll
            for (int kk = 0; kk < 4; kk++) {
                const int ks = s * 4 + kk;
                if (ks == 0) { wgmma64_rs<0>(c0, a, dx); if (OP) wgmma64_ta<0>(c1, dw, dx + 512); else wgmma80_tb<0>(c1, dx, dw); }
                else { wgmma64_rs<1>(c0, a + ks * 4, dx + kk * 16); if (OP) wgmma64_ta<1>(c1, dw + ks * 128, dx + 512 + kk * 16); else wgmma80_tb<1>(c1, dx + kk * 16, dw + ks * 32); }
            }
            wg_commit();
            if (s) {
                wg_wait<1>();
                if (el) { mbar_arrive(sb + G_BAR + (GB_EMPTY + prev) * 8); if (s == (OP ? OLAG : QLAG) && !wg) mbar_arrive(sb + G_BAR + GB_LAG * 8); }
            }
            prev = st;
            if (++st == NS) { st = 0; ph ^= 1; }
        }
        const int e = p.list[OP][n];
        wg_wait<0>();
        if (el) mbar_arrive(sb + G_BAR + (GB_EMPTY + prev) * 8);
        PROF(threadIdx.x == 128, 1024 + n * 4 + 1);
        if (OP) {
            uint4* dst = g_pp + (e * 4 + (id >> 2)) * 4096 + ((u & 7) * 32 + t * 8) * 16 + (lane >> 2) * 16 + (lane & 3);
#pragma unroll
            for (int j = 0; j < 4; j++) {
                const float* x = c0 + j * 8; const float* y = c1 + j * 8;
                st_rlx128(dst + j * 4, (pack2(x[0] + y[0], x[1] + y[1]) & ~1u) | tag, pack2(x[2] + y[2], x[3] + y[3]), (pack2(x[4] + y[4], x[5] + y[5]) & ~1u) | tag, pack2(x[6] + y[6], x[7] + y[7]));
            }
            if (lane == 0) red_relaxed(cnt_ptr(C_PP + e * 8 + (u & 7)), 1);
            PROF(threadIdx.x == 128, 1024 + n * 4 + 3);
        } else {
            uint4* dst = g_qkv + (size_t)e * 2 * 32 * 1536 + lane;
            const uint64_t pol = POL_N;
#pragma unroll
            for (int j = 0; j < 4; j++) {
                const float* x = c0 + j * 8;
                uint4 v = make_uint4(pack2(x[0], x[1]), pack2(x[2], x[3]), pack2(x[4], x[5]), pack2(x[6], x[7]));
                if (u >= 64) v = make_uint4(movm(v.x), movm(v.z), movm(v.y), movm(v.w));
                stg128(dst + (((j >> 1) * 32 + ((u & 63) >> 1)) * 1536 + (u < 64 ? 1024 : 0) + (j & 1) * 256 + ((u & 1) * 4 + t) * 32), v, pol);
            }
#pragma unroll
            for (int j = 0; j < 5; j++) {
                const float* x = c1 + (OP ? 0 : j * 8);
                const int blk = qkv_blk(id, wg * 5 + j);
                if (blk < 512) stg128(dst + (((t >> 1) * 32 + ((blk >> 3) & 31)) * 1536 + (blk >> 8) * 512 + (t & 1) * 256 + (blk & 7) * 32),
                                      make_uint4(pack2(x[0], x[1]), pack2(x[2], x[3]), pack2(x[4], x[5]), pack2(x[6], x[7])), pol);
            }
        }
        __syncwarp();
        if (!OP && lane == 0) mbar_arrive(sb + G_BAR + (GB_DONE + (n & 1) * 2 + wg) * 8);
        PROF(threadIdx.x == 128, 1024 + n * 4 + 2);
    }
}

template <int NP, bool MMA>
__device__ __forceinline__ void sum_partials(float* x, const uint2* src, const uint32_t* r0, const uint32_t* r1, uint32_t idm, uint32_t tag, bool on) {
    uint2 v[4][NP];
    int n = 0;
    while (true) {
        uint32_t bad = 0;
#pragma unroll
        for (int s = 0; s < 4; s++)
#pragma unroll
            for (int i = 0; i < NP; i++)
                asm volatile("{.reg .pred p; .reg .b64 t; setp.ne.u32 p,%4,0; mov.b64 t,0; @p ld.relaxed.gpu.global.L2::cache_hint.b64 t,[%2],%3; mov.b64 {%0,%1},t;}"
                             : "=r"(v[s][i].x), "=r"(v[s][i].y) : "l"(src + s * 8192 + i * 32), "l"(POL_LAST), "r"((uint32_t)on) : "memory");
#pragma unroll
        for (int s = 0; s < 4; s++) bad = or3(bad, mism(v[s][0].x, v[s][1].x, tag), mism(v[s][NP - 2].x, v[s][NP - 1].x, tag));
        if (!__any_sync(0xffffffffu, (bad & 1) && on)) break;
        if (++n > 2000000) __trap();
    }
#pragma unroll
    for (int i = 0; i < NP; i++) {
        uint32_t a, b;
        if (MMA) {
            float t[4] = {0, 0, 0, 0};
            mma16(t, v[0][i].x, v[0][i].y, v[1][i].x, v[1][i].y, idm, idm); mma16(t, v[2][i].x, v[2][i].y, v[3][i].x, v[3][i].y, idm, idm);
            a = pack2(t[0], t[2]); b = pack2(t[1], t[3]);
        } else {
            a = pack2((blo(v[0][i].x) + blo(v[1][i].x)) + (blo(v[2][i].x) + blo(v[3][i].x)), (blo(v[0][i].y) + blo(v[1][i].y)) + (blo(v[2][i].y) + blo(v[3][i].y)));
            b = pack2((bhi(v[0][i].x) + bhi(v[1][i].x)) + (bhi(v[2][i].x) + bhi(v[3][i].x)), (bhi(v[0][i].y) + bhi(v[1][i].y)) + (bhi(v[2][i].y) + bhi(v[3][i].y)));
        }
        const uint32_t s0 = hadd2(a, r0[i]), s1 = hadd2(b, r1[i]);
        x[4 * i] = blo(s0); x[4 * i + 2] = bhi(s0); x[4 * i + 1] = blo(s1); x[4 * i + 3] = bhi(s1);
    }
}
__device__ __forceinline__ const uint2* pp_src(int e, int tile, int lane) { return (const uint2*)g_pp + e * 32768 + tile * 128 + (lane >> 3) * 8 + (lane & 3) * 2 + ((lane >> 2) & 1); }

__device__ __forceinline__ void fin_warp(const Params& p, uint32_t sb, int id0) {
    wait_slow_warp(g_gate, lds32(sb + S_GATE));
#pragma unroll 1
    for (int e = id0 < 2 * NQ ? 32 : FJ; e < 64; e++)
#pragma unroll 1
    for (int id = id0; id < (e < FJ ? 128 : id0 + 1); id += 2 * NQ) {
        const int grp = (id & ~3) + (threadIdx.x & 3), tp = (id & 3) * 8 + ((threadIdx.x & 31) >> 2);
        wait_slow_warp(cnt_ptr(C_XN + e), 16);
        const uint4 r = ldcg128(g_x + ((128 + grp) * XP + (e - 32) * 32 + tp));
        if (e < 63) wait_slow_warp(cnt_ptr(C_PP + e * 8 + (id >> 4)), 16); else wait_slow_warp(cnt_ptr(C_O + 63 * 4), 16);
        wait_flag_warp(cnt_ptr(C_PP + e * 8 + (id >> 4)), 16);
        const uint32_t a[2] = {r.x, r.y}, b[2] = {r.z, r.w};
        float x[8];
        sum_partials<2, false>(x, pp_src(e, 0, tp) + grp * 64, a, b, 0, lds32(sb + S_TAG), true);
        uint2* dst = (uint2*)p.out + ((e - 32) * 64 + tp * 2) * 128 + grp;
#pragma unroll
        for (int t = 0; t < 2; t++)
            dst[t * 128] = make_uint2(__byte_perm(__float_as_uint(x[t]), __float_as_uint(x[2 + t]), 0x7632), __byte_perm(__float_as_uint(x[4 + t]), __float_as_uint(x[6 + t]), 0x7632));
        PROF((threadIdx.x & 31) == 0, 1536 + e);
    }
}

constexpr int PROW = 272, UROW = 2560, UPRE = 512;
constexpr int C_UR = 0  , C_TB = 65536  , C_BG = C_TB + 51200,
              CB_M = 7168, CB_U = CB_M + 1792, CB_BIG = CB_U + 2048, C_ST = C_BG + 8 * CB_BIG  ;
static_assert(C_ST + 4736 <= B_BAR, "smem map");
enum { CB_TB = 0, CB_UF = 1  , CB_CF = 5  , CB_LD = 9   };
__device__ __forceinline__ void conv_init(uint32_t sb, bool spare) {
    const int i = threadIdx.x & 31;
    mbar_init(sb + B_BAR + i * 8, (i >= CB_UF && i < CB_CF && !spare) ? 2 : 1);
    if (i == CB_TB && !spare) mbar_expect(sb + B_BAR + i * 8, 51200);
    asm volatile("fence.mbarrier_init.release.cluster;" ::: "memory");
}
__device__ __forceinline__ void mma_q(float* c, const uint32_t* a, const uint4& q) {
    mma16(c, a[0], a[1], a[2], a[3], q.x, q.y); mma16(c, a[4], a[5], a[6], a[7], q.z, q.w);
}
__device__ __forceinline__ uint2 ld_acc(const uint2* p, bool on) {
    uint2 v = make_uint2(0, 0);
    asm volatile("{.reg .pred p; setp.ne.u32 p,%3,0; @p ld.global.cg.v2.u32 {%0,%1},[%2];}" : "+r"(v.x), "+r"(v.y) : "l"(p), "r"((uint32_t)on) : "memory");
    return v;
}
__device__ __forceinline__ void add_acc(float* c, uint2 v) { c[0] += blo(v.x); c[1] += bhi(v.x); c[2] += blo(v.y); c[3] += bhi(v.y); }
__device__ __forceinline__ void st_acc(uint2* p, const float* c) { *p = make_uint2(pack2(c[0], c[1]), pack2(c[2], c[3])); }
__device__ __forceinline__ float sum8(const uint4* v, int k) {
#define VK(i) __uint_as_float(k == 0 ? v[i].x : k == 1 ? v[i].y : k == 2 ? v[i].z : v[i].w)
    return ((VK(0) + VK(1)) + (VK(2) + VK(3))) + ((VK(4) + VK(5)) + (VK(6) + VK(7)));
}
template <int XW>
__device__ __forceinline__ void stats_send(uint32_t l16, const float* x, uint4* gs, int q, int w) {
    float s0 = 0, s1 = 0, m0 = 0, m1 = 0;
#pragma unroll
    for (int i = 0; i < 8; i++) { s0 += x[2 * i]; s1 += x[2 * i + 1]; m0 = fmaf(x[2 * i], x[2 * i], m0); m1 = fmaf(x[2 * i + 1], x[2 * i + 1], m1); }
    sts128(l16 + C_ST + w * 512, __float_as_uint(s0), __float_as_uint(m0), __float_as_uint(s1), __float_as_uint(m1));
    if (w == XW) {
        bar_sync(2, 256);
        uint4 v[8];
#pragma unroll
        for (int i = 0; i < 8; i++) v[i] = lds128(l16 + C_ST + i * 512);
        st_rlx128(gs + q * 32, __float_as_uint(sum8(v, 0)), __float_as_uint(sum8(v, 1)) & 0x7fffffffu, __float_as_uint(sum8(v, 2)), __float_as_uint(sum8(v, 3)));
    } else bar_arrive(2, 256);
}
template <int XW>
__device__ __forceinline__ float4 stats_recv(uint32_t l16, const uint4* gs, int w) {
    if (w == XW) {
        uint4 v[8];
        int n = 0;
        while (true) {
            uint32_t bad = 0;
#pragma unroll
            for (int i = 0; i < 8; i++) v[i] = ld_rlx128(gs + i * 32);
#pragma unroll
            for (int i = 0; i < 8; i++) bad |= v[i].y;
            if (!__any_sync(0xffffffffu, bad >> 31)) break;
            if (++n > 2000000) __trap();
        }
        const float s0 = sum8(v, 0) * (1.f / 512.f), s1 = sum8(v, 2) * (1.f / 512.f);
        const float2 l0 = ln_finish(s0, fmaxf(fmaf(sum8(v, 1), 1.f / 512.f, -s0 * s0), 0.f)), l1 = ln_finish(s1, fmaxf(fmaf(sum8(v, 3), 1.f / 512.f, -s1 * s1), 0.f));
        sts128(l16 + C_ST + 4096, __float_as_uint(l0.x), __float_as_uint(rcp(l0.y)), __float_as_uint(l1.x), __float_as_uint(rcp(l1.y)));
    }
    bar_sync(3, 256);
    const uint4 r = lds128(l16 + C_ST + 4096);
    return make_float4(__uint_as_float(r.x), __uint_as_float(r.y), __uint_as_float(r.z), __uint_as_float(r.w));
}

__device__ __forceinline__ void conv_near(float (*acc)[4], uint32_t ta, uint32_t qa) {
    uint32_t a[9][8];
    uint4 x[9];
#pragma unroll
    for (int k = 0; k < 9; k++) {
        if (k < 8) {
            x[k] = ldsm4(qa + k * 1024);
#pragma unroll
            for (int j = 0; j < 8; j++) a[k][j] = lds32(ta + k * 800 + j * 32);
        }
        if (k) mma_q(acc[k - 1], a[k - 1], x[k - 1]);
        PIN(13);
    }
}
template <int K0>
__device__ __forceinline__ void conv_pair(float (*acc)[4], float (*pend)[4], uint32_t ta, uint32_t q0, uint32_t q1, uint32_t q2) {
    uint32_t a[9][8];
    uint4 x[9], y[5];
#pragma unroll
    for (int n = 0; n < 9; n++) {
        if (n < 8) {
            const int k = K0 + (n >> 1);
            if (!(n & 1)) y[n >> 1] = ldsm4(q1 + k * 1024);
            x[n] = ldsm4(((n & 1) ? q0 : q2) + k * 1024);
#pragma unroll
            for (int j = 0; j < 8; j++) a[n][j] = lds32(ta + 256 + (n & 1) * 256 + k * 800 + j * 32);
        }
        if (n == 0) {
#pragma unroll
            for (int i = 0; i < 16; i++) { acc[4 - K0 + (i >> 2)][i & 3] += pend[i >> 2][i & 3]; pend[i >> 2][i & 3] = 0; }
        } else {
            const int m = n - 1, i = m >> 1;
            mma_q(acc[K0 + i], a[m], (m & 1) ? x[m] : y[i]); mma_q(pend[i], a[m], (m & 1) ? y[i] : x[m]);
        }
        PIN(13);
    }
}

__device__ __forceinline__ void conv_tile(const Params& p, uint32_t sb, int q, int w) {
    const int lane = __shfl_sync(0xffffffffu, threadIdx.x & 31, threadIdx.x & 31), g = lane >> 2, c = lane & 3, tile = q * 8 + w;
    const uint32_t l16 = sb + lane * 16;
#pragma unroll
    for (int i = 0; i < 16; i++) sts128(l16 + C_UR + w * 8192 + i * 512, 0, 0, 0, 0);
    wait_slow_warp(g_gate, lds32(sb + S_GATE));
    if (lane < 8) bulk_g2s(sb + C_TB + (w * 8 + lane) * 800, g_P + (tile * 8 + lane) * PROW + 72, 800, sb + B_BAR + CB_TB * 8, POL_N);
    uint32_t A[8][8];
#pragma unroll
    for (int k = 0; k < 8; k++)
#pragma unroll
        for (int j = 0; j < 8; j++) A[k][j] = __ldcg(g_P + (tile * 8 + k) * PROW + 16 + 8 * j + g - 2 * c);
    if (lane == 0) { const uint4 d = __ldg((const uint4*)p.Dskip + tile); sts128(sb + C_ST + 4608 + w * 16, d.x, d.y, d.z, d.w); }
    float acc[8][4], pend[4][4];
#pragma unroll
    for (int k = 0; k < 8; k++) acc[k][0] = acc[k][1] = acc[k][2] = acc[k][3] = pend[k & 3][k >> 2] = pend[k & 3][2 + (k >> 2)] = 0;
    const uint32_t row = sb + C_UR + w * 8192, ta = sb + C_TB + w * 6400 + (8 + g - 2 * c) * 4, qo = (lane & 7) * 16 - (lane >> 3) * 32;
    bar_sync(4, 384);
    mbar_wait(sb + B_BAR + CB_TB * 8, 0);
#pragma unroll 1
    for (int b = -2; b < 32; b++) {
        const int lz = lane + (b & p.zero);
        const bool on = b >= 0;
        uint4 r0 = make_uint4(0, 0, 0, 0), r1 = r0;
        asm volatile("{.reg .pred p; setp.ge.s32 p,%9,0; @p ld.global.cg.v4.u32 {%0,%1,%2,%3},[%8]; @p ld.global.cg.v4.u32 {%4,%5,%6,%7},[%8+%10];}"
                     : "+r"(r0.x), "+r"(r0.y), "+r"(r0.z), "+r"(r0.w), "+r"(r1.x), "+r"(r1.y), "+r"(r1.z), "+r"(r1.w) : "l"(g_x + (tile * 2 * XP + b * 32 + lz)), "r"(b), "n"(XP * 16) : "memory");
        const uint32_t q1 = row + ((qo + (b - 1) * 128) & 1023);
        if ((NTOP >> w) & 1) conv_near(acc, ta, q1);
        PROF2(threadIdx.x == 0 && on, 2048 + b * 8);
        const uint2* pps = pp_src(b, tile, lz);
        asm volatile("" : "+l"(pps));
        const uint32_t tag = lds32(sb + S_TAG);
        wait_flag_warp(cnt_ptr(C_PP + b * 8 + q), on ? 16 : 0);
        PROF2(threadIdx.x == 0 && on, 2048 + b * 8 + 1);
        float x[16];
        {
            const uint32_t a[4] = {r0.x, r0.y, r1.x, r1.y}, bb[4] = {r0.z, r0.w, r1.z, r1.w};
            sum_partials<4, true>(x, pps, a, bb, (2 * (lz & 3) == lz >> 2) ? 0x00003f80u : (2 * (lz & 3) + 1 == lz >> 2) ? 0x3f800000u : 0u, tag, on);
        }
        stats_send<0>(l16, x, g_st + (b + 2) * 256 + lz, q, w);
        {
            PROF2(threadIdx.x == 0 && on, 2048 + b * 8 + 2);
            if (on) mbar_wait(sb + B_BAR + (CB_CF + (w >> 1)) * 8, b & 1);
            const uint2* cb = g_carry + ((tile * 320 + b) * 32 + lz);
            uint2 cr[8];
#pragma unroll
            for (int k = 0; k < 8; k++) cr[k] = ld_acc(cb + k * 1280, b >= 4);
            if (NTOP != 255 && !((NTOP >> w) & 1) && b) conv_near(acc, ta, q1);
#pragma unroll
            for (int k = 0; k < 8; k++) add_acc(acc[k], cr[k]);
        }
        PIN(13);
        float4 ln = stats_recv<0>(l16, g_st + (b + 2) * 256 + lz, w);
        PROF2(threadIdx.x == 0 && on, 2048 + b * 8 + 3);
        uint32_t u[8];
#pragma unroll
        for (int k = 0; k < 8; k++) {
            u[k] = pack2(rbf(x[2 * k] - ln.x) * ln.y, rbf(x[2 * k + 1] - ln.z) * ln.w);
            sts32(row + k * 1024 + (b & 7) * 128 + lane * 4, u[k]);
        }
        __syncwarp();
        const uint32_t qa = row + ((qo + b * 128) & 1023);
        {
            uint4 xq[8];
#pragma unroll
            for (int k = 0; k < 4; k++) xq[k] = ldsm4(qa + k * 1024);
#pragma unroll
            for (int k = 0; k < 8; k += 2) {
                PIN(13);
                mma_q(acc[k], A[k], xq[k]); mma_q(acc[k + 1], A[k + 1], xq[k + 1]);
                if (k < 4) { xq[k + 4] = ldsm4(qa + (k + 4) * 1024); xq[k + 5] = ldsm4(qa + (k + 5) * 1024); }
            }
        }
        const uint4 dk = lds128(sb + C_ST + 4608 + w * 16);
#pragma unroll
        for (int k = 0; k < 8; k++) {
            const float t = __shfl_sync(0xffffffffu, acc[k][3], (lz & ~3) | ((lz - 1) & 3));
            const uint32_t y = movm(pack2(acc[k][0] + (c ? t : 0.f), acc[k][1] + acc[k][2]));
            acc[k][0] = c ? 0.f : t; acc[k][1] = acc[k][2] = acc[k][3] = 0;
            const uint32_t dw = k >> 1 == 0 ? dk.x : k >> 1 == 1 ? dk.y : k >> 1 == 2 ? dk.z : dk.w;
            const uint32_t s = hadd2(hadd2(y, hmul2(u[k], __byte_perm(dw, 0, (k & 1) ? 0x3232 : 0x1010))), __byte_perm(__float_as_uint(x[2 * k]), __float_as_uint(x[2 * k + 1]), 0x7632));
            x[2 * k] = blo(s); x[2 * k + 1] = bhi(s);
        }
        arrive_if(sb + B_BAR + (CB_UF + (w >> 1)) * 8, lz, b < -1 ? 32 : 0);
        stats_send<1>(l16, x, g_st + (36 + b) * 256 + lz, q, w);
        {
            PROF2(threadIdx.x == 0 && on, 2048 + b * 8 + 4);
            uint4* dst = g_x + ((128 + tile * 2) * XP + b * 32 + lz);
#pragma unroll
            for (int e = 0; e < 2; e++) {
                const float* y = x + e * 8;
                if (on) dst[e * XP] = make_uint4(__byte_perm(__float_as_uint(y[0]), __float_as_uint(y[2]), 0x7632), __byte_perm(__float_as_uint(y[4]), __float_as_uint(y[6]), 0x7632),
                                           __byte_perm(__float_as_uint(y[1]), __float_as_uint(y[3]), 0x7632), __byte_perm(__float_as_uint(y[5]), __float_as_uint(y[7]), 0x7632));
            }
            uint32_t* du = g_u + (tile * 8 * (UROW / 2) + UPRE / 2 + b * 32 + lz);
#pragma unroll
            for (int k = 0; k < 8; k++) if (on) du[k * (UROW / 2)] = u[k];
        }
#pragma unroll 1
        for (int pass = 0; pass < 2; pass++) {
            if (pass == ((PLATE >> w) & 1)) {
                const uint32_t q0 = row + ((qo + (b - 2) * 128) & 1023);
                if (b & 1) conv_pair<4>(acc, pend, ta, q0, q1, qa); else conv_pair<0>(acc, pend, ta, q0, q1, qa);
            }
            if (pass) break;
            ln = stats_recv<1>(l16, g_st + (36 + b) * 256 + lz, w);
            PROF2(threadIdx.x == 0 && on, 2048 + b * 8 + 5);
            uint32_t o[2][4];
#pragma unroll
            for (int e = 0; e < 2; e++) {
                const float mu = e ? ln.z : ln.x, rs = e ? ln.w : ln.y;
#pragma unroll
                for (int i = 0; i < 4; i++) o[e][i] = pack2(rbf(x[4 * i + e] - mu) * rs, rbf(x[4 * i + 2 + e] - mu) * rs);
            }
#pragma unroll
            for (int i = 0; i < 4; i++) {
                const uint32_t t = __shfl_xor_sync(0xffffffffu, (lz & 1) ? o[0][i] : o[1][i], 1);
                if (lz & 1) o[0][i] = t; else o[1][i] = t;
            }
            uint4* dst = g_xn + ((32 + b) * 4096 + q * 512 + (lz >> 2) * 64 + w * 8 + (lz & 2) * 2 + (lz & 1));
            if (on) { dst[0] = make_uint4(o[0][0], o[0][1], o[0][2], o[0][3]); dst[2] = make_uint4(o[1][0], o[1][1], o[1][2], o[1][3]); }
            if (w == 7) {
                bar_sync(5, 256);
                if (elect()) red_release(cnt_ptr(on ? C_XN + 32 + b : C_FAR + 8), 2);
                PROF(lane == 0 && on, 2048 + b * 8 + 6);
                __syncwarp();
            } else bar_arrive(5, 256);
        }
    }
}

template <int P0, bool TRI = false, int R0 = 0>
__device__ __forceinline__ void bg_half(float (*acc)[4], uint4* win, uint32_t ta, uint32_t qa, uint32_t mask, uint32_t row) {
#pragma unroll
    for (int i = 0; i < 4; i++) {
        win[P0 + i] = ldsm4(((qa + i * 128) & mask) + row);
        const uint4 a = lds128(ta + (3 - i) * 448), e = lds128(ta + (3 - i) * 448 + 224);
#pragma unroll
        for (int r = TRI ? 7 - P0 - i : R0; r < 8; r++) mma16(acc[r], a.x, a.y, a.z, a.w, win[(P0 + i + 1 + r) & 7].x, win[(P0 + i + 1 + r) & 7].y);
#pragma unroll
        for (int r = TRI ? 7 - P0 - i : R0; r < 8; r++) mma16(acc[r], e.x, e.y, e.z, e.w, win[(P0 + i + 1 + r) & 7].z, win[(P0 + i + 1 + r) & 7].w);
    }
}
__device__ __forceinline__ void bg_fetch(uint32_t sb, int q, int j, int n) {
    const int b0 = n >> 1, ch = q * 64 + j * 16 + (n & 1) * 8 + (b0 & 7), skip = max(12 - b0, 0);
    const uint32_t bar = sb + B_BAR + (CB_LD + j * 2 + (n & 1)) * 8, buf = sb + C_BG + (j * 2 + (n & 1)) * CB_BIG;
    if (elect()) {
        mbar_expect(bar, CB_BIG - skip * 128);
        bulk_g2s(buf, g_W + ch * 784, CB_M, bar, POL_N);
        bulk_g2s(buf + CB_M, g_W + (ch ^ 4) * 784, 1792, bar, POL_N);
        bulk_g2s(buf + CB_U + skip * 128, g_u + ch * (UROW / 2) + UPRE / 2 + (b0 - 20 + skip) * 32, 2048 - skip * 128, bar, POL_N);
    }
    __syncwarp();
}
__device__ __forceinline__ void conv_back(uint32_t sb, int q, int j) {
    const int lane = __shfl_sync(0xffffffffu, threadIdx.x & 31, threadIdx.x & 31), g = lane >> 2, c = lane & 3;
    wait_slow_warp(g_gate, lds32(sb + S_GATE));
    bg_fetch(sb, q, j, 0);
    bar_sync(4, 384);
    const uint32_t to = (6 + g - 2 * c) * 16, qo = (lane & 7) * 16 - (lane >> 3) * 32;
#pragma unroll 1
    for (int n = 0; n < 64; n++) {
        const int b0 = n >> 1, i = n & 1, chl = j * 16 + i * 8 + (b0 & 7);
        const uint32_t buf = sb + C_BG + (j * 2 + i) * CB_BIG, ta = buf + to;
        float acc[8][4];
        uint4 win[8];
        if (n < 63) bg_fetch(sb, q, j, n + 1);
        if (b0 >= 17 && b0 < 29 && (b0 < 21 || b0 >= 25) && i == 0) wait_flag_warp(cnt_ptr(C_FAR + (b0 >= 25) * 4 + ((b0 - 1) & 3)), 12);
        uint2* cr = g_carry + (((q * 64 + chl) * 40 + b0) * 32 + lane);
        uint2* cm = g_carry + (((q * 64 + (chl ^ 4)) * 40 + b0) * 32 + lane);
        uint2 pm[4], pf[8];
#pragma unroll
        for (int r = 0; r < 4; r++) pm[r] = ld_acc(cm + r * 32, b0 > 4);
#pragma unroll
        for (int r = 0; r < 8; r++) acc[r][0] = acc[r][1] = acc[r][2] = acc[r][3] = 0;
        mbar_wait(sb + B_BAR + (CB_LD + j * 2 + i) * 8, b0 & 1);
        if (b0 > 12) {
#pragma unroll
            for (int r = 1; r < 8; r++) win[(r + 4) & 7] = ldsm4(buf + CB_U + qo + r * 128);
        } else {
#pragma unroll
            for (int r = 1; r < 8; r++) win[(r + 4) & 7] = make_uint4(0, 0, 0, 0);
        }
        win[4] = make_uint4(0, 0, 0, 0);
#pragma unroll 1
        for (int h = b0 > 8 ? 4 : 2; h >= 2; h -= 2) {
            if (h == 2) {
                if (b0 > 4) bg_half<0>(acc, win, ta + 2 * 1792, qo + 12 * 128, ~0u, buf + CB_U);
                if (i == 0) mbar_wait(sb + B_BAR + (CB_UF + j) * 8, b0 & 1);
            }
            bg_half<4>(acc, win, ta + (h - 1) * 1792, qo + (h == 2 ? b0 - 4 : 8) * 128, h == 2 ? 1023u : ~0u, h == 2 ? sb + C_UR + chl * 1024 : buf + CB_U);
        }
        uint4 wm[8], a[9], e[9];
#pragma unroll
        for (int r = 1; r < 8; r++) wm[r] = ldsm4(sb + C_UR + (chl ^ 4) * 1024 + ((qo + (b0 + r) * 128) & 1023));
        a[7] = lds128(ta + 7 * 224); e[7] = lds128(ta + CB_M + 7 * 224);
#pragma unroll
        for (int r = 4; r < 8; r++) { st_acc(cr + r * 32, acc[r]); acc[r][0] = blo(pm[r - 4].x); acc[r][1] = bhi(pm[r - 4].x); acc[r][2] = blo(pm[r - 4].y); acc[r][3] = bhi(pm[r - 4].y); }
#pragma unroll
        for (int t = 7; t >= 0; t--) {
            if (t) { a[t - 1] = lds128(ta + (t - 1) * 224); e[t - 1] = lds128(ta + CB_M + (t - 1) * 224); }
            if (t == FT) {
                const uint2* f0 = g_far + (((q * 64 + chl) * 12 + b0 - 20) * 32 + lane);
                const uint2* f1 = g_far + (((q * 64 + (chl ^ 4)) * 12 + b0 - 20) * 32 + lane);
#pragma unroll
                for (int r = 0; r < 4; r++) { const bool on = (unsigned)(b0 + r - 20) < 12u; pf[r] = ld_acc(f0 + r * 32, on); pf[4 + r] = ld_acc(f1 + r * 32, on); }
            }
            PIN(14);
#pragma unroll
            for (int r = 0; r < 4; r++) { const uint4& x = win[4 + r - (t >> 1)]; mma16(acc[r], a[t].x, a[t].y, a[t].z, a[t].w, (t & 1) ? x.z : x.x, (t & 1) ? x.w : x.y); }
#pragma unroll
            for (int r = 0; r < 4; r++) { const uint4& x = wm[4 + r - (t >> 1)]; mma16(acc[4 + r], e[t].x, e[t].y, e[t].z, e[t].w, (t & 1) ? x.z : x.x, (t & 1) ? x.w : x.y); }
        }
#pragma unroll
        for (int r = 0; r < 4; r++) { add_acc(acc[r], pf[r]); add_acc(acc[4 + r], pf[4 + r]); st_acc(cr + r * 32, acc[r]); st_acc(cm + r * 32, acc[4 + r]); }
        __syncwarp();
        arrive_if(sb + B_BAR + (CB_CF + j) * 8, lane, i ? 0 : 32);
        PROF(j == 0 && lane == 0 && i, 2048 + b0 * 8 + 7);
    }
}
template <int PART>
__device__ __forceinline__ void conv_far(uint32_t sb, int w) {
    constexpr int NT = PART ? 5376 : 3584, NU = PART ? 1664 : 1152;
    const int lane = __shfl_sync(0xffffffffu, threadIdx.x & 31, threadIdx.x & 31), g = lane >> 2, c = lane & 3;
    wait_slow_warp(cnt_ptr(C_XN + (PART ? 43 : 39)), 16);
    const uint32_t to = (6 + g - 2 * c) * 16, qo = (lane & 7) * 16 - (lane >> 3) * 32;
#pragma unroll 1
    for (int n = -1; n < 44; n++) {
        const int t = n * 12 + w, tn = min(t + 12, 511), ch = (t & 127) * 4 + (((t >> 7) + 1) & 3), cn = (tn & 127) * 4 + (((tn >> 7) + 1) & 3);
        const uint32_t bar = sb + B_BAR + (w * 2 + (n & 1)) * 8, buf = sb + (w * 2 + (n & 1)) * 7168;
        if (n < 43 && elect()) {
            const uint32_t nb = sb + (w * 2 + (~n & 1)) * 7168;
            mbar_expect(bar ^ 8, NT + NU);
            bulk_g2s(nb, g_W + cn * 784 + 448, NT, bar ^ 8, POL_N);
            bulk_g2s(nb + 5376, g_u + cn * (UROW / 2) + UPRE / 2 - 32, NU, bar ^ 8, POL_N);
        }
        __syncwarp();
        if (n < 0) continue;
        mbar_wait(bar, (n >> 1) & 1);
        if (t >= 512) continue;
        float acc[8][4];
        uint4 win[8];
#pragma unroll
        for (int r = 0; r < 8; r++) acc[r][0] = acc[r][1] = acc[r][2] = acc[r][3] = 0;
        bg_half<0, true, PART * 4>(acc, win, buf + to + NT - 1792, qo + 128, ~0u, buf + 5376);
        bg_half<4, !PART, PART * 4>(acc, win, buf + to + NT - 3584, qo + 640, ~0u, buf + 5376);
        if (PART) bg_half<0, false, 4>(acc, win, buf + to, qo + 1152, ~0u, buf + 5376);
#pragma unroll
        for (int r = PART * 4; r < 8; r++) st_acc(g_far + (ch * 384 + lane) + (r + PART * 4) * 32, acc[r]);
        __syncwarp();
        if (((t + 12) ^ t) >= 128 && elect()) red_release(cnt_ptr(C_FAR + PART * 4 + (t >> 7)), 1);
        __syncwarp();
    }
    PROF(threadIdx.x == 0, 2048 + PART);
}

constexpr int P_X = 131072  , P_K6 = P_X + 32768  , P_P = P_K6 + 10496  , P_U = P_P + 33280  ,
              P_END = P_U + 17408, P_PRM = P_P + 8192  , P_Y = P_P  ;
static_assert(P_END <= B_BAR && P_END <= R_SEL, "prologue scratch");
#define KGUN 2
constexpr int KGU = KGUN;
__device__ __forceinline__ void csq(float& r, float& i) { const float t = r * i; r = fmaf(r, r, -(i * i)); i = t + t; }
__device__ __forceinline__ void cpow(float ar, float ph, float p, float& r, float& i) {
    const float e = ex2(ar * p);
    const float u = ph * p, n = fabsf(u) < 4194304.f ? (u + 12582912.f) - 12582912.f : u;
    const float t = (u - n) * 6.283185307179586f;
    r = e * __cosf(t); i = e * __sinf(t);
}
__device__ __forceinline__ void mma_tf32(float* c, float a0, float a1, float a2, float a3, float b0, float b1) {
    asm volatile("mma.sync.aligned.m16n8k8.row.col.f32.tf32.tf32.f32 {%0,%1,%2,%3},{%4,%5,%6,%7},{%8,%9},{%0,%1,%2,%3};"
                 : "+f"(c[0]), "+f"(c[1]), "+f"(c[2]), "+f"(c[3])
                 : "r"(__float_as_uint(a0)), "r"(__float_as_uint(a1)), "r"(__float_as_uint(a2)), "r"(__float_as_uint(a3)), "r"(__float_as_uint(b0)), "r"(__float_as_uint(b1)));
}

__device__ __forceinline__ void early_fetch(const Params& p, uint32_t sb) {
    const int v = blockIdx.x;
    if (elect()) {
        if (v >= V_QKV) { if (v < V_QKV + NQ && (p.roles & 8)) qkv_fetch(p, sb, v - V_QKV, 0, Q_PRE); }
        else if (v >= V_OP) { if (p.roles & 4) op_fetch(p, sb, v - V_OP, 0); }
        else if (v >= V_REC && (p.roles & 2)) { rec_fetch(p, sb, (v - V_REC) >> 1, v & 1, 0, R_STQ); rec_fetch(p, sb, (v - V_REC) >> 1, v & 1, 2, R_STV); }
    }
    __syncwarp();
}
struct ProRegs { uint32_t v[2][4], ldt[2]; };
__device__ __forceinline__ void prologue_load(const ProArgs& a, int b, ProRegs& pr) {
    const int w = threadIdx.x >> 5;
#pragma unroll
    for (int i = 0; i < 2; i++) {
        const int gi = b * 512 + (w & 3) * 128 + ((w >> 2) & 1) * 64 + i * 32 + (threadIdx.x & 31);
        pr.ldt[i] = __ldg((const uint16_t*)a.ldt + b * 4 + (w & 3));
        pr.v[i][0] = __ldg((const uint16_t*)a.lAr + gi); pr.v[i][1] = __ldg((const uint16_t*)a.Ai + gi);
        pr.v[i][2] = __ldg((const uint16_t*)a.Cr + gi); pr.v[i][3] = __ldg((const uint16_t*)a.Ci + gi);
    }
}
__device__ __forceinline__ void prologue(const Params& p, uint32_t sb, int b, int w, const ProRegs& pr) {
    const ProArgs& a = p.pa;
    const int tid = threadIdx.x, lane = tid & 31, g = lane >> 2, c = lane & 3;
    const int d0 = b * 4;
    if (w >= 8) {
        const int t2 = tid - 256;
        if (w < 10) {
            const int row = b * 16 + (w - 8) * 8 + g;
            uint4 v[16];
            const float2 r = row_stats512(v, (const uint4*)(a.x + (size_t)row * 512) + c, 8, 4);
            const float2 l = ln_finish(r.x * (1.f / 512.f), r.y * (1.f / 512.f));
            if (c == (g >> 1)) asm volatile("st.relaxed.gpu.global.u32 [%0],%1;" ::"l"(g_ln0 + row), "r"(pack2(l.x, l.y)) : "memory");
            __syncwarp();
        }
        if (b + 4 >= V_REC && b + 4 < V_OP) rec_slots(b + 4 - V_REC, (w & 3) ^ 2);
        PROF(t2 == 0, 3516);
        const int gi = b * 128 + t2;
        g_st[gi] = make_uint4(~0u, ~0u, ~0u, ~0u);
        if (gi < 1024) g_st[16384 + gi] = make_uint4(~0u, ~0u, ~0u, ~0u);
        if (gi < 912 * 8) g_cnt[gi] = 0;
        bar_sync(6, 384);
        if (lane < 4 && ((PFM >> (w - 8)) & 1)) asm volatile("cp.async.bulk.prefetch.L2.global [%0],%1;" ::"l"(a.W[w - 8] + (b * 4 + lane) * 4096), "r"(8192) : "memory");
        bar_sync(9, 384);
#pragma unroll 1
        for (int pass = 0; pass < 2; pass++) {
        if (w == 10 && pass == (b + 4 < V_QKV)) early_fetch(p, sb);
        if (pass) break;
#pragma unroll 2
        for (int i = t2; i < 4 * 784; i += 128) {
            const int ch = i / 784, k = i - ch * 784;
            const uint32_t o = sb + P_P + (ch * 2080 + 266 + (k / 14) * 18 + k) * 4;
            g_W[d0 * 784 + i] = make_uint4(lds32(o), lds32(o + 32), lds32(o + 64), lds32(o + 96));
        }
        bar_arrive(10, 384);
        }
        PROF(t2 == 0, 3517);
        return;
    }
#pragma unroll
    for (int i = 0; i < 2; i++) {
        const float dt = rbf(expf(blo(pr.ldt[i])));
        const float ar = -rbf(expf(blo(pr.v[i][0]))) * dt, ai = blo(pr.v[i][1]) * dt;
        sts128(sb + P_PRM + (w * 64 + i * 32 + lane) * 16, __float_as_uint(ar * 1.4426950408889634f), __float_as_uint(ai * 0.15915494309189535f),
               __float_as_uint(2.f * (blo(pr.v[i][2]) * dt)), __float_as_uint(2.f * (blo(pr.v[i][3]) * dt)));
    }
    if (tid < 64) sts128(sb + P_U + (tid >> 3) * 2176 + (tid & 7) * 16, 0, 0, 0, 0);
    bar_arrive(6, 384);
    __syncwarp();
    PROF(tid == 0, 3510);
    const int ch = w & 3, hf = w >> 2;
    {
        float k0[4] = {0, 0, 0, 0}, k1[4] = {0, 0, 0, 0}, k2[4] = {0, 0, 0, 0}, k3[4] = {0, 0, 0, 0}, k4[4] = {0, 0, 0, 0}, kl = 0;
#pragma unroll KGU
        for (int j = 0; j < 16; j++) {
            const uint4 q = lds128(sb + P_PRM + (w * 64 + j * 4 + c) * 16);
            const float cr = __uint_as_float(q.z), ci = __uint_as_float(q.w);
            float wr[4], wi[4], vr[4], vi[4];
            cpow(__uint_as_float(q.x), __uint_as_float(q.y), (float)g, wr[0], wi[0]);
            cpow(__uint_as_float(q.x), __uint_as_float(q.y), (float)(g + 8), vr[0], vi[0]);
#pragma unroll
            for (int i = 1; i < 4; i++) { wr[i] = wr[i - 1]; wi[i] = wi[i - 1]; csq(wr[i], wi[i]); vr[i] = vr[i - 1]; vi[i] = vi[i - 1]; csq(vr[i], vi[i]); }
            float hr = wr[3], hi = wi[3];
            csq(hr, hi);
            mma_tf32(k0, wr[0], vr[0], wi[0], vi[0], cr * hr - ci * hi, -(cr * hi + ci * hr));
            hr = vr[3]; hi = vi[3]; csq(hr, hi);
            mma_tf32(k1, wr[0], vr[0], wi[0], vi[0], cr * hr - ci * hi, -(cr * hi + ci * hr));
            csq(hr, hi);
            mma_tf32(k2, wr[1], vr[1], wi[1], vi[1], cr * hr - ci * hi, -(cr * hi + ci * hr));
            csq(hr, hi);
            mma_tf32(k3, wr[2], vr[2], wi[2], vi[2], cr * hr - ci * hi, -(cr * hi + ci * hr));
            csq(hr, hi);
            mma_tf32(k4, wr[3], vr[3], wi[3], vi[3], cr * hr - ci * hi, -(cr * hi + ci * hr));
            csq(hr, hi);
            kl += cr * hr - ci * hi;
        }
        kl += __shfl_xor_sync(0xffffffffu, kl, 1); kl += __shfl_xor_sync(0xffffffffu, kl, 2);
        const uint32_t o = sb + P_K6 + (ch * 656 + c * 32 + g) * 4, ol = sb + P_K6 + (ch * 656 + 640) * 4;
#define KST(k, base) sts32(o + (base) * 4, __float_as_uint(k[0])); sts32(o + (base) * 4 + 64, __float_as_uint(k[1])); \
                     sts32(o + (base) * 4 + 32, __float_as_uint(k[2])); sts32(o + (base) * 4 + 96, __float_as_uint(k[3]))
#define KAD(k, base) k[0] += __uint_as_float(lds32(o + (base) * 4)); k[1] += __uint_as_float(lds32(o + (base) * 4 + 64)); \
                     k[2] += __uint_as_float(lds32(o + (base) * 4 + 32)); k[3] += __uint_as_float(lds32(o + (base) * 4 + 96))
        if (hf == 0) {
            bar_sync(2 + ch, 64);
            KAD(k0, 0); KAD(k1, 128); KAD(k2, 256); KAD(k3, 384); KAD(k4, 512);
            kl += __uint_as_float(lds32(ol));
            __syncwarp();
        }
        KST(k0, 0); KST(k1, 128); KST(k2, 256); KST(k3, 384); KST(k4, 512);
        if (lane == 0) sts32(ol, __float_as_uint(kl));
        if (hf == 1) { __syncwarp(); bar_arrive(2 + ch, 64); }
    }
    PROF(tid == 0, 3511);
    {
        uint4 l0, l1;
        int n = 0;
        while (true) {
            l0 = ld_rlx128((const uint4*)g_ln0 + tid * 2); l1 = ld_rlx128((const uint4*)g_ln0 + tid * 2 + 1);
            if (__all_sync(0xffffffffu, l0.x && l0.y && l0.z && l0.w && l1.x && l1.y && l1.z && l1.w)) break;
            if (++n > 2000000) __trap();
        }
        sts128(sb + P_P + tid * 32, l0.x, l0.y, l0.z, l0.w); sts128(sb + P_P + tid * 32 + 16, l1.x, l1.y, l1.z, l1.w);
        bar_sync(8, 384);
        mbar_wait(sb + S_XBAR, 0);
        __syncwarp();
#pragma unroll 2
        for (int i = 0; i < 8; i++) {
            const int t = w * 256 + i * 32 + lane;
            const uint32_t ln = lds32(sb + P_P + t * 4);
            const uint2 x = lds64(sb + P_X + t * 16 + (b & 1) * 8);
            const float m = blo(ln), rs = rcp(bhi(ln));
            const uint32_t u0 = pack2(rbf(blo(x.x) - m) * rs, rbf(bhi(x.x) - m) * rs), u1 = pack2(rbf(blo(x.y) - m) * rs, rbf(bhi(x.y) - m) * rs);
            sts128(sb + P_X + t * 16, x.x, x.y, u0, u1);
            const uint32_t o = sb + P_U + ((t >> 3) & 1) * 2176 + ((t >> 4) + 8) * 16 + (t & 7) * 2;
            asm volatile("st.shared.u16 [%0],%1;" ::"r"(o), "h"((uint16_t)u0) : "memory");
            asm volatile("st.shared.u16 [%0],%1;" ::"r"(o + 4352), "h"((uint16_t)(u0 >> 16)) : "memory");
            asm volatile("st.shared.u16 [%0],%1;" ::"r"(o + 8704), "h"((uint16_t)u1) : "memory");
            asm volatile("st.shared.u16 [%0],%1;" ::"r"(o + 13056), "h"((uint16_t)(u1 >> 16)) : "memory");
        }
    }
    bar_sync(1, 256);
    PROF(tid == 0, 3512);
    if (tid < 64) sts32(sb + P_P + ((tid >> 4) * 2080 + (tid & 15)) * 4, 0);
#pragma unroll 1
    for (int x = tid; x < 2048; x += 512) {
        uint32_t pw[2][4];
#pragma unroll
        for (int h = 0; h < 2; h++) {
            const int y = x + h * 256;
            const int i0 = y <= 256 ? y : 256 + (int)((pack2((float)y, 0.f) & 0xffff) - 0x4380);
            const int i1 = y <= 256 ? max(y - 1, 0) : 256 + (int)((pack2((float)(y - 1), 0.f) & 0xffff) - 0x4380);
#pragma unroll
            for (int k = 0; k < 4; k++) {
                const float lo = __uint_as_float(lds32(sb + P_K6 + k * 2624 + i0 * 4)), hi = __uint_as_float(lds32(sb + P_K6 + k * 2624 + i1 * 4));
                pw[h][k] = pack2(lo, y ? hi : 0.f);
            }
        }
#pragma unroll
        for (int h = 0; h < 2; h++)
#pragma unroll
            for (int k = 0; k < 4; k++) sts32(sb + P_P + (k * 2080 + x + h * 256 + 16) * 4, pw[h][k]);
    }
    fence_async_smem();
    bar_arrive(9, 384);
    bar_sync(1, 256);
    if (tid < 4) {
        asm volatile("cp.async.bulk.global.shared::cta.bulk_group [%0],[%1],%2;" ::"l"(g_P + (d0 + tid) * PROW), "r"(sb + P_P + tid * 8320), "r"(PROW * 4) : "memory");
        asm volatile("cp.async.bulk.commit_group;" ::: "memory");
    }
    __syncwarp();
    PROF(tid == 0, 3513);
    {
        float acc[16][4];
#pragma unroll
        for (int j = 0; j < 16; j++) acc[j][0] = acc[j][1] = acc[j][2] = acc[j][3] = 0;
#pragma unroll 1
        for (int e = hf * 4; e < hf * 4 + 4; e++) {
            uint32_t B[16][2];
            const uint32_t ua = sb + P_U + ch * 4352 + ((lane >> 3) & 1) * 2176 + (8 + (lane >> 4) * 8 + (lane & 7) - e) * 16;
#pragma unroll
            for (int j = 0; j < 8; j++) { const uint4 v = ldsm4(ua + j * 256); B[2 * j][0] = v.x; B[2 * j][1] = v.y; B[2 * j + 1][0] = v.z; B[2 * j + 1][1] = v.w; }
            const uint32_t pa = sb + P_P + (ch * 2080 + 16 + e * 16 + g - 2 * c) * 4;
#pragma unroll
            for (int dd = 0; dd < 16; dd++) {
                const int d = (dd & 1) ? 15 - (dd >> 1) : dd >> 1;
                const uint32_t a0 = lds32(pa + d * 512), a1 = lds32(pa + d * 512 + 32), a2 = lds32(pa + d * 512 - 32), a3 = a0 + p.zero;
#pragma unroll
                for (int j = 0; j < 16; j++) if (j >= d) mma16(acc[j], a0, a1, a2, a3, B[(j - d) & 15][0], B[(j - d) & 15][1]);
            }
        }
        PROF(tid == 0, 3514);
        if (tid < 4) asm volatile("cp.async.bulk.wait_group 0;" ::: "memory");
        __syncwarp();
        bar_sync(10, 384);
#pragma unroll
        for (int j = 0; j < 8; j++) {
#pragma unroll
            for (int i = 0; i < 4; i++) { const float t = hf ? acc[j][i] : acc[j + 8][i]; acc[j][i] = hf ? acc[j + 8][i] : acc[j][i]; acc[j + 8][i] = t; }
            sts128(sb + P_Y + w * 4096 + j * 512 + lane * 16, __float_as_uint(acc[j + 8][0]), __float_as_uint(acc[j + 8][1]), __float_as_uint(acc[j + 8][2]), __float_as_uint(acc[j + 8][3]));
        }
        bar_sync(2 + ch, 64);
        uint32_t yp[16];
#pragma unroll
        for (int j = 0; j < 8; j++) {
            const uint4 t = lds128(sb + P_Y + (w ^ 4) * 4096 + j * 512 + lane * 16);
            yp[2 * j] = pack2(acc[j][0] + __uint_as_float(t.x), acc[j][1] + __uint_as_float(t.y)); yp[2 * j + 1] = pack2(acc[j][2] + __uint_as_float(t.z), acc[j][3] + __uint_as_float(t.w));
        }
#pragma unroll
        for (int j = 0; j < 4; j++)
            asm volatile("stmatrix.sync.aligned.m8n8.x4.trans.shared.b16 [%0],{%1,%2,%3,%4};" ::"r"(sb + P_Y + 32768 + ch * 4096 + hf * 2048 + j * 512 + (lane >> 4) * 256 + (lane & 7) * 32 + (lane & 8) * 2),
                         "r"(yp[4 * j]), "r"(yp[4 * j + 1]), "r"(yp[4 * j + 2]), "r"(yp[4 * j + 3]) : "memory");
    }
    const uint2 dk = __ldg((const uint2*)(a.Dk + d0));
    bar_sync(1, 256);
#pragma unroll 2
    for (int i = 0; i < 4; i++) {
        const int t = i * 256 + tid;
        const uint4 x0 = lds128(sb + P_X + t * 32), x1 = lds128(sb + P_X + t * 32 + 16);
        uint32_t y[4];
#pragma unroll
        for (int k = 0; k < 4; k++) y[k] = lds32(sb + P_Y + 32768 + k * 4096 + t * 4);
        g_x[b * XP + t] = make_uint4(hadd2(x0.x, hadd2(__byte_perm(y[0], y[1], 0x5410), hmul2(x0.z, dk.x))), hadd2(x0.y, hadd2(__byte_perm(y[2], y[3], 0x5410), hmul2(x0.w, dk.y))),
                                     hadd2(x1.x, hadd2(__byte_perm(y[0], y[1], 0x7632), hmul2(x1.z, dk.x))), hadd2(x1.y, hadd2(__byte_perm(y[2], y[3], 0x7632), hmul2(x1.w, dk.y))));
    }
    PROF(tid == 0, 3515);
}

__global__ void __cluster_dims__(2, 1, 1) __launch_bounds__(384, 1) main_kernel(const __grid_constant__ Params p) {
    extern __shared__ __align__(1024) uint8_t smem[];
    const uint32_t sb = smem_u32(smem);
    uint32_t rank; asm("mov.u32 %0,%%cluster_ctarank;" : "=r"(rank));
    const int wi = __shfl_sync(0xffffffffu, threadIdx.x >> 5, 0);
    const int v = blockIdx.x, cl = v >> 1, wg = wi >> 2;
    PROF(threadIdx.x == 0, 3500);
    ProRegs pr;
    prologue_load(p.pa, max((int)blockIdx.x - 4, 0), pr);
    if (wi == 11 && p.dopro && cl >= 2 && elect()) {
        mbar_init(sb + S_XBAR, 1);
        asm volatile("fence.mbarrier_init.release.cluster;" ::: "memory");
        mbar_expect(sb + S_XBAR, 32768);
        for (int j = 0; j < 8; j++) tma2d(sb + P_X + j * 4096, &p.tm[3], ((blockIdx.x - 4) >> 1) * 8, j * 256, sb + S_XBAR);
    }
    if (threadIdx.x == 320) {
        unsigned n;
        asm volatile("ld.relaxed.gpu.global.u32 %0,[%1];" : "=r"(n) : "l"(g_gate) : "memory");
        n = n / (4 * NCL) + p.dopro;
        sts64(sb + S_GATE, n * (4 * NCL), n & 1);
    }
    __syncwarp();
    if (wi == 10) {
        if (v < V_REC || v == 131) conv_init(sb, v == 131); else if (v < V_OP) rec_init(sb); else gemm_init(sb, v < V_QKV);
        __syncwarp();
    }
    if (wg == 2) bar_arrive(8, 384);
    asm volatile("barrier.cluster.arrive.relaxed.aligned;" ::: "memory");
    if (p.dopro && cl >= 2) prologue(p, sb, blockIdx.x - 4, wi, pr); else if (wg < 2) bar_sync(8, 384); else if (wi == 10) early_fetch(p, sb);
    asm volatile("barrier.cluster.wait.aligned;" ::: "memory");
    const int role = (v < V_REC ? 1 : v < V_OP ? 2 : v < V_QKV ? 20 : v < V_QKV + NQ ? 24 : 1) & p.roles;
    fence_async_smem();
    bar_sync(wg == 2 ? 7 : 1, wg == 2 ? 128 : 256);
    if (p.dopro && (threadIdx.x == 32 || threadIdx.x == 352)) red_release(g_gate, 1);
    PROF(threadIdx.x == 32, 3509);
    if (wi == 0 && (role & 8) && elect()) qkv_stage(p, sb + 131072, sb + G_BAR + GB_RS * 8, v - V_QKV, 0, 6);
    PROF(threadIdx.x == 0, 3506);
    __syncwarp();
    if (p.dopro && (v == 131 || (v >= V_REC && v < V_QKV && (v < V_OP ? wi == 8 : wi < 8)))) {
        bool on = v >= V_OP;
#pragma unroll 1
        for (int r = v == 131 ? 448 + wi : on ? 64 + (v - V_OP) * 8 + wi : v - V_REC; r < (v == 131 ? 512 : 448);) {
            if (v >= V_OP) wait_slow_warp(g_gate, lds32(sb + S_GATE)); else if (on) wait_flag_warp(g_gate, lds32(sb + S_GATE));
            PROF(threadIdx.x == 256 && on, 3507);
            x1_norm(on ? (const uint2*)g_x : (const uint2*)p.pa.x, r, on);
            __syncwarp();
            if (on && elect()) red_release(cnt_ptr(C_XN + (r >> 4)), 1);
            __syncwarp();
            PROF(threadIdx.x == 256, on ? 3508 : 3499);
            if (on) r += v < V_OP ? 512 : v == 131 ? 12 : 128;
            on = true;
        }
    }
    if (role == 2) {
        const int head = (v - V_REC) >> 1;
        if (wi == 8 && elect()) rec_fetch(p, sb, head, rank, 1, R_STK);
        __syncwarp();
        if (wg == 2) {
            reg_dec<RH>();
            const int w = wi & 3;
            wait_slow_warp(g_gate, lds32(sb + S_GATE));
            if (w < 2) { const uint32_t x = __ldcg(g_sel + (threadIdx.x & 63)); sts32(sb + R_SEL + (threadIdx.x & 63) * 4, (x * 0x01010101u) >> 24); }
            __syncthreads();
            cluster_sync();
            if ((p.chains >> (w & 1)) & 1) { if (w < 2) rec_comm(p, sb, w, head, rank); else rec_attn(p, sb, w & 1, head, rank); }
        } else {
            reg_inc<RW0>();
            rec_weights(p, sb, head, rank, wi);
        }
    } else if (role == 1) {
        if (v == 131) { wait_slow_warp(g_gate, lds32(sb + S_GATE)); conv_far<0>(sb, wi); conv_far<1>(sb, wi); } else if (wg == 2) { reg_dec<RCB>(); conv_back(sb, v, wi & 3); } else { reg_inc<RCU>(); conv_tile(p, sb, v, wi); }
    } else if (role && v < V_QKV) {
        if (wg == 2) {
            reg_dec<40>();
            if (wi == 8) { if (role & 4) gemm_producer<true>(p, sb, v - V_OP); }
            else if (v < V_OP + 14 && (role & 16)) fin_warp(p, sb, 2 * NQ + (v - V_OP) * 3 + wi - 9);
        } else { reg_inc<232>(); if (role & 4) gemm_consumer<true>(p, sb, v - V_OP, wi); }
    } else if (role) {
        if (wg == 2) {
            reg_dec<40>();
            if (wi < 10) {
                if (role & 8) { if (wi == 8) gemm_producer<false>(p, sb, v - V_QKV); else qkv_release(p, sb); }
            } else if (role & 16) fin_warp(p, sb, (v - V_QKV) * 2 + wi - 10);
        } else { reg_inc<232>(); if (role & 8) gemm_consumer<false>(p, sb, v - V_QKV, wi); }
    }
    __syncwarp();
    cluster_sync();
}

typedef CUresult (*EncFn)(CUtensorMap*, CUtensorMapDataType, cuuint32_t, void*, const cuuint64_t*, const cuuint64_t*, const cuuint32_t*, const cuuint32_t*,
                          CUtensorMapInterleave, CUtensorMapSwizzle, CUtensorMapL2promotion, CUtensorMapFloatOOBfill);
constexpr int SMEM_BYTES = 232448;
#define LAG 8
#define QLEAD 6
#define OLEAD (LAG / 2 + 2)
void plan(Params& P) {
    P.roles = 31; P.chains = 3; P.lag = LAG; P.dopro = 1;
    for (int r = 0; r < 2; r++) {
        const int lead = r ? OLEAD : QLEAD;
        int n = 0;
        for (int i = 0; i < 32 + lead; i++) {
            if (i >= lead) P.list[r][n++] = 32 + i - lead;
            if (i < 32) P.list[r][n++] = i;
        }
        P.nl[r] = n;
    }
}

#define TK() do {} while (0)
}

extern "C" void kernel_launch(void* const* d_in, const int* in_sizes, int n_in, void* d_out, int out_size) {
    typedef const __nv_bfloat16* BP;
    static EncFn enc = nullptr;
    if (!enc) {
        void* fn = nullptr; cudaDriverEntryPointQueryResult qr;
        cudaGetDriverEntryPoint("cuTensorMapEncodeTiled", &fn, cudaEnableDefault, &qr);
        enc = (EncFn)fn;
        cudaFuncSetAttribute(main_kernel, cudaFuncAttributeMaxDynamicSharedMemorySize, SMEM_BYTES);
    }
    static Params P;
    for (int i = 0; i < 4; i++) {
        const cuuint64_t cols = i < 3 ? 4096 : 512, rows = i < 3 ? 512 : 4096;
        cuuint64_t d2[2] = {cols, rows}, str[1] = {cols * 2};
        cuuint32_t box[2] = {64, 64}, bn[2] = {16, 256}, es[2] = {1, 1};
        enc(&P.tm[i < 3 ? i : 4], CU_TENSOR_MAP_DATA_TYPE_BFLOAT16, 2, d_in[9 + i], d2, str, box, es, CU_TENSOR_MAP_INTERLEAVE_NONE, CU_TENSOR_MAP_SWIZZLE_128B,
            CU_TENSOR_MAP_L2_PROMOTION_L2_128B, CU_TENSOR_MAP_FLOAT_OOB_FILL_NONE);
        if (i < 2) enc(&P.tn[i], CU_TENSOR_MAP_DATA_TYPE_BFLOAT16, 2, d_in[9 + i], d2, str, bn, es, CU_TENSOR_MAP_INTERLEAVE_NONE, CU_TENSOR_MAP_SWIZZLE_32B,
                       CU_TENSOR_MAP_L2_PROMOTION_L2_128B, CU_TENSOR_MAP_FLOAT_OOB_FILL_NONE);
    }
    {
        cuuint64_t dims[2] = {512, 2048}, str[1] = {1024};
        cuuint32_t box[2] = {8, 256}, es[2] = {1, 1};
        enc(&P.tm[3], CU_TENSOR_MAP_DATA_TYPE_BFLOAT16, 2, d_in[0], dims, str, box, es, CU_TENSOR_MAP_INTERLEAVE_NONE, CU_TENSOR_MAP_SWIZZLE_NONE,
            CU_TENSOR_MAP_L2_PROMOTION_NONE, CU_TENSOR_MAP_FLOAT_OOB_FILL_NONE);
    }
    P.mem0 = (BP)d_in[8]; P.Wo = (BP)d_in[12]; P.Dskip = (BP)d_in[6]; P.out = (__nv_bfloat16*)d_out;
    cudaStream_t s = cudaStreamPerThread;
    P.pa = {(BP)d_in[0], (BP)d_in[1], (BP)d_in[2], (BP)d_in[3], (BP)d_in[4], (BP)d_in[5], (BP)d_in[6], {(BP)d_in[9], (BP)d_in[10], (BP)d_in[11], (BP)d_in[12]}};
    plan(P);
    TK(); main_kernel<<<2 * NCL, 384, SMEM_BYTES, s>>>(P); TK();
}
```

```cpp
#include <cuda_runtime.h>
#include <cuda_bf16.h>
#include <cuda.h>
#include <stdint.h>
#include <string.h>
#include <math.h>

namespace {

constexpr int NCL = 66;
constexpr int NQ = 43;
constexpr int V_REC = 8, V_OP = 72, V_QKV = 88;
static_assert(2 * NQ + 3 * 14 == 128, "warps of the final residual");

constexpr int XP = 1024;
__device__ uint4 g_x[2 * 128 * XP];
__device__ uint4 g_xn[64 * 4096];
__device__ uint4 g_st[68 * 256];
__device__ uint4 g_qkv[128 * 32 * 1536];
__device__ uint4 g_o[64 * 64 * 512];
__device__ uint4 g_pp[64 * 4 * 4096];
__device__ uint4 g_xch[133 * 512];
__device__ unsigned g_sel[64];
__device__ unsigned g_gate[32];
__device__ __align__(16) uint32_t g_P[512 * 272];
__device__ uint4 g_W[512 * 784];
__device__ __align__(16) uint32_t g_u[512 * 1280];
__device__ uint2 g_carry[512 * 40 * 32];
__device__ uint2 g_far[512 * 12 * 32];
__device__ unsigned g_cnt[912 * 8];
__device__ uint32_t g_ln0[2048];

enum { C_XN = 0  , C_QKV = 64  , C_O = 128  , C_PP = 384  , C_FAR = 896 };
__device__ __forceinline__ unsigned* cnt_ptr(int i) { return g_cnt + i * 8; }

struct ProArgs { const __nv_bfloat16 *x, *lAr, *Ai, *Cr, *Ci, *ldt, *Dk; };
struct Params {
    CUtensorMap tm[5];
    CUtensorMap tn[2];
    ProArgs pa;
    int dopro;
    const __nv_bfloat16* mem0;
    const __nv_bfloat16* Wo;
    const __nv_bfloat16* Dskip;
    __nv_bfloat16* out;
    int roles;
    int chains;
    int lag;
    int zero;
    int nl[2];
    uint8_t list[2][64];
};

__device__ __forceinline__ uint32_t smem_u32(const void* p) { return (uint32_t)__cvta_generic_to_shared(p); }
__device__ __forceinline__ uint32_t mapa(uint32_t a, uint32_t r) {
    uint32_t o; asm("mapa.shared::cluster.u32 %0,%1,%2;" : "=r"(o) : "r"(a), "r"(r)); return o;
}
__device__ __forceinline__ void mbar_init(uint32_t b, int c) { asm volatile("mbarrier.init.shared::cta.b64 [%0],%1;" ::"r"(b), "r"(c) : "memory"); }
__device__ __forceinline__ void mbar_expect(uint32_t b, int bytes) { asm volatile("mbarrier.arrive.expect_tx.shared::cta.b64 _,[%0],%1;" ::"r"(b), "r"(bytes) : "memory"); }
__device__ __forceinline__ void mbar_arrive(uint32_t b) { asm volatile("mbarrier.arrive.shared::cta.b64 _,[%0];" ::"r"(b) : "memory"); }
__device__ __forceinline__ void mbar_arrive_cluster(uint32_t b) { asm volatile("mbarrier.arrive.shared::cluster.b64 _,[%0];" ::"r"(b) : "memory"); }
__device__ __forceinline__ void mbar_wait(uint32_t b, uint32_t ph) {
    asm volatile(
        "{.reg .pred p; .reg .u32 n; mov.u32 n,0;\n"
        "W%=: mbarrier.try_wait.parity.shared::cta.b64 p,[%0],%1;\n"
        "@p bra D%=;\n"
        "add.u32 n,n,1; setp.lt.u32 p,n,2000000; @p bra W%=;\n"
        "trap;\n"
        "D%=: }" ::"r"(b), "r"(ph) : "memory");
}
__device__ __forceinline__ bool elect() {
    uint32_t r; asm volatile("{.reg .pred p; elect.sync _|p,0xffffffff; selp.u32 %0,1,0,p;}" : "=r"(r)); return r;
}
__device__ __forceinline__ void bar_sync(int id, int n) { asm volatile("bar.sync %0,%1;" ::"r"(id), "r"(n) : "memory"); }
__device__ __forceinline__ void bar_arrive(int id, int n) { asm volatile("bar.arrive %0,%1;" ::"r"(id), "r"(n) : "memory"); }
__device__ __forceinline__ void cluster_sync() { asm volatile("barrier.cluster.arrive.relaxed.aligned; barrier.cluster.wait.aligned;" ::: "memory"); }
__device__ __forceinline__ void fence_async_smem() { asm volatile("fence.proxy.async.shared::cta;" ::: "memory"); }
constexpr uint64_t POL_N = 0x1000000000000000ull  , POL_LAST = 0x12F0000000000000ull  ;
__device__ __forceinline__ void bulk_g2s(uint32_t dst, const void* src, int bytes, uint32_t bar, uint64_t pol) {
    asm volatile("cp.async.bulk.shared::cluster.global.mbarrier::complete_tx::bytes.L2::cache_hint [%0],[%1],%2,[%3],%4;" ::"r"(dst), "l"(src), "r"(bytes), "r"(bar), "l"(pol) : "memory");
}
__device__ __forceinline__ void bulk_g2s_mc(uint32_t dst, const void* src, int bytes, uint32_t bar, uint64_t pol) {
    asm volatile("cp.async.bulk.shared::cluster.global.mbarrier::complete_tx::bytes.multicast::cluster.L2::cache_hint [%0],[%1],%2,[%3],%4,%5;" ::"r"(dst), "l"(src), "r"(bytes), "r"(bar), "h"((uint16_t)3), "l"(pol) : "memory");
}
__device__ __forceinline__ void stg128(uint4* p, uint4 v, uint64_t pol) {
    asm volatile("st.global.L2::cache_hint.v4.u32 [%0],{%1,%2,%3,%4},%5;" ::"l"(p), "r"(v.x), "r"(v.y), "r"(v.z), "r"(v.w), "l"(pol));
}
__device__ __forceinline__ void tma2d(uint32_t dst, const CUtensorMap* tm, int x, int y, uint32_t bar) {
    asm volatile("cp.async.bulk.tensor.2d.shared::cluster.global.mbarrier::complete_tx::bytes [%0],[%1,{%2,%3}],[%4];" ::"r"(dst), "l"(tm), "r"(x), "r"(y), "r"(bar) : "memory");
}
__device__ __forceinline__ void st_async4(uint32_t a, uint32_t x, uint32_t y, uint32_t z, uint32_t w, uint32_t mb) {
    asm volatile("st.async.shared::cluster.mbarrier::complete_tx::bytes.v4.b32 [%0],{%1,%2,%3,%4},[%5];" ::"r"(a), "r"(x), "r"(y), "r"(z), "r"(w), "r"(mb) : "memory");
}
__device__ __forceinline__ void st_async2(uint32_t a, uint32_t x, uint32_t y, uint32_t mb) {
    asm volatile("st.async.shared::cluster.mbarrier::complete_tx::bytes.v2.b32 [%0],{%1,%2},[%3];" ::"r"(a), "r"(x), "r"(y), "r"(mb) : "memory");
}
__device__ __forceinline__ uint4 lds128(uint32_t a) { uint4 v; asm volatile("ld.shared.v4.u32 {%0,%1,%2,%3},[%4];" : "=r"(v.x), "=r"(v.y), "=r"(v.z), "=r"(v.w) : "r"(a) : "memory"); return v; }
__device__ __forceinline__ uint4 lds128v(uint32_t a) { uint4 v; asm volatile("ld.volatile.shared.v4.u32 {%0,%1,%2,%3},[%4];" : "=r"(v.x), "=r"(v.y), "=r"(v.z), "=r"(v.w) : "r"(a) : "memory"); return v; }
__device__ __forceinline__ uint2 lds64(uint32_t a) { uint2 v; asm volatile("ld.shared.v2.u32 {%0,%1},[%2];" : "=r"(v.x), "=r"(v.y) : "r"(a) : "memory"); return v; }
__device__ __forceinline__ uint32_t lds32(uint32_t a) { uint32_t v; asm volatile("ld.shared.u32 %0,[%1];" : "=r"(v) : "r"(a) : "memory"); return v; }
__device__ __forceinline__ void sts128(uint32_t a, uint32_t x, uint32_t y, uint32_t z, uint32_t w) { asm volatile("st.shared.v4.u32 [%0],{%1,%2,%3,%4};" ::"r"(a), "r"(x), "r"(y), "r"(z), "r"(w) : "memory"); }
__device__ __forceinline__ void sts64(uint32_t a, uint32_t x, uint32_t y) { asm volatile("st.shared.v2.u32 [%0],{%1,%2};" ::"r"(a), "r"(x), "r"(y) : "memory"); }
__device__ __forceinline__ void sts32(uint32_t a, uint32_t x) { asm volatile("st.shared.u32 [%0],%1;" ::"r"(a), "r"(x) : "memory"); }
__device__ __forceinline__ uint4 ldsm4(uint32_t a) { uint4 v; asm volatile("ldmatrix.sync.aligned.m8n8.x4.shared.b16 {%0,%1,%2,%3},[%4];" : "=r"(v.x), "=r"(v.y), "=r"(v.z), "=r"(v.w) : "r"(a) : "memory"); return v; }
__device__ __forceinline__ uint4 ldsm4t(uint32_t a) { uint4 v; asm volatile("ldmatrix.sync.aligned.m8n8.x4.trans.shared.b16 {%0,%1,%2,%3},[%4];" : "=r"(v.x), "=r"(v.y), "=r"(v.z), "=r"(v.w) : "r"(a) : "memory"); return v; }
__device__ __forceinline__ uint32_t movm(uint32_t a) { uint32_t d; asm volatile("movmatrix.sync.aligned.m8n8.trans.b16 %0,%1;" : "=r"(d) : "r"(a)); return d; }
__device__ __forceinline__ uint32_t pack2(float lo, float hi) { uint32_t d; asm("cvt.rn.bf16x2.f32 %0,%1,%2;" : "=r"(d) : "f"(hi), "f"(lo)); return d; }
__device__ __forceinline__ uint32_t hadd2(uint32_t a, uint32_t b) { uint32_t d; asm("add.rn.bf16x2 %0,%1,%2;" : "=r"(d) : "r"(a), "r"(b)); return d; }
__device__ __forceinline__ uint32_t hmul2(uint32_t a, uint32_t b) { uint32_t d; asm("mul.rn.bf16x2 %0,%1,%2;" : "=r"(d) : "r"(a), "r"(b)); return d; }
__device__ __forceinline__ float blo(uint32_t v) { return __uint_as_float(v << 16); }
__device__ __forceinline__ float bhi(uint32_t v) { return __uint_as_float(v & 0xffff0000u); }
__device__ __forceinline__ float rbf(float x) { return __uint_as_float(pack2(0.f, x)); }
__device__ __forceinline__ float ex2(float x) { float y; asm("ex2.approx.ftz.f32 %0,%1;" : "=f"(y) : "f"(x)); return y; }
__device__ __forceinline__ float rcp(float x) { float y; asm("rcp.approx.ftz.f32 %0,%1;" : "=f"(y) : "f"(x)); return y; }
__device__ __forceinline__ void mma16(float* c, uint32_t a0, uint32_t a1, uint32_t a2, uint32_t a3, uint32_t b0, uint32_t b1) {
    asm volatile("mma.sync.aligned.m16n8k16.row.col.f32.bf16.bf16.f32 {%0,%1,%2,%3},{%4,%5,%6,%7},{%8,%9},{%0,%1,%2,%3};"
                 : "+f"(c[0]), "+f"(c[1]), "+f"(c[2]), "+f"(c[3]) : "r"(a0), "r"(a1), "r"(a2), "r"(a3), "r"(b0), "r"(b1));
}
__device__ __forceinline__ void mma16_top(float& d0, float& d1, uint32_t a0, uint32_t a2, uint32_t b0, uint32_t b1) {
    asm volatile("{.reg .b32 j; .reg .f32 e,f; mma.sync.aligned.m16n8k16.row.col.f32.bf16.bf16.f32 {%0,%1,e,f},{%2,j,%3,j},{%4,%5},{0f00000000,0f00000000,0f00000000,0f00000000};}"
                 : "=f"(d0), "=f"(d1) : "r"(a0), "r"(a2), "r"(b0), "r"(b1));
}
__device__ __forceinline__ void mma8(float* c, uint32_t a0, uint32_t a1, uint32_t b0) {
    asm volatile("mma.sync.aligned.m16n8k8.row.col.f32.bf16.bf16.f32 {%0,%1,%2,%3},{%4,%5},{%6},{%0,%1,%2,%3};"
                 : "+f"(c[0]), "+f"(c[1]), "+f"(c[2]), "+f"(c[3]) : "r"(a0), "r"(a1), "r"(b0));
}
__device__ __forceinline__ uint4 ld_rlx128(const uint4* p) {
    uint4 v;
    asm volatile("{.reg .b128 t; ld.relaxed.gpu.global.b128 t,[%4]; mov.b128 {%0,%1,%2,%3},t;}" : "=r"(v.x), "=r"(v.y), "=r"(v.z), "=r"(v.w) : "l"(p) : "memory");
    return v;
}
__device__ __forceinline__ void st_rlx128(uint4* p, uint32_t x, uint32_t y, uint32_t z, uint32_t w) {
    asm volatile("{.reg .b128 t; mov.b128 t,{%1,%2,%3,%4}; st.relaxed.gpu.global.b128 [%0],t;}" ::"l"(p), "r"(x), "r"(y), "r"(z), "r"(w) : "memory");
}
__device__ __forceinline__ uint4 ldcg128(const uint4* p) { uint4 v; asm volatile("ld.global.cg.v4.u32 {%0,%1,%2,%3},[%4];" : "=r"(v.x), "=r"(v.y), "=r"(v.z), "=r"(v.w) : "l"(p) : "memory"); return v; }
__device__ __forceinline__ void red_release(unsigned* p, unsigned v) {
    asm volatile("fence.proxy.async; red.relaxed.gpu.global.add.u32 [%0],%1;" ::"l"(p), "r"(v) : "memory");
}
__device__ __forceinline__ void red_relaxed(unsigned* p, unsigned v) { asm volatile("red.relaxed.gpu.global.add.u32 [%0],%1;" ::"l"(p), "r"(v) : "memory"); }
__device__ __forceinline__ void wait_cnt(const unsigned* p, unsigned target) {
    asm volatile(
        "{.reg .pred p; .reg .u32 n,v; mov.u32 n,0;\n"
        "W%=: ld.acquire.gpu.global.u32 v,[%0]; setp.ge.u32 p,v,%1; @p bra D%=;\n"
        "nanosleep.u32 20; add.u32 n,n,1; setp.lt.u32 p,n,4000000; @p bra W%=;\n"
        "trap;\n"
        "D%=: }" ::"l"(p), "r"(target) : "memory");
}
__device__ __forceinline__ void wait_slow_warp(const unsigned* p, unsigned target) {
    asm volatile(
        "{.reg .pred p; .reg .u32 n,v; mov.u32 n,0;\n"
        "W%=: ld.relaxed.gpu.global.u32 v,[%0]; setp.ge.u32 p,v,%1; vote.sync.all.pred p,p,0xffffffff; @p bra.uni D%=;\n"
        "nanosleep.u32 400; add.u32 n,n,1; setp.lt.u32 p,n,1000000; @p bra.uni W%=;\n"
        "trap;\n"
        "D%=: }" ::"l"(p), "r"(target) : "memory");
}
__device__ __forceinline__ void wait_flag_warp(const unsigned* p, unsigned target) {
    asm volatile(
        "{.reg .pred p; .reg .u32 n,v; mov.u32 n,0;\n"
        "W%=: ld.relaxed.gpu.global.u32 v,[%0]; setp.ge.u32 p,v,%1; vote.sync.all.pred p,p,0xffffffff; @p bra.uni D%=;\n"
        "add.u32 n,n,1; setp.lt.u32 p,n,10000000; @p bra.uni W%=;\n"
        "trap;\n"
        "D%=: }" ::"l"(p), "r"(target) : "memory");
}
__device__ __forceinline__ uint64_t mkdesc(uint32_t addr, uint32_t lbo, uint32_t sbo, uint32_t sw) {
    return (uint64_t)((addr & 0x3FFFF) >> 4) | ((uint64_t)(lbo >> 4) << 16) | ((uint64_t)(sbo >> 4) << 32) | ((uint64_t)sw << 62);
}
__device__ __forceinline__ void wg_fence() { asm volatile("wgmma.fence.sync.aligned;" ::: "memory"); }
__device__ __forceinline__ void wg_commit() { asm volatile("wgmma.commit_group.sync.aligned;" ::: "memory"); }
template <int N> __device__ __forceinline__ void wg_wait() { asm volatile("wgmma.wait_group.sync.aligned %0;" ::"n"(N) : "memory"); }
#define R8(c, o) "+f"(c[o]), "+f"(c[o + 1]), "+f"(c[o + 2]), "+f"(c[o + 3]), "+f"(c[o + 4]), "+f"(c[o + 5]), "+f"(c[o + 6]), "+f"(c[o + 7])
#define R32(c, o) R8(c, o), R8(c, o + 8), R8(c, o + 16), R8(c, o + 24)
#define S32A "%0,%1,%2,%3,%4,%5,%6,%7,%8,%9,%10,%11,%12,%13,%14,%15,%16,%17,%18,%19,%20,%21,%22,%23,%24,%25,%26,%27,%28,%29,%30,%31"
template <int ACC> __device__ __forceinline__ void wgmma64_rs(float* c, const uint32_t* a, uint64_t db) {
    asm volatile("wgmma.mma_async.sync.aligned.m64n64k16.f32.bf16.bf16 {" S32A "},{%32,%33,%34,%35},%36,%37,1,1,0;"
                 : R32(c, 0) : "r"(a[0]), "r"(a[1]), "r"(a[2]), "r"(a[3]), "l"(db), "n"(ACC));
}
template <int ACC> __device__ __forceinline__ void wgmma64_ta(float* c, uint64_t da, uint64_t db) {
    asm volatile("wgmma.mma_async.sync.aligned.m64n64k16.f32.bf16.bf16 {" S32A "},%32,%33,%34,1,1,1,0;" : R32(c, 0) : "l"(da), "l"(db), "n"(ACC));
}
template <int ACC> __device__ __forceinline__ void wgmma80_tb(float* c, uint64_t da, uint64_t db) {
    asm volatile("wgmma.mma_async.sync.aligned.m64n80k16.f32.bf16.bf16 {" S32A ",%32,%33,%34,%35,%36,%37,%38,%39},%40,%41,%42,1,1,0,1;"
                 : R32(c, 0), R8(c, 32) : "l"(da), "l"(db), "n"(ACC));
}
template <int N> __device__ __forceinline__ void reg_inc() { asm volatile("setmaxnreg.inc.sync.aligned.u32 %0;" ::"n"(N)); }
template <int N> __device__ __forceinline__ void reg_dec() { asm volatile("setmaxnreg.dec.sync.aligned.u32 %0;" ::"n"(N)); }

#define PROF(cond, idx) do {} while (0)
#define PROF2(cond, idx) do {} while (0)

constexpr int S_GATE = 232440, S_TAG = 232444, S_XBAR = 232432, B_BAR = 231936;
#define FT 5
#define FJ 62
#define OLAG 1
#define RCB 136
#define RCU 184
#define NTOP 1
#define PLATE 2
#define QLAG 4
constexpr float SC_LOG2E = 0.08838834764831845f * 1.4426950408889634f;

__device__ __forceinline__ float2 ln_finish(float mean, float var) {
    float sd; asm("sqrt.approx.f32 %0,%1;" : "=f"(sd) : "f"(rbf(rbf(var) + 1e-5f)));
    sd = rbf(sd);
    return make_float2(rbf(mean), sd);
}

__device__ __forceinline__ float2 row_stats512(uint4* v, const uint4* src, int s1, int s2) {
    const int g = (threadIdx.x & 31) >> 2;
#pragma unroll
    for (int i = 0; i < 16; i++) v[i] = ldcg128(src + (i >> 1) * s1 + (i & 1) * s2);
    float a[4] = {0, 0, 0, 0}, q0[4] = {0, 0, 0, 0}, q1[4] = {0, 0, 0, 0};
#pragma unroll
    for (int i = 0; i < 16; i++) {
        mma16(a, v[i].x, v[i].y, v[i].z, v[i].w, 0x3f803f80u, 0x3f803f80u);
        mma8(q0, v[i].x, v[i].y, v[i].x); mma8(q1, v[i].x, v[i].y, v[i].y);
        mma8(q0, v[i].z, v[i].w, v[i].z); mma8(q1, v[i].z, v[i].w, v[i].w);
    }
    const float sum = a[0] + a[2], sq = (g & 1) ? q0[1] + q1[3] : q0[0] + q1[2];
    return make_float2(sum, fmaxf(sq - sum * sum * (1.f / 512.f), 0.f));
}
__device__ __forceinline__ void x1_norm(const uint2* src, int r, bool on) {
    const int lane = threadIdx.x & 31, g = lane >> 2, t = r * 4 + (lane & 3);
    constexpr int xp = XP;
    uint2 v[16];
#pragma unroll
    for (int i = 0; i < 16; i++) asm volatile("ld.global.cg.v2.u32 {%0,%1},[%2];" : "=r"(v[i].x), "=r"(v[i].y) : "l"(src + (g * 4 * xp + t) + ((i >> 1) * 16 + (i & 1)) * 2 * xp) : "memory");
    float s = 0, q = 0;
#pragma unroll
    for (int i = 0; i < 32; i++) {
        const uint32_t w = (i & 1) ? v[i >> 1].y : v[i >> 1].x;
        s += blo(w) + bhi(w); q = fmaf(blo(w), blo(w), fmaf(bhi(w), bhi(w), q));
    }
#pragma unroll
    for (int d = 4; d < 32; d *= 2) { s += __shfl_xor_sync(0xffffffffu, s, d); q += __shfl_xor_sync(0xffffffffu, q, d); }
    if (g == 0 && on) g_ln0[t] = 0;
    s *= 1.f / 512.f;
    const float2 l = ln_finish(s, fmaxf(fmaf(q, 1.f / 512.f, -s * s), 0.f));
    const float rs = rcp(l.y);
    const uint32_t mm = pack2(-l.x, -l.x);
    uint4* dst = g_xn + ((t >> 6) * 4096 + ((t >> 3) & 7) * 64 + g * 8 + (t & 7));
#define NRM(w) pack2(blo(hadd2(w, mm)) * rs, bhi(hadd2(w, mm)) * rs)
#pragma unroll
    for (int i = 0; i < 8; i++)
        asm volatile("{.reg .pred p; setp.ne.u32 p,%5,0; @p st.global.v4.u32 [%0],{%1,%2,%3,%4};}" ::"l"(dst + i * 512), "r"(NRM(v[2 * i].x)), "r"(NRM(v[2 * i].y)),
                     "r"(NRM(v[2 * i + 1].x)), "r"(NRM(v[2 * i + 1].y)), "r"((uint32_t)on) : "memory");
}

#define NWO 10
#define VMASK 0x4444
#define VPRE 2
#define OL 0x16
#define PINS 0x6ae1
#define NPX 2
#define NPF 2
constexpr int SLOT = 24576, SL_V = 8192, SL_Q = 16384, SL_KM = 20480, SL_VM = 22528;
constexpr int R_SL = 0, R_WV = 4 * SLOT  , R_WO = R_WV + 65536, R_M = 196608  , R_U = R_M + 8192  ,
              R_OS = R_U + 8192  , R_SB = R_OS + 8192  , R_OB = R_SB + 5248  , R_PB = R_OB + 2048  ,
              R_IL = R_PB + 1024  , R_SEL = 231680, R_BAR = R_SEL + 256, R_STV = 0, R_STQ = 65536, R_STK = 131072;
static_assert(R_WO + (16 - NWO) * 4096 <= R_M && R_IL + 64 <= R_SEL && R_BAR + 512 <= 232448, "smem map");
enum { RB_XFULL = 0  , RB_GO = 4  , RB_QK = 8  , RB_INIT = 24, RB_SV = 25   };

enum { NB_MFULL = 1  , NB_PART = 3  , NB_S = 5, NB_P = 6, NB_O = 7, NB_W = 10 };
#define XU 4
#define SEARLY 4
#define NPRB 3
#define RH 56
#define RW0 224
#define D1 240
#define D2 300
__device__ __forceinline__ uint32_t clk32() { uint32_t c; asm volatile("mov.u32 %0,%%clock;" : "=r"(c)::"memory"); return c; }
__device__ __forceinline__ void spin(int cycles) {
    if (cycles <= 0) return;
    asm volatile("{.reg .pred p; .reg .u32 a,b; mov.u32 a,%%clock; add.u32 a,a,%0;\nS%=: mov.u32 b,%%clock; sub.u32 b,b,a; setp.lt.s32 p,b,0; @p bra.uni S%=;}" ::"r"(cycles) : "memory");
}
__device__ __forceinline__ uint4* xregion(int X, int r) { return (uint4*)(((size_t)g_xch + 8191) & ~(size_t)8191) + (X * 66 + r) * 512; }

__device__ __forceinline__ void arrive_if(uint32_t bar, uint32_t a, uint32_t b) {
    asm volatile("{.reg .pred p; setp.eq.u32 p,%1,%2; @p mbarrier.arrive.shared::cta.b64 _,[%0];}" ::"r"(bar), "r"(a), "r"(b) : "memory");
}
struct RecW { uint32_t po, dp, lw, sp, w; };
#define PIN(n) if ((PINS >> (n)) & 1) asm volatile("griddepcontrol.launch_dependents;" ::: "memory")
constexpr int v_stream(int n) {
    int ks = 0;
    for (; ks < 16; ks++) if (!((VMASK >> ks) & 1) && n-- == 0) break;
    return ks;
}
constexpr uint64_t v_next() {
    uint64_t r = 0;
    for (int n = 0; v_stream(n + VPRE) < 16; n++) r |= (uint64_t)v_stream(n + VPRE) << (4 * v_stream(n));
    return r;
}
constexpr uint64_t V_NEXT = v_next();
constexpr int V_PRE = v_stream(VPRE);

__device__ __forceinline__ void rec_step(const RecW& k, uint32_t sb, const int X, int s, uint32_t zero, int lo, int hi, int d, const uint32_t (*wq)[4], const uint32_t (*wk)[4], uint4* wv, uint4* wo) {
    const int SL = R_SL + X * 2 * SLOT;
    uint4 mk[8];
    bar_sync(NB_MFULL + X, 288);
    mk[0] = ldsm4(k.lw + X * 4096 + R_M);
    PIN(0);
    mk[1] = ldsm4(k.lw + X * 4096 + R_M + 512);
    PIN(0);
    asm volatile("" : "+r"(s));
    const uint32_t z = s & zero, wz = k.w + z, w5 = wz * 512, so = (s & 1) * SLOT + w5;
    const uint32_t qb = sb + R_BAR + (RB_QK + X * 8) * 8 + wz * 8;
    uint32_t x[4], vv[2], l8;
    {
        float aq[4] = {0, 0, 0, 0}, ak[4] = {0, 0, 0, 0}, av[4] = {0, 0, 0, 0};
#pragma unroll
        for (int t = 0; t < 16; t++) {
            const uint32_t b0 = (t & 1) ? mk[t >> 1].z : mk[t >> 1].x, b1 = (t & 1) ? mk[t >> 1].w : mk[t >> 1].y;
            mma16(aq, wq[t][0], wq[t][1], wq[t][2], wq[t][3], b0, b1);
            PIN(8);
            mma16(ak, wk[t][0], wk[t][1], wk[t][2], wk[t][3], b0, b1);
            PIN(9);
            mma16(av, wv[t].x, wv[t].y, wv[t].z, wv[t].w, b0, b1);
            PIN(10);
            if ((t & 1) && t < 13) mk[(t >> 1) + 2] = ldsm4(k.lw + X * 4096 + R_M + (t >> 1) * 512 + 1024);
            const int nx = (V_NEXT >> (4 * t)) & 15;
            if (nx) wv[nx] = lds128(k.lw + w5 + R_WV + nx * 4096);
            if (t == 14) l8 = ((k.lw + z) >> 1) + (sb - (sb >> 1) + SL + (s & 1) * SLOT + wz * 256);
            if (t < 15) PIN(1);
        }
        x[0] = movm(pack2(aq[0], aq[1])); x[1] = movm(pack2(aq[2], aq[3]));
        x[2] = movm(pack2(ak[0], ak[1])); x[3] = movm(pack2(ak[2], ak[3]));
        vv[0] = pack2(av[0], av[1]); vv[1] = pack2(av[2], av[3]);
        st_async2(l8 + (SL_VM + k.dp), vv[0], vv[1], qb + k.dp);
        st_async4(k.lw + (R_U + X * 4096 + w5 + k.dp), x[0], x[1], x[2], x[3], qb + k.dp);
    }
    {
        arrive_if(sb + R_BAR + (RB_GO + 2 - 2 * X + ((s + d) & 1)) * 8, (k.sp + z) & 0x1ff0, X ? s >= hi : s <= lo);
        const uint32_t swr = ((k.sp + z) & 0x1ff0) + (sb + R_SB);
#pragma unroll
        for (int i = 0; i < NPX; i++) wo[i] = lds128v(k.lw + w5 + R_WO + i * 4096);
        mbar_wait(sb + R_BAR + (RB_XFULL + X * 2) * 8 + (s & 1) * 8, (s >> 1) & 1);
        const uint4 k0 = lds128(k.lw + so + SL), k1 = lds128(k.lw + so + SL + 4096);
        mbar_wait(qb, s & 1);
        const uint4 u = lds128(k.lw + w5 + R_U + X * 4096);
        const uint32_t q0 = hadd2(x[0], u.x), q1 = hadd2(x[1], u.y);
        x[2] = hadd2(x[2], u.z); x[3] = hadd2(x[3], u.w);
        float sa[4] = {0, 0, 0, 0}, sc[4] = {0, 0, 0, 0}, sm0, sm1;
        mma16(sa, k0.x, k0.y, k0.z, k0.w, q0, q1);
        mma16(sc, k1.x, k1.y, k1.z, k1.w, q0, q1);
        mma16_top(sm0, sm1, x[2], x[3], q0, q1);
        asm volatile("stmatrix.sync.aligned.m8n8.x4.trans.shared.b16 [%0],{%1,%2,%3,%4};" ::"r"(swr), "r"(pack2(sa[0], sa[1])), "r"(pack2(sa[2], sa[3])),
                     "r"(pack2(sc[0], sc[1])), "r"(pack2(sc[2], sc[3])) : "memory");
        asm volatile("stmatrix.sync.aligned.m8n8.x1.trans.shared.b16 [%0],{%1};" ::"r"(swr + 512), "r"(pack2(sm0, sm1)) : "memory");
    }
    bar_sync(NB_S, 256);
    uint4 v0, v1;
    uint32_t ls;
    {
        const uint4 y = ldsm4t(k.lw + wz * 656 + R_SB);
        PIN(2);
        uint32_t y4; asm volatile("ldmatrix.sync.aligned.m8n8.x1.trans.shared.b16 {%0},[%1];" : "=r"(y4) : "r"(k.lw + wz * 656 + R_SB + 512) : "memory");
        PIN(2);
        const uint2 vp = lds64(l8 + SL_VM);
        sts64(l8 + SL_KM, x[2], x[3]);
        const uint32_t z1 = k.lw & z, z2 = k.sp & z, ONE = 0x3f803f80u | z2, ONF = 0x3f803f80u | z1;
        float a[4] = {0, 0, 0, 0}, b[4] = {0, 0, 0, 0}, e[4] = {0, 0, 0, 0};
        mma8(e, ONE, z1, y4); mma16(a, ONE, z1, z2, ONF, y.x, y.y); mma16(b, ONE, z1, z2, ONF, y.z, y.w);
        vv[0] = hadd2(vv[0], vp.x); vv[1] = hadd2(vv[1], vp.y);
        sts64(l8 + SL_VM, vv[0], vv[1]);
        float s0, s1;
        asm("{.reg .pred p1,p2,p4; .reg .f32 t0,t1,u0,u1; .reg .b32 m; and.b32 m,%12,64; setp.ne.u32 p1,m,0; and.b32 m,%12,128; setp.ne.u32 p2,m,0; and.b32 m,%12,256; setp.ne.u32 p4,m,0;"
            "selp.f32 t0,%4,%2,p1; selp.f32 t1,%5,%3,p1; selp.f32 u0,%8,%6,p1; selp.f32 u1,%9,%7,p1; selp.f32 t0,u0,t0,p2; selp.f32 t1,u1,t1,p2; selp.f32 %0,%10,t0,p4; selp.f32 %1,%11,t1,p4;}"
            : "=f"(s0), "=f"(s1) : "f"(a[0]), "f"(a[1]), "f"(a[2]), "f"(a[3]), "f"(b[0]), "f"(b[1]), "f"(b[2]), "f"(b[3]), "f"(e[0]), "f"(e[1]), "r"(k.lw));
        const int mi = __float_as_int(fmaxf(s0, s1));
        const int mp = __reduce_max_sync(0xffffffffu, mi), mn = (int)__reduce_min_sync(0xffffffffu, (unsigned)mi);
        PIN(3);
        v0 = lds128(k.lw + so + SL + SL_V); v1 = lds128(k.lw + so + SL + SL_V + 4096);
#pragma unroll
        for (int i = NPX; i < NPF; i++) wo[i] = lds128(k.lw + w5 + R_WO + i * 4096);
        PIN(4);
        const float mo = -__int_as_float(mp >= 0 ? mp : mn) * SC_LOG2E;
        s0 = ex2(fmaf(s0, SC_LOG2E, mo)); s1 = ex2(fmaf(s1, SC_LOG2E, mo));
        sts32((((k.sp + z) >> 11) & 0x1fc) + (k.lw & 256) * 2 + (sb + R_PB), pack2(s0, s1));
        ls = k.lw < sb + 320 ? __float_as_uint((s0 + s1) + 4.f) : 0;
    }
    bar_sync(NB_P, 256);
    {
        const uint4 pp = lds128(k.lw + R_PB);
        PIN(5);
        const uint32_t pm = lds32(((k.lw + z) >> 2) + (sb - (sb >> 2) + R_PB + 512));
        PIN(5);
        sts32(sb + R_IL + (wz >> 1) * 16 + (wz & 1) * 4, __reduce_add_sync(0xffffffffu, ls) - 20u * 0x40800000u);
        float o0[4] = {0, 0, 0, 0}, o1[4] = {0, 0, 0, 0}, o2[4] = {0, 0, 0, 0};
        mma16(o0, v0.x, v0.y, v0.z, v0.w, pp.x, pp.y);
        mma16(o1, v1.x, v1.y, v1.z, v1.w, pp.z, pp.w);
        mma8(o2, vv[0], vv[1], pm);
        asm volatile("stmatrix.sync.aligned.m8n8.x2.trans.shared.b16 [%0],{%1,%2};" ::"r"(k.lw + wz * 256 + R_OB),
                     "r"(pack2(o0[0] + o1[0] + o2[0], o0[1] + o1[1] + o2[1])), "r"(pack2(o0[2] + o1[2] + o2[2], o0[3] + o1[3] + o2[3])) : "memory");
    }
    bar_sync(NB_O, 256);
    {
        float r0[4] = {0, 0, 0, 0}, r1[4] = {0, 0, 0, 0};
        uint4 b[4];
        b[0] = ldsm4(k.lw + R_OB);
        PIN(6);
        b[1] = ldsm4(k.lw + R_OB + 512);
        PIN(6);
#pragma unroll
        for (int m = NWO + NPF; m < 16; m++) if (((OL >> (2 * (15 - m))) & 3) == 3) wo[m] = lds128(k.lw + w5 + R_WO + (m - NWO) * 4096);
        const uint2 il = lds64(sb + R_IL + ((k.lw + z) & 48));
        PIN(6);
        float i0, i1;
        uint4* dst;
#pragma unroll
        for (int i = 0; i < 4; i++) {
            mma16(r0, wo[4 * i].x, wo[4 * i].y, wo[4 * i].z, wo[4 * i].w, b[i].x, b[i].y);
            mma16(r1, wo[4 * i + 1].x, wo[4 * i + 1].y, wo[4 * i + 1].z, wo[4 * i + 1].w, b[i].x, b[i].y);
            mma16(r0, wo[4 * i + 2].x, wo[4 * i + 2].y, wo[4 * i + 2].z, wo[4 * i + 2].w, b[i].z, b[i].w);
            mma16(r1, wo[4 * i + 3].x, wo[4 * i + 3].y, wo[4 * i + 3].z, wo[4 * i + 3].w, b[i].z, b[i].w);
            if (i < 2) b[i + 2] = ldsm4(k.lw + R_OB + (i + 2) * 512);
#pragma unroll
            for (int m = NWO + NPF; m < 16; m++) if (i < 3 && i == ((OL >> (2 * (15 - m))) & 3)) wo[m] = lds128(k.lw + w5 + R_WO + (m - NWO) * 4096);
            if (i == 1) { i0 = rcp(__uint2float_rn(il.x)) * 2097152.f; i1 = rcp(__uint2float_rn(il.y)) * 2097152.f; }
            if (i == 2) {
                const uint32_t po = k.sp + z;
                dst = xregion(X, 0) + k.po + ((po >> 20) ^ ((po & X) << 8));
                asm volatile("" : "+l"(dst));
            }
            PIN(7);
        }
        const uint32_t tag = (s + 1) & 1;
#pragma unroll
        for (int i = 0; i < 4; i++) { r0[i] *= (i & 1) ? i1 : i0; r1[i] *= (i & 1) ? i1 : i0; }
        st_rlx128(dst, (pack2(r0[0], r0[2]) & ~1u) | tag,
                  pack2(r1[0], r1[2]), pack2(r0[1], r0[3]), pack2(r1[1], r1[3]));
        bar_arrive(NB_PART + X, 288);
#pragma unroll
        for (int t = 0; t < V_PRE; t++) if (!((VMASK >> t) & 1)) wv[t] = lds128(k.lw + w5 + R_WV + t * 4096);
        arrive_if(sb + R_BAR + (RB_GO + 2 * X + (s & 1)) * 8, (k.sp + z) & 0x1ff0, X ? s + 1 < hi : s >= lo);
    }
}

__device__ __forceinline__ void rec_fetch(const Params& p, uint32_t sb, int head, uint32_t rank, int which, int dst) {
#pragma unroll 1
    for (int j = 0; j < 8; j++) tma2d(sb + dst + j * 8192, &p.tm[which], head * 128 + (j >> 2) * 64, rank * 256 + (j & 3) * 64, sb + R_BAR + RB_INIT * 8);
}

__device__ __forceinline__ void rec_weights(const Params& p, uint32_t sb, int head, uint32_t rank, int w) {
    const int lane = __shfl_sync(0xffffffffu, threadIdx.x & 31, threadIdx.x & 31),
        g = lane >> 2, c = lane & 3;
    const int t = w & 3, WG = w >> 2;
    uint32_t wq[16][4], wk[16][4];
    uint4 wo[16], wv[16];
    const uint32_t woff = sb + WG * 32768 + (((lane >> 4) << 3) + (lane & 7)) * 128 + (((2 * t + ((lane >> 3) & 1)) ^ (lane & 7)) << 4);
    const uint32_t lw = sb + lane * 16;
    PROF2(threadIdx.x == 0, 3501);
    {
        const __nv_bfloat16* wp = p.Wo + (size_t)(head * 128 + 2 * c) * 512 + rank * 256 + w * 32 + g * 4;
#pragma unroll
        for (int ks = 0; ks < 8; ks++) {
            const uint2 r0 = *(const uint2*)(wp + (ks * 16) * 512), r1 = *(const uint2*)(wp + (ks * 16 + 1) * 512);
            const uint2 r2 = *(const uint2*)(wp + (ks * 16 + 8) * 512), r3 = *(const uint2*)(wp + (ks * 16 + 9) * 512);
            const uint4 f[2] = {make_uint4(__byte_perm(r0.x, r1.x, 0x5410), __byte_perm(r0.x, r1.x, 0x7632), __byte_perm(r2.x, r3.x, 0x5410), __byte_perm(r2.x, r3.x, 0x7632)),
                                make_uint4(__byte_perm(r0.y, r1.y, 0x5410), __byte_perm(r0.y, r1.y, 0x7632), __byte_perm(r2.y, r3.y, 0x5410), __byte_perm(r2.y, r3.y, 0x7632))};
#pragma unroll
            for (int h = 0; h < 2; h++) {
                const int m = 2 * ks + h;
                wo[m] = f[h];
            }
        }
    }
    PROF2(threadIdx.x == 0, 3502);
    mbar_wait(sb + R_BAR + RB_INIT * 8, 0);
    PROF2(threadIdx.x == 0, 3503);
#pragma unroll
    for (int ks = 0; ks < 16; ks++) {
        uint4 a = ldsm4t(woff + R_STQ + ks * 2048), b = ldsm4t(woff + R_STK + ks * 2048);
        wq[ks][0] = a.x; wq[ks][1] = a.y; wq[ks][2] = a.z; wq[ks][3] = a.w;
        wk[ks][0] = b.x; wk[ks][1] = b.y; wk[ks][2] = b.z; wk[ks][3] = b.w;
    }
    bar_sync(NB_W, 256);
#pragma unroll
    for (int m = 0; m < 16; m++)
        if (m < NPF || m >= NPF + NWO) sts128(lw + w * 512 + R_WO + (m < NPF ? m : m - NWO) * 4096, wo[m].x, wo[m].y, wo[m].z, wo[m].w);
#pragma unroll
    for (int i = 0; i < 16; i++) {
        wv[i] = ldsm4t(woff + R_STV + i * 2048);
        if (!((VMASK >> i) & 1)) sts128(lw + w * 512 + R_WV + i * 4096, wv[i].x, wv[i].y, wv[i].z, wv[i].w);
    }
    fence_async_smem();
    PROF2(threadIdx.x == 0, 3504);
    __syncthreads();
    cluster_sync();
    PROF2(threadIdx.x == 0, 3505);
    RecW k;
    {
        const int r = (w * 4 + (lane >> 3)) * 2 + rank;
        const uint32_t sl = lds32(sb + R_SEL + r * 4);
        k.po = (w * 8 + rank) * 512 + (head >> 1) * 16 + (head & 1) * 4;
        k.sp = (((lane >> 3) * 1024 + (sl & 1) * 256 + (lane & 4) * 2 + (lane & 3)) << 20) + (((sl >> 1) ^ sl) & 1) + (lane & 7) * 656 + (lane >> 3) * 128 + w * 16 +
               ((g < 4 ? (w * 4 + c) * 4 + g : w * 4 + c) << 13);
    }
    k.dp = mapa(sb, rank ^ 1) - sb;
    k.lw = lw;
    asm volatile("" : "+r"(k.lw));
    k.w = w;
    const int e0 = (p.chains & 1) ? 64 : 0, o1 = (p.chains & 2) ? p.lag : 1000, nit = (p.chains & 2) ? p.lag + 64 : e0;
    const uint32_t zero = p.zero;
    int it = 0, X = e0 ? 0 : 1;
#pragma unroll 1
    while (it < nit) {
        rec_step(k, sb, X, X ? it - o1 : it, zero, o1, e0 - o1, o1 + 1 - X, wq, wk, wv, wo);
        if (X == 0 && it >= o1) X = 1; else { it++; X = it < e0 ? 0 : 1; }
    }
}

__device__ __forceinline__ uint32_t mism(uint32_t a, uint32_t b, uint32_t t) {
    uint32_t d; asm("lop3.b32 %0,%1,%2,%3,0x7e;" : "=r"(d) : "r"(a), "r"(b), "r"(t)); return d;
}
__device__ __forceinline__ uint32_t or3(uint32_t a, uint32_t b, uint32_t c) {
    uint32_t d; asm("lop3.b32 %0,%1,%2,%3,0xfe;" : "=r"(d) : "r"(a), "r"(b), "r"(c)); return d;
}
template <bool TWO, class F>
__device__ __forceinline__ void poll8(uint4* x, const uint4* src, uint32_t tag, F&& use) {
#pragma unroll
    for (int j = 0; j < 8; j++) x[j] = ld_rlx128(src + j * 32);
    int n = 0;
    while (true) {
        use();
        uint32_t bad = or3(mism(x[0].x, x[1].x, tag), mism(x[2].x, x[3].x, tag), mism(x[4].x, x[5].x, tag));
        if (TWO) bad = or3(bad, or3(mism(x[0].z, x[1].z, tag), mism(x[2].z, x[3].z, tag), mism(x[4].z, x[5].z, tag)), mism(x[6].z, x[7].z, tag));
        if (!__any_sync(0xffffffffu, (bad | mism(x[6].x, x[7].x, tag)) & 1)) break;
#pragma unroll
        for (int j = 0; j < 8; j++)
            asm volatile("{.reg .pred p; .reg .b128 t; .reg .b32 m; lop3.b32 m,%0,%6,%5,0x7e; and.b32 m,m,1; setp.ne.u32 p,m,0; mov.b128 t,{%0,%1,%2,%3};"
                         "@p ld.relaxed.gpu.global.b128 t,[%4]; mov.b128 {%0,%1,%2,%3},t;}"
                         : "+r"(x[j].x), "+r"(x[j].y), "+r"(x[j].z), "+r"(x[j].w) : "l"(src + j * 32), "r"(tag), "r"(TWO ? x[j].z : tag) : "memory");
        if (++n > 2000000) __trap();
    }
}

__device__ __forceinline__ void rec_comm(const Params& p, uint32_t sb, int X, int head, uint32_t rank) {
    const int lane = threadIdx.x & 31, g = lane >> 2, c = lane & 3;
    const int me = head * 2 + rank;
    const uint32_t mb = sb + R_M + X * 4096 + lane * 16;
    uint4 x[8];
#pragma unroll
    for (int j = 0; j < 8; j++) x[j] = *(const uint4*)(p.mem0 + (lane & 7) * 512 + rank * 256 + (j * 4 + (lane >> 3)) * 8);
    const uint32_t sl = lds32(sb + R_SEL + me * 4);
    const uint4* src1 = xregion(X, me) + ((sl >> X) & 1) * 256 + (c >> 1) * 16 + (g >> 2) * 8 + (c & 1) * 4 + (g & 3);
    const uint4* src2 = xregion(X, 64 + rank) + ((sl >> (2 + X)) & 1) * 256 + lane;
    uint2* mdst = (uint2*)(xregion(X, 64 + rank) + (c >> 1) * 256 + head * 8 + (g & 3) * 2 + (c & 1)) + (g >> 2);
    const uint32_t one = (g & 1) ? 0x3f800000u : 0x00003f80u, selA = (g & 2) ? 0u : one, selB = (g & 2) ? one : 0u;
    const uint32_t qb = sb + R_BAR + (RB_QK + X * 8) * 8;
    if (lane < 8) mbar_expect(qb + lane * 8, 768);
    __syncwarp();
#pragma unroll
    for (int j = 0; j < 8; j++) sts128(mb + j * 512, x[j].x, x[j].y, x[j].z, x[j].w);
#pragma unroll 1
    for (int s = 0;; s++) {
        bar_arrive(NB_MFULL + X, 288);
        PROF(lane == 0, X * 64 + s);
        bar_sync(NB_PART + X, 288);
        if (s == 63) break;
        const uint32_t tag = (s + 1) & 1;
        asm volatile("{.reg .pred p; setp.lt.u32 p,%0,%1; @p mbarrier.arrive.expect_tx.shared::cta.b64 _,[%0],768;}"
                     ::"r"(((mb + (s & p.zero)) >> 1) + (qb - ((sb + R_M + X * 4096) >> 1))), "r"(qb + 64) : "memory");
        spin(D1);
        poll8<false>(x, src1, tag, []() {});
        float a[4][4];
#pragma unroll
        for (int j = 0; j < 8; j++) {
            if (j < 4) a[j][0] = a[j][1] = a[j][2] = a[j][3] = 0;
            mma16(a[j & 3], x[j].x, x[j].y, x[j].z, x[j].w, selA, selB);
        }
#pragma unroll
        for (int i = 0; i < 4; i++) a[0][i] = (a[0][i] + a[1][i]) + (a[2][i] + a[3][i]);
        const uint32_t m0 = (pack2(a[0][0], a[0][1]) & ~1u) | tag, m1 = pack2(a[0][2], a[0][3]);
        asm volatile("st.relaxed.gpu.global.b64 [%0],%1;" ::"l"(mdst), "l"(((uint64_t)m1 << 32) | m0) : "memory");
        spin(D2);
        poll8<true>(x, src2, tag, [&]() {
#pragma unroll
            for (int j = 0; j < SEARLY; j++) sts128(mb + j * 512, x[j].x, x[j].y, x[j].z, x[j].w);
        });
#pragma unroll
        for (int j = SEARLY; j < 8; j++) sts128(mb + j * 512, x[j].x, x[j].y, x[j].z, x[j].w);
    }
}

template <int MT>
__device__ __forceinline__ void xattn(uint32_t l16, uint32_t l8, uint32_t os, int g, int c) {
    constexpr int NT = 3 + 2 * MT, XUN = XU;
    float S[NT][4];
#pragma unroll
    for (int i = 0; i < NT; i++) S[i][0] = S[i][1] = S[i][2] = S[i][3] = 0;
#pragma unroll XUN
    for (int ks = 0; ks < 8; ks++) {
        const uint4 q = lds128(l16 + SL_Q + ks * 512);
        const uint2 u = lds64(l8 + SL_KM + ks * 256);
        mma16(S[0], q.x, q.y, q.z, q.w, u.x, u.y);
#pragma unroll
        for (int m = 0; m <= MT; m++) {
            const uint4 kk = lds128(l16 + m * 4096 + ks * 512);
            mma16(S[1 + 2 * m], q.x, q.y, q.z, q.w, kk.x, kk.z); mma16(S[2 + 2 * m], q.x, q.y, q.z, q.w, kk.y, kk.w);
        }
    }
    const float NEG = -__int_as_float(0x7f800000);
    if (2 * c > g) { S[NT - 2][0] = NEG; S[NT - 1][2] = NEG; }
    if (2 * c + 1 > g) { S[NT - 2][1] = NEG; S[NT - 1][3] = NEG; }
    S[NT - 1][0] = S[NT - 1][1] = NEG;
    float m0 = fmaxf(S[0][0], S[0][1]), m1 = fmaxf(S[0][2], S[0][3]);
#pragma unroll
    for (int i = 1; i < NT; i++) { if (i < NT - 1) m0 = fmaxf(m0, fmaxf(S[i][0], S[i][1])); m1 = fmaxf(m1, fmaxf(S[i][2], S[i][3])); }
    m0 = fmaxf(m0, __shfl_xor_sync(0xffffffffu, m0, 1)); m1 = fmaxf(m1, __shfl_xor_sync(0xffffffffu, m1, 1));
    m0 = fmaxf(m0, __shfl_xor_sync(0xffffffffu, m0, 2)); m1 = fmaxf(m1, __shfl_xor_sync(0xffffffffu, m1, 2));
    m0 *= -SC_LOG2E; m1 *= -SC_LOG2E;
    float l0 = 0, l1 = 0;
#pragma unroll
    for (int i = 0; i < NT; i++) {
        if (i < NT - 1) { S[i][0] = ex2(fmaf(S[i][0], SC_LOG2E, m0)); S[i][1] = ex2(fmaf(S[i][1], SC_LOG2E, m0)); l0 += S[i][0] + S[i][1]; }
        S[i][2] = ex2(fmaf(S[i][2], SC_LOG2E, m1)); S[i][3] = ex2(fmaf(S[i][3], SC_LOG2E, m1)); l1 += S[i][2] + S[i][3];
    }
    l0 += __shfl_xor_sync(0xffffffffu, l0, 1); l1 += __shfl_xor_sync(0xffffffffu, l1, 1);
    l0 += __shfl_xor_sync(0xffffffffu, l0, 2); l1 += __shfl_xor_sync(0xffffffffu, l1, 2);
    uint2 vm = lds64(l8 + SL_VM);
    uint4 v[2];
#pragma unroll
    for (int m = 0; m <= MT; m++) v[m] = lds128(l16 + SL_V + m * 4096);
    l0 = rcp(l0); l1 = rcp(l1);
    uint32_t P[NT][2];
#pragma unroll
    for (int i = 0; i < NT; i++) { P[i][0] = i < NT - 1 ? pack2(S[i][0] * l0, S[i][1] * l0) : 0u; P[i][1] = pack2(S[i][2] * l1, S[i][3] * l1); }
#pragma unroll
    for (int et = 0; et < 8; et++) {
        float a[4] = {0, 0, 0, 0}, b[4] = {0, 0, 0, 0};
        const uint2 um = vm;
        const uint4 u[2] = {v[0], v[MT]};
        if (et < 7) {
            vm = lds64(l8 + SL_VM + et * 256 + 256);
#pragma unroll
            for (int m = 0; m <= MT; m++) v[m] = lds128(l16 + SL_V + m * 4096 + et * 512 + 512);
            PIN(11);
        }
        mma8(a, um.x, um.y, P[0][0]); mma8(b, um.x, um.y, P[0][1]);
#pragma unroll
        for (int m = 0; m <= MT; m++) {
            mma16(a, u[m].x, u[m].y, u[m].z, u[m].w, P[1 + 2 * m][0], P[2 + 2 * m][0]); mma16(b, u[m].x, u[m].y, u[m].z, u[m].w, P[1 + 2 * m][1], P[2 + 2 * m][1]);
        }
        asm volatile("stmatrix.sync.aligned.m8n8.x4.trans.shared.b16 [%0],{%1,%2,%3,%4};" ::"r"(os + (et >> 2) * 2048 + (et & 3) * 256),
                     "r"(pack2(a[0], a[1])), "r"(pack2(a[2], a[3])), "r"(pack2(b[0], b[1])), "r"(pack2(b[2], b[3])) : "memory");
    }
}

__device__ __forceinline__ void rec_tiles(uint32_t sb, int X, int head, uint32_t rank, int& nxt, int lim, int need) {
#pragma unroll 1
    while (nxt <= lim) {
        if ((nxt & 1) == 0) {
            unsigned v; int n = 0;
            while (true) {
                asm volatile("ld.relaxed.gpu.global.u32 %0,[%1];" : "=r"(v) : "l"(cnt_ptr(C_QKV + X * 32 + (nxt >> 1))) : "memory");
                if (__all_sync(0xffffffffu, v >= 2 * NQ)) break;
                if (nxt > need) return;
                if (++n > 3000000) __trap();
            }
        }
        if (elect()) {
            const uint32_t bar = sb + R_BAR + (RB_XFULL + X * 2 + (nxt & 1)) * 8, dst = sb + R_SL + (X * 2 + (nxt & 1)) * SLOT;
            const uint4* src = g_qkv + (size_t)((X * 64 + nxt) * 32 + head) * 1536;
            mbar_expect(bar, 20480);
            bulk_g2s_mc(dst + rank * 8192, src + 512 + rank * 512, 8192, bar, POL_LAST);
            bulk_g2s(dst + SL_Q, src + (rank ^ X) * 256, 4096, bar, POL_LAST);
        }
        __syncwarp();
        nxt++;
    }
}

__device__ __forceinline__ void rec_attn(const Params& p, uint32_t sb, int X, int head, uint32_t rank) {
    const int lane = __shfl_sync(0xffffffffu, threadIdx.x & 31, threadIdx.x & 31), g = lane >> 2, c = lane & 3;
    const int mt = rank ^ X;
    const uint32_t dp = mapa(sb, rank ^ 1) - sb;
    int nxt = 0;
    rec_tiles(sb, X, head, rank, nxt, 1, 0);
#pragma unroll 1
    for (int s = 0; s < 64; s++) {
        const uint32_t so = sb + R_SL + (X * 2 + (s & 1)) * SLOT;
        while (nxt <= min(s + 1, 63)) {
            uint32_t ok;
            asm volatile("{.reg .pred p; mbarrier.test_wait.parity.shared::cta.b64 p,[%1],%2; selp.u32 %0,1,0,p;}" : "=r"(ok) : "r"(sb + R_BAR + (RB_GO + X * 2 + (s & 1)) * 8), "r"((s >> 1) & 1) : "memory");
            if (__any_sync(0xffffffffu, ok)) break;
            rec_tiles(sb, X, head, rank, nxt, s + 1, -1);
        }
        mbar_wait(sb + R_BAR + (RB_GO + X * 2 + (s & 1)) * 8, (s >> 1) & 1);
        if (elect()) asm volatile("cp.async.bulk.wait_group.read 0;" ::: "memory");
        __syncwarp();
        const uint32_t os = sb + R_OS + X * 4096 + (lane >> 4) * 1024 + (lane & 15) * 16;
        if (mt) xattn<1>(so + lane * 16, so + lane * 8, os, g, c); else xattn<0>(so + lane * 16, so + lane * 8, os, g, c);
        fence_async_smem();
        __syncwarp();
        const uint32_t svb = sb + R_BAR + (RB_SV + X * 2 + (s & 1)) * 8;
        if (elect()) {
            mbar_arrive(svb); mbar_arrive_cluster(svb + dp);
            const uint64_t pol = POL_N;
#pragma unroll
            for (int kb = 0; kb < 2; kb++)
                asm volatile("cp.async.bulk.global.shared::cta.bulk_group.L2::cache_hint [%0],[%1],%2,%3;" ::"l"(g_o + ((X * 32 + (s >> 1)) * 64 + head * 2 + kb) * 512 + ((s & 1) * 4 + mt * 2) * 64),
                             "r"(sb + R_OS + X * 4096 + kb * 2048), "r"(2048), "l"(pol) : "memory");
            asm volatile("cp.async.bulk.commit_group;" ::: "memory");
        }
        __syncwarp();
        if (s & 1) {
            if (elect()) { asm volatile("cp.async.bulk.wait_group 0;" ::: "memory"); red_relaxed(cnt_ptr(C_O + (X * 32 + (s >> 1)) * 4 + (head >> 3)), 1); }
            __syncwarp();
        }
        rec_tiles(sb, X, head, rank, nxt, min(s + 1, 63), s + 1);
        mbar_wait(svb, (s >> 1) & 1);
        rec_tiles(sb, X, head, rank, nxt, min(s + 2, 63), -1);
    }
}

__device__ __forceinline__ uint32_t timed_clear(unsigned* r, int lane) {
    uint32_t v = 0;
    const uint32_t t0 = clk32();
    asm volatile("{.reg .pred p; setp.eq.u32 p,%2,0; @p atom.relaxed.gpu.global.exch.b32 %0,[%1],0;}" : "+r"(v) : "l"(r), "r"(lane) : "memory");
    v = __shfl_sync(0xffffffffu, v, 0);
    asm volatile("{.reg .pred p; setp.eq.u32 p,%0,0x5a5a5a5b; @p nanosleep.u32 1;}" ::"r"(v) : "memory");
    return clk32() - t0;
}
__device__ __forceinline__ void rec_slots(int me, int w) {
    const int lane = threadIdx.x & 31;
    uint4* r = xregion(w & 1, (w & 2) ? 64 + (me & 1) : me) + ((w & 2) ? (me >> 1) * 8 : 0);
#pragma unroll 1
    for (int i = lane; i < ((w & 2) ? 8 : 256); i += 32) r[i] = r[i + 256] = make_uint4(0, 0, 0, 0);
    __syncwarp();
    uint32_t b0 = ~0u, b1 = ~0u;
#pragma unroll 1
    for (int i = 0; i < NPRB; i++) { b0 = min(b0, timed_clear((unsigned*)r, lane)); b1 = min(b1, timed_clear((unsigned*)(r + 256), lane)); }
    if (lane == 0) ((uint8_t*)g_sel)[me * 4 + w] = (b1 < b0) << w;
}

__device__ __forceinline__ void rec_init(uint32_t sb) {
    const uint32_t b = sb + R_BAR;
    const int i = threadIdx.x & 31;
    mbar_init(b + i * 8, i >= RB_SV ? 2 : 1);
    if (i == RB_INIT) mbar_expect(b + RB_INIT * 8, 196608);
    asm volatile("fence.mbarrier_init.release.cluster;" ::: "memory");
}
constexpr int G_BAR = B_BAR;
enum { GB_FULL = 0  , GB_EMPTY = 8  , GB_RS = 16, GB_SS = 17, GB_LAG = 18, GB_FREE = 19, GB_DONE = 20  , GB_N = 24 };
constexpr int Q_PRE = 8;
constexpr int NQRS = 2 * NQ - 64;
__device__ __forceinline__ void gemm_init(uint32_t sb, bool op) {
    const int i = threadIdx.x & 31;
    if (i < GB_N) mbar_init(sb + G_BAR + i * 8, i >= GB_DONE ? 4 : i == GB_FREE ? 8 : (i >= GB_EMPTY && i < GB_RS) ? 2 : 1);
    if (i == GB_RS) mbar_expect(sb + G_BAR + i * 8, op ? 131072 : 98304);
    if (i == GB_SS) mbar_expect(sb + G_BAR + i * 8, op ? 131072 : 163840);
    asm volatile("fence.mbarrier_init.release.cluster;" ::: "memory");
}
__device__ __forceinline__ int qkv_blk(int id, int j) { return NQRS * 4 + id * 10 + j; }
__device__ __forceinline__ void qkv_fetch(const Params& p, uint32_t sb, int id, int j0, int j1) {
#pragma unroll 1
    for (int j = j0 * 2; j < j1 * 2; j++) {
        const int blk = min(qkv_blk(id, j >> 1), 511);
        tma2d(sb + j * 8192, &p.tn[blk >> 8], (blk & 255) * 16, (j & 1) * 256, sb + G_BAR + GB_SS * 8);
    }
}
__device__ __forceinline__ void qkv_stage(const Params& p, uint32_t dst, uint32_t bar, int id, int k0, int nk) {
#pragma unroll 1
    for (int j = 0; j < 2 * nk; j++) {
        const int u = id * 2 + (j >= nk);
        tma2d(dst + j * 8192, &p.tm[u < 64 ? 2 : 0], (u & 63) * 64, (k0 + (j >= nk ? j - nk : j)) * 64, bar);
    }
}
__device__ __forceinline__ void op_fetch(const Params& p, uint32_t sb, int id, int half) {
#pragma unroll 1
    for (int j = 0; j < 16; j++) tma2d(sb + j * 8192, &p.tm[4], ((id * 2 + (j >> 3)) & 7) * 64, (id >> 2) * 1024 + (j & 7) * 128 + half * 64, sb + G_BAR + (GB_RS + half) * 8);
}
template <bool OP>
__device__ __forceinline__ void gemm_producer(const Params& p, uint32_t sb, int id) {
    constexpr int NS = OP ? 6 : 8, SB = OP ? 16384 : 8192, RB = OP ? 131072 : 163840;
    if (!elect()) return;
    mbar_wait(sb + G_BAR + GB_FREE * 8, 0);
    if (OP) op_fetch(p, sb, id, 1);
    else {
        mbar_expect(sb + G_BAR + GB_RS * 8, 32768);
        qkv_stage(p, sb + 196608, sb + G_BAR + GB_RS * 8, id, 6, 2);
        qkv_fetch(p, sb, id, Q_PRE, 10);
        mbar_wait(sb + G_BAR + GB_FREE * 8, 1);
    }
    wait_cnt(g_gate, lds32(sb + S_GATE));
    int st = 0; uint32_t ph = 1;
#pragma unroll 1
    for (int n = 0; n < p.nl[OP]; n++) {
        const int e = p.list[OP][n];
        wait_cnt(OP ? cnt_ptr(C_O + e * 4 + (id >> 2)) : cnt_ptr(C_XN + e), 16);
        PROF(true, 1024 + n * 4);
        const uint4* src = OP ? g_o + (e * 64 + (id >> 2) * 16) * 512 : g_xn + e * 4096;
#pragma unroll 1
        for (int s = 0; s < 8; s++) {
            mbar_wait(sb + G_BAR + (GB_EMPTY + st) * 8, ph);
            mbar_expect(sb + G_BAR + (GB_FULL + st) * 8, SB);
            bulk_g2s(sb + RB + st * SB, src + s * (SB / 16), SB, sb + G_BAR + (GB_FULL + st) * 8, POL_N);
            if (++st == NS) { st = 0; ph ^= 1; }
        }
    }
}
__device__ __forceinline__ void qkv_release(const Params& p, uint32_t sb) {
    if (!elect()) return;
#pragma unroll 1
    for (int n = 0; n < 2 * p.nl[0]; n++) {
        const int e = p.list[0][n >> 1];
        mbar_wait(sb + G_BAR + (GB_DONE + (n & 3)) * 8, (n >> 2) & 1);
        red_release(cnt_ptr(C_QKV + e), 1);
        PROF(n & 1, 1024 + (n >> 1) * 4 + 3);
    }
}
__device__ __forceinline__ void op_permute(uint32_t sb) {
#pragma unroll 2
    for (int i = threadIdx.x; i < 4096; i += 256) {
        const uint32_t a = sb + i * 32 + ((i >> 2) & 1) * 16, b = a ^ 16;
        const uint4 x = lds128(a), y = lds128(b);
        sts128(a, __byte_perm(x.x, x.y, 0x5410), __byte_perm(x.z, x.w, 0x5410), __byte_perm(y.x, y.y, 0x5410), __byte_perm(y.z, y.w, 0x5410));
        sts128(b, __byte_perm(x.x, x.y, 0x7632), __byte_perm(x.z, x.w, 0x7632), __byte_perm(y.x, y.y, 0x7632), __byte_perm(y.z, y.w, 0x7632));
    }
    fence_async_smem();
    bar_sync(1, 256);
}
template <bool OP>
__device__ __forceinline__ void gemm_consumer(const Params& p, uint32_t sb, int id, int w) {
    constexpr int NS = OP ? 6 : 8, SB = OP ? 16384 : 8192, RB = OP ? 131072 : 163840;
    const int lane = threadIdx.x & 31, wg = w >> 2, t = w & 3, u = id * 2 + wg;
    uint32_t a[128];
    mbar_wait(sb + G_BAR + GB_RS * 8, 0);
    PROF2(threadIdx.x == 0, 3501);
    if (OP) op_permute(sb);
    const uint32_t wo = sb + (((lane >> 4) << 3) + (lane & 7)) * 128 + (((2 * t + ((lane >> 3) & 1)) ^ (lane & 7)) << 4);
#pragma unroll
    for (int ks = 0; ks < 32; ks++) {
        const uint4 v = ldsm4t(wo + ks * 2048 + (OP ? wg * 65536 : ks < 24 ? 131072 + wg * 49152 : 196608 - 49152 + wg * 16384));
        a[ks * 4] = v.x; a[ks * 4 + 1] = v.y; a[ks * 4 + 2] = v.z; a[ks * 4 + 3] = v.w;
        if (ks == 31 || (!OP && ks == 23)) {
            fence_async_smem();
            __syncwarp();
            if (lane == 0) mbar_arrive(sb + G_BAR + GB_FREE * 8);
            if (ks == 23) mbar_wait(sb + G_BAR + GB_RS * 8, 1);
        }
    }
    PROF2(threadIdx.x == 0, 3502);
    mbar_wait(sb + G_BAR + GB_SS * 8, 0);
    if (OP) op_permute(sb);
    PROF2(threadIdx.x == 0, 3503);
    const uint32_t tag = OP ? lds32(sb + S_TAG) : 0;
    float c0[32], c1[OP ? 32 : 40];
    int st = 0; uint32_t ph = 0;
    const bool el = (threadIdx.x & 127) == 0;
#pragma unroll 1
    for (int n = 0; n < p.nl[OP]; n++) {
        int prev = 0;
        const uint32_t wb = sb + wg * (OP ? 65536 : 81920) + (n & p.zero);
        const uint64_t dw = OP ? mkdesc(wb, 0, 1024, 1) : mkdesc(wb, 16384, 256, 3);
        if ((!OP || OLAG) && wg) mbar_wait(sb + G_BAR + GB_LAG * 8, n & 1);
#pragma unroll
        for (int s = 0; s < 8; s++) {
            mbar_wait(sb + G_BAR + (GB_FULL + st) * 8, ph);
            const uint64_t dx = mkdesc(sb + RB + st * SB, 128, 1024, 0);
            wg_fence();
#pragma unroll
            for (int kk = 0; kk < 4; kk++) {
                const int ks = s * 4 + kk;
                if (ks == 0) { wgmma64_rs<0>(c0, a, dx); if (OP) wgmma64_ta<0>(c1, dw, dx + 512); else wgmma80_tb<0>(c1, dx, dw); }
                else { wgmma64_rs<1>(c0, a + ks * 4, dx + kk * 16); if (OP) wgmma64_ta<1>(c1, dw + ks * 128, dx + 512 + kk * 16); else wgmma80_tb<1>(c1, dx + kk * 16, dw + ks * 32); }
            }
            wg_commit();
            if (s) {
                wg_wait<1>();
                if (el) { mbar_arrive(sb + G_BAR + (GB_EMPTY + prev) * 8); if (s == (OP ? OLAG : QLAG) && !wg) mbar_arrive(sb + G_BAR + GB_LAG * 8); }
            }
            prev = st;
            if (++st == NS) { st = 0; ph ^= 1; }
        }
        const int e = p.list[OP][n];
        wg_wait<0>();
        if (el) mbar_arrive(sb + G_BAR + (GB_EMPTY + prev) * 8);
        PROF(threadIdx.x == 128, 1024 + n * 4 + 1);
        if (OP) {
            uint4* dst = g_pp + (e * 4 + (id >> 2)) * 4096 + ((u & 7) * 32 + t * 8) * 16 + (lane >> 2) * 16 + (lane & 3);
#pragma unroll
            for (int j = 0; j < 4; j++) {
                const float* x = c0 + j * 8; const float* y = c1 + j * 8;
                st_rlx128(dst + j * 4, (pack2(x[0] + y[0], x[1] + y[1]) & ~1u) | tag, pack2(x[2] + y[2], x[3] + y[3]), (pack2(x[4] + y[4], x[5] + y[5]) & ~1u) | tag, pack2(x[6] + y[6], x[7] + y[7]));
            }
            if (lane == 0) red_relaxed(cnt_ptr(C_PP + e * 8 + (u & 7)), 1);
            PROF(threadIdx.x == 128, 1024 + n * 4 + 3);
        } else {
            uint4* dst = g_qkv + (size_t)e * 2 * 32 * 1536 + lane;
            const uint64_t pol = POL_N;
#pragma unroll
            for (int j = 0; j < 4; j++) {
                const float* x = c0 + j * 8;
                uint4 v = make_uint4(pack2(x[0], x[1]), pack2(x[2], x[3]), pack2(x[4], x[5]), pack2(x[6], x[7]));
                if (u >= 64) v = make_uint4(movm(v.x), movm(v.z), movm(v.y), movm(v.w));
                stg128(dst + (((j >> 1) * 32 + ((u & 63) >> 1)) * 1536 + (u < 64 ? 1024 : 0) + (j & 1) * 256 + ((u & 1) * 4 + t) * 32), v, pol);
            }
#pragma unroll
            for (int j = 0; j < 5; j++) {
                const float* x = c1 + (OP ? 0 : j * 8);
                const int blk = qkv_blk(id, wg * 5 + j);
                if (blk < 512) stg128(dst + (((t >> 1) * 32 + ((blk >> 3) & 31)) * 1536 + (blk >> 8) * 512 + (t & 1) * 256 + (blk & 7) * 32),
                                      make_uint4(pack2(x[0], x[1]), pack2(x[2], x[3]), pack2(x[4], x[5]), pack2(x[6], x[7])), pol);
            }
        }
        __syncwarp();
        if (!OP && lane == 0) mbar_arrive(sb + G_BAR + (GB_DONE + (n & 1) * 2 + wg) * 8);
        PROF(threadIdx.x == 128, 1024 + n * 4 + 2);
    }
}

template <int NP, bool MMA>
__device__ __forceinline__ void sum_partials(float* x, const uint2* src, const uint32_t* r0, const uint32_t* r1, uint32_t idm, uint32_t tag, bool on) {
    uint2 v[4][NP];
    int n = 0;
    while (true) {
        uint32_t bad = 0;
#pragma unroll
        for (int s = 0; s < 4; s++)
#pragma unroll
            for (int i = 0; i < NP; i++)
                asm volatile("{.reg .pred p; .reg .b64 t; setp.ne.u32 p,%4,0; mov.b64 t,0; @p ld.relaxed.gpu.global.L2::cache_hint.b64 t,[%2],%3; mov.b64 {%0,%1},t;}"
                             : "=r"(v[s][i].x), "=r"(v[s][i].y) : "l"(src + s * 8192 + i * 32), "l"(POL_LAST), "r"((uint32_t)on) : "memory");
#pragma unroll
        for (int s = 0; s < 4; s++) bad = or3(bad, mism(v[s][0].x, v[s][1].x, tag), mism(v[s][NP - 2].x, v[s][NP - 1].x, tag));
        if (!__any_sync(0xffffffffu, (bad & 1) && on)) break;
        if (++n > 2000000) __trap();
    }
#pragma unroll
    for (int i = 0; i < NP; i++) {
        uint32_t a, b;
        if (MMA) {
            float t[4] = {0, 0, 0, 0};
            mma16(t, v[0][i].x, v[0][i].y, v[1][i].x, v[1][i].y, idm, idm); mma16(t, v[2][i].x, v[2][i].y, v[3][i].x, v[3][i].y, idm, idm);
            a = pack2(t[0], t[2]); b = pack2(t[1], t[3]);
        } else {
            a = pack2((blo(v[0][i].x) + blo(v[1][i].x)) + (blo(v[2][i].x) + blo(v[3][i].x)), (blo(v[0][i].y) + blo(v[1][i].y)) + (blo(v[2][i].y) + blo(v[3][i].y)));
            b = pack2((bhi(v[0][i].x) + bhi(v[1][i].x)) + (bhi(v[2][i].x) + bhi(v[3][i].x)), (bhi(v[0][i].y) + bhi(v[1][i].y)) + (bhi(v[2][i].y) + bhi(v[3][i].y)));
        }
        const uint32_t s0 = hadd2(a, r0[i]), s1 = hadd2(b, r1[i]);
        x[4 * i] = blo(s0); x[4 * i + 2] = bhi(s0); x[4 * i + 1] = blo(s1); x[4 * i + 3] = bhi(s1);
    }
}
__device__ __forceinline__ const uint2* pp_src(int e, int tile, int lane) { return (const uint2*)g_pp + e * 32768 + tile * 128 + (lane >> 3) * 8 + (lane & 3) * 2 + ((lane >> 2) & 1); }

__device__ __forceinline__ void fin_warp(const Params& p, uint32_t sb, int id0) {
    wait_slow_warp(g_gate, lds32(sb + S_GATE));
#pragma unroll 1
    for (int e = id0 < 2 * NQ ? 32 : FJ; e < 64; e++)
#pragma unroll 1
    for (int id = id0; id < (e < FJ ? 128 : id0 + 1); id += 2 * NQ) {
        const int grp = (id & ~3) + (threadIdx.x & 3), tp = (id & 3) * 8 + ((threadIdx.x & 31) >> 2);
        wait_slow_warp(cnt_ptr(C_XN + e), 16);
        const uint4 r = ldcg128(g_x + ((128 + grp) * XP + (e - 32) * 32 + tp));
        if (e < 63) wait_slow_warp(cnt_ptr(C_PP + e * 8 + (id >> 4)), 16); else wait_slow_warp(cnt_ptr(C_O + 63 * 4), 16);
        wait_flag_warp(cnt_ptr(C_PP + e * 8 + (id >> 4)), 16);
        const uint32_t a[2] = {r.x, r.y}, b[2] = {r.z, r.w};
        float x[8];
        sum_partials<2, false>(x, pp_src(e, 0, tp) + grp * 64, a, b, 0, lds32(sb + S_TAG), true);
        uint2* dst = (uint2*)p.out + ((e - 32) * 64 + tp * 2) * 128 + grp;
#pragma unroll
        for (int t = 0; t < 2; t++)
            dst[t * 128] = make_uint2(__byte_perm(__float_as_uint(x[t]), __float_as_uint(x[2 + t]), 0x7632), __byte_perm(__float_as_uint(x[4 + t]), __float_as_uint(x[6 + t]), 0x7632));
        PROF((threadIdx.x & 31) == 0, 1536 + e);
    }
}

constexpr int PROW = 272, UROW = 2560, UPRE = 512;
constexpr int C_UR = 0  , C_TB = 65536  , C_BG = C_TB + 51200,
              CB_M = 7168, CB_U = CB_M + 1792, CB_BIG = CB_U + 2048, C_ST = C_BG + 8 * CB_BIG  ;
static_assert(C_ST + 4736 <= B_BAR, "smem map");
enum { CB_TB = 0, CB_UF = 1  , CB_CF = 5  , CB_LD = 9   };
__device__ __forceinline__ void conv_init(uint32_t sb, bool spare) {
    const int i = threadIdx.x & 31;
    mbar_init(sb + B_BAR + i * 8, (i >= CB_UF && i < CB_CF && !spare) ? 2 : 1);
    if (i == CB_TB && !spare) mbar_expect(sb + B_BAR + i * 8, 51200);
    asm volatile("fence.mbarrier_init.release.cluster;" ::: "memory");
}
__device__ __forceinline__ void mma_q(float* c, const uint32_t* a, const uint4& q) {
    mma16(c, a[0], a[1], a[2], a[3], q.x, q.y); mma16(c, a[4], a[5], a[6], a[7], q.z, q.w);
}
__device__ __forceinline__ uint2 ld_acc(const uint2* p, bool on) {
    uint2 v = make_uint2(0, 0);
    asm volatile("{.reg .pred p; setp.ne.u32 p,%3,0; @p ld.global.cg.v2.u32 {%0,%1},[%2];}" : "+r"(v.x), "+r"(v.y) : "l"(p), "r"((uint32_t)on) : "memory");
    return v;
}
__device__ __forceinline__ void add_acc(float* c, uint2 v) { c[0] += blo(v.x); c[1] += bhi(v.x); c[2] += blo(v.y); c[3] += bhi(v.y); }
__device__ __forceinline__ void st_acc(uint2* p, const float* c) { *p = make_uint2(pack2(c[0], c[1]), pack2(c[2], c[3])); }
__device__ __forceinline__ float sum8(const uint4* v, int k) {
#define VK(i) __uint_as_float(k == 0 ? v[i].x : k == 1 ? v[i].y : k == 2 ? v[i].z : v[i].w)
    return ((VK(0) + VK(1)) + (VK(2) + VK(3))) + ((VK(4) + VK(5)) + (VK(6) + VK(7)));
}
template <int XW>
__device__ __forceinline__ void stats_send(uint32_t l16, const float* x, uint4* gs, int q, int w) {
    float s0 = 0, s1 = 0, m0 = 0, m1 = 0;
#pragma unroll
    for (int i = 0; i < 8; i++) { s0 += x[2 * i]; s1 += x[2 * i + 1]; m0 = fmaf(x[2 * i], x[2 * i], m0); m1 = fmaf(x[2 * i + 1], x[2 * i + 1], m1); }
    sts128(l16 + C_ST + w * 512, __float_as_uint(s0), __float_as_uint(m0), __float_as_uint(s1), __float_as_uint(m1));
    if (w == XW) {
        bar_sync(2, 256);
        uint4 v[8];
#pragma unroll
        for (int i = 0; i < 8; i++) v[i] = lds128(l16 + C_ST + i * 512);
        st_rlx128(gs + q * 32, __float_as_uint(sum8(v, 0)), __float_as_uint(sum8(v, 1)) & 0x7fffffffu, __float_as_uint(sum8(v, 2)), __float_as_uint(sum8(v, 3)));
    } else bar_arrive(2, 256);
}
template <int XW>
__device__ __forceinline__ float4 stats_recv(uint32_t l16, const uint4* gs, int w) {
    if (w == XW) {
        uint4 v[8];
        int n = 0;
        while (true) {
            uint32_t bad = 0;
#pragma unroll
            for (int i = 0; i < 8; i++) v[i] = ld_rlx128(gs + i * 32);
#pragma unroll
            for (int i = 0; i < 8; i++) bad |= v[i].y;
            if (!__any_sync(0xffffffffu, bad >> 31)) break;
            if (++n > 2000000) __trap();
        }
        const float s0 = sum8(v, 0) * (1.f / 512.f), s1 = sum8(v, 2) * (1.f / 512.f);
        const float2 l0 = ln_finish(s0, fmaxf(fmaf(sum8(v, 1), 1.f / 512.f, -s0 * s0), 0.f)), l1 = ln_finish(s1, fmaxf(fmaf(sum8(v, 3), 1.f / 512.f, -s1 * s1), 0.f));
        sts128(l16 + C_ST + 4096, __float_as_uint(l0.x), __float_as_uint(rcp(l0.y)), __float_as_uint(l1.x), __float_as_uint(rcp(l1.y)));
    }
    bar_sync(3, 256);
    const uint4 r = lds128(l16 + C_ST + 4096);
    return make_float4(__uint_as_float(r.x), __uint_as_float(r.y), __uint_as_float(r.z), __uint_as_float(r.w));
}

__device__ __forceinline__ void conv_near(float (*acc)[4], uint32_t ta, uint32_t qa) {
    uint32_t a[9][8];
    uint4 x[9];
#pragma unroll
    for (int k = 0; k < 9; k++) {
        if (k < 8) {
            x[k] = ldsm4(qa + k * 1024);
#pragma unroll
            for (int j = 0; j < 8; j++) a[k][j] = lds32(ta + k * 800 + j * 32);
        }
        if (k) mma_q(acc[k - 1], a[k - 1], x[k - 1]);
        PIN(13);
    }
}
template <int K0>
__device__ __forceinline__ void conv_pair(float (*acc)[4], float (*pend)[4], uint32_t ta, uint32_t q0, uint32_t q1, uint32_t q2) {
    uint32_t a[9][8];
    uint4 x[9], y[5];
#pragma unroll
    for (int n = 0; n < 9; n++) {
        if (n < 8) {
            const int k = K0 + (n >> 1);
            if (!(n & 1)) y[n >> 1] = ldsm4(q1 + k * 1024);
            x[n] = ldsm4(((n & 1) ? q0 : q2) + k * 1024);
#pragma unroll
            for (int j = 0; j < 8; j++) a[n][j] = lds32(ta + 256 + (n & 1) * 256 + k * 800 + j * 32);
        }
        if (n == 0) {
#pragma unroll
            for (int i = 0; i < 16; i++) { acc[4 - K0 + (i >> 2)][i & 3] += pend[i >> 2][i & 3]; pend[i >> 2][i & 3] = 0; }
        } else {
            const int m = n - 1, i = m >> 1;
            mma_q(acc[K0 + i], a[m], (m & 1) ? x[m] : y[i]); mma_q(pend[i], a[m], (m & 1) ? y[i] : x[m]);
        }
        PIN(13);
    }
}

__device__ __forceinline__ void conv_tile(const Params& p, uint32_t sb, int q, int w) {
    const int lane = __shfl_sync(0xffffffffu, threadIdx.x & 31, threadIdx.x & 31), g = lane >> 2, c = lane & 3, tile = q * 8 + w;
    const uint32_t l16 = sb + lane * 16;
#pragma unroll
    for (int i = 0; i < 16; i++) sts128(l16 + C_UR + w * 8192 + i * 512, 0, 0, 0, 0);
    wait_slow_warp(g_gate, lds32(sb + S_GATE));
    if (lane < 8) bulk_g2s(sb + C_TB + (w * 8 + lane) * 800, g_P + (tile * 8 + lane) * PROW + 72, 800, sb + B_BAR + CB_TB * 8, POL_N);
    uint32_t A[8][8];
#pragma unroll
    for (int k = 0; k < 8; k++)
#pragma unroll
        for (int j = 0; j < 8; j++) A[k][j] = __ldcg(g_P + (tile * 8 + k) * PROW + 16 + 8 * j + g - 2 * c);
    if (lane == 0) { const uint4 d = __ldg((const uint4*)p.Dskip + tile); sts128(sb + C_ST + 4608 + w * 16, d.x, d.y, d.z, d.w); }
    float acc[8][4], pend[4][4];
#pragma unroll
    for (int k = 0; k < 8; k++) acc[k][0] = acc[k][1] = acc[k][2] = acc[k][3] = pend[k & 3][k >> 2] = pend[k & 3][2 + (k >> 2)] = 0;
    const uint32_t row = sb + C_UR + w * 8192, ta = sb + C_TB + w * 6400 + (8 + g - 2 * c) * 4, qo = (lane & 7) * 16 - (lane >> 3) * 32;
    bar_sync(4, 384);
    mbar_wait(sb + B_BAR + CB_TB * 8, 0);
#pragma unroll 1
    for (int b = -2; b < 32; b++) {
        const int lz = lane + (b & p.zero);
        const bool on = b >= 0;
        uint4 r0 = make_uint4(0, 0, 0, 0), r1 = r0;
        asm volatile("{.reg .pred p; setp.ge.s32 p,%9,0; @p ld.global.cg.v4.u32 {%0,%1,%2,%3},[%8]; @p ld.global.cg.v4.u32 {%4,%5,%6,%7},[%8+%10];}"
                     : "+r"(r0.x), "+r"(r0.y), "+r"(r0.z), "+r"(r0.w), "+r"(r1.x), "+r"(r1.y), "+r"(r1.z), "+r"(r1.w) : "l"(g_x + (tile * 2 * XP + b * 32 + lz)), "r"(b), "n"(XP * 16) : "memory");
        const uint32_t q1 = row + ((qo + (b - 1) * 128) & 1023);
        if ((NTOP >> w) & 1) conv_near(acc, ta, q1);
        PROF2(threadIdx.x == 0 && on, 2048 + b * 8);
        const uint2* pps = pp_src(b, tile, lz);
        asm volatile("" : "+l"(pps));
        const uint32_t tag = lds32(sb + S_TAG);
        wait_flag_warp(cnt_ptr(C_PP + b * 8 + q), on ? 16 : 0);
        PROF2(threadIdx.x == 0 && on, 2048 + b * 8 + 1);
        float x[16];
        {
            const uint32_t a[4] = {r0.x, r0.y, r1.x, r1.y}, bb[4] = {r0.z, r0.w, r1.z, r1.w};
            sum_partials<4, true>(x, pps, a, bb, (2 * (lz & 3) == lz >> 2) ? 0x00003f80u : (2 * (lz & 3) + 1 == lz >> 2) ? 0x3f800000u : 0u, tag, on);
        }
        stats_send<0>(l16, x, g_st + (b + 2) * 256 + lz, q, w);
        {
            PROF2(threadIdx.x == 0 && on, 2048 + b * 8 + 2);
            if (on) mbar_wait(sb + B_BAR + (CB_CF + (w >> 1)) * 8, b & 1);
            const uint2* cb = g_carry + ((tile * 320 + b) * 32 + lz);
            uint2 cr[8];
#pragma unroll
            for (int k = 0; k < 8; k++) cr[k] = ld_acc(cb + k * 1280, b >= 4);
            if (NTOP != 255 && !((NTOP >> w) & 1) && b) conv_near(acc, ta, q1);
#pragma unroll
            for (int k = 0; k < 8; k++) add_acc(acc[k], cr[k]);
        }
        PIN(13);
        float4 ln = stats_recv<0>(l16, g_st + (b + 2) * 256 + lz, w);
        PROF2(threadIdx.x == 0 && on, 2048 + b * 8 + 3);
        uint32_t u[8];
#pragma unroll
        for (int k = 0; k < 8; k++) {
            u[k] = pack2(rbf(x[2 * k] - ln.x) * ln.y, rbf(x[2 * k + 1] - ln.z) * ln.w);
            sts32(row + k * 1024 + (b & 7) * 128 + lane * 4, u[k]);
        }
        __syncwarp();
        const uint32_t qa = row + ((qo + b * 128) & 1023);
        {
            uint4 xq[8];
#pragma unroll
            for (int k = 0; k < 4; k++) xq[k] = ldsm4(qa + k * 1024);
#pragma unroll
            for (int k = 0; k < 8; k += 2) {
                PIN(13);
                mma_q(acc[k], A[k], xq[k]); mma_q(acc[k + 1], A[k + 1], xq[k + 1]);
                if (k < 4) { xq[k + 4] = ldsm4(qa + (k + 4) * 1024); xq[k + 5] = ldsm4(qa + (k + 5) * 1024); }
            }
        }
        const uint4 dk = lds128(sb + C_ST + 4608 + w * 16);
#pragma unroll
        for (int k = 0; k < 8; k++) {
            const float t = __shfl_sync(0xffffffffu, acc[k][3], (lz & ~3) | ((lz - 1) & 3));
            const uint32_t y = movm(pack2(acc[k][0] + (c ? t : 0.f), acc[k][1] + acc[k][2]));
            acc[k][0] = c ? 0.f : t; acc[k][1] = acc[k][2] = acc[k][3] = 0;
            const uint32_t dw = k >> 1 == 0 ? dk.x : k >> 1 == 1 ? dk.y : k >> 1 == 2 ? dk.z : dk.w;
            const uint32_t s = hadd2(hadd2(y, hmul2(u[k], __byte_perm(dw, 0, (k & 1) ? 0x3232 : 0x1010))), __byte_perm(__float_as_uint(x[2 * k]), __float_as_uint(x[2 * k + 1]), 0x7632));
            x[2 * k] = blo(s); x[2 * k + 1] = bhi(s);
        }
        arrive_if(sb + B_BAR + (CB_UF + (w >> 1)) * 8, lz, b < -1 ? 32 : 0);
        stats_send<1>(l16, x, g_st + (36 + b) * 256 + lz, q, w);
        {
            PROF2(threadIdx.x == 0 && on, 2048 + b * 8 + 4);
            uint4* dst = g_x + ((128 + tile * 2) * XP + b * 32 + lz);
#pragma unroll
            for (int e = 0; e < 2; e++) {
                const float* y = x + e * 8;
                if (on) dst[e * XP] = make_uint4(__byte_perm(__float_as_uint(y[0]), __float_as_uint(y[2]), 0x7632), __byte_perm(__float_as_uint(y[4]), __float_as_uint(y[6]), 0x7632),
                                           __byte_perm(__float_as_uint(y[1]), __float_as_uint(y[3]), 0x7632), __byte_perm(__float_as_uint(y[5]), __float_as_uint(y[7]), 0x7632));
            }
            uint32_t* du = g_u + (tile * 8 * (UROW / 2) + UPRE / 2 + b * 32 + lz);
#pragma unroll
            for (int k = 0; k < 8; k++) if (on) du[k * (UROW / 2)] = u[k];
        }
#pragma unroll 1
        for (int pass = 0; pass < 2; pass++) {
            if (pass == ((PLATE >> w) & 1)) {
                const uint32_t q0 = row + ((qo + (b - 2) * 128) & 1023);
                if (b & 1) conv_pair<4>(acc, pend, ta, q0, q1, qa); else conv_pair<0>(acc, pend, ta, q0, q1, qa);
            }
            if (pass) break;
            ln = stats_recv<1>(l16, g_st + (36 + b) * 256 + lz, w);
            PROF2(threadIdx.x == 0 && on, 2048 + b * 8 + 5);
            uint32_t o[2][4];
#pragma unroll
            for (int e = 0; e < 2; e++) {
                const float mu = e ? ln.z : ln.x, rs = e ? ln.w : ln.y;
#pragma unroll
                for (int i = 0; i < 4; i++) o[e][i] = pack2(rbf(x[4 * i + e] - mu) * rs, rbf(x[4 * i + 2 + e] - mu) * rs);
            }
#pragma unroll
            for (int i = 0; i < 4; i++) {
                const uint32_t t = __shfl_xor_sync(0xffffffffu, (lz & 1) ? o[0][i] : o[1][i], 1);
                if (lz & 1) o[0][i] = t; else o[1][i] = t;
            }
            uint4* dst = g_xn + ((32 + b) * 4096 + q * 512 + (lz >> 2) * 64 + w * 8 + (lz & 2) * 2 + (lz & 1));
            if (on) { dst[0] = make_uint4(o[0][0], o[0][1], o[0][2], o[0][3]); dst[2] = make_uint4(o[1][0], o[1][1], o[1][2], o[1][3]); }
            if (w == 7) {
                bar_sync(5, 256);
                if (elect()) red_release(cnt_ptr(on ? C_XN + 32 + b : C_FAR + 8), 2);
                PROF(lane == 0 && on, 2048 + b * 8 + 6);
                __syncwarp();
            } else bar_arrive(5, 256);
        }
    }
}

template <int P0, bool TRI = false, int R0 = 0>
__device__ __forceinline__ void bg_half(float (*acc)[4], uint4* win, uint32_t ta, uint32_t qa, uint32_t mask, uint32_t row) {
#pragma unroll
    for (int i = 0; i < 4; i++) {
        win[P0 + i] = ldsm4(((qa + i * 128) & mask) + row);
        const uint4 a = lds128(ta + (3 - i) * 448), e = lds128(ta + (3 - i) * 448 + 224);
#pragma unroll
        for (int r = TRI ? 7 - P0 - i : R0; r < 8; r++) mma16(acc[r], a.x, a.y, a.z, a.w, win[(P0 + i + 1 + r) & 7].x, win[(P0 + i + 1 + r) & 7].y);
#pragma unroll
        for (int r = TRI ? 7 - P0 - i : R0; r < 8; r++) mma16(acc[r], e.x, e.y, e.z, e.w, win[(P0 + i + 1 + r) & 7].z, win[(P0 + i + 1 + r) & 7].w);
    }
}
__device__ __forceinline__ void bg_fetch(uint32_t sb, int q, int j, int n) {
    const int b0 = n >> 1, ch = q * 64 + j * 16 + (n & 1) * 8 + (b0 & 7), skip = max(12 - b0, 0);
    const uint32_t bar = sb + B_BAR + (CB_LD + j * 2 + (n & 1)) * 8, buf = sb + C_BG + (j * 2 + (n & 1)) * CB_BIG;
    if (elect()) {
        mbar_expect(bar, CB_BIG - skip * 128);
        bulk_g2s(buf, g_W + ch * 784, CB_M, bar, POL_N);
        bulk_g2s(buf + CB_M, g_W + (ch ^ 4) * 784, 1792, bar, POL_N);
        bulk_g2s(buf + CB_U + skip * 128, g_u + ch * (UROW / 2) + UPRE / 2 + (b0 - 20 + skip) * 32, 2048 - skip * 128, bar, POL_N);
    }
    __syncwarp();
}
__device__ __forceinline__ void conv_back(uint32_t sb, int q, int j) {
    const int lane = __shfl_sync(0xffffffffu, threadIdx.x & 31, threadIdx.x & 31), g = lane >> 2, c = lane & 3;
    wait_slow_warp(g_gate, lds32(sb + S_GATE));
    bg_fetch(sb, q, j, 0);
    bar_sync(4, 384);
    const uint32_t to = (6 + g - 2 * c) * 16, qo = (lane & 7) * 16 - (lane >> 3) * 32;
#pragma unroll 1
    for (int n = 0; n < 64; n++) {
        const int b0 = n >> 1, i = n & 1, chl = j * 16 + i * 8 + (b0 & 7);
        const uint32_t buf = sb + C_BG + (j * 2 + i) * CB_BIG, ta = buf + to;
        float acc[8][4];
        uint4 win[8];
        if (n < 63) bg_fetch(sb, q, j, n + 1);
        if (b0 >= 17 && b0 < 29 && (b0 < 21 || b0 >= 25) && i == 0) wait_flag_warp(cnt_ptr(C_FAR + (b0 >= 25) * 4 + ((b0 - 1) & 3)), 12);
        uint2* cr = g_carry + (((q * 64 + chl) * 40 + b0) * 32 + lane);
        uint2* cm = g_carry + (((q * 64 + (chl ^ 4)) * 40 + b0) * 32 + lane);
        uint2 pm[4], pf[8];
#pragma unroll
        for (int r = 0; r < 4; r++) pm[r] = ld_acc(cm + r * 32, b0 > 4);
#pragma unroll
        for (int r = 0; r < 8; r++) acc[r][0] = acc[r][1] = acc[r][2] = acc[r][3] = 0;
        mbar_wait(sb + B_BAR + (CB_LD + j * 2 + i) * 8, b0 & 1);
        if (b0 > 12) {
#pragma unroll
            for (int r = 1; r < 8; r++) win[(r + 4) & 7] = ldsm4(buf + CB_U + qo + r * 128);
        } else {
#pragma unroll
            for (int r = 1; r < 8; r++) win[(r + 4) & 7] = make_uint4(0, 0, 0, 0);
        }
        win[4] = make_uint4(0, 0, 0, 0);
#pragma unroll 1
        for (int h = b0 > 8 ? 4 : 2; h >= 2; h -= 2) {
            if (h == 2) {
                if (b0 > 4) bg_half<0>(acc, win, ta + 2 * 1792, qo + 12 * 128, ~0u, buf + CB_U);
                if (i == 0) mbar_wait(sb + B_BAR + (CB_UF + j) * 8, b0 & 1);
            }
            bg_half<4>(acc, win, ta + (h - 1) * 1792, qo + (h == 2 ? b0 - 4 : 8) * 128, h == 2 ? 1023u : ~0u, h == 2 ? sb + C_UR + chl * 1024 : buf + CB_U);
        }
        uint4 wm[8], a[9], e[9];
#pragma unroll
        for (int r = 1; r < 8; r++) wm[r] = ldsm4(sb + C_UR + (chl ^ 4) * 1024 + ((qo + (b0 + r) * 128) & 1023));
        a[7] = lds128(ta + 7 * 224); e[7] = lds128(ta + CB_M + 7 * 224);
#pragma unroll
        for (int r = 4; r < 8; r++) { st_acc(cr + r * 32, acc[r]); acc[r][0] = blo(pm[r - 4].x); acc[r][1] = bhi(pm[r - 4].x); acc[r][2] = blo(pm[r - 4].y); acc[r][3] = bhi(pm[r - 4].y); }
#pragma unroll
        for (int t = 7; t >= 0; t--) {
            if (t) { a[t - 1] = lds128(ta + (t - 1) * 224); e[t - 1] = lds128(ta + CB_M + (t - 1) * 224); }
            if (t == FT) {
                const uint2* f0 = g_far + (((q * 64 + chl) * 12 + b0 - 20) * 32 + lane);
                const uint2* f1 = g_far + (((q * 64 + (chl ^ 4)) * 12 + b0 - 20) * 32 + lane);
#pragma unroll
                for (int r = 0; r < 4; r++) { const bool on = (unsigned)(b0 + r - 20) < 12u; pf[r] = ld_acc(f0 + r * 32, on); pf[4 + r] = ld_acc(f1 + r * 32, on); }
            }
            PIN(14);
#pragma unroll
            for (int r = 0; r < 4; r++) { const uint4& x = win[4 + r - (t >> 1)]; mma16(acc[r], a[t].x, a[t].y, a[t].z, a[t].w, (t & 1) ? x.z : x.x, (t & 1) ? x.w : x.y); }
#pragma unroll
            for (int r = 0; r < 4; r++) { const uint4& x = wm[4 + r - (t >> 1)]; mma16(acc[4 + r], e[t].x, e[t].y, e[t].z, e[t].w, (t & 1) ? x.z : x.x, (t & 1) ? x.w : x.y); }
        }
#pragma unroll
        for (int r = 0; r < 4; r++) { add_acc(acc[r], pf[r]); add_acc(acc[4 + r], pf[4 + r]); st_acc(cr + r * 32, acc[r]); st_acc(cm + r * 32, acc[4 + r]); }
        __syncwarp();
        arrive_if(sb + B_BAR + (CB_CF + j) * 8, lane, i ? 0 : 32);
        PROF(j == 0 && lane == 0 && i, 2048 + b0 * 8 + 7);
    }
}
template <int PART>
__device__ __forceinline__ void conv_far(uint32_t sb, int w) {
    constexpr int NT = PART ? 5376 : 3584, NU = PART ? 1664 : 1152;
    const int lane = __shfl_sync(0xffffffffu, threadIdx.x & 31, threadIdx.x & 31), g = lane >> 2, c = lane & 3;
    wait_slow_warp(cnt_ptr(C_XN + (PART ? 43 : 39)), 16);
    const uint32_t to = (6 + g - 2 * c) * 16, qo = (lane & 7) * 16 - (lane >> 3) * 32;
#pragma unroll 1
    for (int n = -1; n < 44; n++) {
        const int t = n * 12 + w, tn = min(t + 12, 511), ch = (t & 127) * 4 + (((t >> 7) + 1) & 3), cn = (tn & 127) * 4 + (((tn >> 7) + 1) & 3);
        const uint32_t bar = sb + B_BAR + (w * 2 + (n & 1)) * 8, buf = sb + (w * 2 + (n & 1)) * 7168;
        if (n < 43 && elect()) {
            const uint32_t nb = sb + (w * 2 + (~n & 1)) * 7168;
            mbar_expect(bar ^ 8, NT + NU);
            bulk_g2s(nb, g_W + cn * 784 + 448, NT, bar ^ 8, POL_N);
            bulk_g2s(nb + 5376, g_u + cn * (UROW / 2) + UPRE / 2 - 32, NU, bar ^ 8, POL_N);
        }
        __syncwarp();
        if (n < 0) continue;
        mbar_wait(bar, (n >> 1) & 1);
        if (t >= 512) continue;
        float acc[8][4];
        uint4 win[8];
#pragma unroll
        for (int r = 0; r < 8; r++) acc[r][0] = acc[r][1] = acc[r][2] = acc[r][3] = 0;
        bg_half<0, true, PART * 4>(acc, win, buf + to + NT - 1792, qo + 128, ~0u, buf + 5376);
        bg_half<4, !PART, PART * 4>(acc, win, buf + to + NT - 3584, qo + 640, ~0u, buf + 5376);
        if (PART) bg_half<0, false, 4>(acc, win, buf + to, qo + 1152, ~0u, buf + 5376);
#pragma unroll
        for (int r = PART * 4; r < 8; r++) st_acc(g_far + (ch * 384 + lane) + (r + PART * 4) * 32, acc[r]);
        __syncwarp();
        if (((t + 12) ^ t) >= 128 && elect()) red_release(cnt_ptr(C_FAR + PART * 4 + (t >> 7)), 1);
        __syncwarp();
    }
    PROF(threadIdx.x == 0, 2048 + PART);
}

constexpr int P_X = 131072  , P_K6 = P_X + 32768  , P_P = P_K6 + 10496  , P_U = P_P + 33280  ,
              P_END = P_U + 17408, P_PRM = P_P  , P_Y = P_P  ;
static_assert(P_END <= B_BAR && P_END <= R_SEL, "prologue scratch");
#define KGUN 2
constexpr int KGU = KGUN;
__device__ __forceinline__ void csq(float& r, float& i) { const float t = r * i; r = fmaf(r, r, -(i * i)); i = t + t; }
__device__ __forceinline__ void cpow(float ar, float ph, float p, float& r, float& i) {
    const float e = ex2(ar * p);
    const float u = ph * p, n = (u + 12582912.f) - 12582912.f;
    const float t = (u - n) * 6.283185307179586f;
    r = e * __cosf(t); i = e * __sinf(t);
}
__device__ __forceinline__ void mma_tf32(float* c, float a0, float a1, float a2, float a3, float b0, float b1) {
    asm volatile("mma.sync.aligned.m16n8k8.row.col.f32.tf32.tf32.f32 {%0,%1,%2,%3},{%4,%5,%6,%7},{%8,%9},{%0,%1,%2,%3};"
                 : "+f"(c[0]), "+f"(c[1]), "+f"(c[2]), "+f"(c[3])
                 : "r"(__float_as_uint(a0)), "r"(__float_as_uint(a1)), "r"(__float_as_uint(a2)), "r"(__float_as_uint(a3)), "r"(__float_as_uint(b0)), "r"(__float_as_uint(b1)));
}

__device__ __forceinline__ void early_fetch(const Params& p, uint32_t sb) {
    const int v = blockIdx.x;
    if (elect()) {
        if (v >= V_QKV) { if (v < V_QKV + NQ && (p.roles & 8)) qkv_fetch(p, sb, v - V_QKV, 0, Q_PRE); }
        else if (v >= V_OP) { if (p.roles & 4) op_fetch(p, sb, v - V_OP, 0); }
        else if (v >= V_REC && (p.roles & 2)) { rec_fetch(p, sb, (v - V_REC) >> 1, v & 1, 0, R_STQ); rec_fetch(p, sb, (v - V_REC) >> 1, v & 1, 2, R_STV); }
    }
    __syncwarp();
}
struct ProRegs { uint32_t v[2][4], ldt[2]; };
__device__ __forceinline__ void prologue_load(const ProArgs& a, int b, ProRegs& pr) {
    const int w = threadIdx.x >> 5;
#pragma unroll
    for (int i = 0; i < 2; i++) {
        const int gi = b * 512 + (w & 3) * 128 + ((w >> 2) & 1) * 64 + i * 32 + (threadIdx.x & 31);
        pr.ldt[i] = __ldg((const uint16_t*)a.ldt + b * 4 + (w & 3));
        pr.v[i][0] = __ldg((const uint16_t*)a.lAr + gi); pr.v[i][1] = __ldg((const uint16_t*)a.Ai + gi);
        pr.v[i][2] = __ldg((const uint16_t*)a.Cr + gi); pr.v[i][3] = __ldg((const uint16_t*)a.Ci + gi);
    }
}
__device__ __forceinline__ void prologue(const Params& p, uint32_t sb, int b, int w, const ProRegs& pr) {
    const ProArgs& a = p.pa;
    const int tid = threadIdx.x, lane = tid & 31, g = lane >> 2, c = lane & 3;
    const int d0 = b * 4;
    if (w >= 8) {
        const int t2 = tid - 256;
        if (w < 10) {
            const int row = b * 16 + (w - 8) * 8 + g;
            uint4 v[16];
            const float2 r = row_stats512(v, (const uint4*)(a.x + (size_t)row * 512) + c, 8, 4);
            const float2 l = ln_finish(r.x * (1.f / 512.f), r.y * (1.f / 512.f));
            if (c == (g >> 1)) asm volatile("st.relaxed.gpu.global.u32 [%0],%1;" ::"l"(g_ln0 + row), "r"(pack2(l.x, l.y)) : "memory");
            __syncwarp();
        }
        if (b + 4 >= V_REC && b + 4 < V_OP) rec_slots(b + 4 - V_REC, (w & 3) ^ 2);
        PROF(t2 == 0, 3516);
        const int gi = b * 128 + t2;
        g_st[gi] = make_uint4(~0u, ~0u, ~0u, ~0u);
        if (gi < 1024) g_st[16384 + gi] = make_uint4(~0u, ~0u, ~0u, ~0u);
        if (gi < 912 * 8) g_cnt[gi] = 0;
        bar_sync(9, 384);
#pragma unroll 1
        for (int pass = 0; pass < 2; pass++) {
        if (w == 10 && pass == (b + 4 < V_QKV)) early_fetch(p, sb);
        if (pass) break;
#pragma unroll 2
        for (int i = t2; i < 4 * 784; i += 128) {
            const int ch = i / 784, k = i - ch * 784;
            const uint32_t o = sb + P_P + (ch * 2080 + 266 + (k / 14) * 18 + k) * 4;
            g_W[d0 * 784 + i] = make_uint4(lds32(o), lds32(o + 32), lds32(o + 64), lds32(o + 96));
        }
        bar_arrive(10, 384);
        }
        PROF(t2 == 0, 3517);
        return;
    }
    float kl = 0;
#pragma unroll
    for (int i = 0; i < 2; i++) {
        const float dt = rbf(expf(blo(pr.ldt[i])));
        const float ar = -rbf(expf(blo(pr.v[i][0]))) * dt, ai = blo(pr.v[i][1]) * dt;
        const float lg = ar * 1.4426950408889634f, tn = ai * 0.15915494309189535f, ph = tn - rintf(tn);
        const float cr = 2.f * (blo(pr.v[i][2]) * dt), ci = 2.f * (blo(pr.v[i][3]) * dt);
        float zr, zi;
        cpow(lg, ph, 2048.f, zr, zi);
        kl += cr * zr - ci * zi;
        cpow(lg, ph, 8.f, zr, zi);
        sts128(sb + P_PRM + (w * 64 + i * 32 + lane) * 16, __float_as_uint(lg), __float_as_uint(ph), __float_as_uint(cr), __float_as_uint(ci));
        sts64(sb + P_PRM + 8192 + (w * 64 + i * 32 + lane) * 8, __float_as_uint(zr), __float_as_uint(zi));
    }
    if (tid < 64) sts128(sb + P_U + (tid >> 3) * 2176 + (tid & 7) * 16, 0, 0, 0, 0);
    __syncwarp();
    PROF(tid == 0, 3510);
    uint2 ln[4];
#define LDLN _Pragma("unroll") for (int i = 0; i < 4; i++) asm volatile("ld.relaxed.gpu.global.v2.u32 {%0,%1},[%2];" : "=r"(ln[i].x), "=r"(ln[i].y) : "l"((const uint2*)g_ln0 + i * 256 + tid) : "memory")
    const int ch = w & 3, hf = w >> 2;
    {
        float k0[4] = {0, 0, 0, 0}, k1[4] = {0, 0, 0, 0}, k2[4] = {0, 0, 0, 0}, k3[4] = {0, 0, 0, 0}, k4[4] = {0, 0, 0, 0};
#pragma unroll KGU
        for (int j = 0; j < 16; j++) {
            const uint4 q = lds128(sb + P_PRM + (w * 64 + j * 4 + c) * 16);
            const float cr = __uint_as_float(q.z), ci = __uint_as_float(q.w);
            float wr[4], wi[4], vr[4], vi[4];
            cpow(__uint_as_float(q.x), __uint_as_float(q.y), (float)g, wr[0], wi[0]);
            const uint2 z8 = lds64(sb + P_PRM + 8192 + (w * 64 + j * 4 + c) * 8);
            vr[0] = wr[0] * __uint_as_float(z8.x) - wi[0] * __uint_as_float(z8.y); vi[0] = wr[0] * __uint_as_float(z8.y) + wi[0] * __uint_as_float(z8.x);
#pragma unroll
            for (int i = 1; i < 4; i++) { wr[i] = wr[i - 1]; wi[i] = wi[i - 1]; csq(wr[i], wi[i]); vr[i] = vr[i - 1]; vi[i] = vi[i - 1]; csq(vr[i], vi[i]); }
            float hr = wr[3], hi = wi[3];
            csq(hr, hi);
            mma_tf32(k0, wr[0], vr[0], wi[0], vi[0], cr * hr - ci * hi, -(cr * hi + ci * hr));
            hr = vr[3]; hi = vi[3]; csq(hr, hi);
            mma_tf32(k1, wr[0], vr[0], wi[0], vi[0], cr * hr - ci * hi, -(cr * hi + ci * hr));
            csq(hr, hi);
            mma_tf32(k2, wr[1], vr[1], wi[1], vi[1], cr * hr - ci * hi, -(cr * hi + ci * hr));
            csq(hr, hi);
            mma_tf32(k3, wr[2], vr[2], wi[2], vi[2], cr * hr - ci * hi, -(cr * hi + ci * hr));
            csq(hr, hi);
            mma_tf32(k4, wr[3], vr[3], wi[3], vi[3], cr * hr - ci * hi, -(cr * hi + ci * hr));
        }
        LDLN;
#pragma unroll
        for (int d = 1; d < 32; d *= 2) kl += __shfl_xor_sync(0xffffffffu, kl, d);
        const uint32_t o = sb + P_K6 + (ch * 656 + c * 32 + g) * 4, ol = sb + P_K6 + (ch * 656 + 640) * 4;
#define KST(k, base) sts32(o + (base) * 4, __float_as_uint(k[0])); sts32(o + (base) * 4 + 64, __float_as_uint(k[1])); \
                     sts32(o + (base) * 4 + 32, __float_as_uint(k[2])); sts32(o + (base) * 4 + 96, __float_as_uint(k[3]))
#define KAD(k, base) k[0] += __uint_as_float(lds32(o + (base) * 4)); k[1] += __uint_as_float(lds32(o + (base) * 4 + 64)); \
                     k[2] += __uint_as_float(lds32(o + (base) * 4 + 32)); k[3] += __uint_as_float(lds32(o + (base) * 4 + 96))
        if (hf == 0) {
            bar_sync(2 + ch, 64);
            KAD(k0, 0); KAD(k1, 128); KAD(k2, 256); KAD(k3, 384); KAD(k4, 512);
            kl += __uint_as_float(lds32(ol));
            __syncwarp();
        }
        KST(k0, 0); KST(k1, 128); KST(k2, 256); KST(k3, 384); KST(k4, 512);
        if (lane == 0) sts32(ol, __float_as_uint(kl));
        if (hf == 1) { __syncwarp(); bar_arrive(2 + ch, 64); }
    }
    PROF(tid == 0, 3511);
    {
        int n = 0;
        while (!__all_sync(0xffffffffu, ln[0].x && ln[0].y && ln[1].x && ln[1].y && ln[2].x && ln[2].y && ln[3].x && ln[3].y)) {
            LDLN;
            if (++n > 2000000) __trap();
        }
        bar_sync(8, 384);
        mbar_wait(sb + S_XBAR, 0);
#pragma unroll
        for (int i = 0; i < 4; i++) {
            const int t = i * 512 + tid * 2;
            uint32_t u[2][2];
#pragma unroll
            for (int e = 0; e < 2; e++) {
                const uint32_t l = e ? ln[i].y : ln[i].x, mm = __byte_perm(l, 0, 0x1010) ^ 0x80008000u;
                const float rs = rcp(bhi(l));
                const uint2 x = lds64(sb + P_X + (t + e) * 16 + (b & 1) * 8);
                u[e][0] = NRM(x.x); u[e][1] = NRM(x.y);
                sts64(sb + P_X + (t + e) * 16 + 8 - (b & 1) * 8, u[e][0], u[e][1]);
            }
            const uint32_t o = sb + P_U + ((t >> 3) & 1) * 2176 + ((t >> 4) + 8) * 16 + (t & 7) * 2;
#pragma unroll
            for (int k = 0; k < 4; k++) sts32(o + k * 4352, __byte_perm(u[0][k >> 1], u[1][k >> 1], (k & 1) ? 0x7632 : 0x5410));
        }
    }
    PROF(tid == 0, 3512);
    if (tid < 64) sts32(sb + P_P + ((tid >> 4) * 2080 + (tid & 15)) * 4, 0);
#pragma unroll 1
    for (int x = tid; x < 2048; x += 512) {
        uint32_t pw[2][4];
#pragma unroll
        for (int h = 0; h < 2; h++) {
            const int y = x + h * 256;
            const int i0 = y <= 256 ? y : 256 + (int)((pack2((float)y, 0.f) & 0xffff) - 0x4380);
            const int i1 = y <= 256 ? max(y - 1, 0) : 256 + (int)((pack2((float)(y - 1), 0.f) & 0xffff) - 0x4380);
#pragma unroll
            for (int k = 0; k < 4; k++) {
                const float lo = __uint_as_float(lds32(sb + P_K6 + k * 2624 + i0 * 4)), hi = __uint_as_float(lds32(sb + P_K6 + k * 2624 + i1 * 4));
                pw[h][k] = pack2(lo, y ? hi : 0.f);
            }
        }
#pragma unroll
        for (int h = 0; h < 2; h++)
#pragma unroll
            for (int k = 0; k < 4; k++) sts32(sb + P_P + (k * 2080 + x + h * 256 + 16) * 4, pw[h][k]);
    }
    fence_async_smem();
    bar_arrive(9, 384);
    bar_sync(1, 256);
    if (tid < 4) {
        asm volatile("cp.async.bulk.global.shared::cta.bulk_group [%0],[%1],%2;" ::"l"(g_P + (d0 + tid) * PROW), "r"(sb + P_P + tid * 8320), "r"(PROW * 4) : "memory");
        asm volatile("cp.async.bulk.commit_group;" ::: "memory");
    }
    __syncwarp();
    PROF(tid == 0, 3513);
    {
        float acc[16][4];
#pragma unroll
        for (int j = 0; j < 16; j++) acc[j][0] = acc[j][1] = acc[j][2] = acc[j][3] = 0;
#pragma unroll 1
        for (int e = hf * 4; e < hf * 4 + 4; e++) {
            uint32_t B[16][2];
            const uint32_t ua = sb + P_U + ch * 4352 + ((lane >> 3) & 1) * 2176 + (8 + (lane >> 4) * 8 + (lane & 7) - e) * 16;
#pragma unroll
            for (int j = 0; j < 8; j++) { const uint4 v = ldsm4(ua + j * 256); B[2 * j][0] = v.x; B[2 * j][1] = v.y; B[2 * j + 1][0] = v.z; B[2 * j + 1][1] = v.w; }
            const uint32_t pa = sb + P_P + (ch * 2080 + 16 + e * 16 + g - 2 * c) * 4;
#pragma unroll
            for (int dd = 0; dd < 16; dd++) {
                const int d = (dd & 1) ? 15 - (dd >> 1) : dd >> 1;
                const uint32_t a0 = lds32(pa + d * 512), a1 = lds32(pa + d * 512 + 32), a2 = lds32(pa + d * 512 - 32), a3 = a0 + p.zero;
#pragma unroll
                for (int j = 0; j < 16; j++) if (j >= d) mma16(acc[j], a0, a1, a2, a3, B[(j - d) & 15][0], B[(j - d) & 15][1]);
            }
        }
        PROF(tid == 0, 3514);
        if (tid < 4) asm volatile("cp.async.bulk.wait_group 0;" ::: "memory");
        __syncwarp();
        bar_sync(10, 384);
#pragma unroll
        for (int j = 0; j < 8; j++) {
#pragma unroll
            for (int i = 0; i < 4; i++) { const float t = hf ? acc[j][i] : acc[j + 8][i]; acc[j][i] = hf ? acc[j + 8][i] : acc[j][i]; acc[j + 8][i] = t; }
            sts128(sb + P_Y + w * 4096 + j * 512 + lane * 16, __float_as_uint(acc[j + 8][0]), __float_as_uint(acc[j + 8][1]), __float_as_uint(acc[j + 8][2]), __float_as_uint(acc[j + 8][3]));
        }
        bar_sync(2 + ch, 64);
        uint32_t yp[16];
#pragma unroll
        for (int j = 0; j < 8; j++) {
            const uint4 t = lds128(sb + P_Y + (w ^ 4) * 4096 + j * 512 + lane * 16);
            yp[2 * j] = pack2(acc[j][0] + __uint_as_float(t.x), acc[j][1] + __uint_as_float(t.y)); yp[2 * j + 1] = pack2(acc[j][2] + __uint_as_float(t.z), acc[j][3] + __uint_as_float(t.w));
        }
#pragma unroll
        for (int j = 0; j < 4; j++)
            asm volatile("stmatrix.sync.aligned.m8n8.x4.trans.shared.b16 [%0],{%1,%2,%3,%4};" ::"r"(sb + P_Y + 32768 + ch * 4096 + hf * 2048 + j * 512 + (lane >> 4) * 256 + (lane & 7) * 32 + (lane & 8) * 2),
                         "r"(yp[4 * j]), "r"(yp[4 * j + 1]), "r"(yp[4 * j + 2]), "r"(yp[4 * j + 3]) : "memory");
    }
    const uint2 dk = __ldg((const uint2*)(a.Dk + d0));
    bar_sync(1, 256);
#pragma unroll 2
    for (int i = 0; i < 4; i++) {
        const int t = i * 256 + tid;
        uint4 x0 = lds128(sb + P_X + t * 32), x1 = lds128(sb + P_X + t * 32 + 16);
        if (b & 1) { x0 = make_uint4(x0.z, x0.w, x0.x, x0.y); x1 = make_uint4(x1.z, x1.w, x1.x, x1.y); }
        uint32_t y[4];
#pragma unroll
        for (int k = 0; k < 4; k++) y[k] = lds32(sb + P_Y + 32768 + k * 4096 + t * 4);
        g_x[b * XP + t] = make_uint4(hadd2(x0.x, hadd2(__byte_perm(y[0], y[1], 0x5410), hmul2(x0.z, dk.x))), hadd2(x0.y, hadd2(__byte_perm(y[2], y[3], 0x5410), hmul2(x0.w, dk.y))),
                                     hadd2(x1.x, hadd2(__byte_perm(y[0], y[1], 0x7632), hmul2(x1.z, dk.x))), hadd2(x1.y, hadd2(__byte_perm(y[2], y[3], 0x7632), hmul2(x1.w, dk.y))));
    }
    PROF(tid == 0, 3515);
}

__global__ void __cluster_dims__(2, 1, 1) __launch_bounds__(384, 1) main_kernel(const __grid_constant__ Params p) {
    extern __shared__ __align__(1024) uint8_t smem[];
    const uint32_t sb = smem_u32(smem);
    uint32_t rank; asm("mov.u32 %0,%%cluster_ctarank;" : "=r"(rank));
    const int wi = __shfl_sync(0xffffffffu, threadIdx.x >> 5, 0);
    const int v = blockIdx.x, cl = v >> 1, wg = wi >> 2;
    PROF(threadIdx.x == 0, 3500);
    ProRegs pr;
    prologue_load(p.pa, max((int)blockIdx.x - 4, 0), pr);
    if (wi == 11 && p.dopro && cl >= 2 && elect()) {
        mbar_init(sb + S_XBAR, 1);
        asm volatile("fence.mbarrier_init.release.cluster;" ::: "memory");
        mbar_expect(sb + S_XBAR, 32768);
        for (int j = 0; j < 8; j++) tma2d(sb + P_X + j * 4096, &p.tm[3], ((blockIdx.x - 4) >> 1) * 8, j * 256, sb + S_XBAR);
    }
    if (threadIdx.x == 320) {
        unsigned n;
        asm volatile("ld.relaxed.gpu.global.u32 %0,[%1];" : "=r"(n) : "l"(g_gate) : "memory");
        n = n / (4 * NCL) + p.dopro;
        sts64(sb + S_GATE, n * (4 * NCL), n & 1);
    }
    __syncwarp();
    if (wi == 10) {
        if (v < V_REC || v == 131) conv_init(sb, v == 131); else if (v < V_OP) rec_init(sb); else gemm_init(sb, v < V_QKV);
        __syncwarp();
    }
    if (wg == 2) bar_arrive(8, 384);
    asm volatile("barrier.cluster.arrive.relaxed.aligned;" ::: "memory");
    if (p.dopro && cl >= 2) prologue(p, sb, blockIdx.x - 4, wi, pr); else if (wg < 2) bar_sync(8, 384); else if (wi == 10) early_fetch(p, sb);
    asm volatile("barrier.cluster.wait.aligned;" ::: "memory");
    const int role = (v < V_REC ? 1 : v < V_OP ? 2 : v < V_QKV ? 20 : v < V_QKV + NQ ? 24 : 1) & p.roles;
    fence_async_smem();
    bar_sync(wg == 2 ? 7 : 1, wg == 2 ? 128 : 256);
    if (p.dopro && (threadIdx.x == 32 || threadIdx.x == 352)) red_release(g_gate, 1);
    PROF(threadIdx.x == 32, 3509);
    if (wi == 0 && (role & 8) && elect()) qkv_stage(p, sb + 131072, sb + G_BAR + GB_RS * 8, v - V_QKV, 0, 6);
    PROF(threadIdx.x == 0, 3506);
    __syncwarp();
    if (p.dopro && (v == 131 || (v >= V_REC && v < V_QKV && (v < V_OP ? wi == 8 : wi < 8)))) {
        bool on = v >= V_OP;
#pragma unroll 1
        for (int r = v == 131 ? 448 + wi : on ? 64 + (v - V_OP) * 8 + wi : v - V_REC; r < (v == 131 ? 512 : 448);) {
            if (v >= V_OP) wait_slow_warp(g_gate, lds32(sb + S_GATE)); else if (on) wait_flag_warp(g_gate, lds32(sb + S_GATE));
            PROF(threadIdx.x == 256 && on, 3507);
            x1_norm(on ? (const uint2*)g_x : (const uint2*)p.pa.x, r, on);
            __syncwarp();
            if (on && elect()) red_release(cnt_ptr(C_XN + (r >> 4)), 1);
            __syncwarp();
            PROF(threadIdx.x == 256, on ? 3508 : 3499);
            if (on) r += v < V_OP ? 512 : v == 131 ? 12 : 128;
            on = true;
        }
    }
    if (role == 2) {
        const int head = (v - V_REC) >> 1;
        if (wi == 8 && elect()) rec_fetch(p, sb, head, rank, 1, R_STK);
        __syncwarp();
        if (wg == 2) {
            reg_dec<RH>();
            const int w = wi & 3;
            wait_slow_warp(g_gate, lds32(sb + S_GATE));
            if (w < 2) { const uint32_t x = __ldcg(g_sel + (threadIdx.x & 63)); sts32(sb + R_SEL + (threadIdx.x & 63) * 4, (x * 0x01010101u) >> 24); }
            __syncthreads();
            cluster_sync();
            if ((p.chains >> (w & 1)) & 1) { if (w < 2) rec_comm(p, sb, w, head, rank); else rec_attn(p, sb, w & 1, head, rank); }
        } else {
            reg_inc<RW0>();
            rec_weights(p, sb, head, rank, wi);
        }
    } else if (role == 1) {
        if (v == 131) { wait_slow_warp(g_gate, lds32(sb + S_GATE)); conv_far<0>(sb, wi); conv_far<1>(sb, wi); } else if (wg == 2) { reg_dec<RCB>(); conv_back(sb, v, wi & 3); } else { reg_inc<RCU>(); conv_tile(p, sb, v, wi); }
    } else if (role && v < V_QKV) {
        if (wg == 2) {
            reg_dec<40>();
            if (wi == 8) { if (role & 4) gemm_producer<true>(p, sb, v - V_OP); }
            else if (v < V_OP + 14 && (role & 16)) fin_warp(p, sb, 2 * NQ + (v - V_OP) * 3 + wi - 9);
        } else { reg_inc<232>(); if (role & 4) gemm_consumer<true>(p, sb, v - V_OP, wi); }
    } else if (role) {
        if (wg == 2) {
            reg_dec<40>();
            if (wi < 10) {
                if (role & 8) { if (wi == 8) gemm_producer<false>(p, sb, v - V_QKV); else qkv_release(p, sb); }
            } else if (role & 16) fin_warp(p, sb, (v - V_QKV) * 2 + wi - 10);
        } else { reg_inc<232>(); if (role & 8) gemm_consumer<false>(p, sb, v - V_QKV, wi); }
    }
    __syncwarp();
    cluster_sync();
}

typedef CUresult (*EncFn)(CUtensorMap*, CUtensorMapDataType, cuuint32_t, void*, const cuuint64_t*, const cuuint64_t*, const cuuint32_t*, const cuuint32_t*,
                          CUtensorMapInterleave, CUtensorMapSwizzle, CUtensorMapL2promotion, CUtensorMapFloatOOBfill);
constexpr int SMEM_BYTES = 232448;
#define LAG 8
#define QLEAD 6
#define OLEAD (LAG / 2 + 2)
void plan(Params& P) {
    P.roles = 31; P.chains = 3; P.lag = LAG; P.dopro = 1;
    for (int r = 0; r < 2; r++) {
        const int lead = r ? OLEAD : QLEAD;
        int n = 0;
        for (int i = 0; i < 32 + lead; i++) {
            if (i >= lead) P.list[r][n++] = 32 + i - lead;
            if (i < 32) P.list[r][n++] = i;
        }
        P.nl[r] = n;
    }
}

#define TK() do {} while (0)
}

extern "C" void kernel_launch(void* const* d_in, const int* in_sizes, int n_in, void* d_out, int out_size) {
    typedef const __nv_bfloat16* BP;
    static EncFn enc = nullptr;
    if (!enc) {
        void* fn = nullptr; cudaDriverEntryPointQueryResult qr;
        cudaGetDriverEntryPoint("cuTensorMapEncodeTiled", &fn, cudaEnableDefault, &qr);
        enc = (EncFn)fn;
        cudaFuncSetAttribute(main_kernel, cudaFuncAttributeMaxDynamicSharedMemorySize, SMEM_BYTES);
    }
    static Params P;
    for (int i = 0; i < 4; i++) {
        const cuuint64_t cols = i < 3 ? 4096 : 512, rows = i < 3 ? 512 : 4096;
        cuuint64_t d2[2] = {cols, rows}, str[1] = {cols * 2};
        cuuint32_t box[2] = {64, 64}, bn[2] = {16, 256}, es[2] = {1, 1};
        enc(&P.tm[i < 3 ? i : 4], CU_TENSOR_MAP_DATA_TYPE_BFLOAT16, 2, d_in[9 + i], d2, str, box, es, CU_TENSOR_MAP_INTERLEAVE_NONE, CU_TENSOR_MAP_SWIZZLE_128B,
            CU_TENSOR_MAP_L2_PROMOTION_L2_128B, CU_TENSOR_MAP_FLOAT_OOB_FILL_NONE);
        if (i < 2) enc(&P.tn[i], CU_TENSOR_MAP_DATA_TYPE_BFLOAT16, 2, d_in[9 + i], d2, str, bn, es, CU_TENSOR_MAP_INTERLEAVE_NONE, CU_TENSOR_MAP_SWIZZLE_32B,
                       CU_TENSOR_MAP_L2_PROMOTION_L2_128B, CU_TENSOR_MAP_FLOAT_OOB_FILL_NONE);
    }
    {
        cuuint64_t dims[2] = {512, 2048}, str[1] = {1024};
        cuuint32_t box[2] = {8, 256}, es[2] = {1, 1};
        enc(&P.tm[3], CU_TENSOR_MAP_DATA_TYPE_BFLOAT16, 2, d_in[0], dims, str, box, es, CU_TENSOR_MAP_INTERLEAVE_NONE, CU_TENSOR_MAP_SWIZZLE_NONE,
            CU_TENSOR_MAP_L2_PROMOTION_NONE, CU_TENSOR_MAP_FLOAT_OOB_FILL_NONE);
    }
    P.mem0 = (BP)d_in[8]; P.Wo = (BP)d_in[12]; P.Dskip = (BP)d_in[6]; P.out = (__nv_bfloat16*)d_out;
    cudaStream_t s = cudaStreamPerThread;
    P.pa = {(BP)d_in[0], (BP)d_in[1], (BP)d_in[2], (BP)d_in[3], (BP)d_in[4], (BP)d_in[5], (BP)d_in[6]};
    plan(P);
    TK(); main_kernel<<<2 * NCL, 384, SMEM_BYTES, s>>>(P); TK();
}
```

```cpp
#include <cuda_runtime.h>
#include <cuda_bf16.h>
#include <cuda.h>
#include <stdint.h>
#include <string.h>
#include <math.h>

namespace {

constexpr int NCL = 66;
constexpr int NQ = 43;
constexpr int V_REC = 8, V_OP = 72, V_QKV = 88;
static_assert(2 * NQ + 3 * 14 == 128, "warps of the final residual");

constexpr int XP = 1024;
__device__ uint4 g_x[2 * 128 * XP];
__device__ uint4 g_xn[64 * 4096];
__device__ uint4 g_st[68 * 256];
__device__ uint4 g_qkv[128 * 32 * 1536];
__device__ uint4 g_o[64 * 64 * 512];
__device__ uint4 g_pp[64 * 4 * 4096];
__device__ uint4 g_xch[133 * 512];
__device__ unsigned g_sel[64];
__device__ unsigned g_gate[32];
__device__ __align__(16) uint32_t g_P[512 * 272];
__device__ uint4 g_W[512 * 784];
__device__ __align__(16) uint32_t g_u[512 * 1280];
__device__ uint2 g_carry[512 * 40 * 32];
__device__ uint2 g_far[512 * 12 * 32];
__device__ unsigned g_cnt[912 * 8];
__device__ uint32_t g_ln0[2048];

enum { C_XN = 0  , C_QKV = 64  , C_O = 128  , C_PP = 384  , C_FAR = 896 };
__device__ __forceinline__ unsigned* cnt_ptr(int i) { return g_cnt + i * 8; }

struct ProArgs { const __nv_bfloat16 *x, *lAr, *Ai, *Cr, *Ci, *ldt, *Dk; };
struct Params {
    CUtensorMap tm[5];
    CUtensorMap tn[2];
    ProArgs pa;
    int dopro;
    const __nv_bfloat16* mem0;
    const __nv_bfloat16* Wo;
    const __nv_bfloat16* Dskip;
    __nv_bfloat16* out;
    int roles;
    int chains;
    int lag;
    int zero;
    int nl[2];
    uint8_t list[2][64];
};

__device__ __forceinline__ uint32_t smem_u32(const void* p) { return (uint32_t)__cvta_generic_to_shared(p); }
__device__ __forceinline__ uint32_t mapa(uint32_t a, uint32_t r) {
    uint32_t o; asm("mapa.shared::cluster.u32 %0,%1,%2;" : "=r"(o) : "r"(a), "r"(r)); return o;
}
__device__ __forceinline__ void mbar_init(uint32_t b, int c) { asm volatile("mbarrier.init.shared::cta.b64 [%0],%1;" ::"r"(b), "r"(c) : "memory"); }
__device__ __forceinline__ void mbar_expect(uint32_t b, int bytes) { asm volatile("mbarrier.arrive.expect_tx.shared::cta.b64 _,[%0],%1;" ::"r"(b), "r"(bytes) : "memory"); }
__device__ __forceinline__ void mbar_arrive(uint32_t b) { asm volatile("mbarrier.arrive.shared::cta.b64 _,[%0];" ::"r"(b) : "memory"); }
__device__ __forceinline__ void mbar_arrive_cluster(uint32_t b) { asm volatile("mbarrier.arrive.shared::cluster.b64 _,[%0];" ::"r"(b) : "memory"); }
__device__ __forceinline__ void mbar_wait(uint32_t b, uint32_t ph) {
    asm volatile(
        "{.reg .pred p; .reg .u32 n; mov.u32 n,0;\n"
        "W%=: mbarrier.try_wait.parity.shared::cta.b64 p,[%0],%1;\n"
        "@p bra D%=;\n"
        "add.u32 n,n,1; setp.lt.u32 p,n,2000000; @p bra W%=;\n"
        "trap;\n"
        "D%=: }" ::"r"(b), "r"(ph) : "memory");
}
__device__ __forceinline__ bool elect() {
    uint32_t r; asm volatile("{.reg .pred p; elect.sync _|p,0xffffffff; selp.u32 %0,1,0,p;}" : "=r"(r)); return r;
}
__device__ __forceinline__ void bar_sync(int id, int n) { asm volatile("bar.sync %0,%1;" ::"r"(id), "r"(n) : "memory"); }
__device__ __forceinline__ void bar_arrive(int id, int n) { asm volatile("bar.arrive %0,%1;" ::"r"(id), "r"(n) : "memory"); }
__device__ __forceinline__ void cluster_sync() { asm volatile("barrier.cluster.arrive.relaxed.aligned; barrier.cluster.wait.aligned;" ::: "memory"); }
__device__ __forceinline__ void fence_async_smem() { asm volatile("fence.proxy.async.shared::cta;" ::: "memory"); }
constexpr uint64_t POL_N = 0x1000000000000000ull  , POL_LAST = 0x12F0000000000000ull  ;
__device__ __forceinline__ void bulk_g2s(uint32_t dst, const void* src, int bytes, uint32_t bar, uint64_t pol) {
    asm volatile("cp.async.bulk.shared::cluster.global.mbarrier::complete_tx::bytes.L2::cache_hint [%0],[%1],%2,[%3],%4;" ::"r"(dst), "l"(src), "r"(bytes), "r"(bar), "l"(pol) : "memory");
}
__device__ __forceinline__ void bulk_g2s_mc(uint32_t dst, const void* src, int bytes, uint32_t bar, uint64_t pol) {
    asm volatile("cp.async.bulk.shared::cluster.global.mbarrier::complete_tx::bytes.multicast::cluster.L2::cache_hint [%0],[%1],%2,[%3],%4,%5;" ::"r"(dst), "l"(src), "r"(bytes), "r"(bar), "h"((uint16_t)3), "l"(pol) : "memory");
}
__device__ __forceinline__ void stg128(uint4* p, uint4 v, uint64_t pol) {
    asm volatile("st.global.L2::cache_hint.v4.u32 [%0],{%1,%2,%3,%4},%5;" ::"l"(p), "r"(v.x), "r"(v.y), "r"(v.z), "r"(v.w), "l"(pol));
}
__device__ __forceinline__ void tma2d(uint32_t dst, const CUtensorMap* tm, int x, int y, uint32_t bar) {
    asm volatile("cp.async.bulk.tensor.2d.shared::cluster.global.mbarrier::complete_tx::bytes [%0],[%1,{%2,%3}],[%4];" ::"r"(dst), "l"(tm), "r"(x), "r"(y), "r"(bar) : "memory");
}
__device__ __forceinline__ void st_async4(uint32_t a, uint32_t x, uint32_t y, uint32_t z, uint32_t w, uint32_t mb) {
    asm volatile("st.async.shared::cluster.mbarrier::complete_tx::bytes.v4.b32 [%0],{%1,%2,%3,%4},[%5];" ::"r"(a), "r"(x), "r"(y), "r"(z), "r"(w), "r"(mb) : "memory");
}
__device__ __forceinline__ void st_async2(uint32_t a, uint32_t x, uint32_t y, uint32_t mb) {
    asm volatile("st.async.shared::cluster.mbarrier::complete_tx::bytes.v2.b32 [%0],{%1,%2},[%3];" ::"r"(a), "r"(x), "r"(y), "r"(mb) : "memory");
}
__device__ __forceinline__ uint4 lds128(uint32_t a) { uint4 v; asm volatile("ld.shared.v4.u32 {%0,%1,%2,%3},[%4];" : "=r"(v.x), "=r"(v.y), "=r"(v.z), "=r"(v.w) : "r"(a) : "memory"); return v; }
__device__ __forceinline__ uint4 lds128v(uint32_t a) { uint4 v; asm volatile("ld.volatile.shared.v4.u32 {%0,%1,%2,%3},[%4];" : "=r"(v.x), "=r"(v.y), "=r"(v.z), "=r"(v.w) : "r"(a) : "memory"); return v; }
__device__ __forceinline__ uint2 lds64(uint32_t a) { uint2 v; asm volatile("ld.shared.v2.u32 {%0,%1},[%2];" : "=r"(v.x), "=r"(v.y) : "r"(a) : "memory"); return v; }
__device__ __forceinline__ uint32_t lds32(uint32_t a) { uint32_t v; asm volatile("ld.shared.u32 %0,[%1];" : "=r"(v) : "r"(a) : "memory"); return v; }
__device__ __forceinline__ void sts128(uint32_t a, uint32_t x, uint32_t y, uint32_t z, uint32_t w) { asm volatile("st.shared.v4.u32 [%0],{%1,%2,%3,%4};" ::"r"(a), "r"(x), "r"(y), "r"(z), "r"(w) : "memory"); }
__device__ __forceinline__ void sts64(uint32_t a, uint32_t x, uint32_t y) { asm volatile("st.shared.v2.u32 [%0],{%1,%2};" ::"r"(a), "r"(x), "r"(y) : "memory"); }
__device__ __forceinline__ void sts32(uint32_t a, uint32_t x) { asm volatile("st.shared.u32 [%0],%1;" ::"r"(a), "r"(x) : "memory"); }
__device__ __forceinline__ uint4 ldsm4(uint32_t a) { uint4 v; asm volatile("ldmatrix.sync.aligned.m8n8.x4.shared.b16 {%0,%1,%2,%3},[%4];" : "=r"(v.x), "=r"(v.y), "=r"(v.z), "=r"(v.w) : "r"(a) : "memory"); return v; }
__device__ __forceinline__ uint4 ldsm4t(uint32_t a) { uint4 v; asm volatile("ldmatrix.sync.aligned.m8n8.x4.trans.shared.b16 {%0,%1,%2,%3},[%4];" : "=r"(v.x), "=r"(v.y), "=r"(v.z), "=r"(v.w) : "r"(a) : "memory"); return v; }
__device__ __forceinline__ uint32_t movm(uint32_t a) { uint32_t d; asm volatile("movmatrix.sync.aligned.m8n8.trans.b16 %0,%1;" : "=r"(d) : "r"(a)); return d; }
__device__ __forceinline__ uint32_t pack2(float lo, float hi) { uint32_t d; asm("cvt.rn.bf16x2.f32 %0,%1,%2;" : "=r"(d) : "f"(hi), "f"(lo)); return d; }
__device__ __forceinline__ uint32_t hadd2(uint32_t a, uint32_t b) { uint32_t d; asm("add.rn.bf16x2 %0,%1,%2;" : "=r"(d) : "r"(a), "r"(b)); return d; }
__device__ __forceinline__ uint32_t hmul2(uint32_t a, uint32_t b) { uint32_t d; asm("mul.rn.bf16x2 %0,%1,%2;" : "=r"(d) : "r"(a), "r"(b)); return d; }
__device__ __forceinline__ float blo(uint32_t v) { return __uint_as_float(v << 16); }
__device__ __forceinline__ float bhi(uint32_t v) { return __uint_as_float(v & 0xffff0000u); }
__device__ __forceinline__ float rbf(float x) { return __uint_as_float(pack2(0.f, x)); }
__device__ __forceinline__ float ex2(float x) { float y; asm("ex2.approx.ftz.f32 %0,%1;" : "=f"(y) : "f"(x)); return y; }
__device__ __forceinline__ float rcp(float x) { float y; asm("rcp.approx.ftz.f32 %0,%1;" : "=f"(y) : "f"(x)); return y; }
__device__ __forceinline__ void mma16(float* c, uint32_t a0, uint32_t a1, uint32_t a2, uint32_t a3, uint32_t b0, uint32_t b1) {
    asm volatile("mma.sync.aligned.m16n8k16.row.col.f32.bf16.bf16.f32 {%0,%1,%2,%3},{%4,%5,%6,%7},{%8,%9},{%0,%1,%2,%3};"
                 : "+f"(c[0]), "+f"(c[1]), "+f"(c[2]), "+f"(c[3]) : "r"(a0), "r"(a1), "r"(a2), "r"(a3), "r"(b0), "r"(b1));
}
__device__ __forceinline__ void mma16_top(float& d0, float& d1, uint32_t a0, uint32_t a2, uint32_t b0, uint32_t b1) {
    asm volatile("{.reg .b32 j; .reg .f32 e,f; mma.sync.aligned.m16n8k16.row.col.f32.bf16.bf16.f32 {%0,%1,e,f},{%2,j,%3,j},{%4,%5},{0f00000000,0f00000000,0f00000000,0f00000000};}"
                 : "=f"(d0), "=f"(d1) : "r"(a0), "r"(a2), "r"(b0), "r"(b1));
}
__device__ __forceinline__ void mma8(float* c, uint32_t a0, uint32_t a1, uint32_t b0) {
    asm volatile("mma.sync.aligned.m16n8k8.row.col.f32.bf16.bf16.f32 {%0,%1,%2,%3},{%4,%5},{%6},{%0,%1,%2,%3};"
                 : "+f"(c[0]), "+f"(c[1]), "+f"(c[2]), "+f"(c[3]) : "r"(a0), "r"(a1), "r"(b0));
}
__device__ __forceinline__ uint4 ld_rlx128(const uint4* p) {
    uint4 v;
    asm volatile("{.reg .b128 t; ld.relaxed.gpu.global.b128 t,[%4]; mov.b128 {%0,%1,%2,%3},t;}" : "=r"(v.x), "=r"(v.y), "=r"(v.z), "=r"(v.w) : "l"(p) : "memory");
    return v;
}
__device__ __forceinline__ void st_rlx128(uint4* p, uint32_t x, uint32_t y, uint32_t z, uint32_t w) {
    asm volatile("{.reg .b128 t; mov.b128 t,{%1,%2,%3,%4}; st.relaxed.gpu.global.b128 [%0],t;}" ::"l"(p), "r"(x), "r"(y), "r"(z), "r"(w) : "memory");
}
__device__ __forceinline__ uint4 ldcg128(const uint4* p) { uint4 v; asm volatile("ld.global.cg.v4.u32 {%0,%1,%2,%3},[%4];" : "=r"(v.x), "=r"(v.y), "=r"(v.z), "=r"(v.w) : "l"(p) : "memory"); return v; }
__device__ __forceinline__ void red_release(unsigned* p, unsigned v) {
    asm volatile("fence.proxy.async; red.relaxed.gpu.global.add.u32 [%0],%1;" ::"l"(p), "r"(v) : "memory");
}
__device__ __forceinline__ void red_relaxed(unsigned* p, unsigned v) { asm volatile("red.relaxed.gpu.global.add.u32 [%0],%1;" ::"l"(p), "r"(v) : "memory"); }
__device__ __forceinline__ void wait_cnt(const unsigned* p, unsigned target) {
    asm volatile(
        "{.reg .pred p; .reg .u32 n,v; mov.u32 n,0;\n"
        "W%=: ld.relaxed.gpu.global.u32 v,[%0]; setp.ge.u32 p,v,%1; @p bra D%=;\n"
        "add.u32 n,n,1; setp.lt.u32 p,n,10000000; @p bra W%=;\n"
        "trap;\n"
        "D%=: }" ::"l"(p), "r"(target) : "memory");
}
__device__ __forceinline__ void wait_slow_warp(const unsigned* p, unsigned target) {
    asm volatile(
        "{.reg .pred p; .reg .u32 n,v; mov.u32 n,0;\n"
        "W%=: ld.relaxed.gpu.global.u32 v,[%0]; setp.ge.u32 p,v,%1; vote.sync.all.pred p,p,0xffffffff; @p bra.uni D%=;\n"
        "nanosleep.u32 400; add.u32 n,n,1; setp.lt.u32 p,n,1000000; @p bra.uni W%=;\n"
        "trap;\n"
        "D%=: }" ::"l"(p), "r"(target) : "memory");
}
__device__ __forceinline__ void wait_flag_warp(const unsigned* p, unsigned target) {
    asm volatile(
        "{.reg .pred p; .reg .u32 n,v; mov.u32 n,0;\n"
        "W%=: ld.relaxed.gpu.global.u32 v,[%0]; setp.ge.u32 p,v,%1; vote.sync.all.pred p,p,0xffffffff; @p bra.uni D%=;\n"
        "add.u32 n,n,1; setp.lt.u32 p,n,10000000; @p bra.uni W%=;\n"
        "trap;\n"
        "D%=: }" ::"l"(p), "r"(target) : "memory");
}
__device__ __forceinline__ uint64_t mkdesc(uint32_t addr, uint32_t lbo, uint32_t sbo, uint32_t sw) {
    return (uint64_t)((addr & 0x3FFFF) >> 4) | ((uint64_t)(lbo >> 4) << 16) | ((uint64_t)(sbo >> 4) << 32) | ((uint64_t)sw << 62);
}
__device__ __forceinline__ void wg_fence() { asm volatile("wgmma.fence.sync.aligned;" ::: "memory"); }
__device__ __forceinline__ void wg_commit() { asm volatile("wgmma.commit_group.sync.aligned;" ::: "memory"); }
template <int N> __device__ __forceinline__ void wg_wait() { asm volatile("wgmma.wait_group.sync.aligned %0;" ::"n"(N) : "memory"); }
#define R8(c, o) "+f"(c[o]), "+f"(c[o + 1]), "+f"(c[o + 2]), "+f"(c[o + 3]), "+f"(c[o + 4]), "+f"(c[o + 5]), "+f"(c[o + 6]), "+f"(c[o + 7])
#define R32(c, o) R8(c, o), R8(c, o + 8), R8(c, o + 16), R8(c, o + 24)
#define S32A "%0,%1,%2,%3,%4,%5,%6,%7,%8,%9,%10,%11,%12,%13,%14,%15,%16,%17,%18,%19,%20,%21,%22,%23,%24,%25,%26,%27,%28,%29,%30,%31"
template <int ACC> __device__ __forceinline__ void wgmma64_rs(float* c, const uint32_t* a, uint64_t db) {
    asm volatile("wgmma.mma_async.sync.aligned.m64n64k16.f32.bf16.bf16 {" S32A "},{%32,%33,%34,%35},%36,%37,1,1,0;"
                 : R32(c, 0) : "r"(a[0]), "r"(a[1]), "r"(a[2]), "r"(a[3]), "l"(db), "n"(ACC));
}
template <int ACC> __device__ __forceinline__ void wgmma64_ta(float* c, uint64_t da, uint64_t db) {
    asm volatile("wgmma.mma_async.sync.aligned.m64n64k16.f32.bf16.bf16 {" S32A "},%32,%33,%34,1,1,1,0;" : R32(c, 0) : "l"(da), "l"(db), "n"(ACC));
}
template <int ACC> __device__ __forceinline__ void wgmma80_tb(float* c, uint64_t da, uint64_t db) {
    asm volatile("wgmma.mma_async.sync.aligned.m64n80k16.f32.bf16.bf16 {" S32A ",%32,%33,%34,%35,%36,%37,%38,%39},%40,%41,%42,1,1,0,1;"
                 : R32(c, 0), R8(c, 32) : "l"(da), "l"(db), "n"(ACC));
}
template <int N> __device__ __forceinline__ void reg_inc() { asm volatile("setmaxnreg.inc.sync.aligned.u32 %0;" ::"n"(N)); }
template <int N> __device__ __forceinline__ void reg_dec() { asm volatile("setmaxnreg.dec.sync.aligned.u32 %0;" ::"n"(N)); }

#define PROF(cond, idx) do {} while (0)
#define PROF2(cond, idx) do {} while (0)

constexpr int S_GATE = 232440, S_TAG = 232444, S_XBAR = 232432, B_BAR = 231936;
#define FT 5
#define FJ 62
#define OLAG 1
#define RCB 136
#define RCU 184
#define NTOP 1
#define PLATE 2
#define QLAG 4
constexpr float SC_LOG2E = 0.08838834764831845f * 1.4426950408889634f;

__device__ __forceinline__ float2 ln_finish(float mean, float var) {
    float sd; asm("sqrt.approx.f32 %0,%1;" : "=f"(sd) : "f"(rbf(rbf(var) + 1e-5f)));
    sd = rbf(sd);
    return make_float2(rbf(mean), sd);
}

__device__ __forceinline__ float2 row_stats512(uint4* v, const uint4* src, int s1, int s2) {
    const int g = (threadIdx.x & 31) >> 2;
#pragma unroll
    for (int i = 0; i < 16; i++) v[i] = ldcg128(src + (i >> 1) * s1 + (i & 1) * s2);
    float a[4] = {0, 0, 0, 0}, q0[4] = {0, 0, 0, 0}, q1[4] = {0, 0, 0, 0};
#pragma unroll
    for (int i = 0; i < 16; i++) {
        mma16(a, v[i].x, v[i].y, v[i].z, v[i].w, 0x3f803f80u, 0x3f803f80u);
        mma8(q0, v[i].x, v[i].y, v[i].x); mma8(q1, v[i].x, v[i].y, v[i].y);
        mma8(q0, v[i].z, v[i].w, v[i].z); mma8(q1, v[i].z, v[i].w, v[i].w);
    }
    const float sum = a[0] + a[2], sq = (g & 1) ? q0[1] + q1[3] : q0[0] + q1[2];
    return make_float2(sum, fmaxf(sq - sum * sum * (1.f / 512.f), 0.f));
}
__device__ __forceinline__ void x1_norm(const uint2* src, int r, bool on) {
    const int lane = threadIdx.x & 31, g = lane >> 2, t = r * 4 + (lane & 3);
    constexpr int xp = XP;
    uint2 v[16];
#pragma unroll
    for (int i = 0; i < 16; i++) asm volatile("ld.global.cg.v2.u32 {%0,%1},[%2];" : "=r"(v[i].x), "=r"(v[i].y) : "l"(src + (g * 4 * xp + t) + ((i >> 1) * 16 + (i & 1)) * 2 * xp) : "memory");
    float s = 0, q = 0;
#pragma unroll
    for (int i = 0; i < 32; i++) {
        const uint32_t w = (i & 1) ? v[i >> 1].y : v[i >> 1].x;
        s += blo(w) + bhi(w); q = fmaf(blo(w), blo(w), fmaf(bhi(w), bhi(w), q));
    }
#pragma unroll
    for (int d = 4; d < 32; d *= 2) { s += __shfl_xor_sync(0xffffffffu, s, d); q += __shfl_xor_sync(0xffffffffu, q, d); }
    if (g == 0 && on) g_ln0[t] = 0;
    s *= 1.f / 512.f;
    const float2 l = ln_finish(s, fmaxf(fmaf(q, 1.f / 512.f, -s * s), 0.f));
    const float rs = rcp(l.y);
    const uint32_t mm = pack2(-l.x, -l.x);
    uint4* dst = g_xn + ((t >> 6) * 4096 + ((t >> 3) & 7) * 64 + g * 8 + (t & 7));
#define NRM(w) pack2(blo(hadd2(w, mm)) * rs, bhi(hadd2(w, mm)) * rs)
#pragma unroll
    for (int i = 0; i < 8; i++)
        asm volatile("{.reg .pred p; setp.ne.u32 p,%5,0; @p st.global.v4.u32 [%0],{%1,%2,%3,%4};}" ::"l"(dst + i * 512), "r"(NRM(v[2 * i].x)), "r"(NRM(v[2 * i].y)),
                     "r"(NRM(v[2 * i + 1].x)), "r"(NRM(v[2 * i + 1].y)), "r"((uint32_t)on) : "memory");
}

#define NWO 10
#define VMASK 0x4444
#define VPRE 2
#define OL 0x16
#define PINS 0x6ae5
#define NPX 2
#define NPF 2
constexpr int SLOT = 24576, SL_V = 8192, SL_Q = 16384, SL_KM = 20480, SL_VM = 22528;
constexpr int R_SL = 0, R_WV = 4 * SLOT  , R_WO = R_WV + 65536, R_M = 196608  , R_U = R_M + 8192  ,
              R_OS = R_U + 8192  , R_SB = R_OS + 8192  , R_OB = R_SB + 5248  , R_PB = R_OB + 2048  ,
              R_IL = R_PB + 1024  , R_SEL = 231680, R_BAR = R_SEL + 256, R_STV = 0, R_STQ = 65536, R_STK = 131072;
static_assert(R_WO + (16 - NWO) * 4096 <= R_M && R_IL + 64 <= R_SEL && R_BAR + 512 <= 232448, "smem map");
enum { RB_XFULL = 0  , RB_GO = 4  , RB_QK = 8  , RB_INIT = 24, RB_SV = 25   };

enum { NB_MFULL = 1  , NB_PART = 3  , NB_S = 5, NB_P = 6, NB_O = 7, NB_W = 10 };
#define XU 4
#define NPRB 3
#define RH 56
#define RW0 224
#define D1 240
#define D2 300
__device__ __forceinline__ uint32_t clk32() { uint32_t c; asm volatile("mov.u32 %0,%%clock;" : "=r"(c)::"memory"); return c; }
__device__ __forceinline__ void spin(int cycles) {
    if (cycles <= 0) return;
    asm volatile("{.reg .pred p; .reg .u32 a,b; mov.u32 a,%%clock; add.u32 a,a,%0;\nS%=: mov.u32 b,%%clock; sub.u32 b,b,a; setp.lt.s32 p,b,0; @p bra.uni S%=;}" ::"r"(cycles) : "memory");
}
__device__ __forceinline__ uint4* xregion(int X, int r) { return (uint4*)(((size_t)g_xch + 8191) & ~(size_t)8191) + (X * 66 + r) * 512; }

__device__ __forceinline__ void arrive_if(uint32_t bar, uint32_t a, uint32_t b) {
    asm volatile("{.reg .pred p; setp.eq.u32 p,%1,%2; @p mbarrier.arrive.shared::cta.b64 _,[%0];}" ::"r"(bar), "r"(a), "r"(b) : "memory");
}
struct RecW { uint32_t po, dp, lw, sp, w; };
#define PIN(n) if ((PINS >> (n)) & 1) asm volatile("griddepcontrol.launch_dependents;" ::: "memory")
constexpr int v_stream(int n) {
    int ks = 0;
    for (; ks < 16; ks++) if (!((VMASK >> ks) & 1) && n-- == 0) break;
    return ks;
}
constexpr uint64_t v_next() {
    uint64_t r = 0;
    for (int n = 0; v_stream(n + VPRE) < 16; n++) r |= (uint64_t)v_stream(n + VPRE) << (4 * v_stream(n));
    return r;
}
constexpr uint64_t V_NEXT = v_next();
constexpr int V_PRE = v_stream(VPRE);

__device__ __forceinline__ void rec_step(const RecW& k, uint32_t sb, const int X, int s, uint32_t zero, int lo, int hi, int d, const uint32_t (*wq)[4], const uint32_t (*wk)[4], uint4* wv, uint4* wo) {
    const int SL = R_SL + X * 2 * SLOT;
    uint4 mk[8];
    bar_sync(NB_MFULL + X, 288);
    mk[0] = ldsm4(k.lw + X * 4096 + R_M);
    PIN(0);
    mk[1] = ldsm4(k.lw + X * 4096 + R_M + 512);
    PIN(0);
    asm volatile("" : "+r"(s));
    const uint32_t z = s & zero, wz = k.w + z, w5 = wz * 512, so = (s & 1) * SLOT + w5;
    const uint32_t qb = sb + R_BAR + (RB_QK + X * 8) * 8 + wz * 8;
    uint32_t x[4], vv[2], l8;
    {
        float aq[4] = {0, 0, 0, 0}, ak[4] = {0, 0, 0, 0}, av[4] = {0, 0, 0, 0};
#pragma unroll
        for (int t = 0; t < 16; t++) {
            const uint32_t b0 = (t & 1) ? mk[t >> 1].z : mk[t >> 1].x, b1 = (t & 1) ? mk[t >> 1].w : mk[t >> 1].y;
            mma16(aq, wq[t][0], wq[t][1], wq[t][2], wq[t][3], b0, b1);
            PIN(8);
            mma16(ak, wk[t][0], wk[t][1], wk[t][2], wk[t][3], b0, b1);
            PIN(9);
            mma16(av, wv[t].x, wv[t].y, wv[t].z, wv[t].w, b0, b1);
            PIN(10);
            if ((t & 1) && t < 13) mk[(t >> 1) + 2] = ldsm4(k.lw + X * 4096 + R_M + (t >> 1) * 512 + 1024);
            const int nx = (V_NEXT >> (4 * t)) & 15;
            if (nx) wv[nx] = lds128(k.lw + w5 + R_WV + nx * 4096);
            if (t == 14) l8 = ((k.lw + z) >> 1) + (sb - (sb >> 1) + SL + (s & 1) * SLOT + wz * 256);
            if (t < 15) PIN(1);
        }
        x[0] = movm(pack2(aq[0], aq[1])); x[1] = movm(pack2(aq[2], aq[3]));
        x[2] = movm(pack2(ak[0], ak[1])); x[3] = movm(pack2(ak[2], ak[3]));
        vv[0] = pack2(av[0], av[1]); vv[1] = pack2(av[2], av[3]);
        st_async2(l8 + (SL_VM + k.dp), vv[0], vv[1], qb + k.dp);
        st_async4(k.lw + (R_U + X * 4096 + w5 + k.dp), x[0], x[1], x[2], x[3], qb + k.dp);
    }
    {
        arrive_if(sb + R_BAR + (RB_GO + 2 - 2 * X + ((s + d) & 1)) * 8, (k.sp + z) & 0x1ff0, X ? s >= hi : s <= lo);
        const uint32_t swr = ((k.sp + z) & 0x1ff0) + (sb + R_SB);
#pragma unroll
        for (int i = 0; i < NPX; i++) wo[i] = lds128v(k.lw + w5 + R_WO + i * 4096);
        mbar_wait(sb + R_BAR + (RB_XFULL + X * 2) * 8 + (s & 1) * 8, (s >> 1) & 1);
        const uint4 k0 = lds128(k.lw + so + SL), k1 = lds128(k.lw + so + SL + 4096);
        mbar_wait(qb, s & 1);
        const uint4 u = lds128(k.lw + w5 + R_U + X * 4096);
        const uint32_t q0 = hadd2(x[0], u.x), q1 = hadd2(x[1], u.y);
        x[2] = hadd2(x[2], u.z); x[3] = hadd2(x[3], u.w);
        float sa[4] = {0, 0, 0, 0}, sc[4] = {0, 0, 0, 0}, sm0, sm1;
        mma16(sa, k0.x, k0.y, k0.z, k0.w, q0, q1);
        mma16(sc, k1.x, k1.y, k1.z, k1.w, q0, q1);
        mma16_top(sm0, sm1, x[2], x[3], q0, q1);
        asm volatile("stmatrix.sync.aligned.m8n8.x4.trans.shared.b16 [%0],{%1,%2,%3,%4};" ::"r"(swr), "r"(pack2(sa[0], sa[1])), "r"(pack2(sa[2], sa[3])),
                     "r"(pack2(sc[0], sc[1])), "r"(pack2(sc[2], sc[3])) : "memory");
        asm volatile("stmatrix.sync.aligned.m8n8.x1.trans.shared.b16 [%0],{%1};" ::"r"(swr + 512), "r"(pack2(sm0, sm1)) : "memory");
    }
    bar_sync(NB_S, 256);
    uint4 v0, v1;
    uint32_t ls;
    {
        const uint4 y = ldsm4t(k.lw + wz * 656 + R_SB);
        PIN(2);
        uint32_t y4; asm volatile("ldmatrix.sync.aligned.m8n8.x1.trans.shared.b16 {%0},[%1];" : "=r"(y4) : "r"(k.lw + wz * 656 + R_SB + 512) : "memory");
        PIN(2);
        const uint2 vp = lds64(l8 + SL_VM);
        sts64(l8 + SL_KM, x[2], x[3]);
        const uint32_t z1 = k.lw & z, z2 = k.sp & z, ONE = 0x3f803f80u | z2, ONF = 0x3f803f80u | z1;
        float a[4] = {0, 0, 0, 0}, b[4] = {0, 0, 0, 0}, e[4] = {0, 0, 0, 0};
        mma8(e, ONE, z1, y4); mma16(a, ONE, z1, z2, ONF, y.x, y.y); mma16(b, ONE, z1, z2, ONF, y.z, y.w);
        vv[0] = hadd2(vv[0], vp.x); vv[1] = hadd2(vv[1], vp.y);
        sts64(l8 + SL_VM, vv[0], vv[1]);
        float s0, s1;
        asm("{.reg .pred p1,p2,p4; .reg .f32 t0,t1,u0,u1; .reg .b32 m; and.b32 m,%12,64; setp.ne.u32 p1,m,0; and.b32 m,%12,128; setp.ne.u32 p2,m,0; and.b32 m,%12,256; setp.ne.u32 p4,m,0;"
            "selp.f32 t0,%4,%2,p1; selp.f32 t1,%5,%3,p1; selp.f32 u0,%8,%6,p1; selp.f32 u1,%9,%7,p1; selp.f32 t0,u0,t0,p2; selp.f32 t1,u1,t1,p2; selp.f32 %0,%10,t0,p4; selp.f32 %1,%11,t1,p4;}"
            : "=f"(s0), "=f"(s1) : "f"(a[0]), "f"(a[1]), "f"(a[2]), "f"(a[3]), "f"(b[0]), "f"(b[1]), "f"(b[2]), "f"(b[3]), "f"(e[0]), "f"(e[1]), "r"(k.lw));
        const int mi = __float_as_int(fmaxf(s0, s1));
        const int mp = __reduce_max_sync(0xffffffffu, mi), mn = (int)__reduce_min_sync(0xffffffffu, (unsigned)mi);
        PIN(3);
        v0 = lds128(k.lw + so + SL + SL_V); v1 = lds128(k.lw + so + SL + SL_V + 4096);
#pragma unroll
        for (int i = NPX; i < NPF; i++) wo[i] = lds128(k.lw + w5 + R_WO + i * 4096);
        PIN(4);
        const float mo = -__int_as_float(mp >= 0 ? mp : mn) * SC_LOG2E;
        s0 = ex2(fmaf(s0, SC_LOG2E, mo)); s1 = ex2(fmaf(s1, SC_LOG2E, mo));
        sts32((((k.sp + z) >> 11) & 0x1fc) + (k.lw & 256) * 2 + (sb + R_PB), pack2(s0, s1));
        ls = k.lw < sb + 320 ? __float_as_uint((s0 + s1) + 4.f) : 0;
    }
    bar_sync(NB_P, 256);
    {
        const uint4 pp = lds128(k.lw + R_PB);
        PIN(5);
        const uint32_t pm = lds32(((k.lw + z) >> 2) + (sb - (sb >> 2) + R_PB + 512));
        PIN(5);
        sts32(sb + R_IL + (wz >> 1) * 16 + (wz & 1) * 4, __reduce_add_sync(0xffffffffu, ls) - 20u * 0x40800000u);
        float o0[4] = {0, 0, 0, 0}, o1[4] = {0, 0, 0, 0}, o2[4] = {0, 0, 0, 0};
        mma16(o0, v0.x, v0.y, v0.z, v0.w, pp.x, pp.y);
        mma16(o1, v1.x, v1.y, v1.z, v1.w, pp.z, pp.w);
        mma8(o2, vv[0], vv[1], pm);
        asm volatile("stmatrix.sync.aligned.m8n8.x2.trans.shared.b16 [%0],{%1,%2};" ::"r"(k.lw + wz * 256 + R_OB),
                     "r"(pack2(o0[0] + o1[0] + o2[0], o0[1] + o1[1] + o2[1])), "r"(pack2(o0[2] + o1[2] + o2[2], o0[3] + o1[3] + o2[3])) : "memory");
    }
    bar_sync(NB_O, 256);
    {
        float r0[4] = {0, 0, 0, 0}, r1[4] = {0, 0, 0, 0};
        uint4 b[4];
        b[0] = ldsm4(k.lw + R_OB);
        PIN(6);
        b[1] = ldsm4(k.lw + R_OB + 512);
        PIN(6);
#pragma unroll
        for (int m = NWO + NPF; m < 16; m++) if (((OL >> (2 * (15 - m))) & 3) == 3) wo[m] = lds128(k.lw + w5 + R_WO + (m - NWO) * 4096);
        const uint2 il = lds64(sb + R_IL + ((k.lw + z) & 48));
        PIN(6);
        float i0, i1;
        uint4* dst;
#pragma unroll
        for (int i = 0; i < 4; i++) {
            mma16(r0, wo[4 * i].x, wo[4 * i].y, wo[4 * i].z, wo[4 * i].w, b[i].x, b[i].y);
            mma16(r1, wo[4 * i + 1].x, wo[4 * i + 1].y, wo[4 * i + 1].z, wo[4 * i + 1].w, b[i].x, b[i].y);
            mma16(r0, wo[4 * i + 2].x, wo[4 * i + 2].y, wo[4 * i + 2].z, wo[4 * i + 2].w, b[i].z, b[i].w);
            mma16(r1, wo[4 * i + 3].x, wo[4 * i + 3].y, wo[4 * i + 3].z, wo[4 * i + 3].w, b[i].z, b[i].w);
            if (i < 2) b[i + 2] = ldsm4(k.lw + R_OB + (i + 2) * 512);
#pragma unroll
            for (int m = NWO + NPF; m < 16; m++) if (i < 3 && i == ((OL >> (2 * (15 - m))) & 3)) wo[m] = lds128(k.lw + w5 + R_WO + (m - NWO) * 4096);
            if (i == 1) { i0 = rcp(__uint2float_rn(il.x)) * 2097152.f; i1 = rcp(__uint2float_rn(il.y)) * 2097152.f; }
            if (i == 2) {
                const uint32_t po = k.sp + z;
                dst = xregion(X, 0) + k.po + ((po >> 20) ^ ((po & X) << 8));
                asm volatile("" : "+l"(dst));
            }
            PIN(7);
        }
        const uint32_t tag = (s + 1) & 1;
#pragma unroll
        for (int i = 0; i < 4; i++) { r0[i] *= (i & 1) ? i1 : i0; r1[i] *= (i & 1) ? i1 : i0; }
        st_rlx128(dst, (pack2(r0[0], r0[2]) & ~1u) | tag,
                  pack2(r1[0], r1[2]), pack2(r0[1], r0[3]), pack2(r1[1], r1[3]));
        bar_arrive(NB_PART + X, 288);
#pragma unroll
        for (int t = 0; t < V_PRE; t++) if (!((VMASK >> t) & 1)) wv[t] = lds128(k.lw + w5 + R_WV + t * 4096);
        arrive_if(sb + R_BAR + (RB_GO + 2 * X + (s & 1)) * 8, (k.sp + z) & 0x1ff0, X ? s + 1 < hi : s >= lo);
    }
}

__device__ __forceinline__ void rec_fetch(const Params& p, uint32_t sb, int head, uint32_t rank, int which, int dst) {
#pragma unroll 1
    for (int j = 0; j < 8; j++) tma2d(sb + dst + j * 8192, &p.tm[which], head * 128 + (j >> 2) * 64, rank * 256 + (j & 3) * 64, sb + R_BAR + RB_INIT * 8);
}

__device__ __forceinline__ void rec_weights(const Params& p, uint32_t sb, int head, uint32_t rank, int w) {
    const int lane = __shfl_sync(0xffffffffu, threadIdx.x & 31, threadIdx.x & 31),
        g = lane >> 2, c = lane & 3;
    const int t = w & 3, WG = w >> 2;
    uint32_t wq[16][4], wk[16][4];
    uint4 wo[16], wv[16];
    const uint32_t woff = sb + WG * 32768 + (((lane >> 4) << 3) + (lane & 7)) * 128 + (((2 * t + ((lane >> 3) & 1)) ^ (lane & 7)) << 4);
    const uint32_t lw = sb + lane * 16;
    PROF2(threadIdx.x == 0, 3501);
    {
        const __nv_bfloat16* wp = p.Wo + (size_t)(head * 128 + 2 * c) * 512 + rank * 256 + w * 32 + g * 4;
#pragma unroll
        for (int ks = 0; ks < 8; ks++) {
            const uint2 r0 = *(const uint2*)(wp + (ks * 16) * 512), r1 = *(const uint2*)(wp + (ks * 16 + 1) * 512);
            const uint2 r2 = *(const uint2*)(wp + (ks * 16 + 8) * 512), r3 = *(const uint2*)(wp + (ks * 16 + 9) * 512);
            const uint4 f[2] = {make_uint4(__byte_perm(r0.x, r1.x, 0x5410), __byte_perm(r0.x, r1.x, 0x7632), __byte_perm(r2.x, r3.x, 0x5410), __byte_perm(r2.x, r3.x, 0x7632)),
                                make_uint4(__byte_perm(r0.y, r1.y, 0x5410), __byte_perm(r0.y, r1.y, 0x7632), __byte_perm(r2.y, r3.y, 0x5410), __byte_perm(r2.y, r3.y, 0x7632))};
#pragma unroll
            for (int h = 0; h < 2; h++) {
                const int m = 2 * ks + h;
                wo[m] = f[h];
            }
        }
    }
    PROF2(threadIdx.x == 0, 3502);
    mbar_wait(sb + R_BAR + RB_INIT * 8, 0);
    PROF2(threadIdx.x == 0, 3503);
#pragma unroll
    for (int ks = 0; ks < 16; ks++) {
        uint4 a = ldsm4t(woff + R_STQ + ks * 2048), b = ldsm4t(woff + R_STK + ks * 2048);
        wq[ks][0] = a.x; wq[ks][1] = a.y; wq[ks][2] = a.z; wq[ks][3] = a.w;
        wk[ks][0] = b.x; wk[ks][1] = b.y; wk[ks][2] = b.z; wk[ks][3] = b.w;
    }
    bar_sync(NB_W, 256);
#pragma unroll
    for (int m = 0; m < 16; m++)
        if (m < NPF || m >= NPF + NWO) sts128(lw + w * 512 + R_WO + (m < NPF ? m : m - NWO) * 4096, wo[m].x, wo[m].y, wo[m].z, wo[m].w);
#pragma unroll
    for (int i = 0; i < 16; i++) {
        wv[i] = ldsm4t(woff + R_STV + i * 2048);
        if (!((VMASK >> i) & 1)) sts128(lw + w * 512 + R_WV + i * 4096, wv[i].x, wv[i].y, wv[i].z, wv[i].w);
    }
    fence_async_smem();
    PROF2(threadIdx.x == 0, 3504);
    __syncthreads();
    cluster_sync();
    PROF2(threadIdx.x == 0, 3505);
    RecW k;
    {
        const int r = (w * 4 + (lane >> 3)) * 2 + rank;
        const uint32_t sl = lds32(sb + R_SEL + r * 4);
        k.po = (w * 8 + rank) * 512 + (head >> 1) * 16 + (head & 1) * 4;
        k.sp = (((lane >> 3) * 1024 + (sl & 1) * 256 + (lane & 4) * 2 + (lane & 3)) << 20) + (((sl >> 1) ^ sl) & 1) + (lane & 7) * 656 + (lane >> 3) * 128 + w * 16 +
               ((g < 4 ? (w * 4 + c) * 4 + g : w * 4 + c) << 13);
    }
    k.dp = mapa(sb, rank ^ 1) - sb;
    k.lw = lw;
    asm volatile("" : "+r"(k.lw));
    k.w = w;
    const int e0 = (p.chains & 1) ? 64 : 0, o1 = (p.chains & 2) ? p.lag : 1000, nit = (p.chains & 2) ? p.lag + 64 : e0;
    const uint32_t zero = p.zero;
    int it = 0, X = e0 ? 0 : 1;
#pragma unroll 1
    while (it < nit) {
        rec_step(k, sb, X, X ? it - o1 : it, zero, o1, e0 - o1, o1 + 1 - X, wq, wk, wv, wo);
        if (X == 0 && it >= o1) X = 1; else { it++; X = it < e0 ? 0 : 1; }
    }
}

__device__ __forceinline__ uint32_t mism(uint32_t a, uint32_t b, uint32_t t) {
    uint32_t d; asm("lop3.b32 %0,%1,%2,%3,0x7e;" : "=r"(d) : "r"(a), "r"(b), "r"(t)); return d;
}
__device__ __forceinline__ uint32_t or3(uint32_t a, uint32_t b, uint32_t c) {
    uint32_t d; asm("lop3.b32 %0,%1,%2,%3,0xfe;" : "=r"(d) : "r"(a), "r"(b), "r"(c)); return d;
}
#define X4(j) "=r"(x[j].x), "=r"(x[j].y), "=r"(x[j].z), "=r"(x[j].w)
#define X32 X4(0), X4(1), X4(2), X4(3), X4(4), X4(5), X4(6), X4(7)
template <bool TWO>
__device__ __forceinline__ void poll8(uint4* x, const uint4* src, uint32_t tag) {
    if (TWO) asm volatile(
        "{.reg .pred p,q<8>; .reg .b32 n,m<8>; .reg .b128 t<8>; mov.u32 n,0; ld.relaxed.gpu.global.b128 t0,[%32+0]; ld.relaxed.gpu.global.b128 t1,[%32+512]; "
        "ld.relaxed.gpu.global.b128 t2,[%32+1024]; ld.relaxed.gpu.global.b128 t3,[%32+1536]; ld.relaxed.gpu.global.b128 t4,[%32+2048]; "
        "ld.relaxed.gpu.global.b128 t5,[%32+2560]; ld.relaxed.gpu.global.b128 t6,[%32+3072]; ld.relaxed.gpu.global.b128 t7,[%32+3584]; \nL%=: "
        "mov.b128 {%0,%1,%2,%3},t0; mov.b128 {%4,%5,%6,%7},t1; mov.b128 {%8,%9,%10,%11},t2; mov.b128 {%12,%13,%14,%15},t3; mov.b128 {%16,%17,%18,%19},t4; "
        "mov.b128 {%20,%21,%22,%23},t5; mov.b128 {%24,%25,%26,%27},t6; mov.b128 {%28,%29,%30,%31},t7; lop3.b32 m0,%0,%2,%33,0x7e; lop3.b32 m1,%4,%6,%33,0x7e; "
        "lop3.b32 m2,%8,%10,%33,0x7e; lop3.b32 m3,%12,%14,%33,0x7e; lop3.b32 m4,%16,%18,%33,0x7e; lop3.b32 m5,%20,%22,%33,0x7e; lop3.b32 m6,%24,%26,%33,0x7e; "
        "lop3.b32 m7,%28,%30,%33,0x7e; "
        "{.reg .b32 a,b; lop3.b32 a,m0,m1,m2,0xfe; lop3.b32 b,m3,m4,m5,0xfe; lop3.b32 a,a,m6,m7,0xfe; lop3.b32 a,a,b,1,0xa8; setp.ne.u32 p,a,0;} "
        "vote.sync.any.pred p,p,0xffffffff; @!p bra.uni D%=; and.b32 m0,m0,1; setp.ne.u32 q0,m0,0; and.b32 m1,m1,1; setp.ne.u32 q1,m1,0; "
        "and.b32 m2,m2,1; setp.ne.u32 q2,m2,0; and.b32 m3,m3,1; setp.ne.u32 q3,m3,0; and.b32 m4,m4,1; setp.ne.u32 q4,m4,0; "
        "and.b32 m5,m5,1; setp.ne.u32 q5,m5,0; and.b32 m6,m6,1; setp.ne.u32 q6,m6,0; and.b32 m7,m7,1; setp.ne.u32 q7,m7,0; "
        "@q0 ld.relaxed.gpu.global.b128 t0,[%32+0]; @q1 ld.relaxed.gpu.global.b128 t1,[%32+512]; @q2 ld.relaxed.gpu.global.b128 t2,[%32+1024]; "
        "@q3 ld.relaxed.gpu.global.b128 t3,[%32+1536]; @q4 ld.relaxed.gpu.global.b128 t4,[%32+2048]; @q5 ld.relaxed.gpu.global.b128 t5,[%32+2560]; "
        "@q6 ld.relaxed.gpu.global.b128 t6,[%32+3072]; @q7 ld.relaxed.gpu.global.b128 t7,[%32+3584]; "
        "add.u32 n,n,1; setp.lt.u32 p,n,2000000; @p bra.uni L%=; trap;\nD%=: } " : X32 : "l"(src), "r"(tag) : "memory");
    else asm volatile(
        "{.reg .pred p,q<8>; .reg .b32 n,m<8>; .reg .b128 t<8>; mov.u32 n,0; ld.relaxed.gpu.global.b128 t0,[%32+0]; ld.relaxed.gpu.global.b128 t1,[%32+512]; "
        "ld.relaxed.gpu.global.b128 t2,[%32+1024]; ld.relaxed.gpu.global.b128 t3,[%32+1536]; ld.relaxed.gpu.global.b128 t4,[%32+2048]; "
        "ld.relaxed.gpu.global.b128 t5,[%32+2560]; ld.relaxed.gpu.global.b128 t6,[%32+3072]; ld.relaxed.gpu.global.b128 t7,[%32+3584]; \nL%=: "
        "mov.b128 {%0,%1,%2,%3},t0; mov.b128 {%4,%5,%6,%7},t1; mov.b128 {%8,%9,%10,%11},t2; mov.b128 {%12,%13,%14,%15},t3; mov.b128 {%16,%17,%18,%19},t4; "
        "mov.b128 {%20,%21,%22,%23},t5; mov.b128 {%24,%25,%26,%27},t6; mov.b128 {%28,%29,%30,%31},t7; lop3.b32 m0,%0,%4,%33,0x7e; lop3.b32 m1,%8,%12,%33,0x7e; "
        "lop3.b32 m2,%16,%20,%33,0x7e; lop3.b32 m3,%24,%28,%33,0x7e; {.reg .b32 a; lop3.b32 a,m0,m1,m2,0xfe; lop3.b32 a,a,m3,1,0xa8; setp.ne.u32 p,a,0;} "
        "vote.sync.any.pred p,p,0xffffffff; @!p bra.uni D%=; lop3.b32 m0,%0,%33,1,0x28; setp.ne.u32 q0,m0,0; lop3.b32 m1,%4,%33,1,0x28; setp.ne.u32 q1,m1,0; "
        "lop3.b32 m2,%8,%33,1,0x28; setp.ne.u32 q2,m2,0; lop3.b32 m3,%12,%33,1,0x28; setp.ne.u32 q3,m3,0; lop3.b32 m4,%16,%33,1,0x28; setp.ne.u32 q4,m4,0; "
        "lop3.b32 m5,%20,%33,1,0x28; setp.ne.u32 q5,m5,0; lop3.b32 m6,%24,%33,1,0x28; setp.ne.u32 q6,m6,0; lop3.b32 m7,%28,%33,1,0x28; setp.ne.u32 q7,m7,0; "
        "@q0 ld.relaxed.gpu.global.b128 t0,[%32+0]; @q1 ld.relaxed.gpu.global.b128 t1,[%32+512]; @q2 ld.relaxed.gpu.global.b128 t2,[%32+1024]; "
        "@q3 ld.relaxed.gpu.global.b128 t3,[%32+1536]; @q4 ld.relaxed.gpu.global.b128 t4,[%32+2048]; @q5 ld.relaxed.gpu.global.b128 t5,[%32+2560]; "
        "@q6 ld.relaxed.gpu.global.b128 t6,[%32+3072]; @q7 ld.relaxed.gpu.global.b128 t7,[%32+3584]; "
        "add.u32 n,n,1; setp.lt.u32 p,n,2000000; @p bra.uni L%=; trap;\nD%=: } " : X32 : "l"(src), "r"(tag) : "memory");
}

__device__ __forceinline__ void rec_comm(const Params& p, uint32_t sb, int X, int head, uint32_t rank) {
    const int lane = threadIdx.x & 31, g = lane >> 2, c = lane & 3;
    const int me = head * 2 + rank;
    const uint32_t mb = sb + R_M + X * 4096 + lane * 16;
    uint4 x[8];
#pragma unroll
    for (int j = 0; j < 8; j++) x[j] = *(const uint4*)(p.mem0 + (lane & 7) * 512 + rank * 256 + (j * 4 + (lane >> 3)) * 8);
    const uint32_t sl = lds32(sb + R_SEL + me * 4);
    const uint32_t o1 = ((sl >> X) & 1) * 256 + (c >> 1) * 16 + (g >> 2) * 8 + (c & 1) * 4 + (g & 3);
    const uint32_t o2 = ((sl >> (2 + X)) & 1) * 256 + lane;
    const uint32_t offs = __shfl_sync(0xffffffffu, o1 + (o2 << 10) + ((((c >> 1) * 256 + head * 8 + (g & 3) * 2 + (c & 1)) * 2 + (g >> 2)) << 20), lane);
    const uint32_t one = (g & 1) ? 0x3f800000u : 0x00003f80u, selA = (g & 2) ? 0u : one, selB = (g & 2) ? one : 0u;
    const uint32_t qb = sb + R_BAR + (RB_QK + X * 8) * 8;
    if (lane < 8) mbar_expect(qb + lane * 8, 768);
    __syncwarp();
#pragma unroll
    for (int j = 0; j < 8; j++) sts128(mb + j * 512, x[j].x, x[j].y, x[j].z, x[j].w);
#pragma unroll 1
    for (int s = 0;; s++) {
        bar_arrive(NB_MFULL + X, 288);
        PROF(lane == 0, X * 64 + s);
        const uint32_t of = offs + (s & p.zero);
        const uint4* src = xregion(X, me) + (of & 1023);
        uint2* mdst = (uint2*)xregion(X, 64 + rank) + (of >> 20);
        asm volatile("" : "+l"(src), "+l"(mdst));
        bar_sync(NB_PART + X, 288);
        if (s == 63) break;
        const uint32_t tag = (s + 1) & 1;
        asm volatile("{.reg .pred p; setp.lt.u32 p,%0,%1; @p mbarrier.arrive.expect_tx.shared::cta.b64 _,[%0],768;}"
                     ::"r"(((mb + (s & p.zero)) >> 1) + (qb - ((sb + R_M + X * 4096) >> 1))), "r"(qb + 64) : "memory");
        spin(D1);
        poll8<false>(x, src, tag);
        float a[4][4];
#pragma unroll
        for (int j = 0; j < 8; j++) {
            if (j < 4) a[j][0] = a[j][1] = a[j][2] = a[j][3] = 0;
            mma16(a[j & 3], x[j].x, x[j].y, x[j].z, x[j].w, selA, selB);
        }
#pragma unroll
        for (int i = 0; i < 4; i++) a[0][i] = (a[0][i] + a[1][i]) + (a[2][i] + a[3][i]);
        const uint32_t m0 = (pack2(a[0][0], a[0][1]) & ~1u) | tag, m1 = pack2(a[0][2], a[0][3]);
        asm volatile("st.relaxed.gpu.global.b64 [%0],%1;" ::"l"(mdst), "l"(((uint64_t)m1 << 32) | m0) : "memory");
        src = xregion(X, 64 + rank) + ((of >> 10) & 1023);
        asm volatile("" : "+l"(src));
        spin(D2);
        poll8<true>(x, src, tag);
#pragma unroll
        for (int j = 0; j < 8; j++) sts128(mb + j * 512, x[j].x, x[j].y, x[j].z, x[j].w);
    }
}

template <int MT>
__device__ __forceinline__ void xattn(uint32_t l16, uint32_t l8, uint32_t os, int g, int c) {
    constexpr int NT = 3 + 2 * MT, XUN = XU;
    float S[NT][4];
#pragma unroll
    for (int i = 0; i < NT; i++) S[i][0] = S[i][1] = S[i][2] = S[i][3] = 0;
#pragma unroll XUN
    for (int ks = 0; ks < 8; ks++) {
        const uint4 q = lds128(l16 + SL_Q + ks * 512);
        const uint2 u = lds64(l8 + SL_KM + ks * 256);
        mma16(S[0], q.x, q.y, q.z, q.w, u.x, u.y);
#pragma unroll
        for (int m = 0; m <= MT; m++) {
            const uint4 kk = lds128(l16 + m * 4096 + ks * 512);
            mma16(S[1 + 2 * m], q.x, q.y, q.z, q.w, kk.x, kk.z); mma16(S[2 + 2 * m], q.x, q.y, q.z, q.w, kk.y, kk.w);
        }
    }
    const float NEG = -__int_as_float(0x7f800000);
    if (2 * c > g) { S[NT - 2][0] = NEG; S[NT - 1][2] = NEG; }
    if (2 * c + 1 > g) { S[NT - 2][1] = NEG; S[NT - 1][3] = NEG; }
    S[NT - 1][0] = S[NT - 1][1] = NEG;
    float m0 = fmaxf(S[0][0], S[0][1]), m1 = fmaxf(S[0][2], S[0][3]);
#pragma unroll
    for (int i = 1; i < NT; i++) { if (i < NT - 1) m0 = fmaxf(m0, fmaxf(S[i][0], S[i][1])); m1 = fmaxf(m1, fmaxf(S[i][2], S[i][3])); }
    m0 = fmaxf(m0, __shfl_xor_sync(0xffffffffu, m0, 1)); m1 = fmaxf(m1, __shfl_xor_sync(0xffffffffu, m1, 1));
    m0 = fmaxf(m0, __shfl_xor_sync(0xffffffffu, m0, 2)); m1 = fmaxf(m1, __shfl_xor_sync(0xffffffffu, m1, 2));
    m0 *= -SC_LOG2E; m1 *= -SC_LOG2E;
    float l0 = 0, l1 = 0;
#pragma unroll
    for (int i = 0; i < NT; i++) {
        if (i < NT - 1) { S[i][0] = ex2(fmaf(S[i][0], SC_LOG2E, m0)); S[i][1] = ex2(fmaf(S[i][1], SC_LOG2E, m0)); l0 += S[i][0] + S[i][1]; }
        S[i][2] = ex2(fmaf(S[i][2], SC_LOG2E, m1)); S[i][3] = ex2(fmaf(S[i][3], SC_LOG2E, m1)); l1 += S[i][2] + S[i][3];
    }
    l0 += __shfl_xor_sync(0xffffffffu, l0, 1); l1 += __shfl_xor_sync(0xffffffffu, l1, 1);
    l0 += __shfl_xor_sync(0xffffffffu, l0, 2); l1 += __shfl_xor_sync(0xffffffffu, l1, 2);
    uint2 vm = lds64(l8 + SL_VM);
    uint4 v[2];
#pragma unroll
    for (int m = 0; m <= MT; m++) v[m] = lds128(l16 + SL_V + m * 4096);
    l0 = rcp(l0); l1 = rcp(l1);
    uint32_t P[NT][2];
#pragma unroll
    for (int i = 0; i < NT; i++) { P[i][0] = i < NT - 1 ? pack2(S[i][0] * l0, S[i][1] * l0) : 0u; P[i][1] = pack2(S[i][2] * l1, S[i][3] * l1); }
#pragma unroll
    for (int et = 0; et < 8; et++) {
        float a[4] = {0, 0, 0, 0}, b[4] = {0, 0, 0, 0};
        const uint2 um = vm;
        const uint4 u[2] = {v[0], v[MT]};
        if (et < 7) {
            vm = lds64(l8 + SL_VM + et * 256 + 256);
#pragma unroll
            for (int m = 0; m <= MT; m++) v[m] = lds128(l16 + SL_V + m * 4096 + et * 512 + 512);
            PIN(11);
        }
        mma8(a, um.x, um.y, P[0][0]); mma8(b, um.x, um.y, P[0][1]);
#pragma unroll
        for (int m = 0; m <= MT; m++) {
            mma16(a, u[m].x, u[m].y, u[m].z, u[m].w, P[1 + 2 * m][0], P[2 + 2 * m][0]); mma16(b, u[m].x, u[m].y, u[m].z, u[m].w, P[1 + 2 * m][1], P[2 + 2 * m][1]);
        }
        asm volatile("stmatrix.sync.aligned.m8n8.x4.trans.shared.b16 [%0],{%1,%2,%3,%4};" ::"r"(os + (et >> 2) * 2048 + (et & 3) * 256),
                     "r"(pack2(a[0], a[1])), "r"(pack2(a[2], a[3])), "r"(pack2(b[0], b[1])), "r"(pack2(b[2], b[3])) : "memory");
    }
}

__device__ __forceinline__ void rec_tiles(uint32_t sb, int X, int head, uint32_t rank, int& nxt, int lim, int need) {
#pragma unroll 1
    while (nxt <= lim) {
        if ((nxt & 1) == 0) {
            unsigned v; int n = 0;
            while (true) {
                asm volatile("ld.relaxed.gpu.global.u32 %0,[%1];" : "=r"(v) : "l"(cnt_ptr(C_QKV + X * 32 + (nxt >> 1))) : "memory");
                if (__all_sync(0xffffffffu, v >= 2 * NQ)) break;
                if (nxt > need) return;
                if (++n > 3000000) __trap();
            }
        }
        if (elect()) {
            const uint32_t bar = sb + R_BAR + (RB_XFULL + X * 2 + (nxt & 1)) * 8, dst = sb + R_SL + (X * 2 + (nxt & 1)) * SLOT;
            const uint4* src = g_qkv + (size_t)((X * 64 + nxt) * 32 + head) * 1536;
            mbar_expect(bar, 20480);
            bulk_g2s_mc(dst + rank * 8192, src + 512 + rank * 512, 8192, bar, POL_LAST);
            bulk_g2s(dst + SL_Q, src + (rank ^ X) * 256, 4096, bar, POL_LAST);
        }
        __syncwarp();
        nxt++;
    }
}

__device__ __forceinline__ void rec_attn(const Params& p, uint32_t sb, int X, int head, uint32_t rank) {
    const int lane = __shfl_sync(0xffffffffu, threadIdx.x & 31, threadIdx.x & 31), g = lane >> 2, c = lane & 3;
    const int mt = rank ^ X;
    const uint32_t dp = mapa(sb, rank ^ 1) - sb;
    int nxt = 0;
    rec_tiles(sb, X, head, rank, nxt, 1, 0);
#pragma unroll 1
    for (int s = 0; s < 64; s++) {
        const uint32_t so = sb + R_SL + (X * 2 + (s & 1)) * SLOT;
        while (nxt <= min(s + 1, 63)) {
            uint32_t ok;
            asm volatile("{.reg .pred p; mbarrier.test_wait.parity.shared::cta.b64 p,[%1],%2; selp.u32 %0,1,0,p;}" : "=r"(ok) : "r"(sb + R_BAR + (RB_GO + X * 2 + (s & 1)) * 8), "r"((s >> 1) & 1) : "memory");
            if (__any_sync(0xffffffffu, ok)) break;
            rec_tiles(sb, X, head, rank, nxt, s + 1, -1);
        }
        mbar_wait(sb + R_BAR + (RB_GO + X * 2 + (s & 1)) * 8, (s >> 1) & 1);
        if (elect()) asm volatile("cp.async.bulk.wait_group.read 0;" ::: "memory");
        __syncwarp();
        const uint32_t os = sb + R_OS + X * 4096 + (lane >> 4) * 1024 + (lane & 15) * 16;
        if (mt) xattn<1>(so + lane * 16, so + lane * 8, os, g, c); else xattn<0>(so + lane * 16, so + lane * 8, os, g, c);
        fence_async_smem();
        __syncwarp();
        const uint32_t svb = sb + R_BAR + (RB_SV + X * 2 + (s & 1)) * 8;
        if (elect()) {
            mbar_arrive(svb); mbar_arrive_cluster(svb + dp);
            const uint64_t pol = POL_N;
#pragma unroll
            for (int kb = 0; kb < 2; kb++)
                asm volatile("cp.async.bulk.global.shared::cta.bulk_group.L2::cache_hint [%0],[%1],%2,%3;" ::"l"(g_o + ((X * 32 + (s >> 1)) * 64 + head * 2 + kb) * 512 + ((s & 1) * 4 + mt * 2) * 64),
                             "r"(sb + R_OS + X * 4096 + kb * 2048), "r"(2048), "l"(pol) : "memory");
            asm volatile("cp.async.bulk.commit_group;" ::: "memory");
        }
        __syncwarp();
        if (s & 1) {
            if (elect()) { asm volatile("cp.async.bulk.wait_group 0;" ::: "memory"); red_relaxed(cnt_ptr(C_O + (X * 32 + (s >> 1)) * 4 + (head >> 3)), 1); }
            __syncwarp();
        }
        rec_tiles(sb, X, head, rank, nxt, min(s + 1, 63), s + 1);
        mbar_wait(svb, (s >> 1) & 1);
        rec_tiles(sb, X, head, rank, nxt, min(s + 2, 63), -1);
    }
}

__device__ __forceinline__ uint32_t timed_clear(unsigned* r, int lane) {
    uint32_t v = 0;
    const uint32_t t0 = clk32();
    asm volatile("{.reg .pred p; setp.eq.u32 p,%2,0; @p atom.relaxed.gpu.global.exch.b32 %0,[%1],0;}" : "+r"(v) : "l"(r), "r"(lane) : "memory");
    v = __shfl_sync(0xffffffffu, v, 0);
    asm volatile("{.reg .pred p; setp.eq.u32 p,%0,0x5a5a5a5b; @p nanosleep.u32 1;}" ::"r"(v) : "memory");
    return clk32() - t0;
}
__device__ __forceinline__ void rec_slots(int me, int w) {
    const int lane = threadIdx.x & 31;
    uint4* r = xregion(w & 1, (w & 2) ? 64 + (me & 1) : me) + ((w & 2) ? (me >> 1) * 8 : 0);
#pragma unroll 1
    for (int i = lane; i < ((w & 2) ? 8 : 256); i += 32) r[i] = r[i + 256] = make_uint4(0, 0, 0, 0);
    __syncwarp();
    uint32_t b0 = ~0u, b1 = ~0u;
#pragma unroll 1
    for (int i = 0; i < NPRB; i++) { b0 = min(b0, timed_clear((unsigned*)r, lane)); b1 = min(b1, timed_clear((unsigned*)(r + 256), lane)); }
    if (lane == 0) ((uint8_t*)g_sel)[me * 4 + w] = (b1 < b0) << w;
}

__device__ __forceinline__ void rec_init(uint32_t sb) {
    const uint32_t b = sb + R_BAR;
    const int i = threadIdx.x & 31;
    mbar_init(b + i * 8, i >= RB_SV ? 2 : 1);
    if (i == RB_INIT) mbar_expect(b + RB_INIT * 8, 196608);
    asm volatile("fence.mbarrier_init.release.cluster;" ::: "memory");
}
constexpr int G_BAR = B_BAR;
enum { GB_FULL = 0  , GB_EMPTY = 8  , GB_RS = 16, GB_SS = 17, GB_LAG = 18, GB_FREE = 19, GB_DONE = 20  , GB_N = 24 };
constexpr int Q_PRE = 8;
constexpr int NQRS = 2 * NQ - 64;
__device__ __forceinline__ void gemm_init(uint32_t sb, bool op) {
    const int i = threadIdx.x & 31;
    if (i < GB_N) mbar_init(sb + G_BAR + i * 8, i >= GB_DONE ? 4 : i == GB_FREE ? 8 : (i >= GB_EMPTY && i < GB_RS) ? 2 : 1);
    if (i == GB_RS) mbar_expect(sb + G_BAR + i * 8, op ? 131072 : 98304);
    if (i == GB_SS) mbar_expect(sb + G_BAR + i * 8, op ? 131072 : 163840);
    asm volatile("fence.mbarrier_init.release.cluster;" ::: "memory");
}
__device__ __forceinline__ int qkv_blk(int id, int j) { return NQRS * 4 + id * 10 + j; }
__device__ __forceinline__ void qkv_fetch(const Params& p, uint32_t sb, int id, int j0, int j1) {
#pragma unroll 1
    for (int j = j0 * 2; j < j1 * 2; j++) {
        const int blk = min(qkv_blk(id, j >> 1), 511);
        tma2d(sb + j * 8192, &p.tn[blk >> 8], (blk & 255) * 16, (j & 1) * 256, sb + G_BAR + GB_SS * 8);
    }
}
__device__ __forceinline__ void qkv_stage(const Params& p, uint32_t dst, uint32_t bar, int id, int k0, int nk) {
#pragma unroll 1
    for (int j = 0; j < 2 * nk; j++) {
        const int u = id * 2 + (j >= nk);
        tma2d(dst + j * 8192, &p.tm[u < 64 ? 2 : 0], (u & 63) * 64, (k0 + (j >= nk ? j - nk : j)) * 64, bar);
    }
}
__device__ __forceinline__ void op_fetch(const Params& p, uint32_t sb, int id, int half) {
#pragma unroll 1
    for (int j = 0; j < 16; j++) tma2d(sb + j * 8192, &p.tm[4], ((id * 2 + (j >> 3)) & 7) * 64, (id >> 2) * 1024 + (j & 7) * 128 + half * 64, sb + G_BAR + (GB_RS + half) * 8);
}
template <bool OP>
__device__ __forceinline__ void gemm_producer(const Params& p, uint32_t sb, int id) {
    constexpr int NS = OP ? 6 : 8, SB = OP ? 16384 : 8192, RB = OP ? 131072 : 163840;
    if (!elect()) return;
    mbar_wait(sb + G_BAR + GB_FREE * 8, 0);
    if (OP) op_fetch(p, sb, id, 1);
    else {
        mbar_expect(sb + G_BAR + GB_RS * 8, 32768);
        qkv_stage(p, sb + 196608, sb + G_BAR + GB_RS * 8, id, 6, 2);
        qkv_fetch(p, sb, id, Q_PRE, 10);
        mbar_wait(sb + G_BAR + GB_FREE * 8, 1);
    }
    wait_cnt(g_gate, lds32(sb + S_GATE));
    int st = 0; uint32_t ph = 1;
#pragma unroll 1
    for (int n = 0; n < p.nl[OP]; n++) {
        const int e = p.list[OP][n];
        wait_cnt(OP ? cnt_ptr(C_O + e * 4 + (id >> 2)) : cnt_ptr(C_XN + e), 16);
        PROF(true, 1024 + n * 4);
        const uint4* src = OP ? g_o + (e * 64 + (id >> 2) * 16) * 512 : g_xn + e * 4096;
#pragma unroll 1
        for (int s = 0; s < 8; s++) {
            mbar_wait(sb + G_BAR + (GB_EMPTY + st) * 8, ph);
            mbar_expect(sb + G_BAR + (GB_FULL + st) * 8, SB);
            bulk_g2s(sb + RB + st * SB, src + s * (SB / 16), SB, sb + G_BAR + (GB_FULL + st) * 8, POL_N);
            if (++st == NS) { st = 0; ph ^= 1; }
        }
    }
}
__device__ __forceinline__ void qkv_release(const Params& p, uint32_t sb) {
    if (!elect()) return;
#pragma unroll 1
    for (int n = 0; n < 2 * p.nl[0]; n++) {
        const int e = p.list[0][n >> 1];
        mbar_wait(sb + G_BAR + (GB_DONE + (n & 3)) * 8, (n >> 2) & 1);
        red_release(cnt_ptr(C_QKV + e), 1);
        PROF(n & 1, 1024 + (n >> 1) * 4 + 3);
    }
}
__device__ __forceinline__ void op_permute(uint32_t sb) {
#pragma unroll 2
    for (int i = threadIdx.x; i < 4096; i += 256) {
        const uint32_t a = sb + i * 32 + ((i >> 2) & 1) * 16, b = a ^ 16;
        const uint4 x = lds128(a), y = lds128(b);
        sts128(a, __byte_perm(x.x, x.y, 0x5410), __byte_perm(x.z, x.w, 0x5410), __byte_perm(y.x, y.y, 0x5410), __byte_perm(y.z, y.w, 0x5410));
        sts128(b, __byte_perm(x.x, x.y, 0x7632), __byte_perm(x.z, x.w, 0x7632), __byte_perm(y.x, y.y, 0x7632), __byte_perm(y.z, y.w, 0x7632));
    }
    fence_async_smem();
    bar_sync(1, 256);
}
template <bool OP>
__device__ __forceinline__ void gemm_consumer(const Params& p, uint32_t sb, int id, int w) {
    constexpr int NS = OP ? 6 : 8, SB = OP ? 16384 : 8192, RB = OP ? 131072 : 163840;
    const int lane = threadIdx.x & 31, wg = w >> 2, t = w & 3, u = id * 2 + wg;
    uint32_t a[128];
    mbar_wait(sb + G_BAR + GB_RS * 8, 0);
    PROF2(threadIdx.x == 0, 3501);
    if (OP) op_permute(sb);
    const uint32_t wo = sb + (((lane >> 4) << 3) + (lane & 7)) * 128 + (((2 * t + ((lane >> 3) & 1)) ^ (lane & 7)) << 4);
#pragma unroll
    for (int ks = 0; ks < 32; ks++) {
        const uint4 v = ldsm4t(wo + ks * 2048 + (OP ? wg * 65536 : ks < 24 ? 131072 + wg * 49152 : 196608 - 49152 + wg * 16384));
        a[ks * 4] = v.x; a[ks * 4 + 1] = v.y; a[ks * 4 + 2] = v.z; a[ks * 4 + 3] = v.w;
        if (ks == 31 || (!OP && ks == 23)) {
            fence_async_smem();
            __syncwarp();
            if (lane == 0) mbar_arrive(sb + G_BAR + GB_FREE * 8);
            if (ks == 23) mbar_wait(sb + G_BAR + GB_RS * 8, 1);
        }
    }
    PROF2(threadIdx.x == 0, 3502);
    mbar_wait(sb + G_BAR + GB_SS * 8, 0);
    if (OP) op_permute(sb);
    PROF2(threadIdx.x == 0, 3503);
    const uint32_t tag = OP ? lds32(sb + S_TAG) : 0;
    float c0[32], c1[OP ? 32 : 40];
    int st = 0; uint32_t ph = 0;
    const bool el = (threadIdx.x & 127) == 0;
#pragma unroll 1
    for (int n = 0; n < p.nl[OP]; n++) {
        int prev = 0;
        const uint32_t wb = sb + wg * (OP ? 65536 : 81920) + (n & p.zero);
        const uint64_t dw = OP ? mkdesc(wb, 0, 1024, 1) : mkdesc(wb, 16384, 256, 3);
        if ((!OP || OLAG) && wg) mbar_wait(sb + G_BAR + GB_LAG * 8, n & 1);
#pragma unroll
        for (int s = 0; s < 8; s++) {
            mbar_wait(sb + G_BAR + (GB_FULL + st) * 8, ph);
            const uint64_t dx = mkdesc(sb + RB + st * SB, 128, 1024, 0);
            wg_fence();
#pragma unroll
            for (int kk = 0; kk < 4; kk++) {
                const int ks = s * 4 + kk;
                if (ks == 0) { wgmma64_rs<0>(c0, a, dx); if (OP) wgmma64_ta<0>(c1, dw, dx + 512); else wgmma80_tb<0>(c1, dx, dw); }
                else { wgmma64_rs<1>(c0, a + ks * 4, dx + kk * 16); if (OP) wgmma64_ta<1>(c1, dw + ks * 128, dx + 512 + kk * 16); else wgmma80_tb<1>(c1, dx + kk * 16, dw + ks * 32); }
            }
            wg_commit();
            if (s) {
                wg_wait<1>();
                if (el) { mbar_arrive(sb + G_BAR + (GB_EMPTY + prev) * 8); if (s == (OP ? OLAG : QLAG) && !wg) mbar_arrive(sb + G_BAR + GB_LAG * 8); }
            }
            prev = st;
            if (++st == NS) { st = 0; ph ^= 1; }
        }
        const int e = p.list[OP][n];
        wg_wait<0>();
        if (el) mbar_arrive(sb + G_BAR + (GB_EMPTY + prev) * 8);
        PROF(threadIdx.x == 128, 1024 + n * 4 + 1);
        if (OP) {
            uint4* dst = g_pp + (e * 4 + (id >> 2)) * 4096 + ((u & 7) * 32 + t * 8) * 16 + (lane >> 2) * 16 + (lane & 3);
#pragma unroll
            for (int j = 0; j < 4; j++) {
                const float* x = c0 + j * 8; const float* y = c1 + j * 8;
                st_rlx128(dst + j * 4, (pack2(x[0] + y[0], x[1] + y[1]) & ~1u) | tag, pack2(x[2] + y[2], x[3] + y[3]), (pack2(x[4] + y[4], x[5] + y[5]) & ~1u) | tag, pack2(x[6] + y[6], x[7] + y[7]));
            }
            if (lane == 0) red_relaxed(cnt_ptr(C_PP + e * 8 + (u & 7)), 1);
            PROF(threadIdx.x == 128, 1024 + n * 4 + 3);
        } else {
            uint4* dst = g_qkv + (size_t)e * 2 * 32 * 1536 + lane;
            const uint64_t pol = POL_N;
#pragma unroll
            for (int j = 0; j < 4; j++) {
                const float* x = c0 + j * 8;
                uint4 v = make_uint4(pack2(x[0], x[1]), pack2(x[2], x[3]), pack2(x[4], x[5]), pack2(x[6], x[7]));
                if (u >= 64) v = make_uint4(movm(v.x), movm(v.z), movm(v.y), movm(v.w));
                stg128(dst + (((j >> 1) * 32 + ((u & 63) >> 1)) * 1536 + (u < 64 ? 1024 : 0) + (j & 1) * 256 + ((u & 1) * 4 + t) * 32), v, pol);
            }
#pragma unroll
            for (int j = 0; j < 5; j++) {
                const float* x = c1 + (OP ? 0 : j * 8);
                const int blk = qkv_blk(id, wg * 5 + j);
                if (blk < 512) stg128(dst + (((t >> 1) * 32 + ((blk >> 3) & 31)) * 1536 + (blk >> 8) * 512 + (t & 1) * 256 + (blk & 7) * 32),
                                      make_uint4(pack2(x[0], x[1]), pack2(x[2], x[3]), pack2(x[4], x[5]), pack2(x[6], x[7])), pol);
            }
        }
        __syncwarp();
        if (!OP && lane == 0) mbar_arrive(sb + G_BAR + (GB_DONE + (n & 1) * 2 + wg) * 8);
        PROF(threadIdx.x == 128, 1024 + n * 4 + 2);
    }
}

template <int NP, bool MMA>
__device__ __forceinline__ void sum_partials(float* x, const uint2* src, const uint32_t* r0, const uint32_t* r1, uint32_t idm, uint32_t tag, bool on) {
    uint2 v[4][NP];
    int n = 0;
    while (true) {
        uint32_t bad = 0;
#pragma unroll
        for (int s = 0; s < 4; s++)
#pragma unroll
            for (int i = 0; i < NP; i++)
                asm volatile("{.reg .pred p; .reg .b64 t; setp.ne.u32 p,%4,0; mov.b64 t,0; @p ld.relaxed.gpu.global.L2::cache_hint.b64 t,[%2],%3; mov.b64 {%0,%1},t;}"
                             : "=r"(v[s][i].x), "=r"(v[s][i].y) : "l"(src + s * 8192 + i * 32), "l"(POL_LAST), "r"((uint32_t)on) : "memory");
#pragma unroll
        for (int s = 0; s < 4; s++) bad = or3(bad, mism(v[s][0].x, v[s][1].x, tag), mism(v[s][NP - 2].x, v[s][NP - 1].x, tag));
        if (!__any_sync(0xffffffffu, (bad & 1) && on)) break;
        if (++n > 2000000) __trap();
    }
#pragma unroll
    for (int i = 0; i < NP; i++) {
        uint32_t a, b;
        if (MMA) {
            float t[4] = {0, 0, 0, 0};
            mma16(t, v[0][i].x, v[0][i].y, v[1][i].x, v[1][i].y, idm, idm); mma16(t, v[2][i].x, v[2][i].y, v[3][i].x, v[3][i].y, idm, idm);
            a = pack2(t[0], t[2]); b = pack2(t[1], t[3]);
        } else {
            a = pack2((blo(v[0][i].x) + blo(v[1][i].x)) + (blo(v[2][i].x) + blo(v[3][i].x)), (blo(v[0][i].y) + blo(v[1][i].y)) + (blo(v[2][i].y) + blo(v[3][i].y)));
            b = pack2((bhi(v[0][i].x) + bhi(v[1][i].x)) + (bhi(v[2][i].x) + bhi(v[3][i].x)), (bhi(v[0][i].y) + bhi(v[1][i].y)) + (bhi(v[2][i].y) + bhi(v[3][i].y)));
        }
        const uint32_t s0 = hadd2(a, r0[i]), s1 = hadd2(b, r1[i]);
        x[4 * i] = blo(s0); x[4 * i + 2] = bhi(s0); x[4 * i + 1] = blo(s1); x[4 * i + 3] = bhi(s1);
    }
}
__device__ __forceinline__ const uint2* pp_src(int e, int tile, int lane) { return (const uint2*)g_pp + e * 32768 + tile * 128 + (lane >> 3) * 8 + (lane & 3) * 2 + ((lane >> 2) & 1); }

__device__ __forceinline__ void fin_warp(const Params& p, uint32_t sb, int id0) {
    wait_slow_warp(g_gate, lds32(sb + S_GATE));
#pragma unroll 1
    for (int e = id0 < 2 * NQ ? 32 : FJ; e < 64; e++)
#pragma unroll 1
    for (int id = id0; id < (e < FJ ? 128 : id0 + 1); id += 2 * NQ) {
        const int grp = (id & ~3) + (threadIdx.x & 3), tp = (id & 3) * 8 + ((threadIdx.x & 31) >> 2);
        wait_slow_warp(cnt_ptr(C_XN + e), 16);
        const uint4 r = ldcg128(g_x + ((128 + grp) * XP + (e - 32) * 32 + tp));
        if (e < 63) wait_slow_warp(cnt_ptr(C_PP + e * 8 + (id >> 4)), 16); else wait_slow_warp(cnt_ptr(C_O + 63 * 4), 16);
        wait_flag_warp(cnt_ptr(C_PP + e * 8 + (id >> 4)), 16);
        const uint32_t a[2] = {r.x, r.y}, b[2] = {r.z, r.w};
        float x[8];
        sum_partials<2, false>(x, pp_src(e, 0, tp) + grp * 64, a, b, 0, lds32(sb + S_TAG), true);
        uint2* dst = (uint2*)p.out + ((e - 32) * 64 + tp * 2) * 128 + grp;
#pragma unroll
        for (int t = 0; t < 2; t++)
            dst[t * 128] = make_uint2(__byte_perm(__float_as_uint(x[t]), __float_as_uint(x[2 + t]), 0x7632), __byte_perm(__float_as_uint(x[4 + t]), __float_as_uint(x[6 + t]), 0x7632));
        PROF((threadIdx.x & 31) == 0, 1536 + e);
    }
}

constexpr int PROW = 272, UROW = 2560, UPRE = 512;
constexpr int C_UR = 0  , C_TB = 65536  , C_BG = C_TB + 51200,
              CB_M = 7168, CB_U = CB_M + 1792, CB_BIG = CB_U + 2048, C_ST = C_BG + 8 * CB_BIG  ;
static_assert(C_ST + 4736 <= B_BAR, "smem map");
enum { CB_TB = 0, CB_UF = 1  , CB_CF = 5  , CB_LD = 9   };
__device__ __forceinline__ void conv_init(uint32_t sb, bool spare) {
    const int i = threadIdx.x & 31;
    mbar_init(sb + B_BAR + i * 8, (i >= CB_UF && i < CB_CF && !spare) ? 2 : 1);
    if (i == CB_TB && !spare) mbar_expect(sb + B_BAR + i * 8, 51200);
    asm volatile("fence.mbarrier_init.release.cluster;" ::: "memory");
}
__device__ __forceinline__ void mma_q(float* c, const uint32_t* a, const uint4& q) {
    mma16(c, a[0], a[1], a[2], a[3], q.x, q.y); mma16(c, a[4], a[5], a[6], a[7], q.z, q.w);
}
__device__ __forceinline__ uint2 ld_acc(const uint2* p, bool on) {
    uint2 v = make_uint2(0, 0);
    asm volatile("{.reg .pred p; setp.ne.u32 p,%3,0; @p ld.global.cg.v2.u32 {%0,%1},[%2];}" : "+r"(v.x), "+r"(v.y) : "l"(p), "r"((uint32_t)on) : "memory");
    return v;
}
__device__ __forceinline__ void add_acc(float* c, uint2 v) { c[0] += blo(v.x); c[1] += bhi(v.x); c[2] += blo(v.y); c[3] += bhi(v.y); }
__device__ __forceinline__ void st_acc(uint2* p, const float* c) { *p = make_uint2(pack2(c[0], c[1]), pack2(c[2], c[3])); }
__device__ __forceinline__ float sum8(const uint4* v, int k) {
#define VK(i) __uint_as_float(k == 0 ? v[i].x : k == 1 ? v[i].y : k == 2 ? v[i].z : v[i].w)
    return ((VK(0) + VK(1)) + (VK(2) + VK(3))) + ((VK(4) + VK(5)) + (VK(6) + VK(7)));
}
template <int XW>
__device__ __forceinline__ void stats_send(uint32_t l16, const float* x, uint4* gs, int q, int w) {
    float s0 = 0, s1 = 0, m0 = 0, m1 = 0;
#pragma unroll
    for (int i = 0; i < 8; i++) { s0 += x[2 * i]; s1 += x[2 * i + 1]; m0 = fmaf(x[2 * i], x[2 * i], m0); m1 = fmaf(x[2 * i + 1], x[2 * i + 1], m1); }
    sts128(l16 + C_ST + w * 512, __float_as_uint(s0), __float_as_uint(m0), __float_as_uint(s1), __float_as_uint(m1));
    if (w == XW) {
        bar_sync(2, 256);
        uint4 v[8];
#pragma unroll
        for (int i = 0; i < 8; i++) v[i] = lds128(l16 + C_ST + i * 512);
        st_rlx128(gs + q * 32, __float_as_uint(sum8(v, 0)), __float_as_uint(sum8(v, 1)) & 0x7fffffffu, __float_as_uint(sum8(v, 2)), __float_as_uint(sum8(v, 3)));
    } else bar_arrive(2, 256);
}
template <int XW>
__device__ __forceinline__ float4 stats_recv(uint32_t l16, const uint4* gs, int w) {
    if (w == XW) {
        uint4 v[8];
        int n = 0;
        while (true) {
            uint32_t bad = 0;
#pragma unroll
            for (int i = 0; i < 8; i++) v[i] = ld_rlx128(gs + i * 32);
#pragma unroll
            for (int i = 0; i < 8; i++) bad |= v[i].y;
            if (!__any_sync(0xffffffffu, bad >> 31)) break;
            if (++n > 2000000) __trap();
        }
        const float s0 = sum8(v, 0) * (1.f / 512.f), s1 = sum8(v, 2) * (1.f / 512.f);
        const float2 l0 = ln_finish(s0, fmaxf(fmaf(sum8(v, 1), 1.f / 512.f, -s0 * s0), 0.f)), l1 = ln_finish(s1, fmaxf(fmaf(sum8(v, 3), 1.f / 512.f, -s1 * s1), 0.f));
        sts128(l16 + C_ST + 4096, __float_as_uint(l0.x), __float_as_uint(rcp(l0.y)), __float_as_uint(l1.x), __float_as_uint(rcp(l1.y)));
    }
    bar_sync(3, 256);
    const uint4 r = lds128(l16 + C_ST + 4096);
    return make_float4(__uint_as_float(r.x), __uint_as_float(r.y), __uint_as_float(r.z), __uint_as_float(r.w));
}

__device__ __forceinline__ void conv_near(float (*acc)[4], uint32_t ta, uint32_t qa) {
    uint32_t a[9][8];
    uint4 x[9];
#pragma unroll
    for (int k = 0; k < 9; k++) {
        if (k < 8) {
            x[k] = ldsm4(qa + k * 1024);
#pragma unroll
            for (int j = 0; j < 8; j++) a[k][j] = lds32(ta + k * 800 + j * 32);
        }
        if (k) mma_q(acc[k - 1], a[k - 1], x[k - 1]);
        PIN(13);
    }
}
template <int K0>
__device__ __forceinline__ void conv_pair(float (*acc)[4], float (*pend)[4], uint32_t ta, uint32_t q0, uint32_t q1, uint32_t q2) {
    uint32_t a[9][8];
    uint4 x[9], y[5];
#pragma unroll
    for (int n = 0; n < 9; n++) {
        if (n < 8) {
            const int k = K0 + (n >> 1);
            if (!(n & 1)) y[n >> 1] = ldsm4(q1 + k * 1024);
            x[n] = ldsm4(((n & 1) ? q0 : q2) + k * 1024);
#pragma unroll
            for (int j = 0; j < 8; j++) a[n][j] = lds32(ta + 256 + (n & 1) * 256 + k * 800 + j * 32);
        }
        if (n == 0) {
#pragma unroll
            for (int i = 0; i < 16; i++) { acc[4 - K0 + (i >> 2)][i & 3] += pend[i >> 2][i & 3]; pend[i >> 2][i & 3] = 0; }
        } else {
            const int m = n - 1, i = m >> 1;
            mma_q(acc[K0 + i], a[m], (m & 1) ? x[m] : y[i]); mma_q(pend[i], a[m], (m & 1) ? y[i] : x[m]);
        }
        PIN(13);
    }
}

__device__ __forceinline__ void conv_tile(const Params& p, uint32_t sb, int q, int w) {
    const int lane = __shfl_sync(0xffffffffu, threadIdx.x & 31, threadIdx.x & 31), g = lane >> 2, c = lane & 3, tile = q * 8 + w;
    const uint32_t l16 = sb + lane * 16;
#pragma unroll
    for (int i = 0; i < 16; i++) sts128(l16 + C_UR + w * 8192 + i * 512, 0, 0, 0, 0);
    wait_slow_warp(g_gate, lds32(sb + S_GATE));
    if (lane < 8) bulk_g2s(sb + C_TB + (w * 8 + lane) * 800, g_P + (tile * 8 + lane) * PROW + 72, 800, sb + B_BAR + CB_TB * 8, POL_N);
    uint32_t A[8][8];
#pragma unroll
    for (int k = 0; k < 8; k++)
#pragma unroll
        for (int j = 0; j < 8; j++) A[k][j] = __ldcg(g_P + (tile * 8 + k) * PROW + 16 + 8 * j + g - 2 * c);
    if (lane == 0) { const uint4 d = __ldg((const uint4*)p.Dskip + tile); sts128(sb + C_ST + 4608 + w * 16, d.x, d.y, d.z, d.w); }
    float acc[8][4], pend[4][4];
#pragma unroll
    for (int k = 0; k < 8; k++) acc[k][0] = acc[k][1] = acc[k][2] = acc[k][3] = pend[k & 3][k >> 2] = pend[k & 3][2 + (k >> 2)] = 0;
    const uint32_t row = sb + C_UR + w * 8192, ta = sb + C_TB + w * 6400 + (8 + g - 2 * c) * 4, qo = (lane & 7) * 16 - (lane >> 3) * 32;
    bar_sync(4, 384);
    mbar_wait(sb + B_BAR + CB_TB * 8, 0);
#pragma unroll 1
    for (int b = -2; b < 32; b++) {
        const int lz = lane + (b & p.zero);
        const bool on = b >= 0;
        uint4 r0 = make_uint4(0, 0, 0, 0), r1 = r0;
        asm volatile("{.reg .pred p; setp.ge.s32 p,%9,0; @p ld.global.cg.v4.u32 {%0,%1,%2,%3},[%8]; @p ld.global.cg.v4.u32 {%4,%5,%6,%7},[%8+%10];}"
                     : "+r"(r0.x), "+r"(r0.y), "+r"(r0.z), "+r"(r0.w), "+r"(r1.x), "+r"(r1.y), "+r"(r1.z), "+r"(r1.w) : "l"(g_x + (tile * 2 * XP + b * 32 + lz)), "r"(b), "n"(XP * 16) : "memory");
        const uint32_t q1 = row + ((qo + (b - 1) * 128) & 1023);
        if ((NTOP >> w) & 1) conv_near(acc, ta, q1);
        PROF2(threadIdx.x == 0 && on, 2048 + b * 8);
        const uint2* pps = pp_src(b, tile, lz);
        asm volatile("" : "+l"(pps));
        const uint32_t tag = lds32(sb + S_TAG);
        wait_flag_warp(cnt_ptr(C_PP + b * 8 + q), on ? 16 : 0);
        PROF2(threadIdx.x == 0 && on, 2048 + b * 8 + 1);
        float x[16];
        {
            const uint32_t a[4] = {r0.x, r0.y, r1.x, r1.y}, bb[4] = {r0.z, r0.w, r1.z, r1.w};
            sum_partials<4, true>(x, pps, a, bb, (2 * (lz & 3) == lz >> 2) ? 0x00003f80u : (2 * (lz & 3) + 1 == lz >> 2) ? 0x3f800000u : 0u, tag, on);
        }
        stats_send<0>(l16, x, g_st + (b + 2) * 256 + lz, q, w);
        {
            PROF2(threadIdx.x == 0 && on, 2048 + b * 8 + 2);
            if (on) mbar_wait(sb + B_BAR + (CB_CF + (w >> 1)) * 8, b & 1);
            const uint2* cb = g_carry + ((tile * 320 + b) * 32 + lz);
            uint2 cr[8];
#pragma unroll
            for (int k = 0; k < 8; k++) cr[k] = ld_acc(cb + k * 1280, b >= 4);
            if (NTOP != 255 && !((NTOP >> w) & 1) && b) conv_near(acc, ta, q1);
#pragma unroll
            for (int k = 0; k < 8; k++) add_acc(acc[k], cr[k]);
        }
        PIN(13);
        float4 ln = stats_recv<0>(l16, g_st + (b + 2) * 256 + lz, w);
        PROF2(threadIdx.x == 0 && on, 2048 + b * 8 + 3);
        uint32_t u[8];
#pragma unroll
        for (int k = 0; k < 8; k++) {
            u[k] = pack2(rbf(x[2 * k] - ln.x) * ln.y, rbf(x[2 * k + 1] - ln.z) * ln.w);
            sts32(row + k * 1024 + (b & 7) * 128 + lane * 4, u[k]);
        }
        __syncwarp();
        const uint32_t qa = row + ((qo + b * 128) & 1023);
        {
            uint4 xq[8];
#pragma unroll
            for (int k = 0; k < 4; k++) xq[k] = ldsm4(qa + k * 1024);
#pragma unroll
            for (int k = 0; k < 8; k += 2) {
                PIN(13);
                mma_q(acc[k], A[k], xq[k]); mma_q(acc[k + 1], A[k + 1], xq[k + 1]);
                if (k < 4) { xq[k + 4] = ldsm4(qa + (k + 4) * 1024); xq[k + 5] = ldsm4(qa + (k + 5) * 1024); }
            }
        }
        const uint4 dk = lds128(sb + C_ST + 4608 + w * 16);
#pragma unroll
        for (int k = 0; k < 8; k++) {
            const float t = __shfl_sync(0xffffffffu, acc[k][3], (lz & ~3) | ((lz - 1) & 3));
            const uint32_t y = movm(pack2(acc[k][0] + (c ? t : 0.f), acc[k][1] + acc[k][2]));
            acc[k][0] = c ? 0.f : t; acc[k][1] = acc[k][2] = acc[k][3] = 0;
            const uint32_t dw = k >> 1 == 0 ? dk.x : k >> 1 == 1 ? dk.y : k >> 1 == 2 ? dk.z : dk.w;
            const uint32_t s = hadd2(hadd2(y, hmul2(u[k], __byte_perm(dw, 0, (k & 1) ? 0x3232 : 0x1010))), __byte_perm(__float_as_uint(x[2 * k]), __float_as_uint(x[2 * k + 1]), 0x7632));
            x[2 * k] = blo(s); x[2 * k + 1] = bhi(s);
        }
        arrive_if(sb + B_BAR + (CB_UF + (w >> 1)) * 8, lz, b < -1 ? 32 : 0);
        stats_send<1>(l16, x, g_st + (36 + b) * 256 + lz, q, w);
        {
            PROF2(threadIdx.x == 0 && on, 2048 + b * 8 + 4);
            uint4* dst = g_x + ((128 + tile * 2) * XP + b * 32 + lz);
#pragma unroll
            for (int e = 0; e < 2; e++) {
                const float* y = x + e * 8;
                if (on) dst[e * XP] = make_uint4(__byte_perm(__float_as_uint(y[0]), __float_as_uint(y[2]), 0x7632), __byte_perm(__float_as_uint(y[4]), __float_as_uint(y[6]), 0x7632),
                                           __byte_perm(__float_as_uint(y[1]), __float_as_uint(y[3]), 0x7632), __byte_perm(__float_as_uint(y[5]), __float_as_uint(y[7]), 0x7632));
            }
            uint32_t* du = g_u + (tile * 8 * (UROW / 2) + UPRE / 2 + b * 32 + lz);
#pragma unroll
            for (int k = 0; k < 8; k++) if (on) du[k * (UROW / 2)] = u[k];
        }
#pragma unroll 1
        for (int pass = 0; pass < 2; pass++) {
            if (pass == ((PLATE >> w) & 1)) {
                const uint32_t q0 = row + ((qo + (b - 2) * 128) & 1023);
                if (b & 1) conv_pair<4>(acc, pend, ta, q0, q1, qa); else conv_pair<0>(acc, pend, ta, q0, q1, qa);
            }
            if (pass) break;
            ln = stats_recv<1>(l16, g_st + (36 + b) * 256 + lz, w);
            PROF2(threadIdx.x == 0 && on, 2048 + b * 8 + 5);
            uint32_t o[2][4];
#pragma unroll
            for (int e = 0; e < 2; e++) {
                const float mu = e ? ln.z : ln.x, rs = e ? ln.w : ln.y;
#pragma unroll
                for (int i = 0; i < 4; i++) o[e][i] = pack2(rbf(x[4 * i + e] - mu) * rs, rbf(x[4 * i + 2 + e] - mu) * rs);
            }
#pragma unroll
            for (int i = 0; i < 4; i++) {
                const uint32_t t = __shfl_xor_sync(0xffffffffu, (lz & 1) ? o[0][i] : o[1][i], 1);
                if (lz & 1) o[0][i] = t; else o[1][i] = t;
            }
            uint4* dst = g_xn + ((32 + b) * 4096 + q * 512 + (lz >> 2) * 64 + w * 8 + (lz & 2) * 2 + (lz & 1));
            if (on) { dst[0] = make_uint4(o[0][0], o[0][1], o[0][2], o[0][3]); dst[2] = make_uint4(o[1][0], o[1][1], o[1][2], o[1][3]); }
            if (w == 7) {
                bar_sync(5, 256);
                if (elect()) red_release(cnt_ptr(on ? C_XN + 32 + b : C_FAR + 8), 2);
                PROF(lane == 0 && on, 2048 + b * 8 + 6);
                __syncwarp();
            } else bar_arrive(5, 256);
        }
    }
}

template <int P0, bool TRI = false, int R0 = 0>
__device__ __forceinline__ void bg_half(float (*acc)[4], uint4* win, uint32_t ta, uint32_t qa, uint32_t mask, uint32_t row) {
#pragma unroll
    for (int i = 0; i < 4; i++) {
        win[P0 + i] = ldsm4(((qa + i * 128) & mask) + row);
        const uint4 a = lds128(ta + (3 - i) * 448), e = lds128(ta + (3 - i) * 448 + 224);
#pragma unroll
        for (int r = TRI ? 7 - P0 - i : R0; r < 8; r++) mma16(acc[r], a.x, a.y, a.z, a.w, win[(P0 + i + 1 + r) & 7].x, win[(P0 + i + 1 + r) & 7].y);
#pragma unroll
        for (int r = TRI ? 7 - P0 - i : R0; r < 8; r++) mma16(acc[r], e.x, e.y, e.z, e.w, win[(P0 + i + 1 + r) & 7].z, win[(P0 + i + 1 + r) & 7].w);
    }
}
__device__ __forceinline__ void bg_fetch(uint32_t sb, int q, int j, int n) {
    const int b0 = n >> 1, ch = q * 64 + j * 16 + (n & 1) * 8 + (b0 & 7), skip = max(12 - b0, 0);
    const uint32_t bar = sb + B_BAR + (CB_LD + j * 2 + (n & 1)) * 8, buf = sb + C_BG + (j * 2 + (n & 1)) * CB_BIG;
    if (elect()) {
        mbar_expect(bar, CB_BIG - skip * 128);
        bulk_g2s(buf, g_W + ch * 784, CB_M, bar, POL_N);
        bulk_g2s(buf + CB_M, g_W + (ch ^ 4) * 784, 1792, bar, POL_N);
        bulk_g2s(buf + CB_U + skip * 128, g_u + ch * (UROW / 2) + UPRE / 2 + (b0 - 20 + skip) * 32, 2048 - skip * 128, bar, POL_N);
    }
    __syncwarp();
}
__device__ __forceinline__ void conv_back(uint32_t sb, int q, int j) {
    const int lane = __shfl_sync(0xffffffffu, threadIdx.x & 31, threadIdx.x & 31), g = lane >> 2, c = lane & 3;
    wait_slow_warp(g_gate, lds32(sb + S_GATE));
    bg_fetch(sb, q, j, 0);
    bar_sync(4, 384);
    const uint32_t to = (6 + g - 2 * c) * 16, qo = (lane & 7) * 16 - (lane >> 3) * 32;
#pragma unroll 1
    for (int n = 0; n < 64; n++) {
        const int b0 = n >> 1, i = n & 1, chl = j * 16 + i * 8 + (b0 & 7);
        const uint32_t buf = sb + C_BG + (j * 2 + i) * CB_BIG, ta = buf + to;
        float acc[8][4];
        uint4 win[8];
        if (n < 63) bg_fetch(sb, q, j, n + 1);
        if (b0 >= 17 && b0 < 29 && (b0 < 21 || b0 >= 25) && i == 0) wait_flag_warp(cnt_ptr(C_FAR + (b0 >= 25) * 4 + ((b0 - 1) & 3)), 12);
        uint2* cr = g_carry + (((q * 64 + chl) * 40 + b0) * 32 + lane);
        uint2* cm = g_carry + (((q * 64 + (chl ^ 4)) * 40 + b0) * 32 + lane);
        uint2 pm[4], pf[8];
#pragma unroll
        for (int r = 0; r < 4; r++) pm[r] = ld_acc(cm + r * 32, b0 > 4);
#pragma unroll
        for (int r = 0; r < 8; r++) acc[r][0] = acc[r][1] = acc[r][2] = acc[r][3] = 0;
        mbar_wait(sb + B_BAR + (CB_LD + j * 2 + i) * 8, b0 & 1);
        if (b0 > 12) {
#pragma unroll
            for (int r = 1; r < 8; r++) win[(r + 4) & 7] = ldsm4(buf + CB_U + qo + r * 128);
        } else {
#pragma unroll
            for (int r = 1; r < 8; r++) win[(r + 4) & 7] = make_uint4(0, 0, 0, 0);
        }
        win[4] = make_uint4(0, 0, 0, 0);
#pragma unroll 1
        for (int h = b0 > 8 ? 4 : 2; h >= 2; h -= 2) {
            if (h == 2) {
                if (b0 > 4) bg_half<0>(acc, win, ta + 2 * 1792, qo + 12 * 128, ~0u, buf + CB_U);
                if (i == 0) mbar_wait(sb + B_BAR + (CB_UF + j) * 8, b0 & 1);
            }
            bg_half<4>(acc, win, ta + (h - 1) * 1792, qo + (h == 2 ? b0 - 4 : 8) * 128, h == 2 ? 1023u : ~0u, h == 2 ? sb + C_UR + chl * 1024 : buf + CB_U);
        }
        uint4 wm[8], a[9], e[9];
#pragma unroll
        for (int r = 1; r < 8; r++) wm[r] = ldsm4(sb + C_UR + (chl ^ 4) * 1024 + ((qo + (b0 + r) * 128) & 1023));
        a[7] = lds128(ta + 7 * 224); e[7] = lds128(ta + CB_M + 7 * 224);
#pragma unroll
        for (int r = 4; r < 8; r++) { st_acc(cr + r * 32, acc[r]); acc[r][0] = blo(pm[r - 4].x); acc[r][1] = bhi(pm[r - 4].x); acc[r][2] = blo(pm[r - 4].y); acc[r][3] = bhi(pm[r - 4].y); }
#pragma unroll
        for (int t = 7; t >= 0; t--) {
            if (t) { a[t - 1] = lds128(ta + (t - 1) * 224); e[t - 1] = lds128(ta + CB_M + (t - 1) * 224); }
            if (t == FT) {
                const uint2* f0 = g_far + (((q * 64 + chl) * 12 + b0 - 20) * 32 + lane);
                const uint2* f1 = g_far + (((q * 64 + (chl ^ 4)) * 12 + b0 - 20) * 32 + lane);
#pragma unroll
                for (int r = 0; r < 4; r++) { const bool on = (unsigned)(b0 + r - 20) < 12u; pf[r] = ld_acc(f0 + r * 32, on); pf[4 + r] = ld_acc(f1 + r * 32, on); }
            }
            PIN(14);
#pragma unroll
            for (int r = 0; r < 4; r++) { const uint4& x = win[4 + r - (t >> 1)]; mma16(acc[r], a[t].x, a[t].y, a[t].z, a[t].w, (t & 1) ? x.z : x.x, (t & 1) ? x.w : x.y); }
#pragma unroll
            for (int r = 0; r < 4; r++) { const uint4& x = wm[4 + r - (t >> 1)]; mma16(acc[4 + r], e[t].x, e[t].y, e[t].z, e[t].w, (t & 1) ? x.z : x.x, (t & 1) ? x.w : x.y); }
        }
#pragma unroll
        for (int r = 0; r < 4; r++) { add_acc(acc[r], pf[r]); add_acc(acc[4 + r], pf[4 + r]); st_acc(cr + r * 32, acc[r]); st_acc(cm + r * 32, acc[4 + r]); }
        __syncwarp();
        arrive_if(sb + B_BAR + (CB_CF + j) * 8, lane, i ? 0 : 32);
        PROF(j == 0 && lane == 0 && i, 2048 + b0 * 8 + 7);
    }
}
template <int PART>
__device__ __forceinline__ void conv_far(uint32_t sb, int w) {
    constexpr int NT = PART ? 5376 : 3584, NU = PART ? 1664 : 1152;
    const int lane = __shfl_sync(0xffffffffu, threadIdx.x & 31, threadIdx.x & 31), g = lane >> 2, c = lane & 3;
    wait_slow_warp(cnt_ptr(C_XN + (PART ? 43 : 39)), 16);
    const uint32_t to = (6 + g - 2 * c) * 16, qo = (lane & 7) * 16 - (lane >> 3) * 32;
#pragma unroll 1
    for (int n = -1; n < 44; n++) {
        const int t = n * 12 + w, tn = min(t + 12, 511), ch = (t & 127) * 4 + (((t >> 7) + 1) & 3), cn = (tn & 127) * 4 + (((tn >> 7) + 1) & 3);
        const uint32_t bar = sb + B_BAR + (w * 2 + (n & 1)) * 8, buf = sb + (w * 2 + (n & 1)) * 7168;
        if (n < 43 && elect()) {
            const uint32_t nb = sb + (w * 2 + (~n & 1)) * 7168;
            mbar_expect(bar ^ 8, NT + NU);
            bulk_g2s(nb, g_W + cn * 784 + 448, NT, bar ^ 8, POL_N);
            bulk_g2s(nb + 5376, g_u + cn * (UROW / 2) + UPRE / 2 - 32, NU, bar ^ 8, POL_N);
        }
        __syncwarp();
        if (n < 0) continue;
        mbar_wait(bar, (n >> 1) & 1);
        if (t >= 512) continue;
        float acc[8][4];
        uint4 win[8];
#pragma unroll
        for (int r = 0; r < 8; r++) acc[r][0] = acc[r][1] = acc[r][2] = acc[r][3] = 0;
        bg_half<0, true, PART * 4>(acc, win, buf + to + NT - 1792, qo + 128, ~0u, buf + 5376);
        bg_half<4, !PART, PART * 4>(acc, win, buf + to + NT - 3584, qo + 640, ~0u, buf + 5376);
        if (PART) bg_half<0, false, 4>(acc, win, buf + to, qo + 1152, ~0u, buf + 5376);
#pragma unroll
        for (int r = PART * 4; r < 8; r++) st_acc(g_far + (ch * 384 + lane) + (r + PART * 4) * 32, acc[r]);
        __syncwarp();
        if (((t + 12) ^ t) >= 128 && elect()) red_release(cnt_ptr(C_FAR + PART * 4 + (t >> 7)), 1);
        __syncwarp();
    }
    PROF(threadIdx.x == 0, 2048 + PART);
}

constexpr int P_X = 131072  , P_K6 = P_X + 32768  , P_P = P_K6 + 10496  , P_U = P_P + 33280  ,
              P_END = P_U + 17408, P_PRM = P_P  , P_Y = P_P  ;
static_assert(P_END <= B_BAR && P_END <= R_SEL, "prologue scratch");
#define KGUN 2
constexpr int KGU = KGUN;
__device__ __forceinline__ void csq(float& r, float& i) { const float t = r * i; r = fmaf(r, r, -(i * i)); i = t + t; }
__device__ __forceinline__ void cpow(float ar, float ph, float p, float& r, float& i) {
    const float e = ex2(ar * p);
    const float u = ph * p, n = (u + 12582912.f) - 12582912.f;
    const float t = (u - n) * 6.283185307179586f;
    r = e * __cosf(t); i = e * __sinf(t);
}
__device__ __forceinline__ void mma_tf32(float* c, float a0, float a1, float a2, float a3, float b0, float b1) {
    asm volatile("mma.sync.aligned.m16n8k8.row.col.f32.tf32.tf32.f32 {%0,%1,%2,%3},{%4,%5,%6,%7},{%8,%9},{%0,%1,%2,%3};"
                 : "+f"(c[0]), "+f"(c[1]), "+f"(c[2]), "+f"(c[3])
                 : "r"(__float_as_uint(a0)), "r"(__float_as_uint(a1)), "r"(__float_as_uint(a2)), "r"(__float_as_uint(a3)), "r"(__float_as_uint(b0)), "r"(__float_as_uint(b1)));
}

__device__ __forceinline__ void early_fetch(const Params& p, uint32_t sb) {
    const int v = blockIdx.x;
    if (elect()) {
        if (v >= V_QKV) { if (v < V_QKV + NQ && (p.roles & 8)) qkv_fetch(p, sb, v - V_QKV, 0, Q_PRE); }
        else if (v >= V_OP) { if (p.roles & 4) op_fetch(p, sb, v - V_OP, 0); }
        else if (v >= V_REC && (p.roles & 2)) { rec_fetch(p, sb, (v - V_REC) >> 1, v & 1, 0, R_STQ); rec_fetch(p, sb, (v - V_REC) >> 1, v & 1, 2, R_STV); }
    }
    __syncwarp();
}
struct ProRegs { uint32_t v[2][4], ldt[2]; };
__device__ __forceinline__ void prologue_load(const ProArgs& a, int b, ProRegs& pr) {
    const int w = threadIdx.x >> 5;
#pragma unroll
    for (int i = 0; i < 2; i++) {
        const int gi = b * 512 + (w & 3) * 128 + ((w >> 2) & 1) * 64 + i * 32 + (threadIdx.x & 31);
        pr.ldt[i] = __ldg((const uint16_t*)a.ldt + b * 4 + (w & 3));
        pr.v[i][0] = __ldg((const uint16_t*)a.lAr + gi); pr.v[i][1] = __ldg((const uint16_t*)a.Ai + gi);
        pr.v[i][2] = __ldg((const uint16_t*)a.Cr + gi); pr.v[i][3] = __ldg((const uint16_t*)a.Ci + gi);
    }
}
__device__ __forceinline__ void prologue(const Params& p, uint32_t sb, int b, int w, const ProRegs& pr) {
    const ProArgs& a = p.pa;
    const int tid = threadIdx.x, lane = tid & 31, g = lane >> 2, c = lane & 3;
    const int d0 = b * 4;
    if (w >= 8) {
        const int t2 = tid - 256;
        if (w < 10) {
            const int row = b * 16 + (w - 8) * 8 + g;
            uint4 v[16];
            const float2 r = row_stats512(v, (const uint4*)(a.x + (size_t)row * 512) + c, 8, 4);
            const float2 l = ln_finish(r.x * (1.f / 512.f), r.y * (1.f / 512.f));
            if (c == (g >> 1)) asm volatile("st.relaxed.gpu.global.u32 [%0],%1;" ::"l"(g_ln0 + row), "r"(pack2(l.x, l.y)) : "memory");
            __syncwarp();
        }
        if (b + 4 >= V_REC && b + 4 < V_OP) rec_slots(b + 4 - V_REC, (w & 3) ^ 2);
        PROF(t2 == 0, 3516);
        const int gi = b * 128 + t2;
        g_st[gi] = make_uint4(~0u, ~0u, ~0u, ~0u);
        if (gi < 1024) g_st[16384 + gi] = make_uint4(~0u, ~0u, ~0u, ~0u);
        if (gi < 912 * 8) g_cnt[gi] = 0;
        bar_sync(9, 384);
#pragma unroll 1
        for (int pass = 0; pass < 2; pass++) {
        if (w == 10 && pass == (b + 4 < V_QKV)) early_fetch(p, sb);
        if (pass) break;
#pragma unroll 2
        for (int i = t2; i < 4 * 784; i += 128) {
            const int ch = i / 784, k = i - ch * 784;
            const uint32_t o = sb + P_P + (ch * 2080 + 266 + (k / 14) * 18 + k) * 4;
            g_W[d0 * 784 + i] = make_uint4(lds32(o), lds32(o + 32), lds32(o + 64), lds32(o + 96));
        }
        bar_arrive(10, 384);
        }
        PROF(t2 == 0, 3517);
        return;
    }
    float kl = 0;
#pragma unroll
    for (int i = 0; i < 2; i++) {
        const float dt = rbf(expf(blo(pr.ldt[i])));
        const float ar = -rbf(expf(blo(pr.v[i][0]))) * dt, ai = blo(pr.v[i][1]) * dt;
        const float lg = ar * 1.4426950408889634f, tn = ai * 0.15915494309189535f, ph = tn - rintf(tn);
        const float cr = 2.f * (blo(pr.v[i][2]) * dt), ci = 2.f * (blo(pr.v[i][3]) * dt);
        float zr, zi;
        cpow(lg, ph, 2048.f, zr, zi);
        kl += cr * zr - ci * zi;
        cpow(lg, ph, 8.f, zr, zi);
        sts128(sb + P_PRM + (w * 64 + i * 32 + lane) * 16, __float_as_uint(lg), __float_as_uint(ph), __float_as_uint(cr), __float_as_uint(ci));
        sts64(sb + P_PRM + 8192 + (w * 64 + i * 32 + lane) * 8, __float_as_uint(zr), __float_as_uint(zi));
    }
    if (tid < 64) sts128(sb + P_U + (tid >> 3) * 2176 + (tid & 7) * 16, 0, 0, 0, 0);
    __syncwarp();
    PROF(tid == 0, 3510);
    uint2 ln[4];
#define LDLN _Pragma("unroll") for (int i = 0; i < 4; i++) asm volatile("ld.relaxed.gpu.global.v2.u32 {%0,%1},[%2];" : "=r"(ln[i].x), "=r"(ln[i].y) : "l"((const uint2*)g_ln0 + i * 256 + tid) : "memory")
    const int ch = w & 3, hf = w >> 2;
    {
        float k0[4] = {0, 0, 0, 0}, k1[4] = {0, 0, 0, 0}, k2[4] = {0, 0, 0, 0}, k3[4] = {0, 0, 0, 0}, k4[4] = {0, 0, 0, 0};
#pragma unroll KGU
        for (int j = 0; j < 16; j++) {
            const uint4 q = lds128(sb + P_PRM + (w * 64 + j * 4 + c) * 16);
            const float cr = __uint_as_float(q.z), ci = __uint_as_float(q.w);
            float wr[4], wi[4], vr[4], vi[4];
            cpow(__uint_as_float(q.x), __uint_as_float(q.y), (float)g, wr[0], wi[0]);
            const uint2 z8 = lds64(sb + P_PRM + 8192 + (w * 64 + j * 4 + c) * 8);
            vr[0] = wr[0] * __uint_as_float(z8.x) - wi[0] * __uint_as_float(z8.y); vi[0] = wr[0] * __uint_as_float(z8.y) + wi[0] * __uint_as_float(z8.x);
#pragma unroll
            for (int i = 1; i < 4; i++) { wr[i] = wr[i - 1]; wi[i] = wi[i - 1]; csq(wr[i], wi[i]); vr[i] = vr[i - 1]; vi[i] = vi[i - 1]; csq(vr[i], vi[i]); }
            float hr = wr[3], hi = wi[3];
            csq(hr, hi);
            mma_tf32(k0, wr[0], vr[0], wi[0], vi[0], cr * hr - ci * hi, -(cr * hi + ci * hr));
            hr = vr[3]; hi = vi[3]; csq(hr, hi);
            mma_tf32(k1, wr[0], vr[0], wi[0], vi[0], cr * hr - ci * hi, -(cr * hi + ci * hr));
            csq(hr, hi);
            mma_tf32(k2, wr[1], vr[1], wi[1], vi[1], cr * hr - ci * hi, -(cr * hi + ci * hr));
            csq(hr, hi);
            mma_tf32(k3, wr[2], vr[2], wi[2], vi[2], cr * hr - ci * hi, -(cr * hi + ci * hr));
            csq(hr, hi);
            mma_tf32(k4, wr[3], vr[3], wi[3], vi[3], cr * hr - ci * hi, -(cr * hi + ci * hr));
        }
        LDLN;
#pragma unroll
        for (int d = 1; d < 32; d *= 2) kl += __shfl_xor_sync(0xffffffffu, kl, d);
        const uint32_t o = sb + P_K6 + (ch * 656 + c * 32 + g) * 4, ol = sb + P_K6 + (ch * 656 + 640) * 4;
#define KST(k, base) sts32(o + (base) * 4, __float_as_uint(k[0])); sts32(o + (base) * 4 + 64, __float_as_uint(k[1])); \
                     sts32(o + (base) * 4 + 32, __float_as_uint(k[2])); sts32(o + (base) * 4 + 96, __float_as_uint(k[3]))
#define KAD(k, base) k[0] += __uint_as_float(lds32(o + (base) * 4)); k[1] += __uint_as_float(lds32(o + (base) * 4 + 64)); \
                     k[2] += __uint_as_float(lds32(o + (base) * 4 + 32)); k[3] += __uint_as_float(lds32(o + (base) * 4 + 96))
        if (hf == 0) {
            bar_sync(2 + ch, 64);
            KAD(k0, 0); KAD(k1, 128); KAD(k2, 256); KAD(k3, 384); KAD(k4, 512);
            kl += __uint_as_float(lds32(ol));
            __syncwarp();
        }
        KST(k0, 0); KST(k1, 128); KST(k2, 256); KST(k3, 384); KST(k4, 512);
        if (lane == 0) sts32(ol, __float_as_uint(kl));
        if (hf == 1) { __syncwarp(); bar_arrive(2 + ch, 64); }
    }
    PROF(tid == 0, 3511);
    {
        int n = 0;
        while (!__all_sync(0xffffffffu, ln[0].x && ln[0].y && ln[1].x && ln[1].y && ln[2].x && ln[2].y && ln[3].x && ln[3].y)) {
            LDLN;
            if (++n > 2000000) __trap();
        }
        bar_sync(8, 384);
        mbar_wait(sb + S_XBAR, 0);
#pragma unroll
        for (int i = 0; i < 4; i++) {
            const int t = i * 512 + tid * 2;
            uint32_t u[2][2];
#pragma unroll
            for (int e = 0; e < 2; e++) {
                const uint32_t l = e ? ln[i].y : ln[i].x, mm = __byte_perm(l, 0, 0x1010) ^ 0x80008000u;
                const float rs = rcp(bhi(l));
                const uint2 x = lds64(sb + P_X + (t + e) * 16 + (b & 1) * 8);
                u[e][0] = NRM(x.x); u[e][1] = NRM(x.y);
                sts64(sb + P_X + (t + e) * 16 + 8 - (b & 1) * 8, u[e][0], u[e][1]);
            }
            const uint32_t o = sb + P_U + ((t >> 3) & 1) * 2176 + ((t >> 4) + 8) * 16 + (t & 7) * 2;
#pragma unroll
            for (int k = 0; k < 4; k++) sts32(o + k * 4352, __byte_perm(u[0][k >> 1], u[1][k >> 1], (k & 1) ? 0x7632 : 0x5410));
        }
    }
    PROF(tid == 0, 3512);
    if (tid < 64) sts32(sb + P_P + ((tid >> 4) * 2080 + (tid & 15)) * 4, 0);
#pragma unroll 1
    for (int x = tid; x < 2048; x += 512) {
        uint32_t pw[2][4];
#pragma unroll
        for (int h = 0; h < 2; h++) {
            const int y = x + h * 256;
            const int i0 = y <= 256 ? y : 256 + (int)((pack2((float)y, 0.f) & 0xffff) - 0x4380);
            const int i1 = y <= 256 ? max(y - 1, 0) : 256 + (int)((pack2((float)(y - 1), 0.f) & 0xffff) - 0x4380);
#pragma unroll
            for (int k = 0; k < 4; k++) {
                const float lo = __uint_as_float(lds32(sb + P_K6 + k * 2624 + i0 * 4)), hi = __uint_as_float(lds32(sb + P_K6 + k * 2624 + i1 * 4));
                pw[h][k] = pack2(lo, y ? hi : 0.f);
            }
        }
#pragma unroll
        for (int h = 0; h < 2; h++)
#pragma unroll
            for (int k = 0; k < 4; k++) sts32(sb + P_P + (k * 2080 + x + h * 256 + 16) * 4, pw[h][k]);
    }
    fence_async_smem();
    bar_arrive(9, 384);
    bar_sync(1, 256);
    if (tid < 4) {
        asm volatile("cp.async.bulk.global.shared::cta.bulk_group [%0],[%1],%2;" ::"l"(g_P + (d0 + tid) * PROW), "r"(sb + P_P + tid * 8320), "r"(PROW * 4) : "memory");
        asm volatile("cp.async.bulk.commit_group;" ::: "memory");
    }
    __syncwarp();
    PROF(tid == 0, 3513);
    {
        float acc[16][4];
#pragma unroll
        for (int j = 0; j < 16; j++) acc[j][0] = acc[j][1] = acc[j][2] = acc[j][3] = 0;
#pragma unroll 1
        for (int e = hf * 4; e < hf * 4 + 4; e++) {
            uint32_t B[16][2];
            const uint32_t ua = sb + P_U + ch * 4352 + ((lane >> 3) & 1) * 2176 + (8 + (lane >> 4) * 8 + (lane & 7) - e) * 16;
#pragma unroll
            for (int j = 0; j < 8; j++) { const uint4 v = ldsm4(ua + j * 256); B[2 * j][0] = v.x; B[2 * j][1] = v.y; B[2 * j + 1][0] = v.z; B[2 * j + 1][1] = v.w; }
            const uint32_t pa = sb + P_P + (ch * 2080 + 16 + e * 16 + g - 2 * c) * 4;
#pragma unroll
            for (int dd = 0; dd < 16; dd++) {
                const int d = (dd & 1) ? 15 - (dd >> 1) : dd >> 1;
                const uint32_t a0 = lds32(pa + d * 512), a1 = lds32(pa + d * 512 + 32), a2 = lds32(pa + d * 512 - 32), a3 = a0 + p.zero;
#pragma unroll
                for (int j = 0; j < 16; j++) if (j >= d) mma16(acc[j], a0, a1, a2, a3, B[(j - d) & 15][0], B[(j - d) & 15][1]);
            }
        }
        PROF(tid == 0, 3514);
        if (tid < 4) asm volatile("cp.async.bulk.wait_group 0;" ::: "memory");
        __syncwarp();
        bar_sync(10, 384);
#pragma unroll
        for (int j = 0; j < 8; j++) {
#pragma unroll
            for (int i = 0; i < 4; i++) { const float t = hf ? acc[j][i] : acc[j + 8][i]; acc[j][i] = hf ? acc[j + 8][i] : acc[j][i]; acc[j + 8][i] = t; }
            sts128(sb + P_Y + w * 4096 + j * 512 + lane * 16, __float_as_uint(acc[j + 8][0]), __float_as_uint(acc[j + 8][1]), __float_as_uint(acc[j + 8][2]), __float_as_uint(acc[j + 8][3]));
        }
        bar_sync(2 + ch, 64);
        uint32_t yp[16];
#pragma unroll
        for (int j = 0; j < 8; j++) {
            const uint4 t = lds128(sb + P_Y + (w ^ 4) * 4096 + j * 512 + lane * 16);
            yp[2 * j] = pack2(acc[j][0] + __uint_as_float(t.x), acc[j][1] + __uint_as_float(t.y)); yp[2 * j + 1] = pack2(acc[j][2] + __uint_as_float(t.z), acc[j][3] + __uint_as_float(t.w));
        }
#pragma unroll
        for (int j = 0; j < 4; j++)
            asm volatile("stmatrix.sync.aligned.m8n8.x4.trans.shared.b16 [%0],{%1,%2,%3,%4};" ::"r"(sb + P_Y + 32768 + ch * 4096 + hf * 2048 + j * 512 + (lane >> 4) * 256 + (lane & 7) * 32 + (lane & 8) * 2),
                         "r"(yp[4 * j]), "r"(yp[4 * j + 1]), "r"(yp[4 * j + 2]), "r"(yp[4 * j + 3]) : "memory");
    }
    const uint2 dk = __ldg((const uint2*)(a.Dk + d0));
    bar_sync(1, 256);
#pragma unroll 2
    for (int i = 0; i < 4; i++) {
        const int t = i * 256 + tid;
        uint4 x0 = lds128(sb + P_X + t * 32), x1 = lds128(sb + P_X + t * 32 + 16);
        if (b & 1) { x0 = make_uint4(x0.z, x0.w, x0.x, x0.y); x1 = make_uint4(x1.z, x1.w, x1.x, x1.y); }
        uint32_t y[4];
#pragma unroll
        for (int k = 0; k < 4; k++) y[k] = lds32(sb + P_Y + 32768 + k * 4096 + t * 4);
        g_x[b * XP + t] = make_uint4(hadd2(x0.x, hadd2(__byte_perm(y[0], y[1], 0x5410), hmul2(x0.z, dk.x))), hadd2(x0.y, hadd2(__byte_perm(y[2], y[3], 0x5410), hmul2(x0.w, dk.y))),
                                     hadd2(x1.x, hadd2(__byte_perm(y[0], y[1], 0x7632), hmul2(x1.z, dk.x))), hadd2(x1.y, hadd2(__byte_perm(y[2], y[3], 0x7632), hmul2(x1.w, dk.y))));
    }
    PROF(tid == 0, 3515);
}

__global__ void __cluster_dims__(2, 1, 1) __launch_bounds__(384, 1) main_kernel(const __grid_constant__ Params p) {
    extern __shared__ __align__(1024) uint8_t smem[];
    const uint32_t sb = smem_u32(smem);
    uint32_t rank; asm("mov.u32 %0,%%cluster_ctarank;" : "=r"(rank));
    const int wi = __shfl_sync(0xffffffffu, threadIdx.x >> 5, 0);
    const int v = blockIdx.x, cl = v >> 1, wg = wi >> 2;
    PROF(threadIdx.x == 0, 3500);
    ProRegs pr;
    prologue_load(p.pa, max((int)blockIdx.x - 4, 0), pr);
    if (wi == 11 && p.dopro && cl >= 2 && elect()) {
        mbar_init(sb + S_XBAR, 1);
        asm volatile("fence.mbarrier_init.release.cluster;" ::: "memory");
        mbar_expect(sb + S_XBAR, 32768);
        for (int j = 0; j < 8; j++) tma2d(sb + P_X + j * 4096, &p.tm[3], ((blockIdx.x - 4) >> 1) * 8, j * 256, sb + S_XBAR);
    }
    if (threadIdx.x == 320) {
        unsigned n;
        asm volatile("ld.relaxed.gpu.global.u32 %0,[%1];" : "=r"(n) : "l"(g_gate) : "memory");
        n = n / (4 * NCL) + p.dopro;
        sts64(sb + S_GATE, n * (4 * NCL), n & 1);
    }
    __syncwarp();
    if (wi == 10) {
        if (v < V_REC || v == 131) conv_init(sb, v == 131); else if (v < V_OP) rec_init(sb); else gemm_init(sb, v < V_QKV);
        __syncwarp();
    }
    if (wg == 2) bar_arrive(8, 384);
    asm volatile("barrier.cluster.arrive.relaxed.aligned;" ::: "memory");
    if (p.dopro && cl >= 2) prologue(p, sb, blockIdx.x - 4, wi, pr); else if (wg < 2) bar_sync(8, 384); else if (wi == 10) early_fetch(p, sb);
    asm volatile("barrier.cluster.wait.aligned;" ::: "memory");
    const int role = (v < V_REC ? 1 : v < V_OP ? 2 : v < V_QKV ? 20 : v < V_QKV + NQ ? 24 : 1) & p.roles;
    fence_async_smem();
    bar_sync(wg == 2 ? 7 : 1, wg == 2 ? 128 : 256);
    if (p.dopro && (threadIdx.x == 32 || threadIdx.x == 352)) red_release(g_gate, 1);
    PROF(threadIdx.x == 32, 3509);
    if (wi == 0 && (role & 8) && elect()) qkv_stage(p, sb + 131072, sb + G_BAR + GB_RS * 8, v - V_QKV, 0, 6);
    PROF(threadIdx.x == 0, 3506);
    __syncwarp();
    if (p.dopro && (v == 131 || (v >= V_REC && v < V_QKV && (v < V_OP ? wi == 8 : wi < 8)))) {
        bool on = v >= V_OP;
#pragma unroll 1
        for (int r = v == 131 ? 448 + wi : on ? 64 + (v - V_OP) * 8 + wi : v - V_REC; r < (v == 131 ? 512 : 448);) {
            if (v >= V_OP) wait_slow_warp(g_gate, lds32(sb + S_GATE)); else if (on) wait_flag_warp(g_gate, lds32(sb + S_GATE));
            PROF(threadIdx.x == 256 && on, 3507);
            x1_norm(on ? (const uint2*)g_x : (const uint2*)p.pa.x, r, on);
            __syncwarp();
            if (on && elect()) red_release(cnt_ptr(C_XN + (r >> 4)), 1);
            __syncwarp();
            PROF(threadIdx.x == 256, on ? 3508 : 3499);
            if (on) r += v < V_OP ? 512 : v == 131 ? 12 : 128;
            on = true;
        }
    }
    if (role == 2) {
        const int head = (v - V_REC) >> 1;
        if (wi == 8 && elect()) rec_fetch(p, sb, head, rank, 1, R_STK);
        __syncwarp();
        if (wg == 2) {
            reg_dec<RH>();
            const int w = wi & 3;
            wait_slow_warp(g_gate, lds32(sb + S_GATE));
            if (w < 2) { const uint32_t x = __ldcg(g_sel + (threadIdx.x & 63)); sts32(sb + R_SEL + (threadIdx.x & 63) * 4, (x * 0x01010101u) >> 24); }
            __syncthreads();
            cluster_sync();
            if ((p.chains >> (w & 1)) & 1) { if (w < 2) rec_comm(p, sb, w, head, rank); else rec_attn(p, sb, w & 1, head, rank); }
        } else {
            reg_inc<RW0>();
            rec_weights(p, sb, head, rank, wi);
        }
    } else if (role == 1) {
        if (v == 131) { wait_slow_warp(g_gate, lds32(sb + S_GATE)); conv_far<0>(sb, wi); conv_far<1>(sb, wi); } else if (wg == 2) { reg_dec<RCB>(); conv_back(sb, v, wi & 3); } else { reg_inc<RCU>(); conv_tile(p, sb, v, wi); }
    } else if (role && v < V_QKV) {
        if (wg == 2) {
            reg_dec<40>();
            if (wi == 8) { if (role & 4) gemm_producer<true>(p, sb, v - V_OP); }
            else if (v < V_OP + 14 && (role & 16)) fin_warp(p, sb, 2 * NQ + (v - V_OP) * 3 + wi - 9);
        } else { reg_inc<232>(); if (role & 4) gemm_consumer<true>(p, sb, v - V_OP, wi); }
    } else if (role) {
        if (wg == 2) {
            reg_dec<40>();
            if (wi < 10) {
                if (role & 8) { if (wi == 8) gemm_producer<false>(p, sb, v - V_QKV); else qkv_release(p, sb); }
            } else if (role & 16) fin_warp(p, sb, (v - V_QKV) * 2 + wi - 10);
        } else { reg_inc<232>(); if (role & 8) gemm_consumer<false>(p, sb, v - V_QKV, wi); }
    }
    __syncwarp();
    cluster_sync();
}

typedef CUresult (*EncFn)(CUtensorMap*, CUtensorMapDataType, cuuint32_t, void*, const cuuint64_t*, const cuuint64_t*, const cuuint32_t*, const cuuint32_t*,
                          CUtensorMapInterleave, CUtensorMapSwizzle, CUtensorMapL2promotion, CUtensorMapFloatOOBfill);
constexpr int SMEM_BYTES = 232448;
#define LAG 8
#define QLEAD 6
#define OLEAD (LAG / 2 + 2)
void plan(Params& P) {
    P.roles = 31; P.chains = 3; P.lag = LAG; P.dopro = 1;
    for (int r = 0; r < 2; r++) {
        const int lead = r ? OLEAD : QLEAD;
        int n = 0;
        for (int i = 0; i < 32 + lead; i++) {
            if (i >= lead) P.list[r][n++] = 32 + i - lead;
            if (i < 32) P.list[r][n++] = i;
        }
        P.nl[r] = n;
    }
}

#define TK() do {} while (0)
}

extern "C" void kernel_launch(void* const* d_in, const int* in_sizes, int n_in, void* d_out, int out_size) {
    typedef const __nv_bfloat16* BP;
    static EncFn enc = nullptr;
    if (!enc) {
        void* fn = nullptr; cudaDriverEntryPointQueryResult qr;
        cudaGetDriverEntryPoint("cuTensorMapEncodeTiled", &fn, cudaEnableDefault, &qr);
        enc = (EncFn)fn;
        cudaFuncSetAttribute(main_kernel, cudaFuncAttributeMaxDynamicSharedMemorySize, SMEM_BYTES);
    }
    static Params P;
    for (int i = 0; i < 4; i++) {
        const cuuint64_t cols = i < 3 ? 4096 : 512, rows = i < 3 ? 512 : 4096;
        cuuint64_t d2[2] = {cols, rows}, str[1] = {cols * 2};
        cuuint32_t box[2] = {64, 64}, bn[2] = {16, 256}, es[2] = {1, 1};
        enc(&P.tm[i < 3 ? i : 4], CU_TENSOR_MAP_DATA_TYPE_BFLOAT16, 2, d_in[9 + i], d2, str, box, es, CU_TENSOR_MAP_INTERLEAVE_NONE, CU_TENSOR_MAP_SWIZZLE_128B,
            CU_TENSOR_MAP_L2_PROMOTION_L2_128B, CU_TENSOR_MAP_FLOAT_OOB_FILL_NONE);
        if (i < 2) enc(&P.tn[i], CU_TENSOR_MAP_DATA_TYPE_BFLOAT16, 2, d_in[9 + i], d2, str, bn, es, CU_TENSOR_MAP_INTERLEAVE_NONE, CU_TENSOR_MAP_SWIZZLE_32B,
                       CU_TENSOR_MAP_L2_PROMOTION_L2_128B, CU_TENSOR_MAP_FLOAT_OOB_FILL_NONE);
    }
    {
        cuuint64_t dims[2] = {512, 2048}, str[1] = {1024};
        cuuint32_t box[2] = {8, 256}, es[2] = {1, 1};
        enc(&P.tm[3], CU_TENSOR_MAP_DATA_TYPE_BFLOAT16, 2, d_in[0], dims, str, box, es, CU_TENSOR_MAP_INTERLEAVE_NONE, CU_TENSOR_MAP_SWIZZLE_NONE,
            CU_TENSOR_MAP_L2_PROMOTION_NONE, CU_TENSOR_MAP_FLOAT_OOB_FILL_NONE);
    }
    P.mem0 = (BP)d_in[8]; P.Wo = (BP)d_in[12]; P.Dskip = (BP)d_in[6]; P.out = (__nv_bfloat16*)d_out;
    cudaStream_t s = cudaStreamPerThread;
    P.pa = {(BP)d_in[0], (BP)d_in[1], (BP)d_in[2], (BP)d_in[3], (BP)d_in[4], (BP)d_in[5], (BP)d_in[6]};
    plan(P);
    TK(); main_kernel<<<2 * NCL, 384, SMEM_BYTES, s>>>(P); TK();
}
```

```cpp
#include <cuda_runtime.h>
#include <cuda_bf16.h>
#include <cuda.h>
#include <stdint.h>
#include <string.h>
#include <math.h>

namespace {

constexpr int NCL = 66;
constexpr int NQ = 43;
constexpr int V_REC = 8, V_OP = 72, V_QKV = 88;
static_assert(2 * NQ + 3 * 14 == 128, "warps of the final residual");

constexpr int XP = 1024;
__device__ uint4 g_x[2 * 128 * XP];
__device__ uint4 g_xn[64 * 4096];
__device__ uint4 g_st[68 * 256];
__device__ uint4 g_qkv[128 * 32 * 1536];
__device__ uint4 g_o[64 * 64 * 512];
__device__ uint4 g_pp[64 * 4 * 4096];
__device__ uint4 g_xch[133 * 512];
__device__ unsigned g_sel[64];
__device__ unsigned g_gate[32];
__device__ __align__(16) uint32_t g_P[512 * 272];
__device__ uint4 g_W[512 * 784];
__device__ __align__(16) uint32_t g_u[512 * 1280];
__device__ uint2 g_carry[512 * 40 * 32];
__device__ uint2 g_far[512 * 12 * 32];
__device__ unsigned g_cnt[916 * 8];
__device__ uint32_t g_ln0[2048];

enum { C_XN = 0  , C_QKV = 64  , C_O = 128  , C_PP = 384  , C_FAR = 896  , C_OH = 908  , C_N = 916 };
__device__ __forceinline__ unsigned* cnt_ptr(int i) { return g_cnt + i * 8; }

struct ProArgs { const __nv_bfloat16 *x, *lAr, *Ai, *Cr, *Ci, *ldt, *Dk; };
struct Params {
    CUtensorMap tm[5];
    CUtensorMap tn[2];
    ProArgs pa;
    int dopro;
    const __nv_bfloat16* mem0;
    const __nv_bfloat16* Wo;
    const __nv_bfloat16* Dskip;
    __nv_bfloat16* out;
    int roles;
    int chains;
    int lag;
    int zero;
    int h0;
    int nl[2];
    uint8_t list[2][64];
};

__device__ __forceinline__ uint32_t smem_u32(const void* p) { return (uint32_t)__cvta_generic_to_shared(p); }
__device__ __forceinline__ uint32_t mapa(uint32_t a, uint32_t r) {
    uint32_t o; asm("mapa.shared::cluster.u32 %0,%1,%2;" : "=r"(o) : "r"(a), "r"(r)); return o;
}
__device__ __forceinline__ void mbar_init(uint32_t b, int c) { asm volatile("mbarrier.init.shared::cta.b64 [%0],%1;" ::"r"(b), "r"(c) : "memory"); }
__device__ __forceinline__ void mbar_expect(uint32_t b, int bytes) { asm volatile("mbarrier.arrive.expect_tx.shared::cta.b64 _,[%0],%1;" ::"r"(b), "r"(bytes) : "memory"); }
__device__ __forceinline__ void mbar_arrive(uint32_t b) { asm volatile("mbarrier.arrive.shared::cta.b64 _,[%0];" ::"r"(b) : "memory"); }
__device__ __forceinline__ void mbar_arrive_cluster(uint32_t b) { asm volatile("mbarrier.arrive.shared::cluster.b64 _,[%0];" ::"r"(b) : "memory"); }
__device__ __forceinline__ void mbar_wait(uint32_t b, uint32_t ph) {
    asm volatile(
        "{.reg .pred p; .reg .u32 n; mov.u32 n,0;\n"
        "W%=: mbarrier.try_wait.parity.shared::cta.b64 p,[%0],%1;\n"
        "@p bra D%=;\n"
        "add.u32 n,n,1; setp.lt.u32 p,n,2000000; @p bra W%=;\n"
        "trap;\n"
        "D%=: }" ::"r"(b), "r"(ph) : "memory");
}
__device__ __forceinline__ bool elect() {
    uint32_t r; asm volatile("{.reg .pred p; elect.sync _|p,0xffffffff; selp.u32 %0,1,0,p;}" : "=r"(r)); return r;
}
__device__ __forceinline__ void bar_sync(int id, int n) { asm volatile("bar.sync %0,%1;" ::"r"(id), "r"(n) : "memory"); }
__device__ __forceinline__ void bar_arrive(int id, int n) { asm volatile("bar.arrive %0,%1;" ::"r"(id), "r"(n) : "memory"); }
__device__ __forceinline__ void cluster_sync() { asm volatile("barrier.cluster.arrive.relaxed.aligned; barrier.cluster.wait.aligned;" ::: "memory"); }
__device__ __forceinline__ void fence_async_smem() { asm volatile("fence.proxy.async.shared::cta;" ::: "memory"); }
constexpr uint64_t POL_N = 0x1000000000000000ull  , POL_LAST = 0x12F0000000000000ull  ;
__device__ __forceinline__ void bulk_g2s(uint32_t dst, const void* src, int bytes, uint32_t bar, uint64_t pol) {
    asm volatile("cp.async.bulk.shared::cluster.global.mbarrier::complete_tx::bytes.L2::cache_hint [%0],[%1],%2,[%3],%4;" ::"r"(dst), "l"(src), "r"(bytes), "r"(bar), "l"(pol) : "memory");
}
__device__ __forceinline__ void bulk_g2s_mc(uint32_t dst, const void* src, int bytes, uint32_t bar, uint64_t pol) {
    asm volatile("cp.async.bulk.shared::cluster.global.mbarrier::complete_tx::bytes.multicast::cluster.L2::cache_hint [%0],[%1],%2,[%3],%4,%5;" ::"r"(dst), "l"(src), "r"(bytes), "r"(bar), "h"((uint16_t)3), "l"(pol) : "memory");
}
__device__ __forceinline__ void stg128(uint4* p, uint4 v, uint64_t pol) {
    asm volatile("st.global.L2::cache_hint.v4.u32 [%0],{%1,%2,%3,%4},%5;" ::"l"(p), "r"(v.x), "r"(v.y), "r"(v.z), "r"(v.w), "l"(pol));
}
__device__ __forceinline__ void tma2d(uint32_t dst, const CUtensorMap* tm, int x, int y, uint32_t bar) {
    asm volatile("cp.async.bulk.tensor.2d.shared::cluster.global.mbarrier::complete_tx::bytes [%0],[%1,{%2,%3}],[%4];" ::"r"(dst), "l"(tm), "r"(x), "r"(y), "r"(bar) : "memory");
}
__device__ __forceinline__ void st_async4(uint32_t a, uint32_t x, uint32_t y, uint32_t z, uint32_t w, uint32_t mb) {
    asm volatile("st.async.shared::cluster.mbarrier::complete_tx::bytes.v4.b32 [%0],{%1,%2,%3,%4},[%5];" ::"r"(a), "r"(x), "r"(y), "r"(z), "r"(w), "r"(mb) : "memory");
}
__device__ __forceinline__ void st_async2(uint32_t a, uint32_t x, uint32_t y, uint32_t mb) {
    asm volatile("st.async.shared::cluster.mbarrier::complete_tx::bytes.v2.b32 [%0],{%1,%2},[%3];" ::"r"(a), "r"(x), "r"(y), "r"(mb) : "memory");
}
__device__ __forceinline__ uint4 lds128(uint32_t a) { uint4 v; asm volatile("ld.shared.v4.u32 {%0,%1,%2,%3},[%4];" : "=r"(v.x), "=r"(v.y), "=r"(v.z), "=r"(v.w) : "r"(a) : "memory"); return v; }
__device__ __forceinline__ uint4 lds128v(uint32_t a) { uint4 v; asm volatile("ld.volatile.shared.v4.u32 {%0,%1,%2,%3},[%4];" : "=r"(v.x), "=r"(v.y), "=r"(v.z), "=r"(v.w) : "r"(a) : "memory"); return v; }
__device__ __forceinline__ uint2 lds64(uint32_t a) { uint2 v; asm volatile("ld.shared.v2.u32 {%0,%1},[%2];" : "=r"(v.x), "=r"(v.y) : "r"(a) : "memory"); return v; }
__device__ __forceinline__ uint32_t lds32(uint32_t a) { uint32_t v; asm volatile("ld.shared.u32 %0,[%1];" : "=r"(v) : "r"(a) : "memory"); return v; }
__device__ __forceinline__ void sts128(uint32_t a, uint32_t x, uint32_t y, uint32_t z, uint32_t w) { asm volatile("st.shared.v4.u32 [%0],{%1,%2,%3,%4};" ::"r"(a), "r"(x), "r"(y), "r"(z), "r"(w) : "memory"); }
__device__ __forceinline__ void sts64(uint32_t a, uint32_t x, uint32_t y) { asm volatile("st.shared.v2.u32 [%0],{%1,%2};" ::"r"(a), "r"(x), "r"(y) : "memory"); }
__device__ __forceinline__ void sts32(uint32_t a, uint32_t x) { asm volatile("st.shared.u32 [%0],%1;" ::"r"(a), "r"(x) : "memory"); }
__device__ __forceinline__ uint4 ldsm4(uint32_t a) { uint4 v; asm volatile("ldmatrix.sync.aligned.m8n8.x4.shared.b16 {%0,%1,%2,%3},[%4];" : "=r"(v.x), "=r"(v.y), "=r"(v.z), "=r"(v.w) : "r"(a) : "memory"); return v; }
__device__ __forceinline__ uint4 ldsm4t(uint32_t a) { uint4 v; asm volatile("ldmatrix.sync.aligned.m8n8.x4.trans.shared.b16 {%0,%1,%2,%3},[%4];" : "=r"(v.x), "=r"(v.y), "=r"(v.z), "=r"(v.w) : "r"(a) : "memory"); return v; }
__device__ __forceinline__ uint32_t movm(uint32_t a) { uint32_t d; asm volatile("movmatrix.sync.aligned.m8n8.trans.b16 %0,%1;" : "=r"(d) : "r"(a)); return d; }
__device__ __forceinline__ uint32_t pack2(float lo, float hi) { uint32_t d; asm("cvt.rn.bf16x2.f32 %0,%1,%2;" : "=r"(d) : "f"(hi), "f"(lo)); return d; }
__device__ __forceinline__ uint32_t hadd2(uint32_t a, uint32_t b) { uint32_t d; asm("add.rn.bf16x2 %0,%1,%2;" : "=r"(d) : "r"(a), "r"(b)); return d; }
__device__ __forceinline__ uint32_t hmul2(uint32_t a, uint32_t b) { uint32_t d; asm("mul.rn.bf16x2 %0,%1,%2;" : "=r"(d) : "r"(a), "r"(b)); return d; }
__device__ __forceinline__ float blo(uint32_t v) { return __uint_as_float(v << 16); }
__device__ __forceinline__ float bhi(uint32_t v) { return __uint_as_float(v & 0xffff0000u); }
__device__ __forceinline__ float rbf(float x) { return __uint_as_float(pack2(0.f, x)); }
__device__ __forceinline__ float ex2(float x) { float y; asm("ex2.approx.ftz.f32 %0,%1;" : "=f"(y) : "f"(x)); return y; }
__device__ __forceinline__ float rcp(float x) { float y; asm("rcp.approx.ftz.f32 %0,%1;" : "=f"(y) : "f"(x)); return y; }
__device__ __forceinline__ void mma16(float* c, uint32_t a0, uint32_t a1, uint32_t a2, uint32_t a3, uint32_t b0, uint32_t b1) {
    asm volatile("mma.sync.aligned.m16n8k16.row.col.f32.bf16.bf16.f32 {%0,%1,%2,%3},{%4,%5,%6,%7},{%8,%9},{%0,%1,%2,%3};"
                 : "+f"(c[0]), "+f"(c[1]), "+f"(c[2]), "+f"(c[3]) : "r"(a0), "r"(a1), "r"(a2), "r"(a3), "r"(b0), "r"(b1));
}
__device__ __forceinline__ void mma16_top(float& d0, float& d1, uint32_t a0, uint32_t a2, uint32_t b0, uint32_t b1) {
    asm volatile("{.reg .b32 j; .reg .f32 e,f; mma.sync.aligned.m16n8k16.row.col.f32.bf16.bf16.f32 {%0,%1,e,f},{%2,j,%3,j},{%4,%5},{0f00000000,0f00000000,0f00000000,0f00000000};}"
                 : "=f"(d0), "=f"(d1) : "r"(a0), "r"(a2), "r"(b0), "r"(b1));
}
__device__ __forceinline__ void mma8(float* c, uint32_t a0, uint32_t a1, uint32_t b0) {
    asm volatile("mma.sync.aligned.m16n8k8.row.col.f32.bf16.bf16.f32 {%0,%1,%2,%3},{%4,%5},{%6},{%0,%1,%2,%3};"
                 : "+f"(c[0]), "+f"(c[1]), "+f"(c[2]), "+f"(c[3]) : "r"(a0), "r"(a1), "r"(b0));
}
__device__ __forceinline__ uint4 ld_rlx128(const uint4* p) {
    uint4 v;
    asm volatile("{.reg .b128 t; ld.relaxed.gpu.global.b128 t,[%4]; mov.b128 {%0,%1,%2,%3},t;}" : "=r"(v.x), "=r"(v.y), "=r"(v.z), "=r"(v.w) : "l"(p) : "memory");
    return v;
}
__device__ __forceinline__ void st_rlx128(uint4* p, uint32_t x, uint32_t y, uint32_t z, uint32_t w) {
    asm volatile("{.reg .b128 t; mov.b128 t,{%1,%2,%3,%4}; st.relaxed.gpu.global.b128 [%0],t;}" ::"l"(p), "r"(x), "r"(y), "r"(z), "r"(w) : "memory");
}
__device__ __forceinline__ uint4 ldcg128(const uint4* p) { uint4 v; asm volatile("ld.global.cg.v4.u32 {%0,%1,%2,%3},[%4];" : "=r"(v.x), "=r"(v.y), "=r"(v.z), "=r"(v.w) : "l"(p) : "memory"); return v; }
__device__ __forceinline__ void red_release(unsigned* p, unsigned v) {
    asm volatile("fence.proxy.async; red.relaxed.gpu.global.add.u32 [%0],%1;" ::"l"(p), "r"(v) : "memory");
}
__device__ __forceinline__ void red_relaxed(unsigned* p, unsigned v) { asm volatile("red.relaxed.gpu.global.add.u32 [%0],%1;" ::"l"(p), "r"(v) : "memory"); }
__device__ __forceinline__ void wait_cnt(const unsigned* p, unsigned target) {
    asm volatile(
        "{.reg .pred p; .reg .u32 n,v; mov.u32 n,0;\n"
        "W%=: ld.relaxed.gpu.global.u32 v,[%0]; setp.ge.u32 p,v,%1; @p bra D%=;\n"
        "add.u32 n,n,1; setp.lt.u32 p,n,10000000; @p bra W%=;\n"
        "trap;\n"
        "D%=: }" ::"l"(p), "r"(target) : "memory");
}
__device__ __forceinline__ void wait_slow_warp(const unsigned* p, unsigned target) {
    asm volatile(
        "{.reg .pred p; .reg .u32 n,v; mov.u32 n,0;\n"
        "W%=: ld.relaxed.gpu.global.u32 v,[%0]; setp.ge.u32 p,v,%1; vote.sync.all.pred p,p,0xffffffff; @p bra.uni D%=;\n"
        "nanosleep.u32 400; add.u32 n,n,1; setp.lt.u32 p,n,1000000; @p bra.uni W%=;\n"
        "trap;\n"
        "D%=: }" ::"l"(p), "r"(target) : "memory");
}
__device__ __forceinline__ void wait_flag_warp(const unsigned* p, unsigned target) {
    asm volatile(
        "{.reg .pred p; .reg .u32 n,v; mov.u32 n,0;\n"
        "W%=: ld.relaxed.gpu.global.u32 v,[%0]; setp.ge.u32 p,v,%1; vote.sync.all.pred p,p,0xffffffff; @p bra.uni D%=;\n"
        "add.u32 n,n,1; setp.lt.u32 p,n,10000000; @p bra.uni W%=;\n"
        "trap;\n"
        "D%=: }" ::"l"(p), "r"(target) : "memory");
}
__device__ __forceinline__ uint64_t mkdesc(uint32_t addr, uint32_t lbo, uint32_t sbo, uint32_t sw) {
    return (uint64_t)((addr & 0x3FFFF) >> 4) | ((uint64_t)(lbo >> 4) << 16) | ((uint64_t)(sbo >> 4) << 32) | ((uint64_t)sw << 62);
}
__device__ __forceinline__ void wg_fence() { asm volatile("wgmma.fence.sync.aligned;" ::: "memory"); }
__device__ __forceinline__ void wg_commit() { asm volatile("wgmma.commit_group.sync.aligned;" ::: "memory"); }
template <int N> __device__ __forceinline__ void wg_wait() { asm volatile("wgmma.wait_group.sync.aligned %0;" ::"n"(N) : "memory"); }
#define R8(c, o) "+f"(c[o]), "+f"(c[o + 1]), "+f"(c[o + 2]), "+f"(c[o + 3]), "+f"(c[o + 4]), "+f"(c[o + 5]), "+f"(c[o + 6]), "+f"(c[o + 7])
#define R32(c, o) R8(c, o), R8(c, o + 8), R8(c, o + 16), R8(c, o + 24)
#define S32A "%0,%1,%2,%3,%4,%5,%6,%7,%8,%9,%10,%11,%12,%13,%14,%15,%16,%17,%18,%19,%20,%21,%22,%23,%24,%25,%26,%27,%28,%29,%30,%31"
template <int ACC> __device__ __forceinline__ void wgmma64_rs(float* c, const uint32_t* a, uint64_t db) {
    asm volatile("wgmma.mma_async.sync.aligned.m64n64k16.f32.bf16.bf16 {" S32A "},{%32,%33,%34,%35},%36,%37,1,1,0;"
                 : R32(c, 0) : "r"(a[0]), "r"(a[1]), "r"(a[2]), "r"(a[3]), "l"(db), "n"(ACC));
}
template <int ACC> __device__ __forceinline__ void wgmma64_ta(float* c, uint64_t da, uint64_t db) {
    asm volatile("wgmma.mma_async.sync.aligned.m64n64k16.f32.bf16.bf16 {" S32A "},%32,%33,%34,1,1,1,0;" : R32(c, 0) : "l"(da), "l"(db), "n"(ACC));
}
#define S16 "%0,%1,%2,%3,%4,%5,%6,%7,%8,%9,%10,%11,%12,%13,%14,%15"
template <int ACC> __device__ __forceinline__ void wgmma32_rs(float* c, const uint32_t* a, uint64_t db) {
    asm volatile("wgmma.mma_async.sync.aligned.m64n32k16.f32.bf16.bf16 {" S16 "},{%16,%17,%18,%19},%20,%21,1,1,0;"
                 : R8(c, 0), R8(c, 8) : "r"(a[0]), "r"(a[1]), "r"(a[2]), "r"(a[3]), "l"(db), "n"(ACC));
}
template <int ACC> __device__ __forceinline__ void wgmma32_ta(float* c, uint64_t da, uint64_t db) {
    asm volatile("wgmma.mma_async.sync.aligned.m64n32k16.f32.bf16.bf16 {" S16 "},%16,%17,%18,1,1,1,0;" : R8(c, 0), R8(c, 8) : "l"(da), "l"(db), "n"(ACC));
}
template <int ACC> __device__ __forceinline__ void wgmma80_tb(float* c, uint64_t da, uint64_t db) {
    asm volatile("wgmma.mma_async.sync.aligned.m64n80k16.f32.bf16.bf16 {" S32A ",%32,%33,%34,%35,%36,%37,%38,%39},%40,%41,%42,1,1,0,1;"
                 : R32(c, 0), R8(c, 32) : "l"(da), "l"(db), "n"(ACC));
}
template <int N> __device__ __forceinline__ void reg_inc() { asm volatile("setmaxnreg.inc.sync.aligned.u32 %0;" ::"n"(N)); }
template <int N> __device__ __forceinline__ void reg_dec() { asm volatile("setmaxnreg.dec.sync.aligned.u32 %0;" ::"n"(N)); }

#define PROF(cond, idx) do {} while (0)
#define PROF2(cond, idx) do {} while (0)

constexpr int S_GATE = 232440, S_TAG = 232444, S_XBAR = 232432, B_BAR = 231936;
#define FT 5
#define FJ 62
#define OLAG 1
#define RCB 136
#define RCU 184
#define NTOP 1
#define PLATE 2
#define QLAG 4
constexpr float SC_LOG2E = 0.08838834764831845f * 1.4426950408889634f;

__device__ __forceinline__ float2 ln_finish(float mean, float var) {
    float sd; asm("sqrt.approx.f32 %0,%1;" : "=f"(sd) : "f"(rbf(rbf(var) + 1e-5f)));
    sd = rbf(sd);
    return make_float2(rbf(mean), sd);
}

__device__ __forceinline__ float2 row_stats512(uint4* v, const uint4* src, int s1, int s2) {
    const int g = (threadIdx.x & 31) >> 2;
#pragma unroll
    for (int i = 0; i < 16; i++) v[i] = ldcg128(src + (i >> 1) * s1 + (i & 1) * s2);
    float a[4] = {0, 0, 0, 0}, q0[4] = {0, 0, 0, 0}, q1[4] = {0, 0, 0, 0};
#pragma unroll
    for (int i = 0; i < 16; i++) {
        mma16(a, v[i].x, v[i].y, v[i].z, v[i].w, 0x3f803f80u, 0x3f803f80u);
        mma8(q0, v[i].x, v[i].y, v[i].x); mma8(q1, v[i].x, v[i].y, v[i].y);
        mma8(q0, v[i].z, v[i].w, v[i].z); mma8(q1, v[i].z, v[i].w, v[i].w);
    }
    const float sum = a[0] + a[2], sq = (g & 1) ? q0[1] + q1[3] : q0[0] + q1[2];
    return make_float2(sum, fmaxf(sq - sum * sum * (1.f / 512.f), 0.f));
}
__device__ __forceinline__ void x1_norm(const uint2* src, int r, bool on) {
    const int lane = threadIdx.x & 31, g = lane >> 2, t = r * 4 + (lane & 3);
    constexpr int xp = XP;
    uint2 v[16];
#pragma unroll
    for (int i = 0; i < 16; i++) asm volatile("ld.global.cg.v2.u32 {%0,%1},[%2];" : "=r"(v[i].x), "=r"(v[i].y) : "l"(src + (g * 4 * xp + t) + ((i >> 1) * 16 + (i & 1)) * 2 * xp) : "memory");
    float s = 0, q = 0;
#pragma unroll
    for (int i = 0; i < 32; i++) {
        const uint32_t w = (i & 1) ? v[i >> 1].y : v[i >> 1].x;
        s += blo(w) + bhi(w); q = fmaf(blo(w), blo(w), fmaf(bhi(w), bhi(w), q));
    }
#pragma unroll
    for (int d = 4; d < 32; d *= 2) { s += __shfl_xor_sync(0xffffffffu, s, d); q += __shfl_xor_sync(0xffffffffu, q, d); }
    if (g == 0 && on) g_ln0[t] = 0;
    s *= 1.f / 512.f;
    const float2 l = ln_finish(s, fmaxf(fmaf(q, 1.f / 512.f, -s * s), 0.f));
    const float rs = rcp(l.y);
    const uint32_t mm = pack2(-l.x, -l.x);
    uint4* dst = g_xn + ((t >> 6) * 4096 + ((t >> 3) & 7) * 64 + g * 8 + (t & 7));
#define NRM(w) pack2(blo(hadd2(w, mm)) * rs, bhi(hadd2(w, mm)) * rs)
#pragma unroll
    for (int i = 0; i < 8; i++)
        asm volatile("{.reg .pred p; setp.ne.u32 p,%5,0; @p st.global.v4.u32 [%0],{%1,%2,%3,%4};}" ::"l"(dst + i * 512), "r"(NRM(v[2 * i].x)), "r"(NRM(v[2 * i].y)),
                     "r"(NRM(v[2 * i + 1].x)), "r"(NRM(v[2 * i + 1].y)), "r"((uint32_t)on) : "memory");
}

#define NWO 10
#define VMASK 0x4444
#define VPRE 2
#define OL 0x16
#define PINS 0x6ae5
#define NPX 2
#define NPF 2
constexpr int SLOT = 24576, SL_V = 8192, SL_Q = 16384, SL_KM = 20480, SL_VM = 22528;
constexpr int R_SL = 0, R_WV = 4 * SLOT  , R_WO = R_WV + 65536, R_M = 196608  , R_U = R_M + 8192  ,
              R_OS = R_U + 8192  , R_SB = R_OS + 8192  , R_OB = R_SB + 5248  , R_PB = R_OB + 2048  ,
              R_IL = R_PB + 1024  , R_SEL = 231680, R_BAR = R_SEL + 256, R_STV = 0, R_STQ = 65536, R_STK = 131072;
static_assert(R_WO + (16 - NWO) * 4096 <= R_M && R_IL + 64 <= R_SEL && R_BAR + 512 <= 232448, "smem map");
enum { RB_XFULL = 0  , RB_GO = 4  , RB_QK = 8  , RB_INIT = 24, RB_SV = 25   };

enum { NB_MFULL = 1  , NB_PART = 3  , NB_S = 5, NB_P = 6, NB_O = 7, NB_W = 10 };
#define XU 4
#define PADW 7
#define PADH 0
#define NPRB 3
#define RH 56
#define RW0 224
#define D1 240
#define D2 300
__device__ __forceinline__ uint32_t clk32() { uint32_t c; asm volatile("mov.u32 %0,%%clock;" : "=r"(c)::"memory"); return c; }
__device__ __forceinline__ void spin(int cycles) {
    if (cycles <= 0) return;
    asm volatile("{.reg .pred p; .reg .u32 a,b; mov.u32 a,%%clock; add.u32 a,a,%0;\nS%=: mov.u32 b,%%clock; sub.u32 b,b,a; setp.lt.s32 p,b,0; @p bra.uni S%=;}" ::"r"(cycles) : "memory");
}
__device__ __forceinline__ uint4* xregion(int X, int r) { return (uint4*)(((size_t)g_xch + 8191) & ~(size_t)8191) + (X * 66 + r) * 512; }

__device__ __forceinline__ void arrive_if(uint32_t bar, uint32_t a, uint32_t b) {
    asm volatile("{.reg .pred p; setp.eq.u32 p,%1,%2; @p mbarrier.arrive.shared::cta.b64 _,[%0];}" ::"r"(bar), "r"(a), "r"(b) : "memory");
}
struct RecW { uint32_t po, dp, lw, sp, w; };
#define PIN(n) if ((PINS >> (n)) & 1) asm volatile("griddepcontrol.launch_dependents;" ::: "memory")
constexpr int v_stream(int n) {
    int ks = 0;
    for (; ks < 16; ks++) if (!((VMASK >> ks) & 1) && n-- == 0) break;
    return ks;
}
constexpr uint64_t v_next() {
    uint64_t r = 0;
    for (int n = 0; v_stream(n + VPRE) < 16; n++) r |= (uint64_t)v_stream(n + VPRE) << (4 * v_stream(n));
    return r;
}
constexpr uint64_t V_NEXT = v_next();
constexpr int V_PRE = v_stream(VPRE);

__device__ __forceinline__ void rec_step(const RecW& k, uint32_t sb, const int X, int s, uint32_t zero, int lo, int hi, int d, const uint32_t (*wq)[4], const uint32_t (*wk)[4], uint4* wv, uint4* wo) {
    const int SL = R_SL + X * 2 * SLOT;
    uint4 mk[8];
    bar_sync(NB_MFULL + X, 288);
    mk[0] = ldsm4(k.lw + X * 4096 + R_M);
    PIN(0);
    mk[1] = ldsm4(k.lw + X * 4096 + R_M + 512);
    PIN(0);
    asm volatile("" : "+r"(s));
    const uint32_t z = s & zero, wz = k.w + z, w5 = wz * 512, so = (s & 1) * SLOT + w5;
    const uint32_t qb = sb + R_BAR + (RB_QK + X * 8) * 8 + wz * 8;
    uint32_t x[4], vv[2], l8;
    {
        float aq[4] = {0, 0, 0, 0}, ak[4] = {0, 0, 0, 0}, av[4] = {0, 0, 0, 0};
#pragma unroll
        for (int t = 0; t < 16; t++) {
            const uint32_t b0 = (t & 1) ? mk[t >> 1].z : mk[t >> 1].x, b1 = (t & 1) ? mk[t >> 1].w : mk[t >> 1].y;
            mma16(aq, wq[t][0], wq[t][1], wq[t][2], wq[t][3], b0, b1);
            PIN(8);
            mma16(ak, wk[t][0], wk[t][1], wk[t][2], wk[t][3], b0, b1);
            PIN(9);
            mma16(av, wv[t].x, wv[t].y, wv[t].z, wv[t].w, b0, b1);
            PIN(10);
            if ((t & 1) && t < 13) mk[(t >> 1) + 2] = ldsm4(k.lw + X * 4096 + R_M + (t >> 1) * 512 + 1024);
            const int nx = (V_NEXT >> (4 * t)) & 15;
            if (nx) wv[nx] = lds128(k.lw + w5 + R_WV + nx * 4096);
            if (t == 14) l8 = ((k.lw + z) >> 1) + (sb - (sb >> 1) + SL + (s & 1) * SLOT + wz * 256);
            if (t < 15) PIN(1);
        }
        x[0] = movm(pack2(aq[0], aq[1])); x[1] = movm(pack2(aq[2], aq[3]));
        x[2] = movm(pack2(ak[0], ak[1])); x[3] = movm(pack2(ak[2], ak[3]));
        vv[0] = pack2(av[0], av[1]); vv[1] = pack2(av[2], av[3]);
        st_async2(l8 + (SL_VM + k.dp), vv[0], vv[1], qb + k.dp);
        st_async4(k.lw + (R_U + X * 4096 + w5 + k.dp), x[0], x[1], x[2], x[3], qb + k.dp);
    }
    {
        arrive_if(sb + R_BAR + (RB_GO + 2 - 2 * X + ((s + d) & 1)) * 8, (k.sp + z) & 0x1ff0, X ? s >= hi : s <= lo);
        const uint32_t swr = ((k.sp + z) & 0x1ff0) + (sb + R_SB);
#pragma unroll
        for (int i = 0; i < NPX; i++) wo[i] = lds128v(k.lw + w5 + R_WO + i * 4096);
        mbar_wait(sb + R_BAR + (RB_XFULL + X * 2) * 8 + (s & 1) * 8, (s >> 1) & 1);
        const uint4 k0 = lds128(k.lw + so + SL), k1 = lds128(k.lw + so + SL + 4096);
        mbar_wait(qb, s & 1);
        const uint4 u = lds128(k.lw + w5 + R_U + X * 4096);
        const uint32_t q0 = hadd2(x[0], u.x), q1 = hadd2(x[1], u.y);
        x[2] = hadd2(x[2], u.z); x[3] = hadd2(x[3], u.w);
        float sa[4] = {0, 0, 0, 0}, sc[4] = {0, 0, 0, 0}, sm0, sm1;
        mma16(sa, k0.x, k0.y, k0.z, k0.w, q0, q1);
        mma16(sc, k1.x, k1.y, k1.z, k1.w, q0, q1);
        mma16_top(sm0, sm1, x[2], x[3], q0, q1);
        asm volatile("stmatrix.sync.aligned.m8n8.x4.trans.shared.b16 [%0],{%1,%2,%3,%4};" ::"r"(swr), "r"(pack2(sa[0], sa[1])), "r"(pack2(sa[2], sa[3])),
                     "r"(pack2(sc[0], sc[1])), "r"(pack2(sc[2], sc[3])) : "memory");
        asm volatile("stmatrix.sync.aligned.m8n8.x1.trans.shared.b16 [%0],{%1};" ::"r"(swr + 512), "r"(pack2(sm0, sm1)) : "memory");
    }
    bar_sync(NB_S, 256);
    uint4 v0, v1;
    uint32_t ls;
    {
        const uint4 y = ldsm4t(k.lw + wz * 656 + R_SB);
        PIN(2);
        uint32_t y4; asm volatile("ldmatrix.sync.aligned.m8n8.x1.trans.shared.b16 {%0},[%1];" : "=r"(y4) : "r"(k.lw + wz * 656 + R_SB + 512) : "memory");
        PIN(2);
        const uint2 vp = lds64(l8 + SL_VM);
        sts64(l8 + SL_KM, x[2], x[3]);
        const uint32_t z1 = k.lw & z, z2 = k.sp & z, ONE = 0x3f803f80u | z2, ONF = 0x3f803f80u | z1;
        float a[4] = {0, 0, 0, 0}, b[4] = {0, 0, 0, 0}, e[4] = {0, 0, 0, 0};
        mma8(e, ONE, z1, y4); mma16(a, ONE, z1, z2, ONF, y.x, y.y); mma16(b, ONE, z1, z2, ONF, y.z, y.w);
        vv[0] = hadd2(vv[0], vp.x); vv[1] = hadd2(vv[1], vp.y);
        sts64(l8 + SL_VM, vv[0], vv[1]);
        float s0, s1;
        asm("{.reg .pred p1,p2,p4; .reg .f32 t0,t1,u0,u1; .reg .b32 m; and.b32 m,%12,64; setp.ne.u32 p1,m,0; and.b32 m,%12,128; setp.ne.u32 p2,m,0; and.b32 m,%12,256; setp.ne.u32 p4,m,0;"
            "selp.f32 t0,%4,%2,p1; selp.f32 t1,%5,%3,p1; selp.f32 u0,%8,%6,p1; selp.f32 u1,%9,%7,p1; selp.f32 t0,u0,t0,p2; selp.f32 t1,u1,t1,p2; selp.f32 %0,%10,t0,p4; selp.f32 %1,%11,t1,p4;}"
            : "=f"(s0), "=f"(s1) : "f"(a[0]), "f"(a[1]), "f"(a[2]), "f"(a[3]), "f"(b[0]), "f"(b[1]), "f"(b[2]), "f"(b[3]), "f"(e[0]), "f"(e[1]), "r"(k.lw));
        const int mi = __float_as_int(fmaxf(s0, s1));
        const int mp = __reduce_max_sync(0xffffffffu, mi), mn = (int)__reduce_min_sync(0xffffffffu, (unsigned)mi);
        PIN(3);
        v0 = lds128(k.lw + so + SL + SL_V); v1 = lds128(k.lw + so + SL + SL_V + 4096);
#pragma unroll
        for (int i = NPX; i < NPF; i++) wo[i] = lds128(k.lw + w5 + R_WO + i * 4096);
        PIN(4);
        const float mo = -__int_as_float(mp >= 0 ? mp : mn) * SC_LOG2E;
        s0 = ex2(fmaf(s0, SC_LOG2E, mo)); s1 = ex2(fmaf(s1, SC_LOG2E, mo));
        sts32((((k.sp + z) >> 11) & 0x1fc) + (k.lw & 256) * 2 + (sb + R_PB), pack2(s0, s1));
        ls = k.lw < sb + 320 ? __float_as_uint((s0 + s1) + 4.f) : 0;
    }
    bar_sync(NB_P, 256);
    {
        const uint4 pp = lds128(k.lw + R_PB);
        PIN(5);
        const uint32_t pm = lds32(((k.lw + z) >> 2) + (sb - (sb >> 2) + R_PB + 512));
        PIN(5);
        sts32(sb + R_IL + (wz >> 1) * 16 + (wz & 1) * 4, __reduce_add_sync(0xffffffffu, ls) - 20u * 0x40800000u);
        float o0[4] = {0, 0, 0, 0}, o1[4] = {0, 0, 0, 0}, o2[4] = {0, 0, 0, 0};
        mma16(o0, v0.x, v0.y, v0.z, v0.w, pp.x, pp.y);
        mma16(o1, v1.x, v1.y, v1.z, v1.w, pp.z, pp.w);
        mma8(o2, vv[0], vv[1], pm);
        asm volatile("stmatrix.sync.aligned.m8n8.x2.trans.shared.b16 [%0],{%1,%2};" ::"r"(k.lw + wz * 256 + R_OB),
                     "r"(pack2(o0[0] + o1[0] + o2[0], o0[1] + o1[1] + o2[1])), "r"(pack2(o0[2] + o1[2] + o2[2], o0[3] + o1[3] + o2[3])) : "memory");
    }
    bar_sync(NB_O, 256);
    {
        float r0[4] = {0, 0, 0, 0}, r1[4] = {0, 0, 0, 0};
        uint4 b[4];
        b[0] = ldsm4(k.lw + R_OB);
        PIN(6);
        b[1] = ldsm4(k.lw + R_OB + 512);
        PIN(6);
#pragma unroll
        for (int m = NWO + NPF; m < 16; m++) if (((OL >> (2 * (15 - m))) & 3) == 3) wo[m] = lds128(k.lw + w5 + R_WO + (m - NWO) * 4096);
        const uint2 il = lds64(sb + R_IL + ((k.lw + z) & 48));
        PIN(6);
        float i0, i1;
        uint4* dst;
#pragma unroll
        for (int i = 0; i < 4; i++) {
            mma16(r0, wo[4 * i].x, wo[4 * i].y, wo[4 * i].z, wo[4 * i].w, b[i].x, b[i].y);
            mma16(r1, wo[4 * i + 1].x, wo[4 * i + 1].y, wo[4 * i + 1].z, wo[4 * i + 1].w, b[i].x, b[i].y);
            mma16(r0, wo[4 * i + 2].x, wo[4 * i + 2].y, wo[4 * i + 2].z, wo[4 * i + 2].w, b[i].z, b[i].w);
            mma16(r1, wo[4 * i + 3].x, wo[4 * i + 3].y, wo[4 * i + 3].z, wo[4 * i + 3].w, b[i].z, b[i].w);
            if (i < 2) b[i + 2] = ldsm4(k.lw + R_OB + (i + 2) * 512);
#pragma unroll
            for (int m = NWO + NPF; m < 16; m++) if (i < 3 && i == ((OL >> (2 * (15 - m))) & 3)) wo[m] = lds128(k.lw + w5 + R_WO + (m - NWO) * 4096);
            if (i == 1) { i0 = rcp(__uint2float_rn(il.x)) * 2097152.f; i1 = rcp(__uint2float_rn(il.y)) * 2097152.f; }
            if (i == 2) {
                const uint32_t po = k.sp + z;
                dst = xregion(X, 0) + k.po + ((po >> 20) ^ ((po & X) << 8));
                asm volatile("" : "+l"(dst));
            }
            PIN(7);
        }
        const uint32_t tag = (s + 1) & 1;
#pragma unroll
        for (int i = 0; i < 4; i++) { r0[i] *= (i & 1) ? i1 : i0; r1[i] *= (i & 1) ? i1 : i0; }
        st_rlx128(dst, (pack2(r0[0], r0[2]) & ~1u) | tag,
                  pack2(r1[0], r1[2]), pack2(r0[1], r0[3]), pack2(r1[1], r1[3]));
        bar_arrive(NB_PART + X, 288);
#pragma unroll
        for (int t = 0; t < V_PRE; t++) if (!((VMASK >> t) & 1)) wv[t] = lds128(k.lw + w5 + R_WV + t * 4096);
        arrive_if(sb + R_BAR + (RB_GO + 2 * X + (s & 1)) * 8, (k.sp + z) & 0x1ff0, X ? s + 1 < hi : s >= lo);
    }
}

__device__ __forceinline__ void rec_fetch(const Params& p, uint32_t sb, int head, uint32_t rank, int which, int dst) {
#pragma unroll 1
    for (int j = 0; j < 8; j++) tma2d(sb + dst + j * 8192, &p.tm[which], head * 128 + (j >> 2) * 64, rank * 256 + (j & 3) * 64, sb + R_BAR + RB_INIT * 8);
}

__device__ __forceinline__ void rec_weights(const Params& p, uint32_t sb, int head, uint32_t rank, int w) {
    const int lane = __shfl_sync(0xffffffffu, threadIdx.x & 31, threadIdx.x & 31),
        g = lane >> 2, c = lane & 3;
    const int t = w & 3, WG = w >> 2;
    uint32_t wq[16][4], wk[16][4];
    uint4 wo[16], wv[16];
    const uint32_t woff = sb + WG * 32768 + (((lane >> 4) << 3) + (lane & 7)) * 128 + (((2 * t + ((lane >> 3) & 1)) ^ (lane & 7)) << 4);
    const uint32_t lw = sb + lane * 16;
    PROF2(threadIdx.x == 0, 3501);
    {
        const __nv_bfloat16* wp = p.Wo + (size_t)(head * 128 + 2 * c) * 512 + rank * 256 + w * 32 + g * 4;
#pragma unroll
        for (int ks = 0; ks < 8; ks++) {
            const uint2 r0 = *(const uint2*)(wp + (ks * 16) * 512), r1 = *(const uint2*)(wp + (ks * 16 + 1) * 512);
            const uint2 r2 = *(const uint2*)(wp + (ks * 16 + 8) * 512), r3 = *(const uint2*)(wp + (ks * 16 + 9) * 512);
            const uint4 f[2] = {make_uint4(__byte_perm(r0.x, r1.x, 0x5410), __byte_perm(r0.x, r1.x, 0x7632), __byte_perm(r2.x, r3.x, 0x5410), __byte_perm(r2.x, r3.x, 0x7632)),
                                make_uint4(__byte_perm(r0.y, r1.y, 0x5410), __byte_perm(r0.y, r1.y, 0x7632), __byte_perm(r2.y, r3.y, 0x5410), __byte_perm(r2.y, r3.y, 0x7632))};
#pragma unroll
            for (int h = 0; h < 2; h++) {
                const int m = 2 * ks + h;
                wo[m] = f[h];
            }
        }
    }
    PROF2(threadIdx.x == 0, 3502);
    mbar_wait(sb + R_BAR + RB_INIT * 8, 0);
    PROF2(threadIdx.x == 0, 3503);
#pragma unroll
    for (int ks = 0; ks < 16; ks++) {
        uint4 a = ldsm4t(woff + R_STQ + ks * 2048), b = ldsm4t(woff + R_STK + ks * 2048);
        wq[ks][0] = a.x; wq[ks][1] = a.y; wq[ks][2] = a.z; wq[ks][3] = a.w;
        wk[ks][0] = b.x; wk[ks][1] = b.y; wk[ks][2] = b.z; wk[ks][3] = b.w;
    }
    bar_sync(NB_W, 256);
#pragma unroll
    for (int m = 0; m < 16; m++)
        if (m < NPF || m >= NPF + NWO) sts128(lw + w * 512 + R_WO + (m < NPF ? m : m - NWO) * 4096, wo[m].x, wo[m].y, wo[m].z, wo[m].w);
#pragma unroll
    for (int i = 0; i < 16; i++) {
        wv[i] = ldsm4t(woff + R_STV + i * 2048);
        if (!((VMASK >> i) & 1)) sts128(lw + w * 512 + R_WV + i * 4096, wv[i].x, wv[i].y, wv[i].z, wv[i].w);
    }
    fence_async_smem();
    PROF2(threadIdx.x == 0, 3504);
    __syncthreads();
    cluster_sync();
    PROF2(threadIdx.x == 0, 3505);
    RecW k;
    {
        const int r = (w * 4 + (lane >> 3)) * 2 + rank;
        const uint32_t sl = lds32(sb + R_SEL + r * 4);
        k.po = (w * 8 + rank) * 512 + (head >> 1) * 16 + (head & 1) * 4;
        k.sp = (((lane >> 3) * 1024 + (sl & 1) * 256 + (lane & 4) * 2 + (lane & 3)) << 20) + (((sl >> 1) ^ sl) & 1) + (lane & 7) * 656 + (lane >> 3) * 128 + w * 16 +
               ((g < 4 ? (w * 4 + c) * 4 + g : w * 4 + c) << 13);
    }
    k.dp = mapa(sb, rank ^ 1) - sb;
    k.lw = lw;
    asm volatile("" : "+r"(k.lw));
    k.w = w;
    const int e0 = (p.chains & 1) ? 64 : 0, o1 = (p.chains & 2) ? p.lag : 1000, nit = (p.chains & 2) ? p.lag + 64 : e0;
    const uint32_t zero = p.zero;
    int it = 0, X = e0 ? 0 : 1;
#pragma unroll 1
    while (it < nit) {
        rec_step(k, sb, X, X ? it - o1 : it, zero, o1, e0 - o1, o1 + 1 - X, wq, wk, wv, wo);
        if (X == 0 && it >= o1) X = 1; else { it++; X = it < e0 ? 0 : 1; }
    }
}

__device__ __forceinline__ uint32_t mism(uint32_t a, uint32_t b, uint32_t t) {
    uint32_t d; asm("lop3.b32 %0,%1,%2,%3,0x7e;" : "=r"(d) : "r"(a), "r"(b), "r"(t)); return d;
}
__device__ __forceinline__ uint32_t or3(uint32_t a, uint32_t b, uint32_t c) {
    uint32_t d; asm("lop3.b32 %0,%1,%2,%3,0xfe;" : "=r"(d) : "r"(a), "r"(b), "r"(c)); return d;
}
#define X4(j) "=r"(x[j].x), "=r"(x[j].y), "=r"(x[j].z), "=r"(x[j].w)
#define X32 X4(0), X4(1), X4(2), X4(3), X4(4), X4(5), X4(6), X4(7)
template <bool TWO>
__device__ __forceinline__ void poll8(uint4* x, const uint4* src, uint32_t tag) {
    if (TWO) asm volatile(
        "{.reg .pred p,q<8>; .reg .b32 n,m<8>; .reg .b128 t<8>; mov.u32 n,0; ld.relaxed.gpu.global.b128 t0,[%32+0]; ld.relaxed.gpu.global.b128 t1,[%32+512]; "
        "ld.relaxed.gpu.global.b128 t2,[%32+1024]; ld.relaxed.gpu.global.b128 t3,[%32+1536]; ld.relaxed.gpu.global.b128 t4,[%32+2048]; "
        "ld.relaxed.gpu.global.b128 t5,[%32+2560]; ld.relaxed.gpu.global.b128 t6,[%32+3072]; ld.relaxed.gpu.global.b128 t7,[%32+3584]; \nL%=: "
        "mov.b128 {%0,%1,%2,%3},t0; mov.b128 {%4,%5,%6,%7},t1; mov.b128 {%8,%9,%10,%11},t2; mov.b128 {%12,%13,%14,%15},t3; mov.b128 {%16,%17,%18,%19},t4; "
        "mov.b128 {%20,%21,%22,%23},t5; mov.b128 {%24,%25,%26,%27},t6; mov.b128 {%28,%29,%30,%31},t7; lop3.b32 m0,%0,%2,%33,0x7e; lop3.b32 m1,%4,%6,%33,0x7e; "
        "lop3.b32 m2,%8,%10,%33,0x7e; lop3.b32 m3,%12,%14,%33,0x7e; lop3.b32 m4,%16,%18,%33,0x7e; lop3.b32 m5,%20,%22,%33,0x7e; lop3.b32 m6,%24,%26,%33,0x7e; "
        "lop3.b32 m7,%28,%30,%33,0x7e; "
        "{.reg .b32 a,b; lop3.b32 a,m0,m1,m2,0xfe; lop3.b32 b,m3,m4,m5,0xfe; lop3.b32 a,a,m6,m7,0xfe; lop3.b32 a,a,b,1,0xa8; setp.ne.u32 p,a,0;} "
        "vote.sync.any.pred p,p,0xffffffff; @!p bra.uni D%=; and.b32 m0,m0,1; setp.ne.u32 q0,m0,0; and.b32 m1,m1,1; setp.ne.u32 q1,m1,0; "
        "and.b32 m2,m2,1; setp.ne.u32 q2,m2,0; and.b32 m3,m3,1; setp.ne.u32 q3,m3,0; and.b32 m4,m4,1; setp.ne.u32 q4,m4,0; "
        "and.b32 m5,m5,1; setp.ne.u32 q5,m5,0; and.b32 m6,m6,1; setp.ne.u32 q6,m6,0; and.b32 m7,m7,1; setp.ne.u32 q7,m7,0; "
        "@q0 ld.relaxed.gpu.global.b128 t0,[%32+0]; @q1 ld.relaxed.gpu.global.b128 t1,[%32+512]; @q2 ld.relaxed.gpu.global.b128 t2,[%32+1024]; "
        "@q3 ld.relaxed.gpu.global.b128 t3,[%32+1536]; @q4 ld.relaxed.gpu.global.b128 t4,[%32+2048]; @q5 ld.relaxed.gpu.global.b128 t5,[%32+2560]; "
        "@q6 ld.relaxed.gpu.global.b128 t6,[%32+3072]; @q7 ld.relaxed.gpu.global.b128 t7,[%32+3584]; "
        "add.u32 n,n,1; setp.lt.u32 p,n,2000000; @p bra.uni L%=; trap;\nD%=: } " : X32 : "l"(src), "r"(tag) : "memory");
    else asm volatile(
        "{.reg .pred p,q<8>; .reg .b32 n,m<8>; .reg .b128 t<8>; mov.u32 n,0; ld.relaxed.gpu.global.b128 t0,[%32+0]; ld.relaxed.gpu.global.b128 t1,[%32+512]; "
        "ld.relaxed.gpu.global.b128 t2,[%32+1024]; ld.relaxed.gpu.global.b128 t3,[%32+1536]; ld.relaxed.gpu.global.b128 t4,[%32+2048]; "
        "ld.relaxed.gpu.global.b128 t5,[%32+2560]; ld.relaxed.gpu.global.b128 t6,[%32+3072]; ld.relaxed.gpu.global.b128 t7,[%32+3584]; \nL%=: "
        "mov.b128 {%0,%1,%2,%3},t0; mov.b128 {%4,%5,%6,%7},t1; mov.b128 {%8,%9,%10,%11},t2; mov.b128 {%12,%13,%14,%15},t3; mov.b128 {%16,%17,%18,%19},t4; "
        "mov.b128 {%20,%21,%22,%23},t5; mov.b128 {%24,%25,%26,%27},t6; mov.b128 {%28,%29,%30,%31},t7; lop3.b32 m0,%0,%4,%33,0x7e; lop3.b32 m1,%8,%12,%33,0x7e; "
        "lop3.b32 m2,%16,%20,%33,0x7e; lop3.b32 m3,%24,%28,%33,0x7e; {.reg .b32 a; lop3.b32 a,m0,m1,m2,0xfe; lop3.b32 a,a,m3,1,0xa8; setp.ne.u32 p,a,0;} "
        "vote.sync.any.pred p,p,0xffffffff; @!p bra.uni D%=; lop3.b32 m0,%0,%33,1,0x28; setp.ne.u32 q0,m0,0; lop3.b32 m1,%4,%33,1,0x28; setp.ne.u32 q1,m1,0; "
        "lop3.b32 m2,%8,%33,1,0x28; setp.ne.u32 q2,m2,0; lop3.b32 m3,%12,%33,1,0x28; setp.ne.u32 q3,m3,0; lop3.b32 m4,%16,%33,1,0x28; setp.ne.u32 q4,m4,0; "
        "lop3.b32 m5,%20,%33,1,0x28; setp.ne.u32 q5,m5,0; lop3.b32 m6,%24,%33,1,0x28; setp.ne.u32 q6,m6,0; lop3.b32 m7,%28,%33,1,0x28; setp.ne.u32 q7,m7,0; "
        "@q0 ld.relaxed.gpu.global.b128 t0,[%32+0]; @q1 ld.relaxed.gpu.global.b128 t1,[%32+512]; @q2 ld.relaxed.gpu.global.b128 t2,[%32+1024]; "
        "@q3 ld.relaxed.gpu.global.b128 t3,[%32+1536]; @q4 ld.relaxed.gpu.global.b128 t4,[%32+2048]; @q5 ld.relaxed.gpu.global.b128 t5,[%32+2560]; "
        "@q6 ld.relaxed.gpu.global.b128 t6,[%32+3072]; @q7 ld.relaxed.gpu.global.b128 t7,[%32+3584]; "
        "add.u32 n,n,1; setp.lt.u32 p,n,2000000; @p bra.uni L%=; trap;\nD%=: } " : X32 : "l"(src), "r"(tag) : "memory");
}

__device__ __forceinline__ void rec_comm(const Params& p, uint32_t sb, int X, int head, uint32_t rank) {
    const int lane = threadIdx.x & 31, g = lane >> 2, c = lane & 3;
    const int me = head * 2 + rank;
    const uint32_t mb = sb + R_M + X * 4096 + lane * 16;
    uint4 x[8];
#pragma unroll
    for (int j = 0; j < 8; j++) x[j] = *(const uint4*)(p.mem0 + (lane & 7) * 512 + rank * 256 + (j * 4 + (lane >> 3)) * 8);
    const uint32_t sl = lds32(sb + R_SEL + me * 4);
    const uint32_t o1 = ((sl >> X) & 1) * 256 + (c >> 1) * 16 + (g >> 2) * 8 + (c & 1) * 4 + (g & 3);
    const uint32_t o2 = ((sl >> (2 + X)) & 1) * 256 + lane;
    const uint32_t offs = __shfl_sync(0xffffffffu, o1 + (o2 << 10) + ((((c >> 1) * 256 + head * 8 + (g & 3) * 2 + (c & 1)) * 2 + (g >> 2)) << 20), lane);
    const uint32_t one = (g & 1) ? 0x3f800000u : 0x00003f80u, selA = (g & 2) ? 0u : one, selB = (g & 2) ? one : 0u;
    const uint32_t qb = sb + R_BAR + (RB_QK + X * 8) * 8;
    if (lane < 8) mbar_expect(qb + lane * 8, 768);
    __syncwarp();
#pragma unroll
    for (int j = 0; j < 8; j++) sts128(mb + j * 512, x[j].x, x[j].y, x[j].z, x[j].w);
#pragma unroll 1
    for (int s = 0;; s++) {
        bar_arrive(NB_MFULL + X, 288);
        PROF(lane == 0, X * 64 + s);
        const uint32_t of = offs + (s & p.zero);
        const uint4* src = xregion(X, me) + (of & 1023);
        uint2* mdst = (uint2*)xregion(X, 64 + rank) + (of >> 20);
        asm volatile("" : "+l"(src), "+l"(mdst));
        bar_sync(NB_PART + X, 288);
        if (s == 63) break;
        const uint32_t tag = (s + 1) & 1;
        asm volatile("{.reg .pred p; setp.lt.u32 p,%0,%1; @p mbarrier.arrive.expect_tx.shared::cta.b64 _,[%0],768;}"
                     ::"r"(((mb + (s & p.zero)) >> 1) + (qb - ((sb + R_M + X * 4096) >> 1))), "r"(qb + 64) : "memory");
        spin(D1);
        poll8<false>(x, src, tag);
        float a[4][4];
#pragma unroll
        for (int j = 0; j < 8; j++) {
            if (j < 4) a[j][0] = a[j][1] = a[j][2] = a[j][3] = 0;
            mma16(a[j & 3], x[j].x, x[j].y, x[j].z, x[j].w, selA, selB);
        }
#pragma unroll
        for (int i = 0; i < 4; i++) a[0][i] = (a[0][i] + a[1][i]) + (a[2][i] + a[3][i]);
        const uint32_t m0 = (pack2(a[0][0], a[0][1]) & ~1u) | tag, m1 = pack2(a[0][2], a[0][3]);
        asm volatile("st.relaxed.gpu.global.b64 [%0],%1;" ::"l"(mdst), "l"(((uint64_t)m1 << 32) | m0) : "memory");
        src = xregion(X, 64 + rank) + ((of >> 10) & 1023);
        asm volatile("" : "+l"(src));
        spin(D2);
        poll8<true>(x, src, tag);
#pragma unroll
        for (int j = 0; j < 8; j++) sts128(mb + j * 512, x[j].x, x[j].y, x[j].z, x[j].w);
    }
}

template <int MT>
__device__ __forceinline__ void xattn(uint32_t l16, uint32_t l8, uint32_t os, int g, int c) {
    constexpr int NT = 3 + 2 * MT, XUN = XU;
    float S[NT][4];
#pragma unroll
    for (int i = 0; i < NT; i++) S[i][0] = S[i][1] = S[i][2] = S[i][3] = 0;
#pragma unroll XUN
    for (int ks = 0; ks < 8; ks++) {
        const uint4 q = lds128(l16 + SL_Q + ks * 512);
        const uint2 u = lds64(l8 + SL_KM + ks * 256);
        mma16(S[0], q.x, q.y, q.z, q.w, u.x, u.y);
#pragma unroll
        for (int m = 0; m <= MT; m++) {
            const uint4 kk = lds128(l16 + m * 4096 + ks * 512);
            mma16(S[1 + 2 * m], q.x, q.y, q.z, q.w, kk.x, kk.z); mma16(S[2 + 2 * m], q.x, q.y, q.z, q.w, kk.y, kk.w);
        }
    }
    const float NEG = -__int_as_float(0x7f800000);
    if (2 * c > g) { S[NT - 2][0] = NEG; S[NT - 1][2] = NEG; }
    if (2 * c + 1 > g) { S[NT - 2][1] = NEG; S[NT - 1][3] = NEG; }
    S[NT - 1][0] = S[NT - 1][1] = NEG;
    float m0 = fmaxf(S[0][0], S[0][1]), m1 = fmaxf(S[0][2], S[0][3]);
#pragma unroll
    for (int i = 1; i < NT; i++) { if (i < NT - 1) m0 = fmaxf(m0, fmaxf(S[i][0], S[i][1])); m1 = fmaxf(m1, fmaxf(S[i][2], S[i][3])); }
    m0 = fmaxf(m0, __shfl_xor_sync(0xffffffffu, m0, 1)); m1 = fmaxf(m1, __shfl_xor_sync(0xffffffffu, m1, 1));
    m0 = fmaxf(m0, __shfl_xor_sync(0xffffffffu, m0, 2)); m1 = fmaxf(m1, __shfl_xor_sync(0xffffffffu, m1, 2));
    m0 *= -SC_LOG2E; m1 *= -SC_LOG2E;
    float l0 = 0, l1 = 0;
#pragma unroll
    for (int i = 0; i < NT; i++) {
        if (i < NT - 1) { S[i][0] = ex2(fmaf(S[i][0], SC_LOG2E, m0)); S[i][1] = ex2(fmaf(S[i][1], SC_LOG2E, m0)); l0 += S[i][0] + S[i][1]; }
        S[i][2] = ex2(fmaf(S[i][2], SC_LOG2E, m1)); S[i][3] = ex2(fmaf(S[i][3], SC_LOG2E, m1)); l1 += S[i][2] + S[i][3];
    }
    l0 += __shfl_xor_sync(0xffffffffu, l0, 1); l1 += __shfl_xor_sync(0xffffffffu, l1, 1);
    l0 += __shfl_xor_sync(0xffffffffu, l0, 2); l1 += __shfl_xor_sync(0xffffffffu, l1, 2);
    uint2 vm = lds64(l8 + SL_VM);
    uint4 v[2];
#pragma unroll
    for (int m = 0; m <= MT; m++) v[m] = lds128(l16 + SL_V + m * 4096);
    l0 = rcp(l0); l1 = rcp(l1);
    uint32_t P[NT][2];
#pragma unroll
    for (int i = 0; i < NT; i++) { P[i][0] = i < NT - 1 ? pack2(S[i][0] * l0, S[i][1] * l0) : 0u; P[i][1] = pack2(S[i][2] * l1, S[i][3] * l1); }
#pragma unroll
    for (int et = 0; et < 8; et++) {
        float a[4] = {0, 0, 0, 0}, b[4] = {0, 0, 0, 0};
        const uint2 um = vm;
        const uint4 u[2] = {v[0], v[MT]};
        if (et < 7) {
            vm = lds64(l8 + SL_VM + et * 256 + 256);
#pragma unroll
            for (int m = 0; m <= MT; m++) v[m] = lds128(l16 + SL_V + m * 4096 + et * 512 + 512);
            PIN(11);
        }
        mma8(a, um.x, um.y, P[0][0]); mma8(b, um.x, um.y, P[0][1]);
#pragma unroll
        for (int m = 0; m <= MT; m++) {
            mma16(a, u[m].x, u[m].y, u[m].z, u[m].w, P[1 + 2 * m][0], P[2 + 2 * m][0]); mma16(b, u[m].x, u[m].y, u[m].z, u[m].w, P[1 + 2 * m][1], P[2 + 2 * m][1]);
        }
        asm volatile("stmatrix.sync.aligned.m8n8.x4.trans.shared.b16 [%0],{%1,%2,%3,%4};" ::"r"(os + (et >> 2) * 2048 + (et & 3) * 256),
                     "r"(pack2(a[0], a[1])), "r"(pack2(a[2], a[3])), "r"(pack2(b[0], b[1])), "r"(pack2(b[2], b[3])) : "memory");
    }
}

__device__ __forceinline__ void rec_tiles(uint32_t sb, int X, int head, uint32_t rank, int& nxt, int lim, int need) {
#pragma unroll 1
    while (nxt <= lim) {
        if ((nxt & 1) == 0) {
            unsigned v; int n = 0;
            while (true) {
                asm volatile("ld.relaxed.gpu.global.u32 %0,[%1];" : "=r"(v) : "l"(cnt_ptr(C_QKV + X * 32 + (nxt >> 1))) : "memory");
                if (__all_sync(0xffffffffu, v >= 2 * NQ)) break;
                if (nxt > need) return;
                if (++n > 3000000) __trap();
            }
        }
        if (elect()) {
            const uint32_t bar = sb + R_BAR + (RB_XFULL + X * 2 + (nxt & 1)) * 8, dst = sb + R_SL + (X * 2 + (nxt & 1)) * SLOT;
            const uint4* src = g_qkv + (size_t)((X * 64 + nxt) * 32 + head) * 1536;
            mbar_expect(bar, 20480);
            bulk_g2s_mc(dst + rank * 8192, src + 512 + rank * 512, 8192, bar, POL_LAST);
            bulk_g2s(dst + SL_Q, src + (rank ^ X) * 256, 4096, bar, POL_LAST);
        }
        __syncwarp();
        nxt++;
    }
}

__device__ __forceinline__ void rec_attn(const Params& p, uint32_t sb, int X, int head, uint32_t rank) {
    const int lane = __shfl_sync(0xffffffffu, threadIdx.x & 31, threadIdx.x & 31), g = lane >> 2, c = lane & 3;
    const int mt = rank ^ X;
    const uint32_t dp = mapa(sb, rank ^ 1) - sb;
    int nxt = 0;
    rec_tiles(sb, X, head, rank, nxt, 1, 0);
#pragma unroll 1
    for (int s = 0; s < 64; s++) {
        const uint32_t so = sb + R_SL + (X * 2 + (s & 1)) * SLOT;
        while (nxt <= min(s + 1, 63)) {
            uint32_t ok;
            asm volatile("{.reg .pred p; mbarrier.test_wait.parity.shared::cta.b64 p,[%1],%2; selp.u32 %0,1,0,p;}" : "=r"(ok) : "r"(sb + R_BAR + (RB_GO + X * 2 + (s & 1)) * 8), "r"((s >> 1) & 1) : "memory");
            if (__any_sync(0xffffffffu, ok)) break;
            rec_tiles(sb, X, head, rank, nxt, s + 1, -1);
        }
        mbar_wait(sb + R_BAR + (RB_GO + X * 2 + (s & 1)) * 8, (s >> 1) & 1);
        if (elect()) asm volatile("cp.async.bulk.wait_group.read 0;" ::: "memory");
        __syncwarp();
        const uint32_t os = sb + R_OS + X * 4096 + (lane >> 4) * 1024 + (lane & 15) * 16;
        if (mt) xattn<1>(so + lane * 16, so + lane * 8, os, g, c); else xattn<0>(so + lane * 16, so + lane * 8, os, g, c);
        fence_async_smem();
        __syncwarp();
        const uint32_t svb = sb + R_BAR + (RB_SV + X * 2 + (s & 1)) * 8;
        if (elect()) {
            mbar_arrive(svb); mbar_arrive_cluster(svb + dp);
            const uint64_t pol = POL_N;
#pragma unroll
            for (int kb = 0; kb < 2; kb++)
                asm volatile("cp.async.bulk.global.shared::cta.bulk_group.L2::cache_hint [%0],[%1],%2,%3;" ::"l"(g_o + ((X * 32 + (s >> 1)) * 64 + head * 2 + kb) * 512 + ((s & 1) * 4 + mt * 2) * 64),
                             "r"(sb + R_OS + X * 4096 + kb * 2048), "r"(2048), "l"(pol) : "memory");
            asm volatile("cp.async.bulk.commit_group;" ::: "memory");
        }
        __syncwarp();
        if ((s & 1) || X * s >= 60) {
            if (elect()) { asm volatile("cp.async.bulk.wait_group 0;" ::: "memory"); red_relaxed(cnt_ptr(((s & 1) ? C_O : C_OH - 62 * 4) + (X * 32 + (s >> 1)) * 4 + (head >> 3)), 1); }
            __syncwarp();
        }
        rec_tiles(sb, X, head, rank, nxt, min(s + 1, 63), s + 1);
        mbar_wait(svb, (s >> 1) & 1);
        rec_tiles(sb, X, head, rank, nxt, min(s + 2, 63), -1);
    }
}

__device__ __forceinline__ uint32_t timed_clear(unsigned* r, int lane) {
    uint32_t v = 0;
    const uint32_t t0 = clk32();
    asm volatile("{.reg .pred p; setp.eq.u32 p,%2,0; @p atom.relaxed.gpu.global.exch.b32 %0,[%1],0;}" : "+r"(v) : "l"(r), "r"(lane) : "memory");
    v = __shfl_sync(0xffffffffu, v, 0);
    asm volatile("{.reg .pred p; setp.eq.u32 p,%0,0x5a5a5a5b; @p nanosleep.u32 1;}" ::"r"(v) : "memory");
    return clk32() - t0;
}
__device__ __forceinline__ void rec_slots(int me, int w) {
    const int lane = threadIdx.x & 31;
    uint4* r = xregion(w & 1, (w & 2) ? 64 + (me & 1) : me) + ((w & 2) ? (me >> 1) * 8 : 0);
#pragma unroll 1
    for (int i = lane; i < ((w & 2) ? 8 : 256); i += 32) r[i] = r[i + 256] = make_uint4(0, 0, 0, 0);
    __syncwarp();
    uint32_t b0 = ~0u, b1 = ~0u;
#pragma unroll 1
    for (int i = 0; i < NPRB; i++) { b0 = min(b0, timed_clear((unsigned*)r, lane)); b1 = min(b1, timed_clear((unsigned*)(r + 256), lane)); }
    if (lane == 0) ((uint8_t*)g_sel)[me * 4 + w] = (b1 < b0) << w;
}

__device__ __forceinline__ void rec_init(uint32_t sb) {
    const uint32_t b = sb + R_BAR;
    const int i = threadIdx.x & 31;
    mbar_init(b + i * 8, i >= RB_SV ? 2 : 1);
    if (i == RB_INIT) mbar_expect(b + RB_INIT * 8, 196608);
    asm volatile("fence.mbarrier_init.release.cluster;" ::: "memory");
}
constexpr int G_BAR = B_BAR;
enum { GB_FULL = 0  , GB_EMPTY = 8  , GB_RS = 16, GB_SS = 17, GB_LAG = 18, GB_FREE = 19, GB_DONE = 20  , GB_N = 24 };
constexpr int Q_PRE = 8;
constexpr int NQRS = 2 * NQ - 64;
__device__ __forceinline__ void gemm_init(uint32_t sb, bool op) {
    const int i = threadIdx.x & 31;
    if (i < GB_N) mbar_init(sb + G_BAR + i * 8, i >= GB_DONE ? 4 : i == GB_FREE ? 8 : (i >= GB_EMPTY && i < GB_RS) ? 2 : 1);
    if (i == GB_RS) mbar_expect(sb + G_BAR + i * 8, op ? 131072 : 98304);
    if (i == GB_SS) mbar_expect(sb + G_BAR + i * 8, op ? 131072 : 163840);
    asm volatile("fence.mbarrier_init.release.cluster;" ::: "memory");
}
__device__ __forceinline__ int qkv_blk(int id, int j) { return NQRS * 4 + id * 10 + j; }
__device__ __forceinline__ void qkv_fetch(const Params& p, uint32_t sb, int id, int j0, int j1) {
#pragma unroll 1
    for (int j = j0 * 2; j < j1 * 2; j++) {
        const int blk = min(qkv_blk(id, j >> 1), 511);
        tma2d(sb + j * 8192, &p.tn[blk >> 8], (blk & 255) * 16, (j & 1) * 256, sb + G_BAR + GB_SS * 8);
    }
}
__device__ __forceinline__ void qkv_stage(const Params& p, uint32_t dst, uint32_t bar, int id, int k0, int nk) {
#pragma unroll 1
    for (int j = 0; j < 2 * nk; j++) {
        const int u = id * 2 + (j >= nk);
        tma2d(dst + j * 8192, &p.tm[u < 64 ? 2 : 0], (u & 63) * 64, (k0 + (j >= nk ? j - nk : j)) * 64, bar);
    }
}
__device__ __forceinline__ void op_fetch(const Params& p, uint32_t sb, int id, int half) {
#pragma unroll 1
    for (int j = 0; j < 16; j++) tma2d(sb + j * 8192, &p.tm[4], ((id * 2 + (j >> 3)) & 7) * 64, (id >> 2) * 1024 + (j & 7) * 128 + half * 64, sb + G_BAR + (GB_RS + half) * 8);
}
template <bool OP>
__device__ __forceinline__ void gemm_producer(const Params& p, uint32_t sb, int id) {
    constexpr int NS = OP ? 6 : 8, SB = OP ? 16384 : 8192, RB = OP ? 131072 : 163840;
    if (!elect()) return;
    mbar_wait(sb + G_BAR + GB_FREE * 8, 0);
    if (OP) op_fetch(p, sb, id, 1);
    else {
        mbar_expect(sb + G_BAR + GB_RS * 8, 32768);
        qkv_stage(p, sb + 196608, sb + G_BAR + GB_RS * 8, id, 6, 2);
        qkv_fetch(p, sb, id, Q_PRE, 10);
        mbar_wait(sb + G_BAR + GB_FREE * 8, 1);
    }
    wait_cnt(g_gate, lds32(sb + S_GATE));
    int st = 0; uint32_t ph = 1;
#pragma unroll 1
    for (int n = 0; n < p.nl[OP]; n++) {
        const int e = p.list[OP][n];
        wait_cnt(OP ? cnt_ptr(C_O + e * 4 + (id >> 2)) : cnt_ptr(C_XN + e), 16);
        PROF(true, 1024 + n * 4);
        const uint4* src = OP ? g_o + (e * 64 + (id >> 2) * 16) * 512 : g_xn + e * 4096;
#pragma unroll 1
        for (int s = 0; s < 8; s++) {
            mbar_wait(sb + G_BAR + (GB_EMPTY + st) * 8, ph);
            mbar_expect(sb + G_BAR + (GB_FULL + st) * 8, SB);
            bulk_g2s(sb + RB + st * SB, src + s * (SB / 16), SB, sb + G_BAR + (GB_FULL + st) * 8, POL_N);
            if (++st == NS) { st = 0; ph ^= 1; }
        }
    }
#pragma unroll 1
    for (int h = p.h0; OP && h < 128; h++) {
        wait_cnt(cnt_ptr(((h & 1) ? C_O : C_OH - 62 * 4) + (h >> 1) * 4 + (id >> 2)), 16);
        PROF(h & 1, 1024 + (h >> 1) * 4);
        const uint4* src = g_o + ((h >> 1) * 64 + (id >> 2) * 16) * 512 + (h & 1) * 256;
#pragma unroll 1
        for (int s = 0; s < 8; s++) {
            mbar_wait(sb + G_BAR + (GB_EMPTY + st) * 8, ph);
            mbar_expect(sb + G_BAR + (GB_FULL + st) * 8, 8192);
            bulk_g2s(sb + RB + st * SB, src + s * 1024, 4096, sb + G_BAR + (GB_FULL + st) * 8, POL_N);
            bulk_g2s(sb + RB + st * SB + 8192, src + s * 1024 + 512, 4096, sb + G_BAR + (GB_FULL + st) * 8, POL_N);
            if (++st == NS) { st = 0; ph ^= 1; }
        }
    }
}
__device__ __forceinline__ void qkv_release(const Params& p, uint32_t sb) {
    if (!elect()) return;
#pragma unroll 1
    for (int n = 0; n < 2 * p.nl[0]; n++) {
        const int e = p.list[0][n >> 1];
        mbar_wait(sb + G_BAR + (GB_DONE + (n & 3)) * 8, (n >> 2) & 1);
        red_release(cnt_ptr(C_QKV + e), 1);
        PROF(n & 1, 1024 + (n >> 1) * 4 + 3);
    }
}
__device__ __forceinline__ void op_permute(uint32_t sb) {
#pragma unroll 2
    for (int i = threadIdx.x; i < 4096; i += 256) {
        const uint32_t a = sb + i * 32 + ((i >> 2) & 1) * 16, b = a ^ 16;
        const uint4 x = lds128(a), y = lds128(b);
        sts128(a, __byte_perm(x.x, x.y, 0x5410), __byte_perm(x.z, x.w, 0x5410), __byte_perm(y.x, y.y, 0x5410), __byte_perm(y.z, y.w, 0x5410));
        sts128(b, __byte_perm(x.x, x.y, 0x7632), __byte_perm(x.z, x.w, 0x7632), __byte_perm(y.x, y.y, 0x7632), __byte_perm(y.z, y.w, 0x7632));
    }
    fence_async_smem();
    bar_sync(1, 256);
}
template <bool OP>
__device__ __forceinline__ void gemm_consumer(const Params& p, uint32_t sb, int id, int w) {
    constexpr int NS = OP ? 6 : 8, SB = OP ? 16384 : 8192, RB = OP ? 131072 : 163840;
    const int lane = threadIdx.x & 31, wg = w >> 2, t = w & 3, u = id * 2 + wg;
    uint32_t a[128];
    mbar_wait(sb + G_BAR + GB_RS * 8, 0);
    PROF2(threadIdx.x == 0, 3501);
    if (OP) op_permute(sb);
    const uint32_t wo = sb + (((lane >> 4) << 3) + (lane & 7)) * 128 + (((2 * t + ((lane >> 3) & 1)) ^ (lane & 7)) << 4);
#pragma unroll
    for (int ks = 0; ks < 32; ks++) {
        const uint4 v = ldsm4t(wo + ks * 2048 + (OP ? wg * 65536 : ks < 24 ? 131072 + wg * 49152 : 196608 - 49152 + wg * 16384));
        a[ks * 4] = v.x; a[ks * 4 + 1] = v.y; a[ks * 4 + 2] = v.z; a[ks * 4 + 3] = v.w;
        if (ks == 31 || (!OP && ks == 23)) {
            fence_async_smem();
            __syncwarp();
            if (lane == 0) mbar_arrive(sb + G_BAR + GB_FREE * 8);
            if (ks == 23) mbar_wait(sb + G_BAR + GB_RS * 8, 1);
        }
    }
    PROF2(threadIdx.x == 0, 3502);
    mbar_wait(sb + G_BAR + GB_SS * 8, 0);
    if (OP) op_permute(sb);
    PROF2(threadIdx.x == 0, 3503);
    const uint32_t tag = OP ? lds32(sb + S_TAG) : 0;
    float c0[32], c1[OP ? 32 : 40];
    int st = 0; uint32_t ph = 0;
    const bool el = (threadIdx.x & 127) == 0;
#pragma unroll 1
    for (int n = 0; n < p.nl[OP]; n++) {
        int prev = 0;
        const uint32_t wb = sb + wg * (OP ? 65536 : 81920) + (n & p.zero);
        const uint64_t dw = OP ? mkdesc(wb, 0, 1024, 1) : mkdesc(wb, 16384, 256, 3);
        if ((!OP || OLAG) && wg) mbar_wait(sb + G_BAR + GB_LAG * 8, n & 1);
#pragma unroll
        for (int s = 0; s < 8; s++) {
            mbar_wait(sb + G_BAR + (GB_FULL + st) * 8, ph);
            const uint64_t dx = mkdesc(sb + RB + st * SB, 128, 1024, 0);
            wg_fence();
#pragma unroll
            for (int kk = 0; kk < 4; kk++) {
                const int ks = s * 4 + kk;
                if (ks == 0) { wgmma64_rs<0>(c0, a, dx); if (OP) wgmma64_ta<0>(c1, dw, dx + 512); else wgmma80_tb<0>(c1, dx, dw); }
                else { wgmma64_rs<1>(c0, a + ks * 4, dx + kk * 16); if (OP) wgmma64_ta<1>(c1, dw + ks * 128, dx + 512 + kk * 16); else wgmma80_tb<1>(c1, dx + kk * 16, dw + ks * 32); }
            }
            wg_commit();
            if (s) {
                wg_wait<1>();
                if (el) { mbar_arrive(sb + G_BAR + (GB_EMPTY + prev) * 8); if (s == (OP ? OLAG : QLAG) && !wg) mbar_arrive(sb + G_BAR + GB_LAG * 8); }
            }
            prev = st;
            if (++st == NS) { st = 0; ph ^= 1; }
        }
        const int e = p.list[OP][n];
        wg_wait<0>();
        if (el) mbar_arrive(sb + G_BAR + (GB_EMPTY + prev) * 8);
        PROF(threadIdx.x == 128, 1024 + n * 4 + 1);
        if (OP) {
            uint4* dst = g_pp + (e * 4 + (id >> 2)) * 4096 + ((u & 7) * 32 + t * 8) * 16 + (lane >> 2) * 16 + (lane & 3);
#pragma unroll
            for (int j = 0; j < 4; j++) {
                const float* x = c0 + j * 8; const float* y = c1 + j * 8;
                st_rlx128(dst + j * 4, (pack2(x[0] + y[0], x[1] + y[1]) & ~1u) | tag, pack2(x[2] + y[2], x[3] + y[3]), (pack2(x[4] + y[4], x[5] + y[5]) & ~1u) | tag, pack2(x[6] + y[6], x[7] + y[7]));
            }
            if (lane == 0) red_relaxed(cnt_ptr(C_PP + e * 8 + (u & 7)), 1);
            PROF(threadIdx.x == 128, 1024 + n * 4 + 3);
        } else {
            uint4* dst = g_qkv + (size_t)e * 2 * 32 * 1536 + lane;
            const uint64_t pol = POL_N;
#pragma unroll
            for (int j = 0; j < 4; j++) {
                const float* x = c0 + j * 8;
                uint4 v = make_uint4(pack2(x[0], x[1]), pack2(x[2], x[3]), pack2(x[4], x[5]), pack2(x[6], x[7]));
                if (u >= 64) v = make_uint4(movm(v.x), movm(v.z), movm(v.y), movm(v.w));
                stg128(dst + (((j >> 1) * 32 + ((u & 63) >> 1)) * 1536 + (u < 64 ? 1024 : 0) + (j & 1) * 256 + ((u & 1) * 4 + t) * 32), v, pol);
            }
#pragma unroll
            for (int j = 0; j < 5; j++) {
                const float* x = c1 + (OP ? 0 : j * 8);
                const int blk = qkv_blk(id, wg * 5 + j);
                if (blk < 512) stg128(dst + (((t >> 1) * 32 + ((blk >> 3) & 31)) * 1536 + (blk >> 8) * 512 + (t & 1) * 256 + (blk & 7) * 32),
                                      make_uint4(pack2(x[0], x[1]), pack2(x[2], x[3]), pack2(x[4], x[5]), pack2(x[6], x[7])), pol);
            }
        }
        __syncwarp();
        if (!OP && lane == 0) mbar_arrive(sb + G_BAR + (GB_DONE + (n & 1) * 2 + wg) * 8);
        PROF(threadIdx.x == 128, 1024 + n * 4 + 2);
    }
#pragma unroll 1
    for (int h = p.h0; OP && h < 128; h++) {
        int prev = 0;
        const uint64_t dw = mkdesc(sb + wg * 65536 + (h & p.zero), 0, 1024, 1);
#pragma unroll
        for (int s = 0; s < 8; s++) {
            mbar_wait(sb + G_BAR + (GB_FULL + st) * 8, ph);
            const uint64_t dx = mkdesc(sb + RB + st * SB, 128, 1024, 0);
            wg_fence();
#pragma unroll
            for (int kk = 0; kk < 4; kk++) {
                const int ks = s * 4 + kk;
                if (ks == 0) { wgmma32_rs<0>(c0, a, dx); wgmma32_ta<0>(c1, dw, dx + 512); }
                else { wgmma32_rs<1>(c0, a + ks * 4, dx + kk * 16); wgmma32_ta<1>(c1, dw + ks * 128, dx + 512 + kk * 16); }
            }
            wg_commit();
            if (s) { wg_wait<1>(); if (el) mbar_arrive(sb + G_BAR + (GB_EMPTY + prev) * 8); }
            prev = st;
            if (++st == NS) { st = 0; ph ^= 1; }
        }
        uint4* dst = g_pp + ((h >> 1) * 4 + (id >> 2)) * 4096 + ((u & 7) * 32 + t * 8) * 16 + (lane >> 2) * 16 + (lane & 3) + (h & 1) * 8;
        wg_wait<0>();
        if (el) mbar_arrive(sb + G_BAR + (GB_EMPTY + prev) * 8);
#pragma unroll
        for (int j = 0; j < 2; j++) {
            const float* x = c0 + j * 8; const float* y = c1 + j * 8;
            st_rlx128(dst + j * 4, (pack2(x[0] + y[0], x[1] + y[1]) & ~1u) | tag, pack2(x[2] + y[2], x[3] + y[3]), (pack2(x[4] + y[4], x[5] + y[5]) & ~1u) | tag, pack2(x[6] + y[6], x[7] + y[7]));
        }
        if (lane == 0 && (h & 1)) red_relaxed(cnt_ptr(C_PP + (h >> 1) * 8 + (u & 7)), 1);
        PROF(threadIdx.x == 128 && (h & 1), 1024 + (h >> 1) * 4 + 3);
        __syncwarp();
    }
}

template <int NP, bool MMA>
__device__ __forceinline__ void sum_partials(float* x, const uint2* src, const uint32_t* r0, const uint32_t* r1, uint32_t idm, uint32_t tag, bool on) {
    uint2 v[4][NP];
    int n = 0;
    while (true) {
        uint32_t bad = 0;
#pragma unroll
        for (int s = 0; s < 4; s++)
#pragma unroll
            for (int i = 0; i < NP; i++)
                asm volatile("{.reg .pred p; .reg .b64 t; setp.ne.u32 p,%4,0; mov.b64 t,0; @p ld.relaxed.gpu.global.L2::cache_hint.b64 t,[%2],%3; mov.b64 {%0,%1},t;}"
                             : "=r"(v[s][i].x), "=r"(v[s][i].y) : "l"(src + s * 8192 + i * 32), "l"(POL_LAST), "r"((uint32_t)on) : "memory");
#pragma unroll
        for (int s = 0; s < 4; s++) bad = or3(bad, mism(v[s][0].x, v[s][1].x, tag), mism(v[s][NP - 2].x, v[s][NP - 1].x, tag));
        if (!__any_sync(0xffffffffu, (bad & 1) && on)) break;
        if (++n > 2000000) __trap();
    }
#pragma unroll
    for (int i = 0; i < NP; i++) {
        uint32_t a, b;
        if (MMA) {
            float t[4] = {0, 0, 0, 0};
            mma16(t, v[0][i].x, v[0][i].y, v[1][i].x, v[1][i].y, idm, idm); mma16(t, v[2][i].x, v[2][i].y, v[3][i].x, v[3][i].y, idm, idm);
            a = pack2(t[0], t[2]); b = pack2(t[1], t[3]);
        } else {
            a = pack2((blo(v[0][i].x) + blo(v[1][i].x)) + (blo(v[2][i].x) + blo(v[3][i].x)), (blo(v[0][i].y) + blo(v[1][i].y)) + (blo(v[2][i].y) + blo(v[3][i].y)));
            b = pack2((bhi(v[0][i].x) + bhi(v[1][i].x)) + (bhi(v[2][i].x) + bhi(v[3][i].x)), (bhi(v[0][i].y) + bhi(v[1][i].y)) + (bhi(v[2][i].y) + bhi(v[3][i].y)));
        }
        const uint32_t s0 = hadd2(a, r0[i]), s1 = hadd2(b, r1[i]);
        x[4 * i] = blo(s0); x[4 * i + 2] = bhi(s0); x[4 * i + 1] = blo(s1); x[4 * i + 3] = bhi(s1);
    }
}
__device__ __forceinline__ const uint2* pp_src(int e, int tile, int lane) { return (const uint2*)g_pp + e * 32768 + tile * 128 + (lane >> 3) * 8 + (lane & 3) * 2 + ((lane >> 2) & 1); }

__device__ __forceinline__ void fin_warp(const Params& p, uint32_t sb, int id0) {
    wait_slow_warp(g_gate, lds32(sb + S_GATE));
#pragma unroll 1
    for (int e = id0 < 2 * NQ ? 32 : FJ; e < 64; e++)
#pragma unroll 1
    for (int id = id0; id < (e < FJ ? 128 : id0 + 1); id += 2 * NQ) {
        const int grp = (id & ~3) + (threadIdx.x & 3), tp = (id & 3) * 8 + ((threadIdx.x & 31) >> 2);
        wait_slow_warp(cnt_ptr(C_XN + e), 16);
        const uint4 r = ldcg128(g_x + ((128 + grp) * XP + (e - 32) * 32 + tp));
        if (e < 63) wait_slow_warp(cnt_ptr(C_PP + e * 8 + (id >> 4)), 16); else wait_slow_warp(cnt_ptr(C_O + 63 * 4), 16);
        wait_flag_warp(cnt_ptr(C_PP + e * 8 + (id >> 4)), 16);
        const uint32_t a[2] = {r.x, r.y}, b[2] = {r.z, r.w};
        float x[8];
        sum_partials<2, false>(x, pp_src(e, 0, tp) + grp * 64, a, b, 0, lds32(sb + S_TAG), true);
        uint2* dst = (uint2*)p.out + ((e - 32) * 64 + tp * 2) * 128 + grp;
#pragma unroll
        for (int t = 0; t < 2; t++)
            dst[t * 128] = make_uint2(__byte_perm(__float_as_uint(x[t]), __float_as_uint(x[2 + t]), 0x7632), __byte_perm(__float_as_uint(x[4 + t]), __float_as_uint(x[6 + t]), 0x7632));
        PROF((threadIdx.x & 31) == 0, 1536 + e);
    }
}

constexpr int PROW = 272, UROW = 2560, UPRE = 512;
constexpr int C_UR = 0  , C_TB = 65536  , C_BG = C_TB + 51200,
              CB_M = 7168, CB_U = CB_M + 1792, CB_BIG = CB_U + 2048, C_ST = C_BG + 8 * CB_BIG  ;
static_assert(C_ST + 4736 <= B_BAR, "smem map");
enum { CB_TB = 0, CB_UF = 1  , CB_CF = 5  , CB_LD = 9   };
__device__ __forceinline__ void conv_init(uint32_t sb, bool spare) {
    const int i = threadIdx.x & 31;
    mbar_init(sb + B_BAR + i * 8, (i >= CB_UF && i < CB_CF && !spare) ? 2 : 1);
    if (i == CB_TB && !spare) mbar_expect(sb + B_BAR + i * 8, 51200);
    asm volatile("fence.mbarrier_init.release.cluster;" ::: "memory");
}
__device__ __forceinline__ void mma_q(float* c, const uint32_t* a, const uint4& q) {
    mma16(c, a[0], a[1], a[2], a[3], q.x, q.y); mma16(c, a[4], a[5], a[6], a[7], q.z, q.w);
}
__device__ __forceinline__ uint2 ld_acc(const uint2* p, bool on) {
    uint2 v = make_uint2(0, 0);
    asm volatile("{.reg .pred p; setp.ne.u32 p,%3,0; @p ld.global.cg.v2.u32 {%0,%1},[%2];}" : "+r"(v.x), "+r"(v.y) : "l"(p), "r"((uint32_t)on) : "memory");
    return v;
}
__device__ __forceinline__ void add_acc(float* c, uint2 v) { c[0] += blo(v.x); c[1] += bhi(v.x); c[2] += blo(v.y); c[3] += bhi(v.y); }
__device__ __forceinline__ void st_acc(uint2* p, const float* c) { *p = make_uint2(pack2(c[0], c[1]), pack2(c[2], c[3])); }
__device__ __forceinline__ float sum8(const uint4* v, int k) {
#define VK(i) __uint_as_float(k == 0 ? v[i].x : k == 1 ? v[i].y : k == 2 ? v[i].z : v[i].w)
    return ((VK(0) + VK(1)) + (VK(2) + VK(3))) + ((VK(4) + VK(5)) + (VK(6) + VK(7)));
}
template <int XW>
__device__ __forceinline__ void stats_send(uint32_t l16, const float* x, uint4* gs, int q, int w) {
    float s0 = 0, s1 = 0, m0 = 0, m1 = 0;
#pragma unroll
    for (int i = 0; i < 8; i++) { s0 += x[2 * i]; s1 += x[2 * i + 1]; m0 = fmaf(x[2 * i], x[2 * i], m0); m1 = fmaf(x[2 * i + 1], x[2 * i + 1], m1); }
    sts128(l16 + C_ST + w * 512, __float_as_uint(s0), __float_as_uint(m0), __float_as_uint(s1), __float_as_uint(m1));
    if (w == XW) {
        bar_sync(2, 256);
        uint4 v[8];
#pragma unroll
        for (int i = 0; i < 8; i++) v[i] = lds128(l16 + C_ST + i * 512);
        st_rlx128(gs + q * 32, __float_as_uint(sum8(v, 0)), __float_as_uint(sum8(v, 1)) & 0x7fffffffu, __float_as_uint(sum8(v, 2)), __float_as_uint(sum8(v, 3)));
    } else bar_arrive(2, 256);
}
template <int XW>
__device__ __forceinline__ float4 stats_recv(uint32_t l16, const uint4* gs, int w) {
    if (w == XW) {
        uint4 v[8];
        int n = 0;
        while (true) {
            uint32_t bad = 0;
#pragma unroll
            for (int i = 0; i < 8; i++) v[i] = ld_rlx128(gs + i * 32);
#pragma unroll
            for (int i = 0; i < 8; i++) bad |= v[i].y;
            if (!__any_sync(0xffffffffu, bad >> 31)) break;
            if (++n > 2000000) __trap();
        }
        const float s0 = sum8(v, 0) * (1.f / 512.f), s1 = sum8(v, 2) * (1.f / 512.f);
        const float2 l0 = ln_finish(s0, fmaxf(fmaf(sum8(v, 1), 1.f / 512.f, -s0 * s0), 0.f)), l1 = ln_finish(s1, fmaxf(fmaf(sum8(v, 3), 1.f / 512.f, -s1 * s1), 0.f));
        sts128(l16 + C_ST + 4096, __float_as_uint(l0.x), __float_as_uint(rcp(l0.y)), __float_as_uint(l1.x), __float_as_uint(rcp(l1.y)));
    }
    bar_sync(3, 256);
    const uint4 r = lds128(l16 + C_ST + 4096);
    return make_float4(__uint_as_float(r.x), __uint_as_float(r.y), __uint_as_float(r.z), __uint_as_float(r.w));
}

__device__ __forceinline__ void conv_near(float (*acc)[4], uint32_t ta, uint32_t qa) {
    uint32_t a[9][8];
    uint4 x[9];
#pragma unroll
    for (int k = 0; k < 9; k++) {
        if (k < 8) {
            x[k] = ldsm4(qa + k * 1024);
#pragma unroll
            for (int j = 0; j < 8; j++) a[k][j] = lds32(ta + k * 800 + j * 32);
        }
        if (k) mma_q(acc[k - 1], a[k - 1], x[k - 1]);
        PIN(13);
    }
}
template <int K0>
__device__ __forceinline__ void conv_pair(float (*acc)[4], float (*pend)[4], uint32_t ta, uint32_t q0, uint32_t q1, uint32_t q2) {
    uint32_t a[9][8];
    uint4 x[9], y[5];
#pragma unroll
    for (int n = 0; n < 9; n++) {
        if (n < 8) {
            const int k = K0 + (n >> 1);
            if (!(n & 1)) y[n >> 1] = ldsm4(q1 + k * 1024);
            x[n] = ldsm4(((n & 1) ? q0 : q2) + k * 1024);
#pragma unroll
            for (int j = 0; j < 8; j++) a[n][j] = lds32(ta + 256 + (n & 1) * 256 + k * 800 + j * 32);
        }
        if (n == 0) {
#pragma unroll
            for (int i = 0; i < 16; i++) { acc[4 - K0 + (i >> 2)][i & 3] += pend[i >> 2][i & 3]; pend[i >> 2][i & 3] = 0; }
        } else {
            const int m = n - 1, i = m >> 1;
            mma_q(acc[K0 + i], a[m], (m & 1) ? x[m] : y[i]); mma_q(pend[i], a[m], (m & 1) ? y[i] : x[m]);
        }
        PIN(13);
    }
}

__device__ __forceinline__ void conv_tile(const Params& p, uint32_t sb, int q, int w) {
    const int lane = __shfl_sync(0xffffffffu, threadIdx.x & 31, threadIdx.x & 31), g = lane >> 2, c = lane & 3, tile = q * 8 + w;
    const uint32_t l16 = sb + lane * 16;
#pragma unroll
    for (int i = 0; i < 16; i++) sts128(l16 + C_UR + w * 8192 + i * 512, 0, 0, 0, 0);
    wait_slow_warp(g_gate, lds32(sb + S_GATE));
    if (lane < 8) bulk_g2s(sb + C_TB + (w * 8 + lane) * 800, g_P + (tile * 8 + lane) * PROW + 72, 800, sb + B_BAR + CB_TB * 8, POL_N);
    uint32_t A[8][8];
#pragma unroll
    for (int k = 0; k < 8; k++)
#pragma unroll
        for (int j = 0; j < 8; j++) A[k][j] = __ldcg(g_P + (tile * 8 + k) * PROW + 16 + 8 * j + g - 2 * c);
    if (lane == 0) { const uint4 d = __ldg((const uint4*)p.Dskip + tile); sts128(sb + C_ST + 4608 + w * 16, d.x, d.y, d.z, d.w); }
    float acc[8][4], pend[4][4];
#pragma unroll
    for (int k = 0; k < 8; k++) acc[k][0] = acc[k][1] = acc[k][2] = acc[k][3] = pend[k & 3][k >> 2] = pend[k & 3][2 + (k >> 2)] = 0;
    const uint32_t row = sb + C_UR + w * 8192, ta = sb + C_TB + w * 6400 + (8 + g - 2 * c) * 4, qo = (lane & 7) * 16 - (lane >> 3) * 32;
    bar_sync(4, 384);
    mbar_wait(sb + B_BAR + CB_TB * 8, 0);
#pragma unroll 1
    for (int b = -2; b < 32; b++) {
        const int lz = lane + (b & p.zero);
        const bool on = b >= 0;
        uint4 r0 = make_uint4(0, 0, 0, 0), r1 = r0;
        asm volatile("{.reg .pred p; setp.ge.s32 p,%9,0; @p ld.global.cg.v4.u32 {%0,%1,%2,%3},[%8]; @p ld.global.cg.v4.u32 {%4,%5,%6,%7},[%8+%10];}"
                     : "+r"(r0.x), "+r"(r0.y), "+r"(r0.z), "+r"(r0.w), "+r"(r1.x), "+r"(r1.y), "+r"(r1.z), "+r"(r1.w) : "l"(g_x + (tile * 2 * XP + b * 32 + lz)), "r"(b), "n"(XP * 16) : "memory");
        const uint32_t q1 = row + ((qo + (b - 1) * 128) & 1023);
        if ((NTOP >> w) & 1) conv_near(acc, ta, q1);
        PROF2(threadIdx.x == 0 && on, 2048 + b * 8);
        const uint2* pps = pp_src(b, tile, lz);
        asm volatile("" : "+l"(pps));
        const uint32_t tag = lds32(sb + S_TAG);
        wait_flag_warp(cnt_ptr(C_PP + b * 8 + q), on ? 16 : 0);
        PROF2(threadIdx.x == 0 && on, 2048 + b * 8 + 1);
        float x[16];
        {
            const uint32_t a[4] = {r0.x, r0.y, r1.x, r1.y}, bb[4] = {r0.z, r0.w, r1.z, r1.w};
            sum_partials<4, true>(x, pps, a, bb, (2 * (lz & 3) == lz >> 2) ? 0x00003f80u : (2 * (lz & 3) + 1 == lz >> 2) ? 0x3f800000u : 0u, tag, on);
        }
        stats_send<0>(l16, x, g_st + (b + 2) * 256 + lz, q, w);
        {
            PROF2(threadIdx.x == 0 && on, 2048 + b * 8 + 2);
            if (on) mbar_wait(sb + B_BAR + (CB_CF + (w >> 1)) * 8, b & 1);
            const uint2* cb = g_carry + ((tile * 320 + b) * 32 + lz);
            uint2 cr[8];
#pragma unroll
            for (int k = 0; k < 8; k++) cr[k] = ld_acc(cb + k * 1280, b >= 4);
            if (NTOP != 255 && !((NTOP >> w) & 1) && b) conv_near(acc, ta, q1);
#pragma unroll
            for (int k = 0; k < 8; k++) add_acc(acc[k], cr[k]);
        }
        PIN(13);
        float4 ln = stats_recv<0>(l16, g_st + (b + 2) * 256 + lz, w);
        PROF2(threadIdx.x == 0 && on, 2048 + b * 8 + 3);
        uint32_t u[8];
#pragma unroll
        for (int k = 0; k < 8; k++) {
            u[k] = pack2(rbf(x[2 * k] - ln.x) * ln.y, rbf(x[2 * k + 1] - ln.z) * ln.w);
            sts32(row + k * 1024 + (b & 7) * 128 + lane * 4, u[k]);
        }
        __syncwarp();
        const uint32_t qa = row + ((qo + b * 128) & 1023);
        {
            uint4 xq[8];
#pragma unroll
            for (int k = 0; k < 4; k++) xq[k] = ldsm4(qa + k * 1024);
#pragma unroll
            for (int k = 0; k < 8; k += 2) {
                PIN(13);
                mma_q(acc[k], A[k], xq[k]); mma_q(acc[k + 1], A[k + 1], xq[k + 1]);
                if (k < 4) { xq[k + 4] = ldsm4(qa + (k + 4) * 1024); xq[k + 5] = ldsm4(qa + (k + 5) * 1024); }
            }
        }
        const uint4 dk = lds128(sb + C_ST + 4608 + w * 16);
#pragma unroll
        for (int k = 0; k < 8; k++) {
            const float t = __shfl_sync(0xffffffffu, acc[k][3], (lz & ~3) | ((lz - 1) & 3));
            const uint32_t y = movm(pack2(acc[k][0] + (c ? t : 0.f), acc[k][1] + acc[k][2]));
            acc[k][0] = c ? 0.f : t; acc[k][1] = acc[k][2] = acc[k][3] = 0;
            const uint32_t dw = k >> 1 == 0 ? dk.x : k >> 1 == 1 ? dk.y : k >> 1 == 2 ? dk.z : dk.w;
            const uint32_t s = hadd2(hadd2(y, hmul2(u[k], __byte_perm(dw, 0, (k & 1) ? 0x3232 : 0x1010))), __byte_perm(__float_as_uint(x[2 * k]), __float_as_uint(x[2 * k + 1]), 0x7632));
            x[2 * k] = blo(s); x[2 * k + 1] = bhi(s);
        }
        arrive_if(sb + B_BAR + (CB_UF + (w >> 1)) * 8, lz, b < -1 ? 32 : 0);
        stats_send<1>(l16, x, g_st + (36 + b) * 256 + lz, q, w);
        {
            PROF2(threadIdx.x == 0 && on, 2048 + b * 8 + 4);
            uint4* dst = g_x + ((128 + tile * 2) * XP + b * 32 + lz);
#pragma unroll
            for (int e = 0; e < 2; e++) {
                const float* y = x + e * 8;
                if (on) dst[e * XP] = make_uint4(__byte_perm(__float_as_uint(y[0]), __float_as_uint(y[2]), 0x7632), __byte_perm(__float_as_uint(y[4]), __float_as_uint(y[6]), 0x7632),
                                           __byte_perm(__float_as_uint(y[1]), __float_as_uint(y[3]), 0x7632), __byte_perm(__float_as_uint(y[5]), __float_as_uint(y[7]), 0x7632));
            }
            uint32_t* du = g_u + (tile * 8 * (UROW / 2) + UPRE / 2 + b * 32 + lz);
#pragma unroll
            for (int k = 0; k < 8; k++) if (on) du[k * (UROW / 2)] = u[k];
        }
#pragma unroll 1
        for (int pass = 0; pass < 2; pass++) {
            if (pass == ((PLATE >> w) & 1)) {
                const uint32_t q0 = row + ((qo + (b - 2) * 128) & 1023);
                if (b & 1) conv_pair<4>(acc, pend, ta, q0, q1, qa); else conv_pair<0>(acc, pend, ta, q0, q1, qa);
            }
            if (pass) break;
            ln = stats_recv<1>(l16, g_st + (36 + b) * 256 + lz, w);
            PROF2(threadIdx.x == 0 && on, 2048 + b * 8 + 5);
            uint32_t o[2][4];
#pragma unroll
            for (int e = 0; e < 2; e++) {
                const float mu = e ? ln.z : ln.x, rs = e ? ln.w : ln.y;
#pragma unroll
                for (int i = 0; i < 4; i++) o[e][i] = pack2(rbf(x[4 * i + e] - mu) * rs, rbf(x[4 * i + 2 + e] - mu) * rs);
            }
#pragma unroll
            for (int i = 0; i < 4; i++) {
                const uint32_t t = __shfl_xor_sync(0xffffffffu, (lz & 1) ? o[0][i] : o[1][i], 1);
                if (lz & 1) o[0][i] = t; else o[1][i] = t;
            }
            uint4* dst = g_xn + ((32 + b) * 4096 + q * 512 + (lz >> 2) * 64 + w * 8 + (lz & 2) * 2 + (lz & 1));
            if (on) { dst[0] = make_uint4(o[0][0], o[0][1], o[0][2], o[0][3]); dst[2] = make_uint4(o[1][0], o[1][1], o[1][2], o[1][3]); }
            if (w == 7) {
                bar_sync(5, 256);
                if (elect()) red_release(cnt_ptr(on ? C_XN + 32 + b : C_FAR + 8), 2);
                PROF(lane == 0 && on, 2048 + b * 8 + 6);
                __syncwarp();
            } else bar_arrive(5, 256);
        }
    }
}

template <int P0, bool TRI = false, int R0 = 0>
__device__ __forceinline__ void bg_half(float (*acc)[4], uint4* win, uint32_t ta, uint32_t qa, uint32_t mask, uint32_t row) {
#pragma unroll
    for (int i = 0; i < 4; i++) {
        win[P0 + i] = ldsm4(((qa + i * 128) & mask) + row);
        const uint4 a = lds128(ta + (3 - i) * 448), e = lds128(ta + (3 - i) * 448 + 224);
#pragma unroll
        for (int r = TRI ? 7 - P0 - i : R0; r < 8; r++) mma16(acc[r], a.x, a.y, a.z, a.w, win[(P0 + i + 1 + r) & 7].x, win[(P0 + i + 1 + r) & 7].y);
#pragma unroll
        for (int r = TRI ? 7 - P0 - i : R0; r < 8; r++) mma16(acc[r], e.x, e.y, e.z, e.w, win[(P0 + i + 1 + r) & 7].z, win[(P0 + i + 1 + r) & 7].w);
    }
}
__device__ __forceinline__ void bg_fetch(uint32_t sb, int q, int j, int n) {
    const int b0 = n >> 1, ch = q * 64 + j * 16 + (n & 1) * 8 + (b0 & 7), skip = max(12 - b0, 0);
    const uint32_t bar = sb + B_BAR + (CB_LD + j * 2 + (n & 1)) * 8, buf = sb + C_BG + (j * 2 + (n & 1)) * CB_BIG;
    if (elect()) {
        mbar_expect(bar, CB_BIG - skip * 128);
        bulk_g2s(buf, g_W + ch * 784, CB_M, bar, POL_N);
        bulk_g2s(buf + CB_M, g_W + (ch ^ 4) * 784, 1792, bar, POL_N);
        bulk_g2s(buf + CB_U + skip * 128, g_u + ch * (UROW / 2) + UPRE / 2 + (b0 - 20 + skip) * 32, 2048 - skip * 128, bar, POL_N);
    }
    __syncwarp();
}
__device__ __forceinline__ void conv_back(uint32_t sb, int q, int j) {
    const int lane = __shfl_sync(0xffffffffu, threadIdx.x & 31, threadIdx.x & 31), g = lane >> 2, c = lane & 3;
    wait_slow_warp(g_gate, lds32(sb + S_GATE));
    bg_fetch(sb, q, j, 0);
    bar_sync(4, 384);
    const uint32_t to = (6 + g - 2 * c) * 16, qo = (lane & 7) * 16 - (lane >> 3) * 32;
#pragma unroll 1
    for (int n = 0; n < 64; n++) {
        const int b0 = n >> 1, i = n & 1, chl = j * 16 + i * 8 + (b0 & 7);
        const uint32_t buf = sb + C_BG + (j * 2 + i) * CB_BIG, ta = buf + to;
        float acc[8][4];
        uint4 win[8];
        if (n < 63) bg_fetch(sb, q, j, n + 1);
        if (b0 >= 17 && b0 < 29 && (b0 < 21 || b0 >= 25) && i == 0) wait_flag_warp(cnt_ptr(C_FAR + (b0 >= 25) * 4 + ((b0 - 1) & 3)), 12);
        uint2* cr = g_carry + (((q * 64 + chl) * 40 + b0) * 32 + lane);
        uint2* cm = g_carry + (((q * 64 + (chl ^ 4)) * 40 + b0) * 32 + lane);
        uint2 pm[4], pf[8];
#pragma unroll
        for (int r = 0; r < 4; r++) pm[r] = ld_acc(cm + r * 32, b0 > 4);
#pragma unroll
        for (int r = 0; r < 8; r++) acc[r][0] = acc[r][1] = acc[r][2] = acc[r][3] = 0;
        mbar_wait(sb + B_BAR + (CB_LD + j * 2 + i) * 8, b0 & 1);
        if (b0 > 12) {
#pragma unroll
            for (int r = 1; r < 8; r++) win[(r + 4) & 7] = ldsm4(buf + CB_U + qo + r * 128);
        } else {
#pragma unroll
            for (int r = 1; r < 8; r++) win[(r + 4) & 7] = make_uint4(0, 0, 0, 0);
        }
        win[4] = make_uint4(0, 0, 0, 0);
#pragma unroll 1
        for (int h = b0 > 8 ? 4 : 2; h >= 2; h -= 2) {
            if (h == 2) {
                if (b0 > 4) bg_half<0>(acc, win, ta + 2 * 1792, qo + 12 * 128, ~0u, buf + CB_U);
                if (i == 0) mbar_wait(sb + B_BAR + (CB_UF + j) * 8, b0 & 1);
            }
            bg_half<4>(acc, win, ta + (h - 1) * 1792, qo + (h == 2 ? b0 - 4 : 8) * 128, h == 2 ? 1023u : ~0u, h == 2 ? sb + C_UR + chl * 1024 : buf + CB_U);
        }
        uint4 wm[8], a[9], e[9];
#pragma unroll
        for (int r = 1; r < 8; r++) wm[r] = ldsm4(sb + C_UR + (chl ^ 4) * 1024 + ((qo + (b0 + r) * 128) & 1023));
        a[7] = lds128(ta + 7 * 224); e[7] = lds128(ta + CB_M + 7 * 224);
#pragma unroll
        for (int r = 4; r < 8; r++) { st_acc(cr + r * 32, acc[r]); acc[r][0] = blo(pm[r - 4].x); acc[r][1] = bhi(pm[r - 4].x); acc[r][2] = blo(pm[r - 4].y); acc[r][3] = bhi(pm[r - 4].y); }
#pragma unroll
        for (int t = 7; t >= 0; t--) {
            if (t) { a[t - 1] = lds128(ta + (t - 1) * 224); e[t - 1] = lds128(ta + CB_M + (t - 1) * 224); }
            if (t == FT) {
                const uint2* f0 = g_far + (((q * 64 + chl) * 12 + b0 - 20) * 32 + lane);
                const uint2* f1 = g_far + (((q * 64 + (chl ^ 4)) * 12 + b0 - 20) * 32 + lane);
#pragma unroll
                for (int r = 0; r < 4; r++) { const bool on = (unsigned)(b0 + r - 20) < 12u; pf[r] = ld_acc(f0 + r * 32, on); pf[4 + r] = ld_acc(f1 + r * 32, on); }
            }
            PIN(14);
#pragma unroll
            for (int r = 0; r < 4; r++) { const uint4& x = win[4 + r - (t >> 1)]; mma16(acc[r], a[t].x, a[t].y, a[t].z, a[t].w, (t & 1) ? x.z : x.x, (t & 1) ? x.w : x.y); }
#pragma unroll
            for (int r = 0; r < 4; r++) { const uint4& x = wm[4 + r - (t >> 1)]; mma16(acc[4 + r], e[t].x, e[t].y, e[t].z, e[t].w, (t & 1) ? x.z : x.x, (t & 1) ? x.w : x.y); }
        }
#pragma unroll
        for (int r = 0; r < 4; r++) { add_acc(acc[r], pf[r]); add_acc(acc[4 + r], pf[4 + r]); st_acc(cr + r * 32, acc[r]); st_acc(cm + r * 32, acc[4 + r]); }
        __syncwarp();
        arrive_if(sb + B_BAR + (CB_CF + j) * 8, lane, i ? 0 : 32);
        PROF(j == 0 && lane == 0 && i, 2048 + b0 * 8 + 7);
    }
}
template <int PART>
__device__ __forceinline__ void conv_far(uint32_t sb, int w) {
    constexpr int NT = PART ? 5376 : 3584, NU = PART ? 1664 : 1152;
    const int lane = __shfl_sync(0xffffffffu, threadIdx.x & 31, threadIdx.x & 31), g = lane >> 2, c = lane & 3;
    wait_slow_warp(cnt_ptr(C_XN + (PART ? 43 : 39)), 16);
    const uint32_t to = (6 + g - 2 * c) * 16, qo = (lane & 7) * 16 - (lane >> 3) * 32;
#pragma unroll 1
    for (int n = -1; n < 44; n++) {
        const int t = n * 12 + w, tn = min(t + 12, 511), ch = (t & 127) * 4 + (((t >> 7) + 1) & 3), cn = (tn & 127) * 4 + (((tn >> 7) + 1) & 3);
        const uint32_t bar = sb + B_BAR + (w * 2 + (n & 1)) * 8, buf = sb + (w * 2 + (n & 1)) * 7168;
        if (n < 43 && elect()) {
            const uint32_t nb = sb + (w * 2 + (~n & 1)) * 7168;
            mbar_expect(bar ^ 8, NT + NU);
            bulk_g2s(nb, g_W + cn * 784 + 448, NT, bar ^ 8, POL_N);
            bulk_g2s(nb + 5376, g_u + cn * (UROW / 2) + UPRE / 2 - 32, NU, bar ^ 8, POL_N);
        }
        __syncwarp();
        if (n < 0) continue;
        mbar_wait(bar, (n >> 1) & 1);
        if (t >= 512) continue;
        float acc[8][4];
        uint4 win[8];
#pragma unroll
        for (int r = 0; r < 8; r++) acc[r][0] = acc[r][1] = acc[r][2] = acc[r][3] = 0;
        bg_half<0, true, PART * 4>(acc, win, buf + to + NT - 1792, qo + 128, ~0u, buf + 5376);
        bg_half<4, !PART, PART * 4>(acc, win, buf + to + NT - 3584, qo + 640, ~0u, buf + 5376);
        if (PART) bg_half<0, false, 4>(acc, win, buf + to, qo + 1152, ~0u, buf + 5376);
#pragma unroll
        for (int r = PART * 4; r < 8; r++) st_acc(g_far + (ch * 384 + lane) + (r + PART * 4) * 32, acc[r]);
        __syncwarp();
        if (((t + 12) ^ t) >= 128 && elect()) red_release(cnt_ptr(C_FAR + PART * 4 + (t >> 7)), 1);
        __syncwarp();
    }
    PROF(threadIdx.x == 0, 2048 + PART);
}

constexpr int P_X = 131072  , P_K6 = P_X + 32768  , P_P = P_K6 + 10496  , P_U = P_P + 33280  ,
              P_END = P_U + 17408, P_PRM = P_P  , P_Y = P_P  ;
static_assert(P_END <= B_BAR && P_END <= R_SEL, "prologue scratch");
#define KGUN 2
constexpr int KGU = KGUN;
__device__ __forceinline__ void csq(float& r, float& i) { const float t = r * i; r = fmaf(r, r, -(i * i)); i = t + t; }
__device__ __forceinline__ void cpow(float ar, float ph, float p, float& r, float& i) {
    const float e = ex2(ar * p);
    const float u = ph * p, n = (u + 12582912.f) - 12582912.f;
    const float t = (u - n) * 6.283185307179586f;
    r = e * __cosf(t); i = e * __sinf(t);
}
__device__ __forceinline__ void mma_tf32(float* c, float a0, float a1, float a2, float a3, float b0, float b1) {
    asm volatile("mma.sync.aligned.m16n8k8.row.col.f32.tf32.tf32.f32 {%0,%1,%2,%3},{%4,%5,%6,%7},{%8,%9},{%0,%1,%2,%3};"
                 : "+f"(c[0]), "+f"(c[1]), "+f"(c[2]), "+f"(c[3])
                 : "r"(__float_as_uint(a0)), "r"(__float_as_uint(a1)), "r"(__float_as_uint(a2)), "r"(__float_as_uint(a3)), "r"(__float_as_uint(b0)), "r"(__float_as_uint(b1)));
}

__device__ __forceinline__ void early_fetch(const Params& p, uint32_t sb) {
    const int v = blockIdx.x;
    if (elect()) {
        if (v >= V_QKV) { if (v < V_QKV + NQ && (p.roles & 8)) qkv_fetch(p, sb, v - V_QKV, 0, Q_PRE); }
        else if (v >= V_OP) { if (p.roles & 4) op_fetch(p, sb, v - V_OP, 0); }
        else if (v >= V_REC && (p.roles & 2)) { rec_fetch(p, sb, (v - V_REC) >> 1, v & 1, 0, R_STQ); rec_fetch(p, sb, (v - V_REC) >> 1, v & 1, 2, R_STV); }
    }
    __syncwarp();
}
struct ProRegs { uint32_t v[2][4], ldt[2]; };
__device__ __forceinline__ void prologue_load(const ProArgs& a, int b, ProRegs& pr) {
    const int w = threadIdx.x >> 5;
#pragma unroll
    for (int i = 0; i < 2; i++) {
        const int gi = b * 512 + (w & 3) * 128 + ((w >> 2) & 1) * 64 + i * 32 + (threadIdx.x & 31);
        pr.ldt[i] = __ldg((const uint16_t*)a.ldt + b * 4 + (w & 3));
        pr.v[i][0] = __ldg((const uint16_t*)a.lAr + gi); pr.v[i][1] = __ldg((const uint16_t*)a.Ai + gi);
        pr.v[i][2] = __ldg((const uint16_t*)a.Cr + gi); pr.v[i][3] = __ldg((const uint16_t*)a.Ci + gi);
    }
}
__device__ __forceinline__ void prologue(const Params& p, uint32_t sb, int b, int w, const ProRegs& pr) {
    const ProArgs& a = p.pa;
    const int tid = threadIdx.x, lane = tid & 31, g = lane >> 2, c = lane & 3;
    const int d0 = b * 4;
    if (w >= 8) {
        const int t2 = tid - 256;
        if (w < 10) {
            const int row = b * 16 + (w - 8) * 8 + g;
            uint4 v[16];
            const float2 r = row_stats512(v, (const uint4*)(a.x + (size_t)row * 512) + c, 8, 4);
            const float2 l = ln_finish(r.x * (1.f / 512.f), r.y * (1.f / 512.f));
            if (c == (g >> 1)) asm volatile("st.relaxed.gpu.global.u32 [%0],%1;" ::"l"(g_ln0 + row), "r"(pack2(l.x, l.y)) : "memory");
            __syncwarp();
        }
        if (b + 4 >= V_REC && b + 4 < V_OP) rec_slots(b + 4 - V_REC, (w & 3) ^ 2);
        PROF(t2 == 0, 3516);
        const int gi = b * 128 + t2;
        g_st[gi] = make_uint4(~0u, ~0u, ~0u, ~0u);
        if (gi < 1024) g_st[16384 + gi] = make_uint4(~0u, ~0u, ~0u, ~0u);
        if (gi < C_N * 8) g_cnt[gi] = 0;
        bar_sync(9, 384);
#pragma unroll 1
        for (int pass = 0; pass < 2; pass++) {
        if (w == 10 && pass == (b + 4 < V_QKV)) early_fetch(p, sb);
        if (pass) break;
#pragma unroll 2
        for (int i = t2; i < 4 * 784; i += 128) {
            const int ch = i / 784, k = i - ch * 784;
            const uint32_t o = sb + P_P + (ch * 2080 + 266 + (k / 14) * 18 + k) * 4;
            g_W[d0 * 784 + i] = make_uint4(lds32(o), lds32(o + 32), lds32(o + 64), lds32(o + 96));
        }
        bar_arrive(10, 384);
        }
        PROF(t2 == 0, 3517);
        return;
    }
    float kl = 0;
#pragma unroll
    for (int i = 0; i < 2; i++) {
        const float dt = rbf(expf(blo(pr.ldt[i])));
        const float ar = -rbf(expf(blo(pr.v[i][0]))) * dt, ai = blo(pr.v[i][1]) * dt;
        const float lg = ar * 1.4426950408889634f, tn = ai * 0.15915494309189535f, ph = tn - rintf(tn);
        const float cr = 2.f * (blo(pr.v[i][2]) * dt), ci = 2.f * (blo(pr.v[i][3]) * dt);
        float zr, zi;
        cpow(lg, ph, 2048.f, zr, zi);
        kl += cr * zr - ci * zi;
        cpow(lg, ph, 8.f, zr, zi);
        sts128(sb + P_PRM + (w * 64 + i * 32 + lane) * 16, __float_as_uint(lg), __float_as_uint(ph), __float_as_uint(cr), __float_as_uint(ci));
        sts64(sb + P_PRM + 8192 + (w * 64 + i * 32 + lane) * 8, __float_as_uint(zr), __float_as_uint(zi));
    }
    if (tid < 64) sts128(sb + P_U + (tid >> 3) * 2176 + (tid & 7) * 16, 0, 0, 0, 0);
    __syncwarp();
    PROF(tid == 0, 3510);
    uint2 ln[4];
#define LDLN _Pragma("unroll") for (int i = 0; i < 4; i++) asm volatile("ld.relaxed.gpu.global.v2.u32 {%0,%1},[%2];" : "=r"(ln[i].x), "=r"(ln[i].y) : "l"((const uint2*)g_ln0 + i * 256 + tid) : "memory")
    const int ch = w & 3, hf = w >> 2;
    {
        float k0[4] = {0, 0, 0, 0}, k1[4] = {0, 0, 0, 0}, k2[4] = {0, 0, 0, 0}, k3[4] = {0, 0, 0, 0}, k4[4] = {0, 0, 0, 0};
#pragma unroll KGU
        for (int j = 0; j < 16; j++) {
            const uint4 q = lds128(sb + P_PRM + (w * 64 + j * 4 + c) * 16);
            const float cr = __uint_as_float(q.z), ci = __uint_as_float(q.w);
            float wr[4], wi[4], vr[4], vi[4];
            cpow(__uint_as_float(q.x), __uint_as_float(q.y), (float)g, wr[0], wi[0]);
            const uint2 z8 = lds64(sb + P_PRM + 8192 + (w * 64 + j * 4 + c) * 8);
            vr[0] = wr[0] * __uint_as_float(z8.x) - wi[0] * __uint_as_float(z8.y); vi[0] = wr[0] * __uint_as_float(z8.y) + wi[0] * __uint_as_float(z8.x);
#pragma unroll
            for (int i = 1; i < 4; i++) { wr[i] = wr[i - 1]; wi[i] = wi[i - 1]; csq(wr[i], wi[i]); vr[i] = vr[i - 1]; vi[i] = vi[i - 1]; csq(vr[i], vi[i]); }
            float hr = wr[3], hi = wi[3];
            csq(hr, hi);
            mma_tf32(k0, wr[0], vr[0], wi[0], vi[0], cr * hr - ci * hi, -(cr * hi + ci * hr));
            hr = vr[3]; hi = vi[3]; csq(hr, hi);
            mma_tf32(k1, wr[0], vr[0], wi[0], vi[0], cr * hr - ci * hi, -(cr * hi + ci * hr));
            csq(hr, hi);
            mma_tf32(k2, wr[1], vr[1], wi[1], vi[1], cr * hr - ci * hi, -(cr * hi + ci * hr));
            csq(hr, hi);
            mma_tf32(k3, wr[2], vr[2], wi[2], vi[2], cr * hr - ci * hi, -(cr * hi + ci * hr));
            csq(hr, hi);
            mma_tf32(k4, wr[3], vr[3], wi[3], vi[3], cr * hr - ci * hi, -(cr * hi + ci * hr));
        }
        LDLN;
#pragma unroll
        for (int d = 1; d < 32; d *= 2) kl += __shfl_xor_sync(0xffffffffu, kl, d);
        const uint32_t o = sb + P_K6 + (ch * 656 + c * 32 + g) * 4, ol = sb + P_K6 + (ch * 656 + 640) * 4;
#define KST(k, base) sts32(o + (base) * 4, __float_as_uint(k[0])); sts32(o + (base) * 4 + 64, __float_as_uint(k[1])); \
                     sts32(o + (base) * 4 + 32, __float_as_uint(k[2])); sts32(o + (base) * 4 + 96, __float_as_uint(k[3]))
#define KAD(k, base) k[0] += __uint_as_float(lds32(o + (base) * 4)); k[1] += __uint_as_float(lds32(o + (base) * 4 + 64)); \
                     k[2] += __uint_as_float(lds32(o + (base) * 4 + 32)); k[3] += __uint_as_float(lds32(o + (base) * 4 + 96))
        if (hf == 0) {
            bar_sync(2 + ch, 64);
            KAD(k0, 0); KAD(k1, 128); KAD(k2, 256); KAD(k3, 384); KAD(k4, 512);
            kl += __uint_as_float(lds32(ol));
            __syncwarp();
        }
        KST(k0, 0); KST(k1, 128); KST(k2, 256); KST(k3, 384); KST(k4, 512);
        if (lane == 0) sts32(ol, __float_as_uint(kl));
        if (hf == 1) { __syncwarp(); bar_arrive(2 + ch, 64); }
    }
    PROF(tid == 0, 3511);
    {
        int n = 0;
        while (!__all_sync(0xffffffffu, ln[0].x && ln[0].y && ln[1].x && ln[1].y && ln[2].x && ln[2].y && ln[3].x && ln[3].y)) {
            LDLN;
            if (++n > 2000000) __trap();
        }
        bar_sync(8, 384);
        mbar_wait(sb + S_XBAR, 0);
#pragma unroll
        for (int i = 0; i < 4; i++) {
            const int t = i * 512 + tid * 2;
            uint32_t u[2][2];
#pragma unroll
            for (int e = 0; e < 2; e++) {
                const uint32_t l = e ? ln[i].y : ln[i].x, mm = __byte_perm(l, 0, 0x1010) ^ 0x80008000u;
                const float rs = rcp(bhi(l));
                const uint2 x = lds64(sb + P_X + (t + e) * 16 + (b & 1) * 8);
                u[e][0] = NRM(x.x); u[e][1] = NRM(x.y);
                sts64(sb + P_X + (t + e) * 16 + 8 - (b & 1) * 8, u[e][0], u[e][1]);
            }
            const uint32_t o = sb + P_U + ((t >> 3) & 1) * 2176 + ((t >> 4) + 8) * 16 + (t & 7) * 2;
#pragma unroll
            for (int k = 0; k < 4; k++) sts32(o + k * 4352, __byte_perm(u[0][k >> 1], u[1][k >> 1], (k & 1) ? 0x7632 : 0x5410));
        }
    }
    PROF(tid == 0, 3512);
    if (tid < 64) sts32(sb + P_P + ((tid >> 4) * 2080 + (tid & 15)) * 4, 0);
#pragma unroll 1
    for (int x = tid; x < 2048; x += 512) {
        uint32_t pw[2][4];
#pragma unroll
        for (int h = 0; h < 2; h++) {
            const int y = x + h * 256;
            const int i0 = y <= 256 ? y : 256 + (int)((pack2((float)y, 0.f) & 0xffff) - 0x4380);
            const int i1 = y <= 256 ? max(y - 1, 0) : 256 + (int)((pack2((float)(y - 1), 0.f) & 0xffff) - 0x4380);
#pragma unroll
            for (int k = 0; k < 4; k++) {
                const float lo = __uint_as_float(lds32(sb + P_K6 + k * 2624 + i0 * 4)), hi = __uint_as_float(lds32(sb + P_K6 + k * 2624 + i1 * 4));
                pw[h][k] = pack2(lo, y ? hi : 0.f);
            }
        }
#pragma unroll
        for (int h = 0; h < 2; h++)
#pragma unroll
            for (int k = 0; k < 4; k++) sts32(sb + P_P + (k * 2080 + x + h * 256 + 16) * 4, pw[h][k]);
    }
    fence_async_smem();
    bar_arrive(9, 384);
    bar_sync(1, 256);
    if (tid < 4) {
        asm volatile("cp.async.bulk.global.shared::cta.bulk_group [%0],[%1],%2;" ::"l"(g_P + (d0 + tid) * PROW), "r"(sb + P_P + tid * 8320), "r"(PROW * 4) : "memory");
        asm volatile("cp.async.bulk.commit_group;" ::: "memory");
    }
    __syncwarp();
    PROF(tid == 0, 3513);
    {
        float acc[16][4];
#pragma unroll
        for (int j = 0; j < 16; j++) acc[j][0] = acc[j][1] = acc[j][2] = acc[j][3] = 0;
#pragma unroll 1
        for (int e = hf * 4; e < hf * 4 + 4; e++) {
            uint32_t B[16][2];
            const uint32_t ua = sb + P_U + ch * 4352 + ((lane >> 3) & 1) * 2176 + (8 + (lane >> 4) * 8 + (lane & 7) - e) * 16;
#pragma unroll
            for (int j = 0; j < 8; j++) { const uint4 v = ldsm4(ua + j * 256); B[2 * j][0] = v.x; B[2 * j][1] = v.y; B[2 * j + 1][0] = v.z; B[2 * j + 1][1] = v.w; }
            const uint32_t pa = sb + P_P + (ch * 2080 + 16 + e * 16 + g - 2 * c) * 4;
#pragma unroll
            for (int dd = 0; dd < 16; dd++) {
                const int d = (dd & 1) ? 15 - (dd >> 1) : dd >> 1;
                const uint32_t a0 = lds32(pa + d * 512), a1 = lds32(pa + d * 512 + 32), a2 = lds32(pa + d * 512 - 32), a3 = a0 + p.zero;
#pragma unroll
                for (int j = 0; j < 16; j++) if (j >= d) mma16(acc[j], a0, a1, a2, a3, B[(j - d) & 15][0], B[(j - d) & 15][1]);
            }
        }
        PROF(tid == 0, 3514);
        if (tid < 4) asm volatile("cp.async.bulk.wait_group 0;" ::: "memory");
        __syncwarp();
        bar_sync(10, 384);
#pragma unroll
        for (int j = 0; j < 8; j++) {
#pragma unroll
            for (int i = 0; i < 4; i++) { const float t = hf ? acc[j][i] : acc[j + 8][i]; acc[j][i] = hf ? acc[j + 8][i] : acc[j][i]; acc[j + 8][i] = t; }
            sts128(sb + P_Y + w * 4096 + j * 512 + lane * 16, __float_as_uint(acc[j + 8][0]), __float_as_uint(acc[j + 8][1]), __float_as_uint(acc[j + 8][2]), __float_as_uint(acc[j + 8][3]));
        }
        bar_sync(2 + ch, 64);
        uint32_t yp[16];
#pragma unroll
        for (int j = 0; j < 8; j++) {
            const uint4 t = lds128(sb + P_Y + (w ^ 4) * 4096 + j * 512 + lane * 16);
            yp[2 * j] = pack2(acc[j][0] + __uint_as_float(t.x), acc[j][1] + __uint_as_float(t.y)); yp[2 * j + 1] = pack2(acc[j][2] + __uint_as_float(t.z), acc[j][3] + __uint_as_float(t.w));
        }
#pragma unroll
        for (int j = 0; j < 4; j++)
            asm volatile("stmatrix.sync.aligned.m8n8.x4.trans.shared.b16 [%0],{%1,%2,%3,%4};" ::"r"(sb + P_Y + 32768 + ch * 4096 + hf * 2048 + j * 512 + (lane >> 4) * 256 + (lane & 7) * 32 + (lane & 8) * 2),
                         "r"(yp[4 * j]), "r"(yp[4 * j + 1]), "r"(yp[4 * j + 2]), "r"(yp[4 * j + 3]) : "memory");
    }
    const uint2 dk = __ldg((const uint2*)(a.Dk + d0));
    bar_sync(1, 256);
#pragma unroll 2
    for (int i = 0; i < 4; i++) {
        const int t = i * 256 + tid;
        uint4 x0 = lds128(sb + P_X + t * 32), x1 = lds128(sb + P_X + t * 32 + 16);
        if (b & 1) { x0 = make_uint4(x0.z, x0.w, x0.x, x0.y); x1 = make_uint4(x1.z, x1.w, x1.x, x1.y); }
        uint32_t y[4];
#pragma unroll
        for (int k = 0; k < 4; k++) y[k] = lds32(sb + P_Y + 32768 + k * 4096 + t * 4);
        g_x[b * XP + t] = make_uint4(hadd2(x0.x, hadd2(__byte_perm(y[0], y[1], 0x5410), hmul2(x0.z, dk.x))), hadd2(x0.y, hadd2(__byte_perm(y[2], y[3], 0x5410), hmul2(x0.w, dk.y))),
                                     hadd2(x1.x, hadd2(__byte_perm(y[0], y[1], 0x7632), hmul2(x1.z, dk.x))), hadd2(x1.y, hadd2(__byte_perm(y[2], y[3], 0x7632), hmul2(x1.w, dk.y))));
    }
    PROF(tid == 0, 3515);
}

__global__ void __cluster_dims__(2, 1, 1) __launch_bounds__(384, 1) main_kernel(const __grid_constant__ Params p) {
    extern __shared__ __align__(1024) uint8_t smem[];
    const uint32_t sb = smem_u32(smem);
    uint32_t rank; asm("mov.u32 %0,%%cluster_ctarank;" : "=r"(rank));
    const int wi = __shfl_sync(0xffffffffu, threadIdx.x >> 5, 0);
    const int v = blockIdx.x, cl = v >> 1, wg = wi >> 2;
    PROF(threadIdx.x == 0, 3500);
    ProRegs pr;
    prologue_load(p.pa, max((int)blockIdx.x - 4, 0), pr);
    if (wi == 11 && p.dopro && cl >= 2 && elect()) {
        mbar_init(sb + S_XBAR, 1);
        asm volatile("fence.mbarrier_init.release.cluster;" ::: "memory");
        mbar_expect(sb + S_XBAR, 32768);
        for (int j = 0; j < 8; j++) tma2d(sb + P_X + j * 4096, &p.tm[3], ((blockIdx.x - 4) >> 1) * 8, j * 256, sb + S_XBAR);
    }
    if (threadIdx.x == 320) {
        unsigned n;
        asm volatile("ld.relaxed.gpu.global.u32 %0,[%1];" : "=r"(n) : "l"(g_gate) : "memory");
        n = n / (4 * NCL) + p.dopro;
        sts64(sb + S_GATE, n * (4 * NCL), n & 1);
    }
    __syncwarp();
    if (wi == 10) {
        if (v < V_REC || v == 131) conv_init(sb, v == 131); else if (v < V_OP) rec_init(sb); else gemm_init(sb, v < V_QKV);
        __syncwarp();
    }
    if (wg == 2) bar_arrive(8, 384);
    asm volatile("barrier.cluster.arrive.relaxed.aligned;" ::: "memory");
    if (p.dopro && cl >= 2) prologue(p, sb, blockIdx.x - 4, wi, pr); else if (wg < 2) bar_sync(8, 384); else if (wi == 10) early_fetch(p, sb);
    asm volatile("barrier.cluster.wait.aligned;" ::: "memory");
    const int role = (v < V_REC ? 1 : v < V_OP ? 2 : v < V_QKV ? 20 : v < V_QKV + NQ ? 24 : 1) & p.roles;
    fence_async_smem();
    bar_sync(wg == 2 ? 7 : 1, wg == 2 ? 128 : 256);
    if (p.dopro && (threadIdx.x == 32 || threadIdx.x == 352)) red_release(g_gate, 1);
    PROF(threadIdx.x == 32, 3509);
    if (wi == 0 && (role & 8) && elect()) qkv_stage(p, sb + 131072, sb + G_BAR + GB_RS * 8, v - V_QKV, 0, 6);
    PROF(threadIdx.x == 0, 3506);
    __syncwarp();
    if (p.dopro && (v == 131 || (v >= V_REC && v < V_QKV && (v < V_OP ? wi == 8 : wi < 8)))) {
        bool on = v >= V_OP;
#pragma unroll 1
        for (int r = v == 131 ? 448 + wi : on ? 64 + (v - V_OP) * 8 + wi : v - V_REC; r < (v == 131 ? 512 : 448);) {
            if (v >= V_OP) wait_slow_warp(g_gate, lds32(sb + S_GATE)); else if (on) wait_flag_warp(g_gate, lds32(sb + S_GATE));
            PROF(threadIdx.x == 256 && on, 3507);
            x1_norm(on ? (const uint2*)g_x : (const uint2*)p.pa.x, r, on);
            __syncwarp();
            if (on && elect()) red_release(cnt_ptr(C_XN + (r >> 4)), 1);
            __syncwarp();
            PROF(threadIdx.x == 256, on ? 3508 : 3499);
            if (on) r += v < V_OP ? 512 : v == 131 ? 12 : 128;
            on = true;
        }
    }
    if (role == 2) {
        const int head = (v - V_REC) >> 1;
        if (wi == 8 && elect()) rec_fetch(p, sb, head, rank, 1, R_STK);
        __syncwarp();
        if (wg == 2) {
            reg_dec<RH>();
#pragma unroll
            for (int i = 0; i < PADH; i++) asm volatile("pmevent 0;");
            const int w = wi & 3;
            wait_slow_warp(g_gate, lds32(sb + S_GATE));
            if (w < 2) { const uint32_t x = __ldcg(g_sel + (threadIdx.x & 63)); sts32(sb + R_SEL + (threadIdx.x & 63) * 4, (x * 0x01010101u) >> 24); }
            __syncthreads();
            cluster_sync();
            if ((p.chains >> (w & 1)) & 1) { if (w < 2) rec_comm(p, sb, w, head, rank); else rec_attn(p, sb, w & 1, head, rank); }
        } else {
            reg_inc<RW0>();
#pragma unroll
            for (int i = 0; i < PADW; i++) asm volatile("pmevent 0;");
            rec_weights(p, sb, head, rank, wi);
        }
    } else if (role == 1) {
        if (v == 131) { wait_slow_warp(g_gate, lds32(sb + S_GATE)); conv_far<0>(sb, wi); conv_far<1>(sb, wi); } else if (wg == 2) { reg_dec<RCB>(); conv_back(sb, v, wi & 3); } else { reg_inc<RCU>(); conv_tile(p, sb, v, wi); }
    } else if (role && v < V_QKV) {
        if (wg == 2) {
            reg_dec<40>();
            if (wi == 8) { if (role & 4) gemm_producer<true>(p, sb, v - V_OP); }
            else if (v < V_OP + 14 && (role & 16)) fin_warp(p, sb, 2 * NQ + (v - V_OP) * 3 + wi - 9);
        } else { reg_inc<232>(); if (role & 4) gemm_consumer<true>(p, sb, v - V_OP, wi); }
    } else if (role) {
        if (wg == 2) {
            reg_dec<40>();
            if (wi < 10) {
                if (role & 8) { if (wi == 8) gemm_producer<false>(p, sb, v - V_QKV); else qkv_release(p, sb); }
            } else if (role & 16) fin_warp(p, sb, (v - V_QKV) * 2 + wi - 10);
        } else { reg_inc<232>(); if (role & 8) gemm_consumer<false>(p, sb, v - V_QKV, wi); }
    }
    __syncwarp();
    cluster_sync();
}

typedef CUresult (*EncFn)(CUtensorMap*, CUtensorMapDataType, cuuint32_t, void*, const cuuint64_t*, const cuuint64_t*, const cuuint32_t*, const cuuint32_t*,
                          CUtensorMapInterleave, CUtensorMapSwizzle, CUtensorMapL2promotion, CUtensorMapFloatOOBfill);
constexpr int SMEM_BYTES = 232448;
#define LAG 8
#define QLEAD 6
#define SPLIT 2
#define OLEAD (LAG / 2 + 2)
void plan(Params& P) {
    P.roles = 31; P.chains = 3; P.lag = LAG; P.dopro = 1; P.h0 = 128 - 2 * SPLIT;
    for (int r = 0; r < 2; r++) {
        const int lead = r ? OLEAD : QLEAD;
        int n = 0;
        for (int i = 0; i < 32 + lead; i++) {
            if (i >= lead) P.list[r][n++] = 32 + i - lead;
            if (i < 32) P.list[r][n++] = i;
        }
        P.nl[r] = n - r * SPLIT;
    }
}

#define TK() do {} while (0)
}

extern "C" void kernel_launch(void* const* d_in, const int* in_sizes, int n_in, void* d_out, int out_size) {
    typedef const __nv_bfloat16* BP;
    static EncFn enc = nullptr;
    if (!enc) {
        void* fn = nullptr; cudaDriverEntryPointQueryResult qr;
        cudaGetDriverEntryPoint("cuTensorMapEncodeTiled", &fn, cudaEnableDefault, &qr);
        enc = (EncFn)fn;
        cudaFuncSetAttribute(main_kernel, cudaFuncAttributeMaxDynamicSharedMemorySize, SMEM_BYTES);
    }
    static Params P;
    for (int i = 0; i < 4; i++) {
        const cuuint64_t cols = i < 3 ? 4096 : 512, rows = i < 3 ? 512 : 4096;
        cuuint64_t d2[2] = {cols, rows}, str[1] = {cols * 2};
        cuuint32_t box[2] = {64, 64}, bn[2] = {16, 256}, es[2] = {1, 1};
        enc(&P.tm[i < 3 ? i : 4], CU_TENSOR_MAP_DATA_TYPE_BFLOAT16, 2, d_in[9 + i], d2, str, box, es, CU_TENSOR_MAP_INTERLEAVE_NONE, CU_TENSOR_MAP_SWIZZLE_128B,
            CU_TENSOR_MAP_L2_PROMOTION_L2_128B, CU_TENSOR_MAP_FLOAT_OOB_FILL_NONE);
        if (i < 2) enc(&P.tn[i], CU_TENSOR_MAP_DATA_TYPE_BFLOAT16, 2, d_in[9 + i], d2, str, bn, es, CU_TENSOR_MAP_INTERLEAVE_NONE, CU_TENSOR_MAP_SWIZZLE_32B,
                       CU_TENSOR_MAP_L2_PROMOTION_L2_128B, CU_TENSOR_MAP_FLOAT_OOB_FILL_NONE);
    }
    {
        cuuint64_t dims[2] = {512, 2048}, str[1] = {1024};
        cuuint32_t box[2] = {8, 256}, es[2] = {1, 1};
        enc(&P.tm[3], CU_TENSOR_MAP_DATA_TYPE_BFLOAT16, 2, d_in[0], dims, str, box, es, CU_TENSOR_MAP_INTERLEAVE_NONE, CU_TENSOR_MAP_SWIZZLE_NONE,
            CU_TENSOR_MAP_L2_PROMOTION_NONE, CU_TENSOR_MAP_FLOAT_OOB_FILL_NONE);
    }
    P.mem0 = (BP)d_in[8]; P.Wo = (BP)d_in[12]; P.Dskip = (BP)d_in[6]; P.out = (__nv_bfloat16*)d_out;
    cudaStream_t s = cudaStreamPerThread;
    P.pa = {(BP)d_in[0], (BP)d_in[1], (BP)d_in[2], (BP)d_in[3], (BP)d_in[4], (BP)d_in[5], (BP)d_in[6]};
    plan(P);
    TK(); main_kernel<<<2 * NCL, 384, SMEM_BYTES, s>>>(P); TK();
}
```

```cpp
#include <cuda_runtime.h>
#include <cuda_bf16.h>
#include <cuda.h>
#include <stdint.h>
#include <string.h>
#include <math.h>

namespace {

constexpr int NCL = 66;
constexpr int NQ = 43;
constexpr int V_REC = 8, V_OP = 72, V_QKV = 88;
static_assert(2 * NQ + 3 * 14 == 128, "warps of the final residual");

constexpr int XP = 1024;
__device__ uint4 g_x[2 * 128 * XP];
__device__ uint4 g_xn[64 * 4096];
__device__ uint4 g_st[68 * 256];
__device__ uint4 g_qkv[128 * 32 * 1536];
__device__ uint4 g_o[64 * 64 * 512];
__device__ uint4 g_pp[64 * 4 * 4096];
__device__ uint4 g_xch[133 * 512];
__device__ unsigned g_sel[64];
__device__ unsigned g_gate[32];
__device__ __align__(16) uint32_t g_P[512 * 272];
__device__ uint4 g_W[512 * 784];
__device__ __align__(16) uint32_t g_u[512 * 1280];
__device__ uint2 g_carry[512 * 40 * 32];
__device__ uint2 g_far[512 * 12 * 32];
__device__ unsigned g_cnt[916 * 8];
__device__ uint32_t g_ln0[2048];

enum { C_XN = 0  , C_QKV = 64  , C_O = 128  , C_PP = 384  , C_FAR = 896  , C_OH = 908  , C_N = 916 };
__device__ __forceinline__ unsigned* cnt_ptr(int i) { return g_cnt + i * 8; }

struct ProArgs { const __nv_bfloat16 *x, *lAr, *Ai, *Cr, *Ci, *ldt, *Dk; };
struct Params {
    CUtensorMap tm[5];
    CUtensorMap tn[2];
    ProArgs pa;
    int dopro;
    const __nv_bfloat16* mem0;
    const __nv_bfloat16* Wo;
    const __nv_bfloat16* Dskip;
    __nv_bfloat16* out;
    int roles;
    int chains;
    int lag;
    int zero;
    int h0;
    int nl[2];
    uint8_t list[2][64];
};

__device__ __forceinline__ uint32_t smem_u32(const void* p) { return (uint32_t)__cvta_generic_to_shared(p); }
__device__ __forceinline__ uint32_t mapa(uint32_t a, uint32_t r) {
    uint32_t o; asm("mapa.shared::cluster.u32 %0,%1,%2;" : "=r"(o) : "r"(a), "r"(r)); return o;
}
__device__ __forceinline__ void mbar_init(uint32_t b, int c) { asm volatile("mbarrier.init.shared::cta.b64 [%0],%1;" ::"r"(b), "r"(c) : "memory"); }
__device__ __forceinline__ void mbar_expect(uint32_t b, int bytes) { asm volatile("mbarrier.arrive.expect_tx.shared::cta.b64 _,[%0],%1;" ::"r"(b), "r"(bytes) : "memory"); }
__device__ __forceinline__ void mbar_arrive(uint32_t b) { asm volatile("mbarrier.arrive.shared::cta.b64 _,[%0];" ::"r"(b) : "memory"); }
__device__ __forceinline__ void mbar_arrive_cluster(uint32_t b) { asm volatile("mbarrier.arrive.shared::cluster.b64 _,[%0];" ::"r"(b) : "memory"); }
__device__ __forceinline__ void mbar_wait(uint32_t b, uint32_t ph) {
    asm volatile(
        "{.reg .pred p; .reg .u32 n; mov.u32 n,0;\n"
        "W%=: mbarrier.try_wait.parity.shared::cta.b64 p,[%0],%1;\n"
        "@p bra D%=;\n"
        "add.u32 n,n,1; setp.lt.u32 p,n,2000000; @p bra W%=;\n"
        "trap;\n"
        "D%=: }" ::"r"(b), "r"(ph) : "memory");
}
__device__ __forceinline__ bool elect() {
    uint32_t r; asm volatile("{.reg .pred p; elect.sync _|p,0xffffffff; selp.u32 %0,1,0,p;}" : "=r"(r)); return r;
}
__device__ __forceinline__ void bar_sync(int id, int n) { asm volatile("bar.sync %0,%1;" ::"r"(id), "r"(n) : "memory"); }
__device__ __forceinline__ void bar_arrive(int id, int n) { asm volatile("bar.arrive %0,%1;" ::"r"(id), "r"(n) : "memory"); }
__device__ __forceinline__ void cluster_sync() { asm volatile("barrier.cluster.arrive.relaxed.aligned; barrier.cluster.wait.aligned;" ::: "memory"); }
__device__ __forceinline__ void fence_async_smem() { asm volatile("fence.proxy.async.shared::cta;" ::: "memory"); }
constexpr uint64_t POL_N = 0x1000000000000000ull  , POL_LAST = 0x12F0000000000000ull  ;
__device__ __forceinline__ void bulk_g2s(uint32_t dst, const void* src, int bytes, uint32_t bar, uint64_t pol) {
    asm volatile("cp.async.bulk.shared::cluster.global.mbarrier::complete_tx::bytes.L2::cache_hint [%0],[%1],%2,[%3],%4;" ::"r"(dst), "l"(src), "r"(bytes), "r"(bar), "l"(pol) : "memory");
}
__device__ __forceinline__ void bulk_g2s_mc(uint32_t dst, const void* src, int bytes, uint32_t bar, uint64_t pol) {
    asm volatile("cp.async.bulk.shared::cluster.global.mbarrier::complete_tx::bytes.multicast::cluster.L2::cache_hint [%0],[%1],%2,[%3],%4,%5;" ::"r"(dst), "l"(src), "r"(bytes), "r"(bar), "h"((uint16_t)3), "l"(pol) : "memory");
}
__device__ __forceinline__ void stg128(uint4* p, uint4 v, uint64_t pol) {
    asm volatile("st.global.L2::cache_hint.v4.u32 [%0],{%1,%2,%3,%4},%5;" ::"l"(p), "r"(v.x), "r"(v.y), "r"(v.z), "r"(v.w), "l"(pol));
}
__device__ __forceinline__ void tma2d(uint32_t dst, const CUtensorMap* tm, int x, int y, uint32_t bar) {
    asm volatile("cp.async.bulk.tensor.2d.shared::cluster.global.mbarrier::complete_tx::bytes [%0],[%1,{%2,%3}],[%4];" ::"r"(dst), "l"(tm), "r"(x), "r"(y), "r"(bar) : "memory");
}
__device__ __forceinline__ void st_async4(uint32_t a, uint32_t x, uint32_t y, uint32_t z, uint32_t w, uint32_t mb) {
    asm volatile("st.async.shared::cluster.mbarrier::complete_tx::bytes.v4.b32 [%0],{%1,%2,%3,%4},[%5];" ::"r"(a), "r"(x), "r"(y), "r"(z), "r"(w), "r"(mb) : "memory");
}
__device__ __forceinline__ void st_async2(uint32_t a, uint32_t x, uint32_t y, uint32_t mb) {
    asm volatile("st.async.shared::cluster.mbarrier::complete_tx::bytes.v2.b32 [%0],{%1,%2},[%3];" ::"r"(a), "r"(x), "r"(y), "r"(mb) : "memory");
}
__device__ __forceinline__ uint4 lds128(uint32_t a) { uint4 v; asm volatile("ld.shared.v4.u32 {%0,%1,%2,%3},[%4];" : "=r"(v.x), "=r"(v.y), "=r"(v.z), "=r"(v.w) : "r"(a) : "memory"); return v; }
__device__ __forceinline__ uint4 lds128v(uint32_t a) { uint4 v; asm volatile("ld.volatile.shared.v4.u32 {%0,%1,%2,%3},[%4];" : "=r"(v.x), "=r"(v.y), "=r"(v.z), "=r"(v.w) : "r"(a) : "memory"); return v; }
__device__ __forceinline__ uint2 lds64(uint32_t a) { uint2 v; asm volatile("ld.shared.v2.u32 {%0,%1},[%2];" : "=r"(v.x), "=r"(v.y) : "r"(a) : "memory"); return v; }
__device__ __forceinline__ uint32_t lds32(uint32_t a) { uint32_t v; asm volatile("ld.shared.u32 %0,[%1];" : "=r"(v) : "r"(a) : "memory"); return v; }
__device__ __forceinline__ void sts128(uint32_t a, uint32_t x, uint32_t y, uint32_t z, uint32_t w) { asm volatile("st.shared.v4.u32 [%0],{%1,%2,%3,%4};" ::"r"(a), "r"(x), "r"(y), "r"(z), "r"(w) : "memory"); }
__device__ __forceinline__ void sts64(uint32_t a, uint32_t x, uint32_t y) { asm volatile("st.shared.v2.u32 [%0],{%1,%2};" ::"r"(a), "r"(x), "r"(y) : "memory"); }
__device__ __forceinline__ void sts32(uint32_t a, uint32_t x) { asm volatile("st.shared.u32 [%0],%1;" ::"r"(a), "r"(x) : "memory"); }
__device__ __forceinline__ uint4 ldsm4(uint32_t a) { uint4 v; asm volatile("ldmatrix.sync.aligned.m8n8.x4.shared.b16 {%0,%1,%2,%3},[%4];" : "=r"(v.x), "=r"(v.y), "=r"(v.z), "=r"(v.w) : "r"(a) : "memory"); return v; }
__device__ __forceinline__ uint4 ldsm4t(uint32_t a) { uint4 v; asm volatile("ldmatrix.sync.aligned.m8n8.x4.trans.shared.b16 {%0,%1,%2,%3},[%4];" : "=r"(v.x), "=r"(v.y), "=r"(v.z), "=r"(v.w) : "r"(a) : "memory"); return v; }
__device__ __forceinline__ uint32_t movm(uint32_t a) { uint32_t d; asm volatile("movmatrix.sync.aligned.m8n8.trans.b16 %0,%1;" : "=r"(d) : "r"(a)); return d; }
__device__ __forceinline__ uint32_t pack2(float lo, float hi) { uint32_t d; asm("cvt.rn.bf16x2.f32 %0,%1,%2;" : "=r"(d) : "f"(hi), "f"(lo)); return d; }
__device__ __forceinline__ uint32_t hadd2(uint32_t a, uint32_t b) { uint32_t d; asm("add.rn.bf16x2 %0,%1,%2;" : "=r"(d) : "r"(a), "r"(b)); return d; }
__device__ __forceinline__ uint32_t hmul2(uint32_t a, uint32_t b) { uint32_t d; asm("mul.rn.bf16x2 %0,%1,%2;" : "=r"(d) : "r"(a), "r"(b)); return d; }
__device__ __forceinline__ float blo(uint32_t v) { return __uint_as_float(v << 16); }
__device__ __forceinline__ float bhi(uint32_t v) { return __uint_as_float(v & 0xffff0000u); }
__device__ __forceinline__ float rbf(float x) { return __uint_as_float(pack2(0.f, x)); }
__device__ __forceinline__ float ex2(float x) { float y; asm("ex2.approx.ftz.f32 %0,%1;" : "=f"(y) : "f"(x)); return y; }
__device__ __forceinline__ float rcp(float x) { float y; asm("rcp.approx.ftz.f32 %0,%1;" : "=f"(y) : "f"(x)); return y; }
__device__ __forceinline__ void mma16(float* c, uint32_t a0, uint32_t a1, uint32_t a2, uint32_t a3, uint32_t b0, uint32_t b1) {
    asm volatile("mma.sync.aligned.m16n8k16.row.col.f32.bf16.bf16.f32 {%0,%1,%2,%3},{%4,%5,%6,%7},{%8,%9},{%0,%1,%2,%3};"
                 : "+f"(c[0]), "+f"(c[1]), "+f"(c[2]), "+f"(c[3]) : "r"(a0), "r"(a1), "r"(a2), "r"(a3), "r"(b0), "r"(b1));
}
__device__ __forceinline__ void mma16_top(float& d0, float& d1, uint32_t a0, uint32_t a2, uint32_t b0, uint32_t b1) {
    asm volatile("{.reg .b32 j; .reg .f32 e,f; mma.sync.aligned.m16n8k16.row.col.f32.bf16.bf16.f32 {%0,%1,e,f},{%2,j,%3,j},{%4,%5},{0f00000000,0f00000000,0f00000000,0f00000000};}"
                 : "=f"(d0), "=f"(d1) : "r"(a0), "r"(a2), "r"(b0), "r"(b1));
}
__device__ __forceinline__ void mma8(float* c, uint32_t a0, uint32_t a1, uint32_t b0) {
    asm volatile("mma.sync.aligned.m16n8k8.row.col.f32.bf16.bf16.f32 {%0,%1,%2,%3},{%4,%5},{%6},{%0,%1,%2,%3};"
                 : "+f"(c[0]), "+f"(c[1]), "+f"(c[2]), "+f"(c[3]) : "r"(a0), "r"(a1), "r"(b0));
}
__device__ __forceinline__ uint4 ld_rlx128(const uint4* p) {
    uint4 v;
    asm volatile("{.reg .b128 t; ld.relaxed.gpu.global.b128 t,[%4]; mov.b128 {%0,%1,%2,%3},t;}" : "=r"(v.x), "=r"(v.y), "=r"(v.z), "=r"(v.w) : "l"(p) : "memory");
    return v;
}
__device__ __forceinline__ void st_rlx128(uint4* p, uint32_t x, uint32_t y, uint32_t z, uint32_t w) {
    asm volatile("{.reg .b128 t; mov.b128 t,{%1,%2,%3,%4}; st.relaxed.gpu.global.b128 [%0],t;}" ::"l"(p), "r"(x), "r"(y), "r"(z), "r"(w) : "memory");
}
__device__ __forceinline__ uint4 ldcg128(const uint4* p) { uint4 v; asm volatile("ld.global.cg.v4.u32 {%0,%1,%2,%3},[%4];" : "=r"(v.x), "=r"(v.y), "=r"(v.z), "=r"(v.w) : "l"(p) : "memory"); return v; }
__device__ __forceinline__ void red_release(unsigned* p, unsigned v) {
    asm volatile("fence.proxy.async; red.relaxed.gpu.global.add.u32 [%0],%1;" ::"l"(p), "r"(v) : "memory");
}
__device__ __forceinline__ void red_relaxed(unsigned* p, unsigned v) { asm volatile("red.relaxed.gpu.global.add.u32 [%0],%1;" ::"l"(p), "r"(v) : "memory"); }
__device__ __forceinline__ void wait_cnt(const unsigned* p, unsigned target) {
    asm volatile(
        "{.reg .pred p; .reg .u32 n,v; mov.u32 n,0;\n"
        "W%=: ld.relaxed.gpu.global.u32 v,[%0]; setp.ge.u32 p,v,%1; @p bra D%=;\n"
        "add.u32 n,n,1; setp.lt.u32 p,n,10000000; @p bra W%=;\n"
        "trap;\n"
        "D%=: }" ::"l"(p), "r"(target) : "memory");
}
__device__ __forceinline__ void wait_slow_warp(const unsigned* p, unsigned target) {
    asm volatile(
        "{.reg .pred p; .reg .u32 n,v; mov.u32 n,0;\n"
        "W%=: ld.relaxed.gpu.global.u32 v,[%0]; setp.ge.u32 p,v,%1; vote.sync.all.pred p,p,0xffffffff; @p bra.uni D%=;\n"
        "nanosleep.u32 400; add.u32 n,n,1; setp.lt.u32 p,n,1000000; @p bra.uni W%=;\n"
        "trap;\n"
        "D%=: }" ::"l"(p), "r"(target) : "memory");
}
__device__ __forceinline__ void wait_flag_warp(const unsigned* p, unsigned target) {
    asm volatile(
        "{.reg .pred p; .reg .u32 n,v; mov.u32 n,0;\n"
        "W%=: ld.relaxed.gpu.global.u32 v,[%0]; setp.ge.u32 p,v,%1; vote.sync.all.pred p,p,0xffffffff; @p bra.uni D%=;\n"
        "add.u32 n,n,1; setp.lt.u32 p,n,10000000; @p bra.uni W%=;\n"
        "trap;\n"
        "D%=: }" ::"l"(p), "r"(target) : "memory");
}
__device__ __forceinline__ uint64_t mkdesc(uint32_t addr, uint32_t lbo, uint32_t sbo, uint32_t sw) {
    return (uint64_t)((addr & 0x3FFFF) >> 4) | ((uint64_t)(lbo >> 4) << 16) | ((uint64_t)(sbo >> 4) << 32) | ((uint64_t)sw << 62);
}
__device__ __forceinline__ void wg_fence() { asm volatile("wgmma.fence.sync.aligned;" ::: "memory"); }
__device__ __forceinline__ void wg_commit() { asm volatile("wgmma.commit_group.sync.aligned;" ::: "memory"); }
template <int N> __device__ __forceinline__ void wg_wait() { asm volatile("wgmma.wait_group.sync.aligned %0;" ::"n"(N) : "memory"); }
#define R8(c, o) "+f"(c[o]), "+f"(c[o + 1]), "+f"(c[o + 2]), "+f"(c[o + 3]), "+f"(c[o + 4]), "+f"(c[o + 5]), "+f"(c[o + 6]), "+f"(c[o + 7])
#define R32(c, o) R8(c, o), R8(c, o + 8), R8(c, o + 16), R8(c, o + 24)
#define S32A "%0,%1,%2,%3,%4,%5,%6,%7,%8,%9,%10,%11,%12,%13,%14,%15,%16,%17,%18,%19,%20,%21,%22,%23,%24,%25,%26,%27,%28,%29,%30,%31"
template <int ACC> __device__ __forceinline__ void wgmma64_rs(float* c, const uint32_t* a, uint64_t db) {
    asm volatile("wgmma.mma_async.sync.aligned.m64n64k16.f32.bf16.bf16 {" S32A "},{%32,%33,%34,%35},%36,%37,1,1,0;"
                 : R32(c, 0) : "r"(a[0]), "r"(a[1]), "r"(a[2]), "r"(a[3]), "l"(db), "n"(ACC));
}
template <int ACC> __device__ __forceinline__ void wgmma64_ta(float* c, uint64_t da, uint64_t db) {
    asm volatile("wgmma.mma_async.sync.aligned.m64n64k16.f32.bf16.bf16 {" S32A "},%32,%33,%34,1,1,1,0;" : R32(c, 0) : "l"(da), "l"(db), "n"(ACC));
}
#define S16 "%0,%1,%2,%3,%4,%5,%6,%7,%8,%9,%10,%11,%12,%13,%14,%15"
template <int ACC> __device__ __forceinline__ void wgmma32_rs(float* c, const uint32_t* a, uint64_t db) {
    asm volatile("wgmma.mma_async.sync.aligned.m64n32k16.f32.bf16.bf16 {" S16 "},{%16,%17,%18,%19},%20,%21,1,1,0;"
                 : R8(c, 0), R8(c, 8) : "r"(a[0]), "r"(a[1]), "r"(a[2]), "r"(a[3]), "l"(db), "n"(ACC));
}
template <int ACC> __device__ __forceinline__ void wgmma32_ta(float* c, uint64_t da, uint64_t db) {
    asm volatile("wgmma.mma_async.sync.aligned.m64n32k16.f32.bf16.bf16 {" S16 "},%16,%17,%18,1,1,1,0;" : R8(c, 0), R8(c, 8) : "l"(da), "l"(db), "n"(ACC));
}
template <int ACC> __device__ __forceinline__ void wgmma80_tb(float* c, uint64_t da, uint64_t db) {
    asm volatile("wgmma.mma_async.sync.aligned.m64n80k16.f32.bf16.bf16 {" S32A ",%32,%33,%34,%35,%36,%37,%38,%39},%40,%41,%42,1,1,0,1;"
                 : R32(c, 0), R8(c, 32) : "l"(da), "l"(db), "n"(ACC));
}
template <int N> __device__ __forceinline__ void reg_inc() { asm volatile("setmaxnreg.inc.sync.aligned.u32 %0;" ::"n"(N)); }
template <int N> __device__ __forceinline__ void reg_dec() { asm volatile("setmaxnreg.dec.sync.aligned.u32 %0;" ::"n"(N)); }

#define PROF(cond, idx) do {} while (0)
#define PROF2(cond, idx) do {} while (0)

constexpr int S_GATE = 232440, S_TAG = 232444, S_XBAR = 232432, B_BAR = 231936;
#define FT 5
#define FJ 62
#define OLAG 1
#define RCB 136
#define RCU 184
#define NTOP 1
#define PLATE 2
#define QLAG 4
constexpr float SC_LOG2E = 0.08838834764831845f * 1.4426950408889634f;

__device__ __forceinline__ float2 ln_finish(float mean, float var) {
    float sd; asm("sqrt.approx.f32 %0,%1;" : "=f"(sd) : "f"(rbf(rbf(var) + 1e-5f)));
    sd = rbf(sd);
    return make_float2(rbf(mean), sd);
}

__device__ __forceinline__ float2 row_stats512(uint4* v, const uint4* src, int s1, int s2) {
    const int g = (threadIdx.x & 31) >> 2;
#pragma unroll
    for (int i = 0; i < 16; i++) v[i] = ldcg128(src + (i >> 1) * s1 + (i & 1) * s2);
    float a[4] = {0, 0, 0, 0}, q0[4] = {0, 0, 0, 0}, q1[4] = {0, 0, 0, 0};
#pragma unroll
    for (int i = 0; i < 16; i++) {
        mma16(a, v[i].x, v[i].y, v[i].z, v[i].w, 0x3f803f80u, 0x3f803f80u);
        mma8(q0, v[i].x, v[i].y, v[i].x); mma8(q1, v[i].x, v[i].y, v[i].y);
        mma8(q0, v[i].z, v[i].w, v[i].z); mma8(q1, v[i].z, v[i].w, v[i].w);
    }
    const float sum = a[0] + a[2], sq = (g & 1) ? q0[1] + q1[3] : q0[0] + q1[2];
    return make_float2(sum, fmaxf(sq - sum * sum * (1.f / 512.f), 0.f));
}
__device__ __forceinline__ void x1_norm(const uint2* src, int r, bool on) {
    const int lane = threadIdx.x & 31, g = lane >> 2, t = r * 4 + (lane & 3);
    constexpr int xp = XP;
    uint2 v[16];
#pragma unroll
    for (int i = 0; i < 16; i++) asm volatile("ld.global.cg.v2.u32 {%0,%1},[%2];" : "=r"(v[i].x), "=r"(v[i].y) : "l"(src + (g * 4 * xp + t) + ((i >> 1) * 16 + (i & 1)) * 2 * xp) : "memory");
    float s = 0, q = 0;
#pragma unroll
    for (int i = 0; i < 32; i++) {
        const uint32_t w = (i & 1) ? v[i >> 1].y : v[i >> 1].x;
        s += blo(w) + bhi(w); q = fmaf(blo(w), blo(w), fmaf(bhi(w), bhi(w), q));
    }
#pragma unroll
    for (int d = 4; d < 32; d *= 2) { s += __shfl_xor_sync(0xffffffffu, s, d); q += __shfl_xor_sync(0xffffffffu, q, d); }
    if (g == 0 && on) g_ln0[t] = 0;
    s *= 1.f / 512.f;
    const float2 l = ln_finish(s, fmaxf(fmaf(q, 1.f / 512.f, -s * s), 0.f));
    const float rs = rcp(l.y);
    const uint32_t mm = pack2(-l.x, -l.x);
    uint4* dst = g_xn + ((t >> 6) * 4096 + ((t >> 3) & 7) * 64 + g * 8 + (t & 7));
#define NRM(w) pack2(blo(hadd2(w, mm)) * rs, bhi(hadd2(w, mm)) * rs)
#pragma unroll
    for (int i = 0; i < 8; i++)
        asm volatile("{.reg .pred p; setp.ne.u32 p,%5,0; @p st.global.v4.u32 [%0],{%1,%2,%3,%4};}" ::"l"(dst + i * 512), "r"(NRM(v[2 * i].x)), "r"(NRM(v[2 * i].y)),
                     "r"(NRM(v[2 * i + 1].x)), "r"(NRM(v[2 * i + 1].y)), "r"((uint32_t)on) : "memory");
}

#define NWO 10
#define VMASK 0x4444
#define VPRE 2
#define OL 0x16
#define PINS 0x6ae5
#define NPX 2
#define NPF 2
constexpr int SLOT = 24576, SL_V = 8192, SL_Q = 16384, SL_KM = 20480, SL_VM = 22528;
constexpr int R_SL = 0, R_WV = 4 * SLOT  , R_WO = R_WV + 65536, R_M = 196608  , R_U = R_M + 8192  ,
              R_OS = R_U + 8192  , R_SB = R_OS + 8192  , R_OB = R_SB + 5248  , R_PB = R_OB + 2048  ,
              R_IL = R_PB + 1024  , R_SEL = 231680, R_BAR = R_SEL + 256, R_STV = 0, R_STQ = 65536, R_STK = 131072;
static_assert(R_WO + (16 - NWO) * 4096 <= R_M && R_IL + 64 <= R_SEL && R_BAR + 512 <= 232448, "smem map");
enum { RB_XFULL = 0  , RB_GO = 4  , RB_QK = 8  , RB_INIT = 24, RB_SV = 25   };

enum { NB_MFULL = 1  , NB_PART = 3  , NB_S = 5, NB_P = 6, NB_O = 7, NB_W = 10 };
#define XU 4
#define PT 0xffff
#define NPRB 3
#define RH 56
#define RW0 224
#define D1 240
#define D2 300
__device__ __forceinline__ uint32_t clk32() { uint32_t c; asm volatile("mov.u32 %0,%%clock;" : "=r"(c)::"memory"); return c; }
__device__ __forceinline__ void spin(int cycles) {
    if (cycles <= 0) return;
    asm volatile("{.reg .pred p; .reg .u32 a,b; mov.u32 a,%%clock; add.u32 a,a,%0;\nS%=: mov.u32 b,%%clock; sub.u32 b,b,a; setp.lt.s32 p,b,0; @p bra.uni S%=;}" ::"r"(cycles) : "memory");
}
__device__ __forceinline__ uint4* xregion(int X, int r) { return (uint4*)(((size_t)g_xch + 8191) & ~(size_t)8191) + (X * 66 + r) * 512; }

__device__ __forceinline__ void arrive_if(uint32_t bar, uint32_t a, uint32_t b) {
    asm volatile("{.reg .pred p; setp.eq.u32 p,%1,%2; @p mbarrier.arrive.shared::cta.b64 _,[%0];}" ::"r"(bar), "r"(a), "r"(b) : "memory");
}
struct RecW { uint32_t po, dp, lw, sp, w; };
#define PIN(n) if ((PINS >> (n)) & 1) asm volatile("griddepcontrol.launch_dependents;" ::: "memory")
constexpr int v_stream(int n) {
    int ks = 0;
    for (; ks < 16; ks++) if (!((VMASK >> ks) & 1) && n-- == 0) break;
    return ks;
}
constexpr uint64_t v_next() {
    uint64_t r = 0;
    for (int n = 0; v_stream(n + VPRE) < 16; n++) r |= (uint64_t)v_stream(n + VPRE) << (4 * v_stream(n));
    return r;
}
constexpr uint64_t V_NEXT = v_next();
constexpr int V_PRE = v_stream(VPRE);

__device__ __forceinline__ void rec_step(const RecW& k, uint32_t sb, const int X, int s, uint32_t zero, int lo, int hi, int d, const uint32_t (*wq)[4], const uint32_t (*wk)[4], uint4* wv, uint4* wo) {
    const int SL = R_SL + X * 2 * SLOT;
    uint4 mk[8];
    bar_sync(NB_MFULL + X, 288);
    mk[0] = ldsm4(k.lw + X * 4096 + R_M);
    PIN(0);
    mk[1] = ldsm4(k.lw + X * 4096 + R_M + 512);
    PIN(0);
    asm volatile("" : "+r"(s));
    const uint32_t z = s & zero, wz = k.w + z, w5 = wz * 512, so = (s & 1) * SLOT + w5;
    const uint32_t qb = sb + R_BAR + (RB_QK + X * 8) * 8 + wz * 8;
    uint32_t x[4], vv[2], l8;
    {
        float aq[4] = {0, 0, 0, 0}, ak[4] = {0, 0, 0, 0}, av[4] = {0, 0, 0, 0};
#pragma unroll
        for (int t = 0; t < 16; t++) {
            const uint32_t b0 = (t & 1) ? mk[t >> 1].z : mk[t >> 1].x, b1 = (t & 1) ? mk[t >> 1].w : mk[t >> 1].y;
            mma16(aq, wq[t][0], wq[t][1], wq[t][2], wq[t][3], b0, b1);
            PIN(8);
            mma16(ak, wk[t][0], wk[t][1], wk[t][2], wk[t][3], b0, b1);
            if ((PT >> t) & 1) PIN(9);
            mma16(av, wv[t].x, wv[t].y, wv[t].z, wv[t].w, b0, b1);
            PIN(10);
            if ((t & 1) && t < 13) mk[(t >> 1) + 2] = ldsm4(k.lw + X * 4096 + R_M + (t >> 1) * 512 + 1024);
            const int nx = (V_NEXT >> (4 * t)) & 15;
            if (nx) wv[nx] = lds128(k.lw + w5 + R_WV + nx * 4096);
            if (t == 14) l8 = ((k.lw + z) >> 1) + (sb - (sb >> 1) + SL + (s & 1) * SLOT + wz * 256);
            if (t < 15) PIN(1);
        }
        x[0] = movm(pack2(aq[0], aq[1])); x[1] = movm(pack2(aq[2], aq[3]));
        x[2] = movm(pack2(ak[0], ak[1])); x[3] = movm(pack2(ak[2], ak[3]));
        vv[0] = pack2(av[0], av[1]); vv[1] = pack2(av[2], av[3]);
        st_async2(l8 + (SL_VM + k.dp), vv[0], vv[1], qb + k.dp);
        st_async4(k.lw + (R_U + X * 4096 + w5 + k.dp), x[0], x[1], x[2], x[3], qb + k.dp);
    }
    {
        arrive_if(sb + R_BAR + (RB_GO + 2 - 2 * X + ((s + d) & 1)) * 8, (k.sp + z) & 0x1ff0, X ? s >= hi : s <= lo);
        const uint32_t swr = ((k.sp + z) & 0x1ff0) + (sb + R_SB);
#pragma unroll
        for (int i = 0; i < NPX; i++) wo[i] = lds128v(k.lw + w5 + R_WO + i * 4096);
        mbar_wait(sb + R_BAR + (RB_XFULL + X * 2) * 8 + (s & 1) * 8, (s >> 1) & 1);
        const uint4 k0 = lds128(k.lw + so + SL), k1 = lds128(k.lw + so + SL + 4096);
        mbar_wait(qb, s & 1);
        const uint4 u = lds128(k.lw + w5 + R_U + X * 4096);
        const uint32_t q0 = hadd2(x[0], u.x), q1 = hadd2(x[1], u.y);
        x[2] = hadd2(x[2], u.z); x[3] = hadd2(x[3], u.w);
        float sa[4] = {0, 0, 0, 0}, sc[4] = {0, 0, 0, 0}, sm0, sm1;
        mma16(sa, k0.x, k0.y, k0.z, k0.w, q0, q1);
        mma16(sc, k1.x, k1.y, k1.z, k1.w, q0, q1);
        mma16_top(sm0, sm1, x[2], x[3], q0, q1);
        asm volatile("stmatrix.sync.aligned.m8n8.x4.trans.shared.b16 [%0],{%1,%2,%3,%4};" ::"r"(swr), "r"(pack2(sa[0], sa[1])), "r"(pack2(sa[2], sa[3])),
                     "r"(pack2(sc[0], sc[1])), "r"(pack2(sc[2], sc[3])) : "memory");
        asm volatile("stmatrix.sync.aligned.m8n8.x1.trans.shared.b16 [%0],{%1};" ::"r"(swr + 512), "r"(pack2(sm0, sm1)) : "memory");
    }
    bar_sync(NB_S, 256);
    uint4 v0, v1;
    uint32_t ls;
    {
        const uint4 y = ldsm4t(k.lw + wz * 656 + R_SB);
        PIN(2);
        uint32_t y4; asm volatile("ldmatrix.sync.aligned.m8n8.x1.trans.shared.b16 {%0},[%1];" : "=r"(y4) : "r"(k.lw + wz * 656 + R_SB + 512) : "memory");
        PIN(2);
        const uint2 vp = lds64(l8 + SL_VM);
        sts64(l8 + SL_KM, x[2], x[3]);
        const uint32_t z1 = k.lw & z, z2 = k.sp & z, ONE = 0x3f803f80u | z2, ONF = 0x3f803f80u | z1;
        float a[4] = {0, 0, 0, 0}, b[4] = {0, 0, 0, 0}, e[4] = {0, 0, 0, 0};
        mma8(e, ONE, z1, y4); mma16(a, ONE, z1, z2, ONF, y.x, y.y); mma16(b, ONE, z1, z2, ONF, y.z, y.w);
        vv[0] = hadd2(vv[0], vp.x); vv[1] = hadd2(vv[1], vp.y);
        sts64(l8 + SL_VM, vv[0], vv[1]);
        float s0, s1;
        asm("{.reg .pred p1,p2,p4; .reg .f32 t0,t1,u0,u1; .reg .b32 m; and.b32 m,%12,64; setp.ne.u32 p1,m,0; and.b32 m,%12,128; setp.ne.u32 p2,m,0; and.b32 m,%12,256; setp.ne.u32 p4,m,0;"
            "selp.f32 t0,%4,%2,p1; selp.f32 t1,%5,%3,p1; selp.f32 u0,%8,%6,p1; selp.f32 u1,%9,%7,p1; selp.f32 t0,u0,t0,p2; selp.f32 t1,u1,t1,p2; selp.f32 %0,%10,t0,p4; selp.f32 %1,%11,t1,p4;}"
            : "=f"(s0), "=f"(s1) : "f"(a[0]), "f"(a[1]), "f"(a[2]), "f"(a[3]), "f"(b[0]), "f"(b[1]), "f"(b[2]), "f"(b[3]), "f"(e[0]), "f"(e[1]), "r"(k.lw));
        const int mi = __float_as_int(fmaxf(s0, s1));
        const int mp = __reduce_max_sync(0xffffffffu, mi), mn = (int)__reduce_min_sync(0xffffffffu, (unsigned)mi);
        PIN(3);
        v0 = lds128(k.lw + so + SL + SL_V); v1 = lds128(k.lw + so + SL + SL_V + 4096);
#pragma unroll
        for (int i = NPX; i < NPF; i++) wo[i] = lds128(k.lw + w5 + R_WO + i * 4096);
        PIN(4);
        const float mo = -__int_as_float(mp >= 0 ? mp : mn) * SC_LOG2E;
        s0 = ex2(fmaf(s0, SC_LOG2E, mo)); s1 = ex2(fmaf(s1, SC_LOG2E, mo));
        sts32((((k.sp + z) >> 11) & 0x1fc) + (k.lw & 256) * 2 + (sb + R_PB), pack2(s0, s1));
        ls = k.lw < sb + 320 ? __float_as_uint((s0 + s1) + 4.f) : 0;
    }
    bar_sync(NB_P, 256);
    {
        const uint4 pp = lds128(k.lw + R_PB);
        PIN(5);
        const uint32_t pm = lds32(((k.lw + z) >> 2) + (sb - (sb >> 2) + R_PB + 512));
        PIN(5);
        sts32(sb + R_IL + (wz >> 1) * 16 + (wz & 1) * 4, __reduce_add_sync(0xffffffffu, ls) - 20u * 0x40800000u);
        float o0[4] = {0, 0, 0, 0}, o1[4] = {0, 0, 0, 0}, o2[4] = {0, 0, 0, 0};
        mma16(o0, v0.x, v0.y, v0.z, v0.w, pp.x, pp.y);
        mma16(o1, v1.x, v1.y, v1.z, v1.w, pp.z, pp.w);
        mma8(o2, vv[0], vv[1], pm);
        asm volatile("stmatrix.sync.aligned.m8n8.x2.trans.shared.b16 [%0],{%1,%2};" ::"r"(k.lw + wz * 256 + R_OB),
                     "r"(pack2(o0[0] + o1[0] + o2[0], o0[1] + o1[1] + o2[1])), "r"(pack2(o0[2] + o1[2] + o2[2], o0[3] + o1[3] + o2[3])) : "memory");
    }
    bar_sync(NB_O, 256);
    {
        float r0[4] = {0, 0, 0, 0}, r1[4] = {0, 0, 0, 0};
        uint4 b[4];
        b[0] = ldsm4(k.lw + R_OB);
        PIN(6);
        b[1] = ldsm4(k.lw + R_OB + 512);
        PIN(6);
#pragma unroll
        for (int m = NWO + NPF; m < 16; m++) if (((OL >> (2 * (15 - m))) & 3) == 3) wo[m] = lds128(k.lw + w5 + R_WO + (m - NWO) * 4096);
        const uint2 il = lds64(sb + R_IL + ((k.lw + z) & 48));
        PIN(6);
        float i0, i1;
        uint4* dst;
#pragma unroll
        for (int i = 0; i < 4; i++) {
            mma16(r0, wo[4 * i].x, wo[4 * i].y, wo[4 * i].z, wo[4 * i].w, b[i].x, b[i].y);
            mma16(r1, wo[4 * i + 1].x, wo[4 * i + 1].y, wo[4 * i + 1].z, wo[4 * i + 1].w, b[i].x, b[i].y);
            mma16(r0, wo[4 * i + 2].x, wo[4 * i + 2].y, wo[4 * i + 2].z, wo[4 * i + 2].w, b[i].z, b[i].w);
            mma16(r1, wo[4 * i + 3].x, wo[4 * i + 3].y, wo[4 * i + 3].z, wo[4 * i + 3].w, b[i].z, b[i].w);
            if (i < 2) b[i + 2] = ldsm4(k.lw + R_OB + (i + 2) * 512);
#pragma unroll
            for (int m = NWO + NPF; m < 16; m++) if (i < 3 && i == ((OL >> (2 * (15 - m))) & 3)) wo[m] = lds128(k.lw + w5 + R_WO + (m - NWO) * 4096);
            if (i == 1) { i0 = rcp(__uint2float_rn(il.x)) * 2097152.f; i1 = rcp(__uint2float_rn(il.y)) * 2097152.f; }
            if (i == 2) {
                const uint32_t po = k.sp + z;
                dst = xregion(X, 0) + k.po + ((po >> 20) ^ ((po & X) << 8));
                asm volatile("" : "+l"(dst));
            }
            PIN(7);
        }
        const uint32_t tag = (s + 1) & 1;
#pragma unroll
        for (int i = 0; i < 4; i++) { r0[i] *= (i & 1) ? i1 : i0; r1[i] *= (i & 1) ? i1 : i0; }
        st_rlx128(dst, (pack2(r0[0], r0[2]) & ~1u) | tag,
                  pack2(r1[0], r1[2]), pack2(r0[1], r0[3]), pack2(r1[1], r1[3]));
        bar_arrive(NB_PART + X, 288);
#pragma unroll
        for (int t = 0; t < V_PRE; t++) if (!((VMASK >> t) & 1)) wv[t] = lds128(k.lw + w5 + R_WV + t * 4096);
        arrive_if(sb + R_BAR + (RB_GO + 2 * X + (s & 1)) * 8, (k.sp + z) & 0x1ff0, X ? s + 1 < hi : s >= lo);
    }
}

__device__ __forceinline__ void rec_fetch(const Params& p, uint32_t sb, int head, uint32_t rank, int which, int dst) {
#pragma unroll 1
    for (int j = 0; j < 8; j++) tma2d(sb + dst + j * 8192, &p.tm[which], head * 128 + (j >> 2) * 64, rank * 256 + (j & 3) * 64, sb + R_BAR + RB_INIT * 8);
}

__device__ __forceinline__ void rec_weights(const Params& p, uint32_t sb, int head, uint32_t rank, int w) {
    const int lane = __shfl_sync(0xffffffffu, threadIdx.x & 31, threadIdx.x & 31),
        g = lane >> 2, c = lane & 3;
    const int t = w & 3, WG = w >> 2;
    uint32_t wq[16][4], wk[16][4];
    uint4 wo[16], wv[16];
    const uint32_t woff = sb + WG * 32768 + (((lane >> 4) << 3) + (lane & 7)) * 128 + (((2 * t + ((lane >> 3) & 1)) ^ (lane & 7)) << 4);
    const uint32_t lw = sb + lane * 16;
    PROF2(threadIdx.x == 0, 3501);
    {
        const __nv_bfloat16* wp = p.Wo + (size_t)(head * 128 + 2 * c) * 512 + rank * 256 + w * 32 + g * 4;
#pragma unroll
        for (int ks = 0; ks < 8; ks++) {
            const uint2 r0 = *(const uint2*)(wp + (ks * 16) * 512), r1 = *(const uint2*)(wp + (ks * 16 + 1) * 512);
            const uint2 r2 = *(const uint2*)(wp + (ks * 16 + 8) * 512), r3 = *(const uint2*)(wp + (ks * 16 + 9) * 512);
            const uint4 f[2] = {make_uint4(__byte_perm(r0.x, r1.x, 0x5410), __byte_perm(r0.x, r1.x, 0x7632), __byte_perm(r2.x, r3.x, 0x5410), __byte_perm(r2.x, r3.x, 0x7632)),
                                make_uint4(__byte_perm(r0.y, r1.y, 0x5410), __byte_perm(r0.y, r1.y, 0x7632), __byte_perm(r2.y, r3.y, 0x5410), __byte_perm(r2.y, r3.y, 0x7632))};
#pragma unroll
            for (int h = 0; h < 2; h++) {
                const int m = 2 * ks + h;
                wo[m] = f[h];
            }
        }
    }
    PROF2(threadIdx.x == 0, 3502);
    mbar_wait(sb + R_BAR + RB_INIT * 8, 0);
    PROF2(threadIdx.x == 0, 3503);
#pragma unroll
    for (int ks = 0; ks < 16; ks++) {
        uint4 a = ldsm4t(woff + R_STQ + ks * 2048), b = ldsm4t(woff + R_STK + ks * 2048);
        wq[ks][0] = a.x; wq[ks][1] = a.y; wq[ks][2] = a.z; wq[ks][3] = a.w;
        wk[ks][0] = b.x; wk[ks][1] = b.y; wk[ks][2] = b.z; wk[ks][3] = b.w;
    }
    bar_sync(NB_W, 256);
#pragma unroll
    for (int m = 0; m < 16; m++)
        if (m < NPF || m >= NPF + NWO) sts128(lw + w * 512 + R_WO + (m < NPF ? m : m - NWO) * 4096, wo[m].x, wo[m].y, wo[m].z, wo[m].w);
#pragma unroll
    for (int i = 0; i < 16; i++) {
        wv[i] = ldsm4t(woff + R_STV + i * 2048);
        if (!((VMASK >> i) & 1)) sts128(lw + w * 512 + R_WV + i * 4096, wv[i].x, wv[i].y, wv[i].z, wv[i].w);
    }
    fence_async_smem();
    PROF2(threadIdx.x == 0, 3504);
    __syncthreads();
    cluster_sync();
    PROF2(threadIdx.x == 0, 3505);
    RecW k;
    {
        const int r = (w * 4 + (lane >> 3)) * 2 + rank;
        const uint32_t sl = lds32(sb + R_SEL + r * 4);
        k.po = (w * 8 + rank) * 512 + (head >> 1) * 16 + (head & 1) * 4;
        k.sp = (((lane >> 3) * 1024 + (sl & 1) * 256 + (lane & 4) * 2 + (lane & 3)) << 20) + (((sl >> 1) ^ sl) & 1) + (lane & 7) * 656 + (lane >> 3) * 128 + w * 16 +
               ((g < 4 ? (w * 4 + c) * 4 + g : w * 4 + c) << 13);
    }
    k.dp = mapa(sb, rank ^ 1) - sb;
    k.lw = lw;
    asm volatile("" : "+r"(k.lw));
    k.w = w;
    const int e0 = (p.chains & 1) ? 64 : 0, o1 = (p.chains & 2) ? p.lag : 1000, nit = (p.chains & 2) ? p.lag + 64 : e0;
    const uint32_t zero = p.zero;
    int it = 0, X = e0 ? 0 : 1;
#pragma unroll 1
    while (it < nit) {
        rec_step(k, sb, X, X ? it - o1 : it, zero, o1, e0 - o1, o1 + 1 - X, wq, wk, wv, wo);
        if (X == 0 && it >= o1) X = 1; else { it++; X = it < e0 ? 0 : 1; }
    }
}

__device__ __forceinline__ uint32_t mism(uint32_t a, uint32_t b, uint32_t t) {
    uint32_t d; asm("lop3.b32 %0,%1,%2,%3,0x7e;" : "=r"(d) : "r"(a), "r"(b), "r"(t)); return d;
}
__device__ __forceinline__ uint32_t or3(uint32_t a, uint32_t b, uint32_t c) {
    uint32_t d; asm("lop3.b32 %0,%1,%2,%3,0xfe;" : "=r"(d) : "r"(a), "r"(b), "r"(c)); return d;
}
#define X4(j) "=r"(x[j].x), "=r"(x[j].y), "=r"(x[j].z), "=r"(x[j].w)
#define X32 X4(0), X4(1), X4(2), X4(3), X4(4), X4(5), X4(6), X4(7)
template <bool TWO>
__device__ __forceinline__ void poll8(uint4* x, const uint4* src, uint32_t tag) {
    if (TWO) asm volatile(
        "{.reg .pred p,q<8>; .reg .b32 n,m<8>; .reg .b128 t<8>; mov.u32 n,0; ld.relaxed.gpu.global.b128 t0,[%32+0]; ld.relaxed.gpu.global.b128 t1,[%32+512]; "
        "ld.relaxed.gpu.global.b128 t2,[%32+1024]; ld.relaxed.gpu.global.b128 t3,[%32+1536]; ld.relaxed.gpu.global.b128 t4,[%32+2048]; "
        "ld.relaxed.gpu.global.b128 t5,[%32+2560]; ld.relaxed.gpu.global.b128 t6,[%32+3072]; ld.relaxed.gpu.global.b128 t7,[%32+3584]; \nL%=: "
        "mov.b128 {%0,%1,%2,%3},t0; mov.b128 {%4,%5,%6,%7},t1; mov.b128 {%8,%9,%10,%11},t2; mov.b128 {%12,%13,%14,%15},t3; mov.b128 {%16,%17,%18,%19},t4; "
        "mov.b128 {%20,%21,%22,%23},t5; mov.b128 {%24,%25,%26,%27},t6; mov.b128 {%28,%29,%30,%31},t7; lop3.b32 m0,%0,%2,%33,0x7e; lop3.b32 m1,%4,%6,%33,0x7e; "
        "lop3.b32 m2,%8,%10,%33,0x7e; lop3.b32 m3,%12,%14,%33,0x7e; lop3.b32 m4,%16,%18,%33,0x7e; lop3.b32 m5,%20,%22,%33,0x7e; lop3.b32 m6,%24,%26,%33,0x7e; "
        "lop3.b32 m7,%28,%30,%33,0x7e; "
        "{.reg .b32 a,b; lop3.b32 a,m0,m1,m2,0xfe; lop3.b32 b,m3,m4,m5,0xfe; lop3.b32 a,a,m6,m7,0xfe; lop3.b32 a,a,b,1,0xa8; setp.ne.u32 p,a,0;} "
        "vote.sync.any.pred p,p,0xffffffff; @!p bra.uni D%=; and.b32 m0,m0,1; setp.ne.u32 q0,m0,0; and.b32 m1,m1,1; setp.ne.u32 q1,m1,0; "
        "and.b32 m2,m2,1; setp.ne.u32 q2,m2,0; and.b32 m3,m3,1; setp.ne.u32 q3,m3,0; and.b32 m4,m4,1; setp.ne.u32 q4,m4,0; "
        "and.b32 m5,m5,1; setp.ne.u32 q5,m5,0; and.b32 m6,m6,1; setp.ne.u32 q6,m6,0; and.b32 m7,m7,1; setp.ne.u32 q7,m7,0; "
        "@q0 ld.relaxed.gpu.global.b128 t0,[%32+0]; @q1 ld.relaxed.gpu.global.b128 t1,[%32+512]; @q2 ld.relaxed.gpu.global.b128 t2,[%32+1024]; "
        "@q3 ld.relaxed.gpu.global.b128 t3,[%32+1536]; @q4 ld.relaxed.gpu.global.b128 t4,[%32+2048]; @q5 ld.relaxed.gpu.global.b128 t5,[%32+2560]; "
        "@q6 ld.relaxed.gpu.global.b128 t6,[%32+3072]; @q7 ld.relaxed.gpu.global.b128 t7,[%32+3584]; "
        "add.u32 n,n,1; setp.lt.u32 p,n,2000000; @p bra.uni L%=; trap;\nD%=: } " : X32 : "l"(src), "r"(tag) : "memory");
    else asm volatile(
        "{.reg .pred p,q<8>; .reg .b32 n,m<8>; .reg .b128 t<8>; mov.u32 n,0; ld.relaxed.gpu.global.b128 t0,[%32+0]; ld.relaxed.gpu.global.b128 t1,[%32+512]; "
        "ld.relaxed.gpu.global.b128 t2,[%32+1024]; ld.relaxed.gpu.global.b128 t3,[%32+1536]; ld.relaxed.gpu.global.b128 t4,[%32+2048]; "
        "ld.relaxed.gpu.global.b128 t5,[%32+2560]; ld.relaxed.gpu.global.b128 t6,[%32+3072]; ld.relaxed.gpu.global.b128 t7,[%32+3584]; \nL%=: "
        "mov.b128 {%0,%1,%2,%3},t0; mov.b128 {%4,%5,%6,%7},t1; mov.b128 {%8,%9,%10,%11},t2; mov.b128 {%12,%13,%14,%15},t3; mov.b128 {%16,%17,%18,%19},t4; "
        "mov.b128 {%20,%21,%22,%23},t5; mov.b128 {%24,%25,%26,%27},t6; mov.b128 {%28,%29,%30,%31},t7; lop3.b32 m0,%0,%4,%33,0x7e; lop3.b32 m1,%8,%12,%33,0x7e; "
        "lop3.b32 m2,%16,%20,%33,0x7e; lop3.b32 m3,%24,%28,%33,0x7e; {.reg .b32 a; lop3.b32 a,m0,m1,m2,0xfe; lop3.b32 a,a,m3,1,0xa8; setp.ne.u32 p,a,0;} "
        "vote.sync.any.pred p,p,0xffffffff; @!p bra.uni D%=; lop3.b32 m0,%0,%33,1,0x28; setp.ne.u32 q0,m0,0; lop3.b32 m1,%4,%33,1,0x28; setp.ne.u32 q1,m1,0; "
        "lop3.b32 m2,%8,%33,1,0x28; setp.ne.u32 q2,m2,0; lop3.b32 m3,%12,%33,1,0x28; setp.ne.u32 q3,m3,0; lop3.b32 m4,%16,%33,1,0x28; setp.ne.u32 q4,m4,0; "
        "lop3.b32 m5,%20,%33,1,0x28; setp.ne.u32 q5,m5,0; lop3.b32 m6,%24,%33,1,0x28; setp.ne.u32 q6,m6,0; lop3.b32 m7,%28,%33,1,0x28; setp.ne.u32 q7,m7,0; "
        "@q0 ld.relaxed.gpu.global.b128 t0,[%32+0]; @q1 ld.relaxed.gpu.global.b128 t1,[%32+512]; @q2 ld.relaxed.gpu.global.b128 t2,[%32+1024]; "
        "@q3 ld.relaxed.gpu.global.b128 t3,[%32+1536]; @q4 ld.relaxed.gpu.global.b128 t4,[%32+2048]; @q5 ld.relaxed.gpu.global.b128 t5,[%32+2560]; "
        "@q6 ld.relaxed.gpu.global.b128 t6,[%32+3072]; @q7 ld.relaxed.gpu.global.b128 t7,[%32+3584]; "
        "add.u32 n,n,1; setp.lt.u32 p,n,2000000; @p bra.uni L%=; trap;\nD%=: } " : X32 : "l"(src), "r"(tag) : "memory");
}

__device__ __forceinline__ void rec_comm(const Params& p, uint32_t sb, int X, int head, uint32_t rank) {
    const int lane = threadIdx.x & 31, g = lane >> 2, c = lane & 3;
    const int me = head * 2 + rank;
    const uint32_t mb = sb + R_M + X * 4096 + lane * 16;
    uint4 x[8];
#pragma unroll
    for (int j = 0; j < 8; j++) x[j] = *(const uint4*)(p.mem0 + (lane & 7) * 512 + rank * 256 + (j * 4 + (lane >> 3)) * 8);
    const uint32_t sl = lds32(sb + R_SEL + me * 4);
    const uint32_t o1 = ((sl >> X) & 1) * 256 + (c >> 1) * 16 + (g >> 2) * 8 + (c & 1) * 4 + (g & 3);
    const uint32_t o2 = ((sl >> (2 + X)) & 1) * 256 + lane;
    const uint32_t offs = __shfl_sync(0xffffffffu, o1 + (o2 << 10) + ((((c >> 1) * 256 + head * 8 + (g & 3) * 2 + (c & 1)) * 2 + (g >> 2)) << 20), lane);
    const uint32_t one = (g & 1) ? 0x3f800000u : 0x00003f80u, selA = (g & 2) ? 0u : one, selB = (g & 2) ? one : 0u;
    const uint32_t qb = sb + R_BAR + (RB_QK + X * 8) * 8;
    if (lane < 8) mbar_expect(qb + lane * 8, 768);
    __syncwarp();
#pragma unroll
    for (int j = 0; j < 8; j++) sts128(mb + j * 512, x[j].x, x[j].y, x[j].z, x[j].w);
#pragma unroll 1
    for (int s = 0;; s++) {
        bar_arrive(NB_MFULL + X, 288);
        PROF(lane == 0, X * 64 + s);
        const uint32_t of = offs + (s & p.zero);
        const uint4* src = xregion(X, me) + (of & 1023);
        uint2* mdst = (uint2*)xregion(X, 64 + rank) + (of >> 20);
        asm volatile("" : "+l"(src), "+l"(mdst));
        bar_sync(NB_PART + X, 288);
        if (s == 63) break;
        const uint32_t tag = (s + 1) & 1;
        asm volatile("{.reg .pred p; setp.lt.u32 p,%0,%1; @p mbarrier.arrive.expect_tx.shared::cta.b64 _,[%0],768;}"
                     ::"r"(((mb + (s & p.zero)) >> 1) + (qb - ((sb + R_M + X * 4096) >> 1))), "r"(qb + 64) : "memory");
        spin(D1);
        poll8<false>(x, src, tag);
        float a[4][4];
#pragma unroll
        for (int j = 0; j < 8; j++) {
            if (j < 4) a[j][0] = a[j][1] = a[j][2] = a[j][3] = 0;
            mma16(a[j & 3], x[j].x, x[j].y, x[j].z, x[j].w, selA, selB);
        }
#pragma unroll
        for (int i = 0; i < 4; i++) a[0][i] = (a[0][i] + a[1][i]) + (a[2][i] + a[3][i]);
        const uint32_t m0 = (pack2(a[0][0], a[0][1]) & ~1u) | tag, m1 = pack2(a[0][2], a[0][3]);
        asm volatile("st.relaxed.gpu.global.b64 [%0],%1;" ::"l"(mdst), "l"(((uint64_t)m1 << 32) | m0) : "memory");
        src = xregion(X, 64 + rank) + ((of >> 10) & 1023);
        asm volatile("" : "+l"(src));
        spin(D2);
        poll8<true>(x, src, tag);
#pragma unroll
        for (int j = 0; j < 8; j++) sts128(mb + j * 512, x[j].x, x[j].y, x[j].z, x[j].w);
    }
}

template <int MT>
__device__ __forceinline__ void xattn(uint32_t l16, uint32_t l8, uint32_t os, int g, int c) {
    constexpr int NT = 3 + 2 * MT, XUN = XU;
    float S[NT][4];
#pragma unroll
    for (int i = 0; i < NT; i++) S[i][0] = S[i][1] = S[i][2] = S[i][3] = 0;
#pragma unroll XUN
    for (int ks = 0; ks < 8; ks++) {
        const uint4 q = lds128(l16 + SL_Q + ks * 512);
        const uint2 u = lds64(l8 + SL_KM + ks * 256);
        mma16(S[0], q.x, q.y, q.z, q.w, u.x, u.y);
#pragma unroll
        for (int m = 0; m <= MT; m++) {
            const uint4 kk = lds128(l16 + m * 4096 + ks * 512);
            mma16(S[1 + 2 * m], q.x, q.y, q.z, q.w, kk.x, kk.z); mma16(S[2 + 2 * m], q.x, q.y, q.z, q.w, kk.y, kk.w);
        }
    }
    const float NEG = -__int_as_float(0x7f800000);
    if (2 * c > g) { S[NT - 2][0] = NEG; S[NT - 1][2] = NEG; }
    if (2 * c + 1 > g) { S[NT - 2][1] = NEG; S[NT - 1][3] = NEG; }
    S[NT - 1][0] = S[NT - 1][1] = NEG;
    float m0 = fmaxf(S[0][0], S[0][1]), m1 = fmaxf(S[0][2], S[0][3]);
#pragma unroll
    for (int i = 1; i < NT; i++) { if (i < NT - 1) m0 = fmaxf(m0, fmaxf(S[i][0], S[i][1])); m1 = fmaxf(m1, fmaxf(S[i][2], S[i][3])); }
    m0 = fmaxf(m0, __shfl_xor_sync(0xffffffffu, m0, 1)); m1 = fmaxf(m1, __shfl_xor_sync(0xffffffffu, m1, 1));
    m0 = fmaxf(m0, __shfl_xor_sync(0xffffffffu, m0, 2)); m1 = fmaxf(m1, __shfl_xor_sync(0xffffffffu, m1, 2));
    m0 *= -SC_LOG2E; m1 *= -SC_LOG2E;
    float l0 = 0, l1 = 0;
#pragma unroll
    for (int i = 0; i < NT; i++) {
        if (i < NT - 1) { S[i][0] = ex2(fmaf(S[i][0], SC_LOG2E, m0)); S[i][1] = ex2(fmaf(S[i][1], SC_LOG2E, m0)); l0 += S[i][0] + S[i][1]; }
        S[i][2] = ex2(fmaf(S[i][2], SC_LOG2E, m1)); S[i][3] = ex2(fmaf(S[i][3], SC_LOG2E, m1)); l1 += S[i][2] + S[i][3];
    }
    l0 += __shfl_xor_sync(0xffffffffu, l0, 1); l1 += __shfl_xor_sync(0xffffffffu, l1, 1);
    l0 += __shfl_xor_sync(0xffffffffu, l0, 2); l1 += __shfl_xor_sync(0xffffffffu, l1, 2);
    uint2 vm = lds64(l8 + SL_VM);
    uint4 v[2];
#pragma unroll
    for (int m = 0; m <= MT; m++) v[m] = lds128(l16 + SL_V + m * 4096);
    l0 = rcp(l0); l1 = rcp(l1);
    uint32_t P[NT][2];
#pragma unroll
    for (int i = 0; i < NT; i++) { P[i][0] = i < NT - 1 ? pack2(S[i][0] * l0, S[i][1] * l0) : 0u; P[i][1] = pack2(S[i][2] * l1, S[i][3] * l1); }
#pragma unroll
    for (int et = 0; et < 8; et++) {
        float a[4] = {0, 0, 0, 0}, b[4] = {0, 0, 0, 0};
        const uint2 um = vm;
        const uint4 u[2] = {v[0], v[MT]};
        if (et < 7) {
            vm = lds64(l8 + SL_VM + et * 256 + 256);
#pragma unroll
            for (int m = 0; m <= MT; m++) v[m] = lds128(l16 + SL_V + m * 4096 + et * 512 + 512);
            PIN(11);
        }
        mma8(a, um.x, um.y, P[0][0]); mma8(b, um.x, um.y, P[0][1]);
#pragma unroll
        for (int m = 0; m <= MT; m++) {
            mma16(a, u[m].x, u[m].y, u[m].z, u[m].w, P[1 + 2 * m][0], P[2 + 2 * m][0]); mma16(b, u[m].x, u[m].y, u[m].z, u[m].w, P[1 + 2 * m][1], P[2 + 2 * m][1]);
        }
        asm volatile("stmatrix.sync.aligned.m8n8.x4.trans.shared.b16 [%0],{%1,%2,%3,%4};" ::"r"(os + (et >> 2) * 2048 + (et & 3) * 256),
                     "r"(pack2(a[0], a[1])), "r"(pack2(a[2], a[3])), "r"(pack2(b[0], b[1])), "r"(pack2(b[2], b[3])) : "memory");
    }
}

__device__ __forceinline__ void rec_tiles(uint32_t sb, int X, int head, uint32_t rank, int& nxt, int lim, int need) {
#pragma unroll 1
    while (nxt <= lim) {
        if ((nxt & 1) == 0) {
            unsigned v; int n = 0;
            while (true) {
                asm volatile("ld.relaxed.gpu.global.u32 %0,[%1];" : "=r"(v) : "l"(cnt_ptr(C_QKV + X * 32 + (nxt >> 1))) : "memory");
                if (__all_sync(0xffffffffu, v >= 2 * NQ)) break;
                if (nxt > need) return;
                if (++n > 3000000) __trap();
            }
        }
        if (elect()) {
            const uint32_t bar = sb + R_BAR + (RB_XFULL + X * 2 + (nxt & 1)) * 8, dst = sb + R_SL + (X * 2 + (nxt & 1)) * SLOT;
            const uint4* src = g_qkv + (size_t)((X * 64 + nxt) * 32 + head) * 1536;
            mbar_expect(bar, 20480);
            bulk_g2s_mc(dst + rank * 8192, src + 512 + rank * 512, 8192, bar, POL_LAST);
            bulk_g2s(dst + SL_Q, src + (rank ^ X) * 256, 4096, bar, POL_LAST);
        }
        __syncwarp();
        nxt++;
    }
}

__device__ __forceinline__ void rec_attn(const Params& p, uint32_t sb, int X, int head, uint32_t rank) {
    const int lane = __shfl_sync(0xffffffffu, threadIdx.x & 31, threadIdx.x & 31), g = lane >> 2, c = lane & 3;
    const int mt = rank ^ X;
    const uint32_t dp = mapa(sb, rank ^ 1) - sb;
    int nxt = 0;
    rec_tiles(sb, X, head, rank, nxt, 1, 0);
#pragma unroll 1
    for (int s = 0; s < 64; s++) {
        const uint32_t so = sb + R_SL + (X * 2 + (s & 1)) * SLOT;
        while (nxt <= min(s + 1, 63)) {
            uint32_t ok;
            asm volatile("{.reg .pred p; mbarrier.test_wait.parity.shared::cta.b64 p,[%1],%2; selp.u32 %0,1,0,p;}" : "=r"(ok) : "r"(sb + R_BAR + (RB_GO + X * 2 + (s & 1)) * 8), "r"((s >> 1) & 1) : "memory");
            if (__any_sync(0xffffffffu, ok)) break;
            rec_tiles(sb, X, head, rank, nxt, s + 1, -1);
        }
        mbar_wait(sb + R_BAR + (RB_GO + X * 2 + (s & 1)) * 8, (s >> 1) & 1);
        if (elect()) asm volatile("cp.async.bulk.wait_group.read 0;" ::: "memory");
        __syncwarp();
        const uint32_t os = sb + R_OS + X * 4096 + (lane >> 4) * 1024 + (lane & 15) * 16;
        if (mt) xattn<1>(so + lane * 16, so + lane * 8, os, g, c); else xattn<0>(so + lane * 16, so + lane * 8, os, g, c);
        fence_async_smem();
        __syncwarp();
        const uint32_t svb = sb + R_BAR + (RB_SV + X * 2 + (s & 1)) * 8;
        if (elect()) {
            mbar_arrive(svb); mbar_arrive_cluster(svb + dp);
            const uint64_t pol = POL_N;
#pragma unroll
            for (int kb = 0; kb < 2; kb++)
                asm volatile("cp.async.bulk.global.shared::cta.bulk_group.L2::cache_hint [%0],[%1],%2,%3;" ::"l"(g_o + ((X * 32 + (s >> 1)) * 64 + head * 2 + kb) * 512 + ((s & 1) * 4 + mt * 2) * 64),
                             "r"(sb + R_OS + X * 4096 + kb * 2048), "r"(2048), "l"(pol) : "memory");
            asm volatile("cp.async.bulk.commit_group;" ::: "memory");
        }
        __syncwarp();
        if ((s & 1) || X * s >= 60) {
            if (X && s < 60) { mbar_wait(svb, (s >> 1) & 1); rec_tiles(sb, X, head, rank, nxt, min(s + 2, 63), -1); }
            if (elect()) { asm volatile("cp.async.bulk.wait_group 0;" ::: "memory"); red_release(cnt_ptr(((s & 1) ? C_O : C_OH - 62 * 4) + (X * 32 + (s >> 1)) * 4 + (head >> 3)), 1); }
            __syncwarp();
        }
        rec_tiles(sb, X, head, rank, nxt, min(s + 1, 63), s + 1);
        mbar_wait(svb, (s >> 1) & 1);
        rec_tiles(sb, X, head, rank, nxt, min(s + 2, 63), -1);
    }
}

__device__ __forceinline__ uint32_t timed_clear(unsigned* r, int lane) {
    uint32_t v = 0;
    const uint32_t t0 = clk32();
    asm volatile("{.reg .pred p; setp.eq.u32 p,%2,0; @p atom.relaxed.gpu.global.exch.b32 %0,[%1],0;}" : "+r"(v) : "l"(r), "r"(lane) : "memory");
    v = __shfl_sync(0xffffffffu, v, 0);
    asm volatile("{.reg .pred p; setp.eq.u32 p,%0,0x5a5a5a5b; @p nanosleep.u32 1;}" ::"r"(v) : "memory");
    return clk32() - t0;
}
__device__ __forceinline__ void rec_slots(int me, int w) {
    const int lane = threadIdx.x & 31;
    uint4* r = xregion(w & 1, (w & 2) ? 64 + (me & 1) : me) + ((w & 2) ? (me >> 1) * 8 : 0);
#pragma unroll 1
    for (int i = lane; i < ((w & 2) ? 8 : 256); i += 32) r[i] = r[i + 256] = make_uint4(0, 0, 0, 0);
    __syncwarp();
    uint32_t b0 = ~0u, b1 = ~0u;
#pragma unroll 1
    for (int i = 0; i < NPRB; i++) { b0 = min(b0, timed_clear((unsigned*)r, lane)); b1 = min(b1, timed_clear((unsigned*)(r + 256), lane)); }
    if (lane == 0) ((uint8_t*)g_sel)[me * 4 + w] = (b1 < b0) << w;
}

__device__ __forceinline__ void rec_init(uint32_t sb) {
    const uint32_t b = sb + R_BAR;
    const int i = threadIdx.x & 31;
    mbar_init(b + i * 8, i >= RB_SV ? 2 : 1);
    if (i == RB_INIT) mbar_expect(b + RB_INIT * 8, 196608);
    asm volatile("fence.mbarrier_init.release.cluster;" ::: "memory");
}
constexpr int G_BAR = B_BAR;
enum { GB_FULL = 0  , GB_EMPTY = 8  , GB_RS = 16, GB_SS = 17, GB_LAG = 18, GB_FREE = 19, GB_DONE = 20  , GB_N = 24 };
constexpr int Q_PRE = 8;
constexpr int NQRS = 2 * NQ - 64;
__device__ __forceinline__ void gemm_init(uint32_t sb, bool op) {
    const int i = threadIdx.x & 31;
    if (i < GB_N) mbar_init(sb + G_BAR + i * 8, i >= GB_DONE ? 4 : i == GB_FREE ? 8 : (i >= GB_EMPTY && i < GB_RS) ? 2 : 1);
    if (i == GB_RS) mbar_expect(sb + G_BAR + i * 8, op ? 131072 : 98304);
    if (i == GB_SS) mbar_expect(sb + G_BAR + i * 8, op ? 131072 : 163840);
    asm volatile("fence.mbarrier_init.release.cluster;" ::: "memory");
}
__device__ __forceinline__ int qkv_blk(int id, int j) { return NQRS * 4 + id * 10 + j; }
__device__ __forceinline__ void qkv_fetch(const Params& p, uint32_t sb, int id, int j0, int j1) {
#pragma unroll 1
    for (int j = j0 * 2; j < j1 * 2; j++) {
        const int blk = min(qkv_blk(id, j >> 1), 511);
        tma2d(sb + j * 8192, &p.tn[blk >> 8], (blk & 255) * 16, (j & 1) * 256, sb + G_BAR + GB_SS * 8);
    }
}
__device__ __forceinline__ void qkv_stage(const Params& p, uint32_t dst, uint32_t bar, int id, int k0, int nk) {
#pragma unroll 1
    for (int j = 0; j < 2 * nk; j++) {
        const int u = id * 2 + (j >= nk);
        tma2d(dst + j * 8192, &p.tm[u < 64 ? 2 : 0], (u & 63) * 64, (k0 + (j >= nk ? j - nk : j)) * 64, bar);
    }
}
__device__ __forceinline__ void op_fetch(const Params& p, uint32_t sb, int id, int half) {
#pragma unroll 1
    for (int j = 0; j < 16; j++) tma2d(sb + j * 8192, &p.tm[4], ((id * 2 + (j >> 3)) & 7) * 64, (id >> 2) * 1024 + (j & 7) * 128 + half * 64, sb + G_BAR + (GB_RS + half) * 8);
}
template <bool OP>
__device__ __forceinline__ void gemm_producer(const Params& p, uint32_t sb, int id) {
    constexpr int NS = OP ? 6 : 8, SB = OP ? 16384 : 8192, RB = OP ? 131072 : 163840;
    if (!elect()) return;
    mbar_wait(sb + G_BAR + GB_FREE * 8, 0);
    if (OP) op_fetch(p, sb, id, 1);
    else {
        mbar_expect(sb + G_BAR + GB_RS * 8, 32768);
        qkv_stage(p, sb + 196608, sb + G_BAR + GB_RS * 8, id, 6, 2);
        qkv_fetch(p, sb, id, Q_PRE, 10);
        mbar_wait(sb + G_BAR + GB_FREE * 8, 1);
    }
    wait_cnt(g_gate, lds32(sb + S_GATE));
    int st = 0; uint32_t ph = 1;
#pragma unroll 1
    for (int n = 0; n < p.nl[OP]; n++) {
        const int e = p.list[OP][n];
        wait_cnt(OP ? cnt_ptr(C_O + e * 4 + (id >> 2)) : cnt_ptr(C_XN + e), 16);
        PROF(true, 1024 + n * 4);
        const uint4* src = OP ? g_o + (e * 64 + (id >> 2) * 16) * 512 : g_xn + e * 4096;
#pragma unroll 1
        for (int s = 0; s < 8; s++) {
            mbar_wait(sb + G_BAR + (GB_EMPTY + st) * 8, ph);
            mbar_expect(sb + G_BAR + (GB_FULL + st) * 8, SB);
            bulk_g2s(sb + RB + st * SB, src + s * (SB / 16), SB, sb + G_BAR + (GB_FULL + st) * 8, POL_N);
            if (++st == NS) { st = 0; ph ^= 1; }
        }
    }
#pragma unroll 1
    for (int h = p.h0; OP && h < 128; h++) {
        wait_cnt(cnt_ptr(((h & 1) ? C_O : C_OH - 62 * 4) + (h >> 1) * 4 + (id >> 2)), 16);
        PROF(h & 1, 1024 + (h >> 1) * 4);
        const uint4* src = g_o + ((h >> 1) * 64 + (id >> 2) * 16) * 512 + (h & 1) * 256;
#pragma unroll 1
        for (int s = 0; s < 8; s++) {
            mbar_wait(sb + G_BAR + (GB_EMPTY + st) * 8, ph);
            mbar_expect(sb + G_BAR + (GB_FULL + st) * 8, 8192);
            bulk_g2s(sb + RB + st * SB, src + s * 1024, 4096, sb + G_BAR + (GB_FULL + st) * 8, POL_N);
            bulk_g2s(sb + RB + st * SB + 8192, src + s * 1024 + 512, 4096, sb + G_BAR + (GB_FULL + st) * 8, POL_N);
            if (++st == NS) { st = 0; ph ^= 1; }
        }
    }
}
__device__ __forceinline__ void qkv_release(const Params& p, uint32_t sb) {
    if (!elect()) return;
#pragma unroll 1
    for (int n = 0; n < 2 * p.nl[0]; n++) {
        const int e = p.list[0][n >> 1];
        mbar_wait(sb + G_BAR + (GB_DONE + (n & 3)) * 8, (n >> 2) & 1);
        red_release(cnt_ptr(C_QKV + e), 1);
        PROF(n & 1, 1024 + (n >> 1) * 4 + 3);
    }
}
__device__ __forceinline__ void op_permute(uint32_t sb) {
#pragma unroll 2
    for (int i = threadIdx.x; i < 4096; i += 256) {
        const uint32_t a = sb + i * 32 + ((i >> 2) & 1) * 16, b = a ^ 16;
        const uint4 x = lds128(a), y = lds128(b);
        sts128(a, __byte_perm(x.x, x.y, 0x5410), __byte_perm(x.z, x.w, 0x5410), __byte_perm(y.x, y.y, 0x5410), __byte_perm(y.z, y.w, 0x5410));
        sts128(b, __byte_perm(x.x, x.y, 0x7632), __byte_perm(x.z, x.w, 0x7632), __byte_perm(y.x, y.y, 0x7632), __byte_perm(y.z, y.w, 0x7632));
    }
    fence_async_smem();
    bar_sync(1, 256);
}
template <bool OP>
__device__ __forceinline__ void gemm_consumer(const Params& p, uint32_t sb, int id, int w) {
    constexpr int NS = OP ? 6 : 8, SB = OP ? 16384 : 8192, RB = OP ? 131072 : 163840;
    const int lane = threadIdx.x & 31, wg = w >> 2, t = w & 3, u = id * 2 + wg;
    uint32_t a[128];
    mbar_wait(sb + G_BAR + GB_RS * 8, 0);
    PROF2(threadIdx.x == 0, 3501);
    if (OP) op_permute(sb);
    const uint32_t wo = sb + (((lane >> 4) << 3) + (lane & 7)) * 128 + (((2 * t + ((lane >> 3) & 1)) ^ (lane & 7)) << 4);
#pragma unroll
    for (int ks = 0; ks < 32; ks++) {
        const uint4 v = ldsm4t(wo + ks * 2048 + (OP ? wg * 65536 : ks < 24 ? 131072 + wg * 49152 : 196608 - 49152 + wg * 16384));
        a[ks * 4] = v.x; a[ks * 4 + 1] = v.y; a[ks * 4 + 2] = v.z; a[ks * 4 + 3] = v.w;
        if (ks == 31 || (!OP && ks == 23)) {
            fence_async_smem();
            __syncwarp();
            if (lane == 0) mbar_arrive(sb + G_BAR + GB_FREE * 8);
            if (ks == 23) mbar_wait(sb + G_BAR + GB_RS * 8, 1);
        }
    }
    PROF2(threadIdx.x == 0, 3502);
    mbar_wait(sb + G_BAR + GB_SS * 8, 0);
    if (OP) op_permute(sb);
    PROF2(threadIdx.x == 0, 3503);
    const uint32_t tag = OP ? lds32(sb + S_TAG) : 0;
    float c0[32], c1[OP ? 32 : 40];
    int st = 0; uint32_t ph = 0;
    const bool el = (threadIdx.x & 127) == 0;
#pragma unroll 1
    for (int n = 0; n < p.nl[OP]; n++) {
        int prev = 0;
        const uint32_t wb = sb + wg * (OP ? 65536 : 81920) + (n & p.zero);
        const uint64_t dw = OP ? mkdesc(wb, 0, 1024, 1) : mkdesc(wb, 16384, 256, 3);
        if ((!OP || OLAG) && wg) mbar_wait(sb + G_BAR + GB_LAG * 8, n & 1);
#pragma unroll
        for (int s = 0; s < 8; s++) {
            mbar_wait(sb + G_BAR + (GB_FULL + st) * 8, ph);
            const uint64_t dx = mkdesc(sb + RB + st * SB, 128, 1024, 0);
            wg_fence();
#pragma unroll
            for (int kk = 0; kk < 4; kk++) {
                const int ks = s * 4 + kk;
                if (ks == 0) { wgmma64_rs<0>(c0, a, dx); if (OP) wgmma64_ta<0>(c1, dw, dx + 512); else wgmma80_tb<0>(c1, dx, dw); }
                else { wgmma64_rs<1>(c0, a + ks * 4, dx + kk * 16); if (OP) wgmma64_ta<1>(c1, dw + ks * 128, dx + 512 + kk * 16); else wgmma80_tb<1>(c1, dx + kk * 16, dw + ks * 32); }
            }
            wg_commit();
            if (s) {
                wg_wait<1>();
                if (el) { mbar_arrive(sb + G_BAR + (GB_EMPTY + prev) * 8); if (s == (OP ? OLAG : QLAG) && !wg) mbar_arrive(sb + G_BAR + GB_LAG * 8); }
            }
            prev = st;
            if (++st == NS) { st = 0; ph ^= 1; }
        }
        const int e = p.list[OP][n];
        wg_wait<0>();
        if (el) mbar_arrive(sb + G_BAR + (GB_EMPTY + prev) * 8);
        PROF(threadIdx.x == 128, 1024 + n * 4 + 1);
        if (OP) {
            uint4* dst = g_pp + (e * 4 + (id >> 2)) * 4096 + ((u & 7) * 32 + t * 8) * 16 + (lane >> 2) * 16 + (lane & 3);
#pragma unroll
            for (int j = 0; j < 4; j++) {
                const float* x = c0 + j * 8; const float* y = c1 + j * 8;
                st_rlx128(dst + j * 4, (pack2(x[0] + y[0], x[1] + y[1]) & ~1u) | tag, pack2(x[2] + y[2], x[3] + y[3]), (pack2(x[4] + y[4], x[5] + y[5]) & ~1u) | tag, pack2(x[6] + y[6], x[7] + y[7]));
            }
            if (lane == 0) red_relaxed(cnt_ptr(C_PP + e * 8 + (u & 7)), 1);
            PROF(threadIdx.x == 128, 1024 + n * 4 + 3);
        } else {
            uint4* dst = g_qkv + (size_t)e * 2 * 32 * 1536 + lane;
            const uint64_t pol = POL_N;
#pragma unroll
            for (int j = 0; j < 4; j++) {
                const float* x = c0 + j * 8;
                uint4 v = make_uint4(pack2(x[0], x[1]), pack2(x[2], x[3]), pack2(x[4], x[5]), pack2(x[6], x[7]));
                if (u >= 64) v = make_uint4(movm(v.x), movm(v.z), movm(v.y), movm(v.w));
                stg128(dst + (((j >> 1) * 32 + ((u & 63) >> 1)) * 1536 + (u < 64 ? 1024 : 0) + (j & 1) * 256 + ((u & 1) * 4 + t) * 32), v, pol);
            }
#pragma unroll
            for (int j = 0; j < 5; j++) {
                const float* x = c1 + (OP ? 0 : j * 8);
                const int blk = qkv_blk(id, wg * 5 + j);
                if (blk < 512) stg128(dst + (((t >> 1) * 32 + ((blk >> 3) & 31)) * 1536 + (blk >> 8) * 512 + (t & 1) * 256 + (blk & 7) * 32),
                                      make_uint4(pack2(x[0], x[1]), pack2(x[2], x[3]), pack2(x[4], x[5]), pack2(x[6], x[7])), pol);
            }
        }
        __syncwarp();
        if (!OP && lane == 0) mbar_arrive(sb + G_BAR + (GB_DONE + (n & 1) * 2 + wg) * 8);
        PROF(threadIdx.x == 128, 1024 + n * 4 + 2);
    }
#pragma unroll 1
    for (int h = p.h0; OP && h < 128; h++) {
        int prev = 0;
        const uint64_t dw = mkdesc(sb + wg * 65536 + (h & p.zero), 0, 1024, 1);
#pragma unroll
        for (int s = 0; s < 8; s++) {
            mbar_wait(sb + G_BAR + (GB_FULL + st) * 8, ph);
            const uint64_t dx = mkdesc(sb + RB + st * SB, 128, 1024, 0);
            wg_fence();
#pragma unroll
            for (int kk = 0; kk < 4; kk++) {
                const int ks = s * 4 + kk;
                if (ks == 0) { wgmma32_rs<0>(c0, a, dx); wgmma32_ta<0>(c1, dw, dx + 512); }
                else { wgmma32_rs<1>(c0, a + ks * 4, dx + kk * 16); wgmma32_ta<1>(c1, dw + ks * 128, dx + 512 + kk * 16); }
            }
            wg_commit();
            if (s) { wg_wait<1>(); if (el) mbar_arrive(sb + G_BAR + (GB_EMPTY + prev) * 8); }
            prev = st;
            if (++st == NS) { st = 0; ph ^= 1; }
        }
        uint4* dst = g_pp + ((h >> 1) * 4 + (id >> 2)) * 4096 + ((u & 7) * 32 + t * 8) * 16 + (lane >> 2) * 16 + (lane & 3) + (h & 1) * 8;
        wg_wait<0>();
        if (el) mbar_arrive(sb + G_BAR + (GB_EMPTY + prev) * 8);
#pragma unroll
        for (int j = 0; j < 2; j++) {
            const float* x = c0 + j * 8; const float* y = c1 + j * 8;
            st_rlx128(dst + j * 4, (pack2(x[0] + y[0], x[1] + y[1]) & ~1u) | tag, pack2(x[2] + y[2], x[3] + y[3]), (pack2(x[4] + y[4], x[5] + y[5]) & ~1u) | tag, pack2(x[6] + y[6], x[7] + y[7]));
        }
        if (lane == 0 && (h & 1)) red_relaxed(cnt_ptr(C_PP + (h >> 1) * 8 + (u & 7)), 1);
        PROF(threadIdx.x == 128 && (h & 1), 1024 + (h >> 1) * 4 + 3);
        __syncwarp();
    }
}

template <int NP, bool MMA>
__device__ __forceinline__ void sum_partials(float* x, const uint2* src, const uint32_t* r0, const uint32_t* r1, uint32_t idm, uint32_t tag, bool on) {
    uint2 v[4][NP];
    int n = 0;
    while (true) {
        uint32_t bad = 0;
#pragma unroll
        for (int s = 0; s < 4; s++)
#pragma unroll
            for (int i = 0; i < NP; i++)
                asm volatile("{.reg .pred p; .reg .b64 t; setp.ne.u32 p,%4,0; mov.b64 t,0; @p ld.relaxed.gpu.global.L2::cache_hint.b64 t,[%2],%3; mov.b64 {%0,%1},t;}"
                             : "=r"(v[s][i].x), "=r"(v[s][i].y) : "l"(src + s * 8192 + i * 32), "l"(POL_LAST), "r"((uint32_t)on) : "memory");
#pragma unroll
        for (int s = 0; s < 4; s++) bad = or3(bad, mism(v[s][0].x, v[s][1].x, tag), mism(v[s][NP - 2].x, v[s][NP - 1].x, tag));
        if (!__any_sync(0xffffffffu, (bad & 1) && on)) break;
        if (++n > 2000000) __trap();
    }
#pragma unroll
    for (int i = 0; i < NP; i++) {
        uint32_t a, b;
        if (MMA) {
            float t[4] = {0, 0, 0, 0};
            mma16(t, v[0][i].x, v[0][i].y, v[1][i].x, v[1][i].y, idm, idm); mma16(t, v[2][i].x, v[2][i].y, v[3][i].x, v[3][i].y, idm, idm);
            a = pack2(t[0], t[2]); b = pack2(t[1], t[3]);
        } else {
            a = pack2((blo(v[0][i].x) + blo(v[1][i].x)) + (blo(v[2][i].x) + blo(v[3][i].x)), (blo(v[0][i].y) + blo(v[1][i].y)) + (blo(v[2][i].y) + blo(v[3][i].y)));
            b = pack2((bhi(v[0][i].x) + bhi(v[1][i].x)) + (bhi(v[2][i].x) + bhi(v[3][i].x)), (bhi(v[0][i].y) + bhi(v[1][i].y)) + (bhi(v[2][i].y) + bhi(v[3][i].y)));
        }
        const uint32_t s0 = hadd2(a, r0[i]), s1 = hadd2(b, r1[i]);
        x[4 * i] = blo(s0); x[4 * i + 2] = bhi(s0); x[4 * i + 1] = blo(s1); x[4 * i + 3] = bhi(s1);
    }
}
__device__ __forceinline__ const uint2* pp_src(int e, int tile, int lane) { return (const uint2*)g_pp + e * 32768 + tile * 128 + (lane >> 3) * 8 + (lane & 3) * 2 + ((lane >> 2) & 1); }

__device__ __forceinline__ void fin_warp(const Params& p, uint32_t sb, int id0) {
    wait_slow_warp(g_gate, lds32(sb + S_GATE));
#pragma unroll 1
    for (int e = id0 < 2 * NQ ? 32 : FJ; e < 64; e++)
#pragma unroll 1
    for (int id = id0; id < (e < FJ ? 128 : id0 + 1); id += 2 * NQ) {
        const int grp = (id & ~3) + (threadIdx.x & 3), tp = (id & 3) * 8 + ((threadIdx.x & 31) >> 2);
        wait_slow_warp(cnt_ptr(C_XN + e), 16);
        const uint4 r = ldcg128(g_x + ((128 + grp) * XP + (e - 32) * 32 + tp));
        if (e < 63) wait_slow_warp(cnt_ptr(C_PP + e * 8 + (id >> 4)), 16); else wait_slow_warp(cnt_ptr(C_O + 63 * 4), 16);
        wait_flag_warp(cnt_ptr(C_PP + e * 8 + (id >> 4)), 16);
        const uint32_t a[2] = {r.x, r.y}, b[2] = {r.z, r.w};
        float x[8];
        sum_partials<2, false>(x, pp_src(e, 0, tp) + grp * 64, a, b, 0, lds32(sb + S_TAG), true);
        uint2* dst = (uint2*)p.out + ((e - 32) * 64 + tp * 2) * 128 + grp;
#pragma unroll
        for (int t = 0; t < 2; t++)
            dst[t * 128] = make_uint2(__byte_perm(__float_as_uint(x[t]), __float_as_uint(x[2 + t]), 0x7632), __byte_perm(__float_as_uint(x[4 + t]), __float_as_uint(x[6 + t]), 0x7632));
        PROF((threadIdx.x & 31) == 0, 1536 + e);
    }
}

constexpr int PROW = 272, UROW = 2560, UPRE = 512;
constexpr int C_UR = 0  , C_TB = 65536  , C_BG = C_TB + 51200,
              CB_M = 7168, CB_U = CB_M + 1792, CB_BIG = CB_U + 2048, C_ST = C_BG + 8 * CB_BIG  ;
static_assert(C_ST + 4736 <= B_BAR, "smem map");
enum { CB_TB = 0, CB_UF = 1  , CB_CF = 5  , CB_LD = 9   };
__device__ __forceinline__ void conv_init(uint32_t sb, bool spare) {
    const int i = threadIdx.x & 31;
    mbar_init(sb + B_BAR + i * 8, (i >= CB_UF && i < CB_CF && !spare) ? 2 : 1);
    if (i == CB_TB && !spare) mbar_expect(sb + B_BAR + i * 8, 51200);
    asm volatile("fence.mbarrier_init.release.cluster;" ::: "memory");
}
__device__ __forceinline__ void mma_q(float* c, const uint32_t* a, const uint4& q) {
    mma16(c, a[0], a[1], a[2], a[3], q.x, q.y); mma16(c, a[4], a[5], a[6], a[7], q.z, q.w);
}
__device__ __forceinline__ uint2 ld_acc(const uint2* p, bool on) {
    uint2 v = make_uint2(0, 0);
    asm volatile("{.reg .pred p; setp.ne.u32 p,%3,0; @p ld.global.cg.v2.u32 {%0,%1},[%2];}" : "+r"(v.x), "+r"(v.y) : "l"(p), "r"((uint32_t)on) : "memory");
    return v;
}
__device__ __forceinline__ void add_acc(float* c, uint2 v) { c[0] += blo(v.x); c[1] += bhi(v.x); c[2] += blo(v.y); c[3] += bhi(v.y); }
__device__ __forceinline__ void st_acc(uint2* p, const float* c) { *p = make_uint2(pack2(c[0], c[1]), pack2(c[2], c[3])); }
__device__ __forceinline__ float sum8(const uint4* v, int k) {
#define VK(i) __uint_as_float(k == 0 ? v[i].x : k == 1 ? v[i].y : k == 2 ? v[i].z : v[i].w)
    return ((VK(0) + VK(1)) + (VK(2) + VK(3))) + ((VK(4) + VK(5)) + (VK(6) + VK(7)));
}
template <int XW>
__device__ __forceinline__ void stats_send(uint32_t l16, const float* x, uint4* gs, int q, int w) {
    float s0 = 0, s1 = 0, m0 = 0, m1 = 0;
#pragma unroll
    for (int i = 0; i < 8; i++) { s0 += x[2 * i]; s1 += x[2 * i + 1]; m0 = fmaf(x[2 * i], x[2 * i], m0); m1 = fmaf(x[2 * i + 1], x[2 * i + 1], m1); }
    sts128(l16 + C_ST + w * 512, __float_as_uint(s0), __float_as_uint(m0), __float_as_uint(s1), __float_as_uint(m1));
    if (w == XW) {
        bar_sync(2, 256);
        uint4 v[8];
#pragma unroll
        for (int i = 0; i < 8; i++) v[i] = lds128(l16 + C_ST + i * 512);
        st_rlx128(gs + q * 32, __float_as_uint(sum8(v, 0)), __float_as_uint(sum8(v, 1)) & 0x7fffffffu, __float_as_uint(sum8(v, 2)), __float_as_uint(sum8(v, 3)));
    } else bar_arrive(2, 256);
}
template <int XW>
__device__ __forceinline__ float4 stats_recv(uint32_t l16, const uint4* gs, int w) {
    if (w == XW) {
        uint4 v[8];
        int n = 0;
        while (true) {
            uint32_t bad = 0;
#pragma unroll
            for (int i = 0; i < 8; i++) v[i] = ld_rlx128(gs + i * 32);
#pragma unroll
            for (int i = 0; i < 8; i++) bad |= v[i].y;
            if (!__any_sync(0xffffffffu, bad >> 31)) break;
            if (++n > 2000000) __trap();
        }
        const float s0 = sum8(v, 0) * (1.f / 512.f), s1 = sum8(v, 2) * (1.f / 512.f);
        const float2 l0 = ln_finish(s0, fmaxf(fmaf(sum8(v, 1), 1.f / 512.f, -s0 * s0), 0.f)), l1 = ln_finish(s1, fmaxf(fmaf(sum8(v, 3), 1.f / 512.f, -s1 * s1), 0.f));
        sts128(l16 + C_ST + 4096, __float_as_uint(l0.x), __float_as_uint(rcp(l0.y)), __float_as_uint(l1.x), __float_as_uint(rcp(l1.y)));
    }
    bar_sync(3, 256);
    const uint4 r = lds128(l16 + C_ST + 4096);
    return make_float4(__uint_as_float(r.x), __uint_as_float(r.y), __uint_as_float(r.z), __uint_as_float(r.w));
}

__device__ __forceinline__ void conv_near(float (*acc)[4], uint32_t ta, uint32_t qa) {
    uint32_t a[9][8];
    uint4 x[9];
#pragma unroll
    for (int k = 0; k < 9; k++) {
        if (k < 8) {
            x[k] = ldsm4(qa + k * 1024);
#pragma unroll
            for (int j = 0; j < 8; j++) a[k][j] = lds32(ta + k * 800 + j * 32);
        }
        if (k) mma_q(acc[k - 1], a[k - 1], x[k - 1]);
        PIN(13);
    }
}
template <int K0>
__device__ __forceinline__ void conv_pair(float (*acc)[4], float (*pend)[4], uint32_t ta, uint32_t q0, uint32_t q1, uint32_t q2) {
    uint32_t a[9][8];
    uint4 x[9], y[5];
#pragma unroll
    for (int n = 0; n < 9; n++) {
        if (n < 8) {
            const int k = K0 + (n >> 1);
            if (!(n & 1)) y[n >> 1] = ldsm4(q1 + k * 1024);
            x[n] = ldsm4(((n & 1) ? q0 : q2) + k * 1024);
#pragma unroll
            for (int j = 0; j < 8; j++) a[n][j] = lds32(ta + 256 + (n & 1) * 256 + k * 800 + j * 32);
        }
        if (n == 0) {
#pragma unroll
            for (int i = 0; i < 16; i++) { acc[4 - K0 + (i >> 2)][i & 3] += pend[i >> 2][i & 3]; pend[i >> 2][i & 3] = 0; }
        } else {
            const int m = n - 1, i = m >> 1;
            mma_q(acc[K0 + i], a[m], (m & 1) ? x[m] : y[i]); mma_q(pend[i], a[m], (m & 1) ? y[i] : x[m]);
        }
        PIN(13);
    }
}

__device__ __forceinline__ void conv_tile(const Params& p, uint32_t sb, int q, int w) {
    const int lane = __shfl_sync(0xffffffffu, threadIdx.x & 31, threadIdx.x & 31), g = lane >> 2, c = lane & 3, tile = q * 8 + w;
    const uint32_t l16 = sb + lane * 16;
#pragma unroll
    for (int i = 0; i < 16; i++) sts128(l16 + C_UR + w * 8192 + i * 512, 0, 0, 0, 0);
    wait_slow_warp(g_gate, lds32(sb + S_GATE));
    if (lane < 8) bulk_g2s(sb + C_TB + (w * 8 + lane) * 800, g_P + (tile * 8 + lane) * PROW + 72, 800, sb + B_BAR + CB_TB * 8, POL_N);
    uint32_t A[8][8];
#pragma unroll
    for (int k = 0; k < 8; k++)
#pragma unroll
        for (int j = 0; j < 8; j++) A[k][j] = __ldcg(g_P + (tile * 8 + k) * PROW + 16 + 8 * j + g - 2 * c);
    if (lane == 0) { const uint4 d = __ldg((const uint4*)p.Dskip + tile); sts128(sb + C_ST + 4608 + w * 16, d.x, d.y, d.z, d.w); }
    float acc[8][4], pend[4][4];
#pragma unroll
    for (int k = 0; k < 8; k++) acc[k][0] = acc[k][1] = acc[k][2] = acc[k][3] = pend[k & 3][k >> 2] = pend[k & 3][2 + (k >> 2)] = 0;
    const uint32_t row = sb + C_UR + w * 8192, ta = sb + C_TB + w * 6400 + (8 + g - 2 * c) * 4, qo = (lane & 7) * 16 - (lane >> 3) * 32;
    bar_sync(4, 384);
    mbar_wait(sb + B_BAR + CB_TB * 8, 0);
#pragma unroll 1
    for (int b = -2; b < 32; b++) {
        const int lz = lane + (b & p.zero);
        const bool on = b >= 0;
        uint4 r0 = make_uint4(0, 0, 0, 0), r1 = r0;
        asm volatile("{.reg .pred p; setp.ge.s32 p,%9,0; @p ld.global.cg.v4.u32 {%0,%1,%2,%3},[%8]; @p ld.global.cg.v4.u32 {%4,%5,%6,%7},[%8+%10];}"
                     : "+r"(r0.x), "+r"(r0.y), "+r"(r0.z), "+r"(r0.w), "+r"(r1.x), "+r"(r1.y), "+r"(r1.z), "+r"(r1.w) : "l"(g_x + (tile * 2 * XP + b * 32 + lz)), "r"(b), "n"(XP * 16) : "memory");
        const uint32_t q1 = row + ((qo + (b - 1) * 128) & 1023);
        if ((NTOP >> w) & 1) conv_near(acc, ta, q1);
        PROF2(threadIdx.x == 0 && on, 2048 + b * 8);
        const uint2* pps = pp_src(b, tile, lz);
        asm volatile("" : "+l"(pps));
        const uint32_t tag = lds32(sb + S_TAG);
        wait_flag_warp(cnt_ptr(C_PP + b * 8 + q), on ? 16 : 0);
        PROF2(threadIdx.x == 0 && on, 2048 + b * 8 + 1);
        float x[16];
        {
            const uint32_t a[4] = {r0.x, r0.y, r1.x, r1.y}, bb[4] = {r0.z, r0.w, r1.z, r1.w};
            sum_partials<4, true>(x, pps, a, bb, (2 * (lz & 3) == lz >> 2) ? 0x00003f80u : (2 * (lz & 3) + 1 == lz >> 2) ? 0x3f800000u : 0u, tag, on);
        }
        stats_send<0>(l16, x, g_st + (b + 2) * 256 + lz, q, w);
        {
            PROF2(threadIdx.x == 0 && on, 2048 + b * 8 + 2);
            if (on) mbar_wait(sb + B_BAR + (CB_CF + (w >> 1)) * 8, b & 1);
            const uint2* cb = g_carry + ((tile * 320 + b) * 32 + lz);
            uint2 cr[8];
#pragma unroll
            for (int k = 0; k < 8; k++) cr[k] = ld_acc(cb + k * 1280, b >= 4);
            if (NTOP != 255 && !((NTOP >> w) & 1) && b) conv_near(acc, ta, q1);
#pragma unroll
            for (int k = 0; k < 8; k++) add_acc(acc[k], cr[k]);
        }
        PIN(13);
        float4 ln = stats_recv<0>(l16, g_st + (b + 2) * 256 + lz, w);
        PROF2(threadIdx.x == 0 && on, 2048 + b * 8 + 3);
        uint32_t u[8];
#pragma unroll
        for (int k = 0; k < 8; k++) {
            u[k] = pack2(rbf(x[2 * k] - ln.x) * ln.y, rbf(x[2 * k + 1] - ln.z) * ln.w);
            sts32(row + k * 1024 + (b & 7) * 128 + lane * 4, u[k]);
        }
        __syncwarp();
        const uint32_t qa = row + ((qo + b * 128) & 1023);
        {
            uint4 xq[8];
#pragma unroll
            for (int k = 0; k < 4; k++) xq[k] = ldsm4(qa + k * 1024);
#pragma unroll
            for (int k = 0; k < 8; k += 2) {
                PIN(13);
                mma_q(acc[k], A[k], xq[k]); mma_q(acc[k + 1], A[k + 1], xq[k + 1]);
                if (k < 4) { xq[k + 4] = ldsm4(qa + (k + 4) * 1024); xq[k + 5] = ldsm4(qa + (k + 5) * 1024); }
            }
        }
        const uint4 dk = lds128(sb + C_ST + 4608 + w * 16);
#pragma unroll
        for (int k = 0; k < 8; k++) {
            const float t = __shfl_sync(0xffffffffu, acc[k][3], (lz & ~3) | ((lz - 1) & 3));
            const uint32_t y = movm(pack2(acc[k][0] + (c ? t : 0.f), acc[k][1] + acc[k][2]));
            acc[k][0] = c ? 0.f : t; acc[k][1] = acc[k][2] = acc[k][3] = 0;
            const uint32_t dw = k >> 1 == 0 ? dk.x : k >> 1 == 1 ? dk.y : k >> 1 == 2 ? dk.z : dk.w;
            const uint32_t s = hadd2(hadd2(y, hmul2(u[k], __byte_perm(dw, 0, (k & 1) ? 0x3232 : 0x1010))), __byte_perm(__float_as_uint(x[2 * k]), __float_as_uint(x[2 * k + 1]), 0x7632));
            x[2 * k] = blo(s); x[2 * k + 1] = bhi(s);
        }
        arrive_if(sb + B_BAR + (CB_UF + (w >> 1)) * 8, lz, b < -1 ? 32 : 0);
        stats_send<1>(l16, x, g_st + (36 + b) * 256 + lz, q, w);
        {
            PROF2(threadIdx.x == 0 && on, 2048 + b * 8 + 4);
            uint4* dst = g_x + ((128 + tile * 2) * XP + b * 32 + lz);
#pragma unroll
            for (int e = 0; e < 2; e++) {
                const float* y = x + e * 8;
                if (on) dst[e * XP] = make_uint4(__byte_perm(__float_as_uint(y[0]), __float_as_uint(y[2]), 0x7632), __byte_perm(__float_as_uint(y[4]), __float_as_uint(y[6]), 0x7632),
                                           __byte_perm(__float_as_uint(y[1]), __float_as_uint(y[3]), 0x7632), __byte_perm(__float_as_uint(y[5]), __float_as_uint(y[7]), 0x7632));
            }
            uint32_t* du = g_u + (tile * 8 * (UROW / 2) + UPRE / 2 + b * 32 + lz);
#pragma unroll
            for (int k = 0; k < 8; k++) if (on) du[k * (UROW / 2)] = u[k];
        }
#pragma unroll 1
        for (int pass = 0; pass < 2; pass++) {
            if (pass == ((PLATE >> w) & 1)) {
                const uint32_t q0 = row + ((qo + (b - 2) * 128) & 1023);
                if (b & 1) conv_pair<4>(acc, pend, ta, q0, q1, qa); else conv_pair<0>(acc, pend, ta, q0, q1, qa);
            }
            if (pass) break;
            ln = stats_recv<1>(l16, g_st + (36 + b) * 256 + lz, w);
            PROF2(threadIdx.x == 0 && on, 2048 + b * 8 + 5);
            uint32_t o[2][4];
#pragma unroll
            for (int e = 0; e < 2; e++) {
                const float mu = e ? ln.z : ln.x, rs = e ? ln.w : ln.y;
#pragma unroll
                for (int i = 0; i < 4; i++) o[e][i] = pack2(rbf(x[4 * i + e] - mu) * rs, rbf(x[4 * i + 2 + e] - mu) * rs);
            }
#pragma unroll
            for (int i = 0; i < 4; i++) {
                const uint32_t t = __shfl_xor_sync(0xffffffffu, (lz & 1) ? o[0][i] : o[1][i], 1);
                if (lz & 1) o[0][i] = t; else o[1][i] = t;
            }
            uint4* dst = g_xn + ((32 + b) * 4096 + q * 512 + (lz >> 2) * 64 + w * 8 + (lz & 2) * 2 + (lz & 1));
            if (on) { dst[0] = make_uint4(o[0][0], o[0][1], o[0][2], o[0][3]); dst[2] = make_uint4(o[1][0], o[1][1], o[1][2], o[1][3]); }
            if (w == 7) {
                bar_sync(5, 256);
                if (elect()) red_release(cnt_ptr(on ? C_XN + 32 + b : C_FAR + 8), 2);
                PROF(lane == 0 && on, 2048 + b * 8 + 6);
                __syncwarp();
            } else bar_arrive(5, 256);
        }
    }
}

template <int P0, bool TRI = false, int R0 = 0>
__device__ __forceinline__ void bg_half(float (*acc)[4], uint4* win, uint32_t ta, uint32_t qa, uint32_t mask, uint32_t row) {
#pragma unroll
    for (int i = 0; i < 4; i++) {
        win[P0 + i] = ldsm4(((qa + i * 128) & mask) + row);
        const uint4 a = lds128(ta + (3 - i) * 448), e = lds128(ta + (3 - i) * 448 + 224);
#pragma unroll
        for (int r = TRI ? 7 - P0 - i : R0; r < 8; r++) mma16(acc[r], a.x, a.y, a.z, a.w, win[(P0 + i + 1 + r) & 7].x, win[(P0 + i + 1 + r) & 7].y);
#pragma unroll
        for (int r = TRI ? 7 - P0 - i : R0; r < 8; r++) mma16(acc[r], e.x, e.y, e.z, e.w, win[(P0 + i + 1 + r) & 7].z, win[(P0 + i + 1 + r) & 7].w);
    }
}
__device__ __forceinline__ void bg_fetch(uint32_t sb, int q, int j, int n) {
    const int b0 = n >> 1, ch = q * 64 + j * 16 + (n & 1) * 8 + (b0 & 7), skip = max(12 - b0, 0);
    const uint32_t bar = sb + B_BAR + (CB_LD + j * 2 + (n & 1)) * 8, buf = sb + C_BG + (j * 2 + (n & 1)) * CB_BIG;
    if (elect()) {
        mbar_expect(bar, CB_BIG - skip * 128);
        bulk_g2s(buf, g_W + ch * 784, CB_M, bar, POL_N);
        bulk_g2s(buf + CB_M, g_W + (ch ^ 4) * 784, 1792, bar, POL_N);
        bulk_g2s(buf + CB_U + skip * 128, g_u + ch * (UROW / 2) + UPRE / 2 + (b0 - 20 + skip) * 32, 2048 - skip * 128, bar, POL_N);
    }
    __syncwarp();
}
__device__ __forceinline__ void conv_back(uint32_t sb, int q, int j) {
    const int lane = __shfl_sync(0xffffffffu, threadIdx.x & 31, threadIdx.x & 31), g = lane >> 2, c = lane & 3;
    wait_slow_warp(g_gate, lds32(sb + S_GATE));
    bg_fetch(sb, q, j, 0);
    bar_sync(4, 384);
    const uint32_t to = (6 + g - 2 * c) * 16, qo = (lane & 7) * 16 - (lane >> 3) * 32;
#pragma unroll 1
    for (int n = 0; n < 64; n++) {
        const int b0 = n >> 1, i = n & 1, chl = j * 16 + i * 8 + (b0 & 7);
        const uint32_t buf = sb + C_BG + (j * 2 + i) * CB_BIG, ta = buf + to;
        float acc[8][4];
        uint4 win[8];
        if (n < 63) bg_fetch(sb, q, j, n + 1);
        if (b0 >= 17 && b0 < 29 && (b0 < 21 || b0 >= 25) && i == 0) wait_flag_warp(cnt_ptr(C_FAR + (b0 >= 25) * 4 + ((b0 - 1) & 3)), 12);
        uint2* cr = g_carry + (((q * 64 + chl) * 40 + b0) * 32 + lane);
        uint2* cm = g_carry + (((q * 64 + (chl ^ 4)) * 40 + b0) * 32 + lane);
        uint2 pm[4], pf[8];
#pragma unroll
        for (int r = 0; r < 4; r++) pm[r] = ld_acc(cm + r * 32, b0 > 4);
#pragma unroll
        for (int r = 0; r < 8; r++) acc[r][0] = acc[r][1] = acc[r][2] = acc[r][3] = 0;
        mbar_wait(sb + B_BAR + (CB_LD + j * 2 + i) * 8, b0 & 1);
        if (b0 > 12) {
#pragma unroll
            for (int r = 1; r < 8; r++) win[(r + 4) & 7] = ldsm4(buf + CB_U + qo + r * 128);
        } else {
#pragma unroll
            for (int r = 1; r < 8; r++) win[(r + 4) & 7] = make_uint4(0, 0, 0, 0);
        }
        win[4] = make_uint4(0, 0, 0, 0);
#pragma unroll 1
        for (int h = b0 > 8 ? 4 : 2; h >= 2; h -= 2) {
            if (h == 2) {
                if (b0 > 4) bg_half<0>(acc, win, ta + 2 * 1792, qo + 12 * 128, ~0u, buf + CB_U);
                if (i == 0) mbar_wait(sb + B_BAR + (CB_UF + j) * 8, b0 & 1);
            }
            bg_half<4>(acc, win, ta + (h - 1) * 1792, qo + (h == 2 ? b0 - 4 : 8) * 128, h == 2 ? 1023u : ~0u, h == 2 ? sb + C_UR + chl * 1024 : buf + CB_U);
        }
        uint4 wm[8], a[9], e[9];
#pragma unroll
        for (int r = 1; r < 8; r++) wm[r] = ldsm4(sb + C_UR + (chl ^ 4) * 1024 + ((qo + (b0 + r) * 128) & 1023));
        a[7] = lds128(ta + 7 * 224); e[7] = lds128(ta + CB_M + 7 * 224);
#pragma unroll
        for (int r = 4; r < 8; r++) { st_acc(cr + r * 32, acc[r]); acc[r][0] = blo(pm[r - 4].x); acc[r][1] = bhi(pm[r - 4].x); acc[r][2] = blo(pm[r - 4].y); acc[r][3] = bhi(pm[r - 4].y); }
#pragma unroll
        for (int t = 7; t >= 0; t--) {
            if (t) { a[t - 1] = lds128(ta + (t - 1) * 224); e[t - 1] = lds128(ta + CB_M + (t - 1) * 224); }
            if (t == FT) {
                const uint2* f0 = g_far + (((q * 64 + chl) * 12 + b0 - 20) * 32 + lane);
                const uint2* f1 = g_far + (((q * 64 + (chl ^ 4)) * 12 + b0 - 20) * 32 + lane);
#pragma unroll
                for (int r = 0; r < 4; r++) { const bool on = (unsigned)(b0 + r - 20) < 12u; pf[r] = ld_acc(f0 + r * 32, on); pf[4 + r] = ld_acc(f1 + r * 32, on); }
            }
            PIN(14);
#pragma unroll
            for (int r = 0; r < 4; r++) { const uint4& x = win[4 + r - (t >> 1)]; mma16(acc[r], a[t].x, a[t].y, a[t].z, a[t].w, (t & 1) ? x.z : x.x, (t & 1) ? x.w : x.y); }
#pragma unroll
            for (int r = 0; r < 4; r++) { const uint4& x = wm[4 + r - (t >> 1)]; mma16(acc[4 + r], e[t].x, e[t].y, e[t].z, e[t].w, (t & 1) ? x.z : x.x, (t & 1) ? x.w : x.y); }
        }
#pragma unroll
        for (int r = 0; r < 4; r++) { add_acc(acc[r], pf[r]); add_acc(acc[4 + r], pf[4 + r]); st_acc(cr + r * 32, acc[r]); st_acc(cm + r * 32, acc[4 + r]); }
        __syncwarp();
        arrive_if(sb + B_BAR + (CB_CF + j) * 8, lane, i ? 0 : 32);
        PROF(j == 0 && lane == 0 && i, 2048 + b0 * 8 + 7);
    }
}
template <int PART>
__device__ __forceinline__ void conv_far(uint32_t sb, int w) {
    constexpr int NT = PART ? 5376 : 3584, NU = PART ? 1664 : 1152;
    const int lane = __shfl_sync(0xffffffffu, threadIdx.x & 31, threadIdx.x & 31), g = lane >> 2, c = lane & 3;
    wait_slow_warp(cnt_ptr(C_XN + (PART ? 43 : 39)), 16);
    const uint32_t to = (6 + g - 2 * c) * 16, qo = (lane & 7) * 16 - (lane >> 3) * 32;
#pragma unroll 1
    for (int n = -1; n < 44; n++) {
        const int t = n * 12 + w, tn = min(t + 12, 511), ch = (t & 127) * 4 + (((t >> 7) + 1) & 3), cn = (tn & 127) * 4 + (((tn >> 7) + 1) & 3);
        const uint32_t bar = sb + B_BAR + (w * 2 + (n & 1)) * 8, buf = sb + (w * 2 + (n & 1)) * 7168;
        if (n < 43 && elect()) {
            const uint32_t nb = sb + (w * 2 + (~n & 1)) * 7168;
            mbar_expect(bar ^ 8, NT + NU);
            bulk_g2s(nb, g_W + cn * 784 + 448, NT, bar ^ 8, POL_N);
            bulk_g2s(nb + 5376, g_u + cn * (UROW / 2) + UPRE / 2 - 32, NU, bar ^ 8, POL_N);
        }
        __syncwarp();
        if (n < 0) continue;
        mbar_wait(bar, (n >> 1) & 1);
        if (t >= 512) continue;
        float acc[8][4];
        uint4 win[8];
#pragma unroll
        for (int r = 0; r < 8; r++) acc[r][0] = acc[r][1] = acc[r][2] = acc[r][3] = 0;
        bg_half<0, true, PART * 4>(acc, win, buf + to + NT - 1792, qo + 128, ~0u, buf + 5376);
        bg_half<4, !PART, PART * 4>(acc, win, buf + to + NT - 3584, qo + 640, ~0u, buf + 5376);
        if (PART) bg_half<0, false, 4>(acc, win, buf + to, qo + 1152, ~0u, buf + 5376);
#pragma unroll
        for (int r = PART * 4; r < 8; r++) st_acc(g_far + (ch * 384 + lane) + (r + PART * 4) * 32, acc[r]);
        __syncwarp();
        if (((t + 12) ^ t) >= 128 && elect()) red_release(cnt_ptr(C_FAR + PART * 4 + (t >> 7)), 1);
        __syncwarp();
    }
    PROF(threadIdx.x == 0, 2048 + PART);
}

constexpr int P_X = 131072  , P_K6 = P_X + 32768  , P_P = P_K6 + 10496  , P_U = P_P + 33280  ,
              P_END = P_U + 17408, P_PRM = P_P  , P_Y = P_P  ;
static_assert(P_END <= B_BAR && P_END <= R_SEL, "prologue scratch");
#define KGUN 2
constexpr int KGU = KGUN;
__device__ __forceinline__ void csq(float& r, float& i) { const float t = r * i; r = fmaf(r, r, -(i * i)); i = t + t; }
__device__ __forceinline__ void cpow(float ar, float ph, float p, float& r, float& i) {
    const float e = ex2(ar * p);
    const float u = ph * p, n = (u + 12582912.f) - 12582912.f;
    const float t = (u - n) * 6.283185307179586f;
    r = e * __cosf(t); i = e * __sinf(t);
}
__device__ __forceinline__ void mma_tf32(float* c, float a0, float a1, float a2, float a3, float b0, float b1) {
    asm volatile("mma.sync.aligned.m16n8k8.row.col.f32.tf32.tf32.f32 {%0,%1,%2,%3},{%4,%5,%6,%7},{%8,%9},{%0,%1,%2,%3};"
                 : "+f"(c[0]), "+f"(c[1]), "+f"(c[2]), "+f"(c[3])
                 : "r"(__float_as_uint(a0)), "r"(__float_as_uint(a1)), "r"(__float_as_uint(a2)), "r"(__float_as_uint(a3)), "r"(__float_as_uint(b0)), "r"(__float_as_uint(b1)));
}

__device__ __forceinline__ void early_fetch(const Params& p, uint32_t sb) {
    const int v = blockIdx.x;
    if (elect()) {
        if (v >= V_QKV) { if (v < V_QKV + NQ && (p.roles & 8)) qkv_fetch(p, sb, v - V_QKV, 0, Q_PRE); }
        else if (v >= V_OP) { if (p.roles & 4) op_fetch(p, sb, v - V_OP, 0); }
        else if (v >= V_REC && (p.roles & 2)) { rec_fetch(p, sb, (v - V_REC) >> 1, v & 1, 0, R_STQ); rec_fetch(p, sb, (v - V_REC) >> 1, v & 1, 2, R_STV); }
    }
    __syncwarp();
}
struct ProRegs { uint32_t v[2][4], ldt[2]; };
__device__ __forceinline__ void prologue_load(const ProArgs& a, int b, ProRegs& pr) {
    const int w = threadIdx.x >> 5;
#pragma unroll
    for (int i = 0; i < 2; i++) {
        const int gi = b * 512 + (w & 3) * 128 + ((w >> 2) & 1) * 64 + i * 32 + (threadIdx.x & 31);
        pr.ldt[i] = __ldg((const uint16_t*)a.ldt + b * 4 + (w & 3));
        pr.v[i][0] = __ldg((const uint16_t*)a.lAr + gi); pr.v[i][1] = __ldg((const uint16_t*)a.Ai + gi);
        pr.v[i][2] = __ldg((const uint16_t*)a.Cr + gi); pr.v[i][3] = __ldg((const uint16_t*)a.Ci + gi);
    }
}
__device__ __forceinline__ void prologue(const Params& p, uint32_t sb, int b, int w, const ProRegs& pr) {
    const ProArgs& a = p.pa;
    const int tid = threadIdx.x, lane = tid & 31, g = lane >> 2, c = lane & 3;
    const int d0 = b * 4;
    if (w >= 8) {
        const int t2 = tid - 256;
        if (w < 10) {
            const int row = b * 16 + (w - 8) * 8 + g;
            uint4 v[16];
            const float2 r = row_stats512(v, (const uint4*)(a.x + (size_t)row * 512) + c, 8, 4);
            const float2 l = ln_finish(r.x * (1.f / 512.f), r.y * (1.f / 512.f));
            if (c == (g >> 1)) asm volatile("st.relaxed.gpu.global.u32 [%0],%1;" ::"l"(g_ln0 + row), "r"(pack2(l.x, l.y)) : "memory");
            __syncwarp();
        }
        if (b + 4 >= V_REC && b + 4 < V_OP) rec_slots(b + 4 - V_REC, (w & 3) ^ 2);
        PROF(t2 == 0, 3516);
        const int gi = b * 128 + t2;
        g_st[gi] = make_uint4(~0u, ~0u, ~0u, ~0u);
        if (gi < 1024) g_st[16384 + gi] = make_uint4(~0u, ~0u, ~0u, ~0u);
        if (gi < C_N * 8) g_cnt[gi] = 0;
        bar_sync(9, 384);
#pragma unroll 1
        for (int pass = 0; pass < 2; pass++) {
        if (w == 10 && pass == (b + 4 < V_QKV)) early_fetch(p, sb);
        if (pass) break;
#pragma unroll 2
        for (int i = t2; i < 4 * 784; i += 128) {
            const int ch = i / 784, k = i - ch * 784;
            const uint32_t o = sb + P_P + (ch * 2080 + 266 + (k / 14) * 18 + k) * 4;
            g_W[d0 * 784 + i] = make_uint4(lds32(o), lds32(o + 32), lds32(o + 64), lds32(o + 96));
        }
        bar_arrive(10, 384);
        }
        PROF(t2 == 0, 3517);
        return;
    }
    float kl = 0;
#pragma unroll
    for (int i = 0; i < 2; i++) {
        const float dt = rbf(expf(blo(pr.ldt[i])));
        const float ar = -rbf(expf(blo(pr.v[i][0]))) * dt, ai = blo(pr.v[i][1]) * dt;
        const float lg = ar * 1.4426950408889634f, tn = ai * 0.15915494309189535f, ph = tn - rintf(tn);
        const float cr = 2.f * (blo(pr.v[i][2]) * dt), ci = 2.f * (blo(pr.v[i][3]) * dt);
        float zr, zi;
        cpow(lg, ph, 2048.f, zr, zi);
        kl += cr * zr - ci * zi;
        cpow(lg, ph, 8.f, zr, zi);
        sts128(sb + P_PRM + (w * 64 + i * 32 + lane) * 16, __float_as_uint(lg), __float_as_uint(ph), __float_as_uint(cr), __float_as_uint(ci));
        sts64(sb + P_PRM + 8192 + (w * 64 + i * 32 + lane) * 8, __float_as_uint(zr), __float_as_uint(zi));
    }
    if (tid < 64) sts128(sb + P_U + (tid >> 3) * 2176 + (tid & 7) * 16, 0, 0, 0, 0);
    __syncwarp();
    PROF(tid == 0, 3510);
    uint2 ln[4];
#define LDLN _Pragma("unroll") for (int i = 0; i < 4; i++) asm volatile("ld.relaxed.gpu.global.v2.u32 {%0,%1},[%2];" : "=r"(ln[i].x), "=r"(ln[i].y) : "l"((const uint2*)g_ln0 + i * 256 + tid) : "memory")
    const int ch = w & 3, hf = w >> 2;
    {
        float k0[4] = {0, 0, 0, 0}, k1[4] = {0, 0, 0, 0}, k2[4] = {0, 0, 0, 0}, k3[4] = {0, 0, 0, 0}, k4[4] = {0, 0, 0, 0};
#pragma unroll KGU
        for (int j = 0; j < 16; j++) {
            const uint4 q = lds128(sb + P_PRM + (w * 64 + j * 4 + c) * 16);
            const float cr = __uint_as_float(q.z), ci = __uint_as_float(q.w);
            float wr[4], wi[4], vr[4], vi[4];
            cpow(__uint_as_float(q.x), __uint_as_float(q.y), (float)g, wr[0], wi[0]);
            const uint2 z8 = lds64(sb + P_PRM + 8192 + (w * 64 + j * 4 + c) * 8);
            vr[0] = wr[0] * __uint_as_float(z8.x) - wi[0] * __uint_as_float(z8.y); vi[0] = wr[0] * __uint_as_float(z8.y) + wi[0] * __uint_as_float(z8.x);
#pragma unroll
            for (int i = 1; i < 4; i++) { wr[i] = wr[i - 1]; wi[i] = wi[i - 1]; csq(wr[i], wi[i]); vr[i] = vr[i - 1]; vi[i] = vi[i - 1]; csq(vr[i], vi[i]); }
            float hr = wr[3], hi = wi[3];
            csq(hr, hi);
            mma_tf32(k0, wr[0], vr[0], wi[0], vi[0], cr * hr - ci * hi, -(cr * hi + ci * hr));
            hr = vr[3]; hi = vi[3]; csq(hr, hi);
            mma_tf32(k1, wr[0], vr[0], wi[0], vi[0], cr * hr - ci * hi, -(cr * hi + ci * hr));
            csq(hr, hi);
            mma_tf32(k2, wr[1], vr[1], wi[1], vi[1], cr * hr - ci * hi, -(cr * hi + ci * hr));
            csq(hr, hi);
            mma_tf32(k3, wr[2], vr[2], wi[2], vi[2], cr * hr - ci * hi, -(cr * hi + ci * hr));
            csq(hr, hi);
            mma_tf32(k4, wr[3], vr[3], wi[3], vi[3], cr * hr - ci * hi, -(cr * hi + ci * hr));
        }
        LDLN;
#pragma unroll
        for (int d = 1; d < 32; d *= 2) kl += __shfl_xor_sync(0xffffffffu, kl, d);
        const uint32_t o = sb + P_K6 + (ch * 656 + c * 32 + g) * 4, ol = sb + P_K6 + (ch * 656 + 640) * 4;
#define KST(k, base) sts32(o + (base) * 4, __float_as_uint(k[0])); sts32(o + (base) * 4 + 64, __float_as_uint(k[1])); \
                     sts32(o + (base) * 4 + 32, __float_as_uint(k[2])); sts32(o + (base) * 4 + 96, __float_as_uint(k[3]))
#define KAD(k, base) k[0] += __uint_as_float(lds32(o + (base) * 4)); k[1] += __uint_as_float(lds32(o + (base) * 4 + 64)); \
                     k[2] += __uint_as_float(lds32(o + (base) * 4 + 32)); k[3] += __uint_as_float(lds32(o + (base) * 4 + 96))
        if (hf == 0) {
            bar_sync(2 + ch, 64);
            KAD(k0, 0); KAD(k1, 128); KAD(k2, 256); KAD(k3, 384); KAD(k4, 512);
            kl += __uint_as_float(lds32(ol));
            __syncwarp();
        }
        KST(k0, 0); KST(k1, 128); KST(k2, 256); KST(k3, 384); KST(k4, 512);
        if (lane == 0) sts32(ol, __float_as_uint(kl));
        if (hf == 1) { __syncwarp(); bar_arrive(2 + ch, 64); }
    }
    PROF(tid == 0, 3511);
    {
        int n = 0;
        while (!__all_sync(0xffffffffu, ln[0].x && ln[0].y && ln[1].x && ln[1].y && ln[2].x && ln[2].y && ln[3].x && ln[3].y)) {
            LDLN;
            if (++n > 2000000) __trap();
        }
        bar_sync(8, 384);
        mbar_wait(sb + S_XBAR, 0);
#pragma unroll
        for (int i = 0; i < 4; i++) {
            const int t = i * 512 + tid * 2;
            uint32_t u[2][2];
#pragma unroll
            for (int e = 0; e < 2; e++) {
                const uint32_t l = e ? ln[i].y : ln[i].x, mm = __byte_perm(l, 0, 0x1010) ^ 0x80008000u;
                const float rs = rcp(bhi(l));
                const uint2 x = lds64(sb + P_X + (t + e) * 16 + (b & 1) * 8);
                u[e][0] = NRM(x.x); u[e][1] = NRM(x.y);
                sts64(sb + P_X + (t + e) * 16 + 8 - (b & 1) * 8, u[e][0], u[e][1]);
            }
            const uint32_t o = sb + P_U + ((t >> 3) & 1) * 2176 + ((t >> 4) + 8) * 16 + (t & 7) * 2;
#pragma unroll
            for (int k = 0; k < 4; k++) sts32(o + k * 4352, __byte_perm(u[0][k >> 1], u[1][k >> 1], (k & 1) ? 0x7632 : 0x5410));
        }
    }
    PROF(tid == 0, 3512);
    if (tid < 64) sts32(sb + P_P + ((tid >> 4) * 2080 + (tid & 15)) * 4, 0);
#pragma unroll 1
    for (int x = tid; x < 2048; x += 512) {
        uint32_t pw[2][4];
#pragma unroll
        for (int h = 0; h < 2; h++) {
            const int y = x + h * 256;
            const int i0 = y <= 256 ? y : 256 + (int)((pack2((float)y, 0.f) & 0xffff) - 0x4380);
            const int i1 = y <= 256 ? max(y - 1, 0) : 256 + (int)((pack2((float)(y - 1), 0.f) & 0xffff) - 0x4380);
#pragma unroll
            for (int k = 0; k < 4; k++) {
                const float lo = __uint_as_float(lds32(sb + P_K6 + k * 2624 + i0 * 4)), hi = __uint_as_float(lds32(sb + P_K6 + k * 2624 + i1 * 4));
                pw[h][k] = pack2(lo, y ? hi : 0.f);
            }
        }
#pragma unroll
        for (int h = 0; h < 2; h++)
#pragma unroll
            for (int k = 0; k < 4; k++) sts32(sb + P_P + (k * 2080 + x + h * 256 + 16) * 4, pw[h][k]);
    }
    fence_async_smem();
    bar_arrive(9, 384);
    bar_sync(1, 256);
    if (tid < 4) {
        asm volatile("cp.async.bulk.global.shared::cta.bulk_group [%0],[%1],%2;" ::"l"(g_P + (d0 + tid) * PROW), "r"(sb + P_P + tid * 8320), "r"(PROW * 4) : "memory");
        asm volatile("cp.async.bulk.commit_group;" ::: "memory");
    }
    __syncwarp();
    PROF(tid == 0, 3513);
    {
        float acc[16][4];
#pragma unroll
        for (int j = 0; j < 16; j++) acc[j][0] = acc[j][1] = acc[j][2] = acc[j][3] = 0;
#pragma unroll 1
        for (int e = hf * 4; e < hf * 4 + 4; e++) {
            uint32_t B[16][2];
            const uint32_t ua = sb + P_U + ch * 4352 + ((lane >> 3) & 1) * 2176 + (8 + (lane >> 4) * 8 + (lane & 7) - e) * 16;
#pragma unroll
            for (int j = 0; j < 8; j++) { const uint4 v = ldsm4(ua + j * 256); B[2 * j][0] = v.x; B[2 * j][1] = v.y; B[2 * j + 1][0] = v.z; B[2 * j + 1][1] = v.w; }
            const uint32_t pa = sb + P_P + (ch * 2080 + 16 + e * 16 + g - 2 * c) * 4;
#pragma unroll
            for (int dd = 0; dd < 16; dd++) {
                const int d = (dd & 1) ? 15 - (dd >> 1) : dd >> 1;
                const uint32_t a0 = lds32(pa + d * 512), a1 = lds32(pa + d * 512 + 32), a2 = lds32(pa + d * 512 - 32), a3 = a0 + p.zero;
#pragma unroll
                for (int j = 0; j < 16; j++) if (j >= d) mma16(acc[j], a0, a1, a2, a3, B[(j - d) & 15][0], B[(j - d) & 15][1]);
            }
        }
        PROF(tid == 0, 3514);
        if (tid < 4) asm volatile("cp.async.bulk.wait_group 0;" ::: "memory");
        __syncwarp();
        bar_sync(10, 384);
#pragma unroll
        for (int j = 0; j < 8; j++) {
#pragma unroll
            for (int i = 0; i < 4; i++) { const float t = hf ? acc[j][i] : acc[j + 8][i]; acc[j][i] = hf ? acc[j + 8][i] : acc[j][i]; acc[j + 8][i] = t; }
            sts128(sb + P_Y + w * 4096 + j * 512 + lane * 16, __float_as_uint(acc[j + 8][0]), __float_as_uint(acc[j + 8][1]), __float_as_uint(acc[j + 8][2]), __float_as_uint(acc[j + 8][3]));
        }
        bar_sync(2 + ch, 64);
        uint32_t yp[16];
#pragma unroll
        for (int j = 0; j < 8; j++) {
            const uint4 t = lds128(sb + P_Y + (w ^ 4) * 4096 + j * 512 + lane * 16);
            yp[2 * j] = pack2(acc[j][0] + __uint_as_float(t.x), acc[j][1] + __uint_as_float(t.y)); yp[2 * j + 1] = pack2(acc[j][2] + __uint_as_float(t.z), acc[j][3] + __uint_as_float(t.w));
        }
#pragma unroll
        for (int j = 0; j < 4; j++)
            asm volatile("stmatrix.sync.aligned.m8n8.x4.trans.shared.b16 [%0],{%1,%2,%3,%4};" ::"r"(sb + P_Y + 32768 + ch * 4096 + hf * 2048 + j * 512 + (lane >> 4) * 256 + (lane & 7) * 32 + (lane & 8) * 2),
                         "r"(yp[4 * j]), "r"(yp[4 * j + 1]), "r"(yp[4 * j + 2]), "r"(yp[4 * j + 3]) : "memory");
    }
    const uint2 dk = __ldg((const uint2*)(a.Dk + d0));
    bar_sync(1, 256);
#pragma unroll 2
    for (int i = 0; i < 4; i++) {
        const int t = i * 256 + tid;
        uint4 x0 = lds128(sb + P_X + t * 32), x1 = lds128(sb + P_X + t * 32 + 16);
        if (b & 1) { x0 = make_uint4(x0.z, x0.w, x0.x, x0.y); x1 = make_uint4(x1.z, x1.w, x1.x, x1.y); }
        uint32_t y[4];
#pragma unroll
        for (int k = 0; k < 4; k++) y[k] = lds32(sb + P_Y + 32768 + k * 4096 + t * 4);
        g_x[b * XP + t] = make_uint4(hadd2(x0.x, hadd2(__byte_perm(y[0], y[1], 0x5410), hmul2(x0.z, dk.x))), hadd2(x0.y, hadd2(__byte_perm(y[2], y[3], 0x5410), hmul2(x0.w, dk.y))),
                                     hadd2(x1.x, hadd2(__byte_perm(y[0], y[1], 0x7632), hmul2(x1.z, dk.x))), hadd2(x1.y, hadd2(__byte_perm(y[2], y[3], 0x7632), hmul2(x1.w, dk.y))));
    }
    PROF(tid == 0, 3515);
}

__global__ void __cluster_dims__(2, 1, 1) __launch_bounds__(384, 1) main_kernel(const __grid_constant__ Params p) {
    extern __shared__ __align__(1024) uint8_t smem[];
    const uint32_t sb = smem_u32(smem);
    uint32_t rank; asm("mov.u32 %0,%%cluster_ctarank;" : "=r"(rank));
    const int wi = __shfl_sync(0xffffffffu, threadIdx.x >> 5, 0);
    const int v = blockIdx.x, cl = v >> 1, wg = wi >> 2;
    PROF(threadIdx.x == 0, 3500);
    ProRegs pr;
    prologue_load(p.pa, max((int)blockIdx.x - 4, 0), pr);
    if (wi == 11 && p.dopro && cl >= 2 && elect()) {
        mbar_init(sb + S_XBAR, 1);
        asm volatile("fence.mbarrier_init.release.cluster;" ::: "memory");
        mbar_expect(sb + S_XBAR, 32768);
        for (int j = 0; j < 8; j++) tma2d(sb + P_X + j * 4096, &p.tm[3], ((blockIdx.x - 4) >> 1) * 8, j * 256, sb + S_XBAR);
    }
    if (threadIdx.x == 320) {
        unsigned n;
        asm volatile("ld.relaxed.gpu.global.u32 %0,[%1];" : "=r"(n) : "l"(g_gate) : "memory");
        n = n / (4 * NCL) + p.dopro;
        sts64(sb + S_GATE, n * (4 * NCL), n & 1);
    }
    __syncwarp();
    if (wi == 10) {
        if (v < V_REC || v == 131) conv_init(sb, v == 131); else if (v < V_OP) rec_init(sb); else gemm_init(sb, v < V_QKV);
        __syncwarp();
    }
    if (wg == 2) bar_arrive(8, 384);
    asm volatile("barrier.cluster.arrive.relaxed.aligned;" ::: "memory");
    if (p.dopro && cl >= 2) prologue(p, sb, blockIdx.x - 4, wi, pr); else if (wg < 2) bar_sync(8, 384); else if (wi == 10) early_fetch(p, sb);
    asm volatile("barrier.cluster.wait.aligned;" ::: "memory");
    const int role = (v < V_REC ? 1 : v < V_OP ? 2 : v < V_QKV ? 20 : v < V_QKV + NQ ? 24 : 1) & p.roles;
    fence_async_smem();
    bar_sync(wg == 2 ? 7 : 1, wg == 2 ? 128 : 256);
    if (p.dopro && (threadIdx.x == 32 || threadIdx.x == 352)) red_release(g_gate, 1);
    PROF(threadIdx.x == 32, 3509);
    if (wi == 0 && (role & 8) && elect()) qkv_stage(p, sb + 131072, sb + G_BAR + GB_RS * 8, v - V_QKV, 0, 6);
    PROF(threadIdx.x == 0, 3506);
    __syncwarp();
    if (p.dopro && (v == 131 || (v >= V_REC && v < V_QKV && (v < V_OP ? wi == 8 : wi < 8)))) {
        bool on = v >= V_OP;
#pragma unroll 1
        for (int r = v == 131 ? 448 + wi : on ? 64 + (v - V_OP) * 8 + wi : v - V_REC; r < (v == 131 ? 512 : 448);) {
            if (v >= V_OP) wait_slow_warp(g_gate, lds32(sb + S_GATE)); else if (on) wait_flag_warp(g_gate, lds32(sb + S_GATE));
            PROF(threadIdx.x == 256 && on, 3507);
            x1_norm(on ? (const uint2*)g_x : (const uint2*)p.pa.x, r, on);
            __syncwarp();
            if (on && elect()) red_release(cnt_ptr(C_XN + (r >> 4)), 1);
            __syncwarp();
            PROF(threadIdx.x == 256, on ? 3508 : 3499);
            if (on) r += v < V_OP ? 512 : v == 131 ? 12 : 128;
            on = true;
        }
    }
    if (role == 2) {
        const int head = (v - V_REC) >> 1;
        if (wi == 8 && elect()) rec_fetch(p, sb, head, rank, 1, R_STK);
        __syncwarp();
        if (wg == 2) {
            reg_dec<RH>();
            const int w = wi & 3;
            wait_slow_warp(g_gate, lds32(sb + S_GATE));
            if (w < 2) { const uint32_t x = __ldcg(g_sel + (threadIdx.x & 63)); sts32(sb + R_SEL + (threadIdx.x & 63) * 4, (x * 0x01010101u) >> 24); }
            __syncthreads();
            cluster_sync();
            if ((p.chains >> (w & 1)) & 1) { if (w < 2) rec_comm(p, sb, w, head, rank); else rec_attn(p, sb, w & 1, head, rank); }
        } else {
            reg_inc<RW0>();
            rec_weights(p, sb, head, rank, wi);
        }
    } else if (role == 1) {
        if (v == 131) { wait_slow_warp(g_gate, lds32(sb + S_GATE)); conv_far<0>(sb, wi); conv_far<1>(sb, wi); } else if (wg == 2) { reg_dec<RCB>(); conv_back(sb, v, wi & 3); } else { reg_inc<RCU>(); conv_tile(p, sb, v, wi); }
    } else if (role && v < V_QKV) {
        if (wg == 2) {
            reg_dec<40>();
            if (wi == 8) { if (role & 4) gemm_producer<true>(p, sb, v - V_OP); }
            else if (v < V_OP + 14 && (role & 16)) fin_warp(p, sb, 2 * NQ + (v - V_OP) * 3 + wi - 9);
        } else { reg_inc<232>(); if (role & 4) gemm_consumer<true>(p, sb, v - V_OP, wi); }
    } else if (role) {
        if (wg == 2) {
            reg_dec<40>();
            if (wi < 10) {
                if (role & 8) { if (wi == 8) gemm_producer<false>(p, sb, v - V_QKV); else qkv_release(p, sb); }
            } else if (role & 16) fin_warp(p, sb, (v - V_QKV) * 2 + wi - 10);
        } else { reg_inc<232>(); if (role & 8) gemm_consumer<false>(p, sb, v - V_QKV, wi); }
    }
    __syncwarp();
    cluster_sync();
}

typedef CUresult (*EncFn)(CUtensorMap*, CUtensorMapDataType, cuuint32_t, void*, const cuuint64_t*, const cuuint64_t*, const cuuint32_t*, const cuuint32_t*,
                          CUtensorMapInterleave, CUtensorMapSwizzle, CUtensorMapL2promotion, CUtensorMapFloatOOBfill);
constexpr int SMEM_BYTES = 232448;
#define LAG 8
#define QLEAD 6
#define SPLIT 2
#define OLEAD (LAG / 2 + 2)
void plan(Params& P) {
    P.roles = 31; P.chains = 3; P.lag = LAG; P.dopro = 1; P.h0 = 128 - 2 * SPLIT;
    for (int r = 0; r < 2; r++) {
        const int lead = r ? OLEAD : QLEAD;
        int n = 0;
        for (int i = 0; i < 32 + lead; i++) {
            if (i >= lead) P.list[r][n++] = 32 + i - lead;
            if (i < 32) P.list[r][n++] = i;
        }
        P.nl[r] = n - r * SPLIT;
    }
}

#define TK() do {} while (0)
}

extern "C" void kernel_launch(void* const* d_in, const int* in_sizes, int n_in, void* d_out, int out_size) {
    typedef const __nv_bfloat16* BP;
    static EncFn enc = nullptr;
    if (!enc) {
        void* fn = nullptr; cudaDriverEntryPointQueryResult qr;
        cudaGetDriverEntryPoint("cuTensorMapEncodeTiled", &fn, cudaEnableDefault, &qr);
        enc = (EncFn)fn;
        cudaFuncSetAttribute(main_kernel, cudaFuncAttributeMaxDynamicSharedMemorySize, SMEM_BYTES);
    }
    static Params P;
    for (int i = 0; i < 4; i++) {
        const cuuint64_t cols = i < 3 ? 4096 : 512, rows = i < 3 ? 512 : 4096;
        cuuint64_t d2[2] = {cols, rows}, str[1] = {cols * 2};
        cuuint32_t box[2] = {64, 64}, bn[2] = {16, 256}, es[2] = {1, 1};
        enc(&P.tm[i < 3 ? i : 4], CU_TENSOR_MAP_DATA_TYPE_BFLOAT16, 2, d_in[9 + i], d2, str, box, es, CU_TENSOR_MAP_INTERLEAVE_NONE, CU_TENSOR_MAP_SWIZZLE_128B,
            CU_TENSOR_MAP_L2_PROMOTION_L2_128B, CU_TENSOR_MAP_FLOAT_OOB_FILL_NONE);
        if (i < 2) enc(&P.tn[i], CU_TENSOR_MAP_DATA_TYPE_BFLOAT16, 2, d_in[9 + i], d2, str, bn, es, CU_TENSOR_MAP_INTERLEAVE_NONE, CU_TENSOR_MAP_SWIZZLE_32B,
                       CU_TENSOR_MAP_L2_PROMOTION_L2_128B, CU_TENSOR_MAP_FLOAT_OOB_FILL_NONE);
    }
    {
        cuuint64_t dims[2] = {512, 2048}, str[1] = {1024};
        cuuint32_t box[2] = {8, 256}, es[2] = {1, 1};
        enc(&P.tm[3], CU_TENSOR_MAP_DATA_TYPE_BFLOAT16, 2, d_in[0], dims, str, box, es, CU_TENSOR_MAP_INTERLEAVE_NONE, CU_TENSOR_MAP_SWIZZLE_NONE,
            CU_TENSOR_MAP_L2_PROMOTION_NONE, CU_TENSOR_MAP_FLOAT_OOB_FILL_NONE);
    }
    P.mem0 = (BP)d_in[8]; P.Wo = (BP)d_in[12]; P.Dskip = (BP)d_in[6]; P.out = (__nv_bfloat16*)d_out;
    cudaStream_t s = cudaStreamPerThread;
    P.pa = {(BP)d_in[0], (BP)d_in[1], (BP)d_in[2], (BP)d_in[3], (BP)d_in[4], (BP)d_in[5], (BP)d_in[6]};
    plan(P);
    TK(); main_kernel<<<2 * NCL, 384, SMEM_BYTES, s>>>(P); TK();
}
```
